```python
import torch

def _softmax(x, axis=-1):
    return torch.softmax(x, dim=axis)
def _gelu(x):
    return torch.nn.functional.gelu(x, approximate="tanh")
def _silu(x):
    return torch.nn.functional.silu(x)
def _sigmoid(x):
    return torch.sigmoid(x)
def _layernorm(x, axis=-1, eps=1e-5):
    m = x.mean(dim=axis, keepdim=True)
    v = x.var(dim=axis, keepdim=True, unbiased=False)
    return (x - m) / torch.sqrt(v + eps)
def _scatter_add(tgt, idx, src, axis=0):
    return tgt.clone().index_add_(axis, idx, src)
def _segment_sum(src, seg, n):
    out = torch.zeros((n,) + src.shape[1:], dtype=src.dtype)
    return out.index_add_(0, seg, src)
def _pad(x, pw):
    flat = tuple(v for pair in reversed(pw) for v in pair)
    return torch.nn.functional.pad(x, flat)

kernel_name = 'standalone__modern_conv_block_slak__vision'

def setup_inputs():

    _w = (lambda a: (lambda t: t.to(torch.bfloat16) if t.is_floating_point() else t)(torch.as_tensor(a)))
    H = W = 384
    C = 384
    K = 1
    return {
        "x": _w((lambda *s: torch.randn(*s, dtype=torch.bfloat16) * 0.05)(1, H, W, C)),
        "dw": _w((lambda *s: torch.randn(*s, dtype=torch.bfloat16) * 0.05)(K, K, C)),
        "w1": _w((lambda *s: torch.randn(*s, dtype=torch.bfloat16) * 0.05)(C, 4 * C)),
        "w2": _w((lambda *s: torch.randn(*s, dtype=torch.bfloat16) * 0.05)(4 * C, C)),
        "grn_g": _w((lambda *s: torch.randn(*s, dtype=torch.bfloat16) * 0.05)(4 * C)),
        "grn_b": _w((lambda *s: torch.randn(*s, dtype=torch.bfloat16) * 0.05)(4 * C)),
    }

def reference(x, dw, w1, w2, grn_g, grn_b):
    B, H, W, C = x.shape
    K = dw.shape[0]
    pad = K // 2
    xp = _pad(x, ((0,0),(pad,pad),(pad,pad),(0,0)))
    out = torch.zeros_like(x)
    for i in range(K):
        for j in range(K):
            out = out + xp[:, i:i+H, j:j+W, :] * dw[i, j][None, None, None, :]
    h = _layernorm(out, axis=-1)
    h = _gelu(h @ w1)
    gx = torch.sqrt((h * h).sum(axis=(1, 2), keepdims=True) + 1e-6)
    nx = gx / (gx.mean(axis=-1, keepdims=True) + 1e-6)
    h = grn_g[None, None, None, :] * (h * nx) + grn_b[None, None, None, :] + h
    return x + h @ w2
```

```cpp
#include <cuda.h>
#include <cuda_runtime.h>
#include <cuda_bf16.h>
#include <cuda_fp16.h>
#include <stdint.h>
#include <stdio.h>

namespace {

constexpr int M_TOTAL = 384 * 384;
constexpr int C_DIM   = 384;
constexpr int HID     = 1536;
constexpr int NT128   = M_TOTAL / 128;
constexpr int NUM_CTAS = 132;

constexpr int NGRP = 11, GRP_CTAS = 12;
constexpr int LN_STEP = NUM_CTAS / 4, LN_RING = 2 * LN_STEP;
constexpr int NT_RING = NT128 - NGRP;
constexpr int LN_TILE = 128 * C_DIM * 2;
constexpr int H_TILE = 64 * HID * 3 / 2;
constexpr int H_HALF = 3072, H_STEP = 6144;

__device__ __align__(1024) uint4 g_h[(size_t)M_TOTAL * HID * 3 / 32];
__device__ __align__(1024) uint4 g_ln[LN_RING * LN_TILE / 16];
__device__ __align__(1024) uint4 g_w2img[HID * C_DIM * 2 / 16];
__device__ __align__(16) float g_sums[2][HID + 512];
__device__ unsigned g_epoch;
__device__ __align__(128) unsigned g_prog;
__device__ __align__(128) unsigned g_half[32][2];
__device__ unsigned g_flag[LN_RING + 3][2][8];
#define TSTAMP(k, i)
#define TRACE(wg, pos, i)
#define TRACEW(pos, i)

#define TR2(i)
__host__ __device__ __forceinline__ int perm32(int n) {
    return (n & ~31) | (((n >> 1) & 3) << 3) | (((n >> 3) & 3) << 1) | (n & 1);
}

__device__ __forceinline__ uint32_t smem_u32(const void* p) { return (uint32_t)__cvta_generic_to_shared(p); }

__device__ __forceinline__ void mbar_init(uint32_t bar, uint32_t count) {
    asm volatile("mbarrier.init.shared::cta.b64 [%0], %1;\n" ::"r"(bar), "r"(count) : "memory");
}
__device__ __forceinline__ void mbar_expect_tx(uint32_t bar, uint32_t bytes) {
    asm volatile("mbarrier.arrive.expect_tx.shared::cta.b64 _, [%0], %1;\n" ::"r"(bar), "r"(bytes) : "memory");
}
__device__ __forceinline__ void mbar_arrive(uint32_t bar) {
    asm volatile("mbarrier.arrive.shared::cta.b64 _, [%0];\n" ::"r"(bar) : "memory");
}
__device__ __forceinline__ void mbar_arrive_cluster(uint32_t bar_cluster_addr) {
    asm volatile("mbarrier.arrive.shared::cluster.b64 _, [%0];\n" ::"r"(bar_cluster_addr) : "memory");
}
__device__ __forceinline__ void mbar_wait(uint32_t bar, uint32_t parity) {
    asm volatile(
        "{\n"
        ".reg .pred p;\n"
        "LAB_WAIT:\n"
        "mbarrier.try_wait.parity.shared::cta.b64 p, [%0], %1;\n"
        "@!p bra LAB_WAIT;\n"
        "}\n" ::"r"(bar), "r"(parity) : "memory");
}
__device__ __forceinline__ bool mbar_test(uint32_t bar, uint32_t parity) {
    uint32_t ok;
    asm volatile("{\n.reg .pred p;\n"
                 "mbarrier.test_wait.parity.shared::cta.b64 p, [%1], %2;\n"
                 "selp.u32 %0, 1, 0, p;\n}\n" : "=r"(ok) : "r"(bar), "r"(parity) : "memory");
    return ok != 0;
}
__device__ __forceinline__ uint32_t mapa(uint32_t addr, uint32_t rank) {
    uint32_t r;
    asm volatile("mapa.shared::cluster.u32 %0, %1, %2;\n" : "=r"(r) : "r"(addr), "r"(rank));
    return r;
}
__device__ __forceinline__ void bulk_g2s(uint32_t dst, const void* src, uint32_t bytes, uint32_t bar) {
    asm volatile("cp.async.bulk.shared::cluster.global.mbarrier::complete_tx::bytes [%0], [%1], %2, [%3];\n"
                 ::"r"(dst), "l"(src), "r"(bytes), "r"(bar) : "memory");
}
__device__ __forceinline__ void bulk_g2s_mc(uint32_t dst, const void* src, uint32_t bytes, uint32_t bar, uint16_t mask) {
    asm volatile("cp.async.bulk.shared::cluster.global.mbarrier::complete_tx::bytes.multicast::cluster [%0], [%1], %2, [%3], %4;\n"
                 ::"r"(dst), "l"(src), "r"(bytes), "r"(bar), "h"(mask) : "memory");
}
__device__ __forceinline__ void tma2(uint32_t dst, const CUtensorMap* map, int c0, int c1, uint32_t bar) {
    asm volatile("cp.async.bulk.tensor.2d.shared::cluster.global.tile.mbarrier::complete_tx::bytes [%0], [%1, {%2, %3}], [%4];\n"
                 ::"r"(dst), "l"(map), "r"(c0), "r"(c1), "r"(bar) : "memory");
}
template <bool ACQ>
__device__ __forceinline__ uint32_t flag_wait(const unsigned* p, unsigned target) {
    unsigned v, n = 0;
    do {
        if (ACQ) asm volatile("ld.acquire.gpu.global.u32 %0, [%1];\n" : "=r"(v) : "l"(p) : "memory");
        else asm volatile("ld.relaxed.gpu.global.u32 %0, [%1];\n" : "=r"(v) : "l"(p) : "memory");
        n++;
    } while (v < target);
    return n == 1;
}
__device__ __forceinline__ void ldsm4t(uint32_t (&r)[4], uint32_t addr) {
    asm volatile("ldmatrix.sync.aligned.m8n8.x4.trans.shared.b16 {%0,%1,%2,%3}, [%4];\n"
                 : "=r"(r[0]), "=r"(r[1]), "=r"(r[2]), "=r"(r[3]) : "r"(addr) : "memory");
}
__device__ __forceinline__ void bulk_s2g(void* dst, uint32_t src, uint32_t bytes) {
    asm volatile("cp.async.bulk.global.shared::cta.bulk_group [%0], [%1], %2;\n" ::"l"(dst), "r"(src), "r"(bytes) : "memory");
}
__device__ __forceinline__ void cluster_sync() {
    asm volatile("barrier.cluster.arrive.aligned;\nbarrier.cluster.wait.aligned;\n" ::: "memory");
}
__device__ __forceinline__ void cluster_sync_relaxed() {
    asm volatile("barrier.cluster.arrive.relaxed.aligned;\nbarrier.cluster.wait.aligned;\n" ::: "memory");
}
__device__ __forceinline__ void gdc_wait() { asm volatile("griddepcontrol.wait;\n" ::: "memory"); }
__device__ __forceinline__ void gdc_launch() { asm volatile("griddepcontrol.launch_dependents;\n" ::: "memory"); }
__device__ __forceinline__ uint32_t cluster_rank() {
    uint32_t r;
    asm volatile("mov.u32 %0, %%cluster_ctarank;\n" : "=r"(r));
    return r;
}
__device__ __forceinline__ bool elect_one() {
    uint32_t pred;
    asm volatile("{\n.reg .pred p;\nelect.sync _|p, 0xffffffff;\nselp.u32 %0, 1, 0, p;\n}\n" : "=r"(pred));
    return pred != 0;
}
__device__ __forceinline__ void wg_fence() { asm volatile("wgmma.fence.sync.aligned;\n" ::: "memory"); }
__device__ __forceinline__ void wg_commit() { asm volatile("wgmma.commit_group.sync.aligned;\n" ::: "memory"); }
template <int N> __device__ __forceinline__ void wg_wait() {
    asm volatile("wgmma.wait_group.sync.aligned %0;\n" ::"n"(N) : "memory");
}
template <int R> __device__ __forceinline__ void reg_inc() { asm volatile("setmaxnreg.inc.sync.aligned.u32 %0;\n" ::"n"(R)); }
template <int R> __device__ __forceinline__ void reg_dec() { asm volatile("setmaxnreg.dec.sync.aligned.u32 %0;\n" ::"n"(R)); }
__device__ __forceinline__ void bar_sync(int id, int n) { asm volatile("bar.sync %0, %1;\n" ::"r"(id), "r"(n) : "memory"); }
__device__ __forceinline__ void bar_arrive(int id, int n) { asm volatile("bar.arrive %0, %1;\n" ::"r"(id), "r"(n) : "memory"); }

__device__ __forceinline__ uint64_t make_desc(uint32_t saddr, uint32_t lbo, uint32_t sbo) {
    return (uint64_t)((saddr & 0x3FFFF) >> 4) | ((uint64_t)(lbo >> 4) << 16) | ((uint64_t)(sbo >> 4) << 32);
}

__device__ __forceinline__ void stg128_cs(void* p, uint32_t a, uint32_t b, uint32_t c, uint32_t d) {
    asm volatile("st.global.cs.v4.u32 [%0], {%1,%2,%3,%4};\n" ::"l"(p), "r"(a), "r"(b), "r"(c), "r"(d) : "memory");
}
__device__ __forceinline__ uint32_t pack_bf16(float lo, float hi) {
    uint32_t r;
    asm("cvt.rn.bf16x2.f32 %0, %1, %2;\n" : "=r"(r) : "f"(hi), "f"(lo));
    return r;
}
__device__ __forceinline__ float bf_lo(uint32_t v) { return __uint_as_float(v << 16); }
__device__ __forceinline__ float bf_hi(uint32_t v) { return __uint_as_float(v & 0xffff0000u); }
__device__ __forceinline__ uint32_t bf2_mul(uint32_t a, uint32_t b) {
    uint32_t r;
    asm("mul.rn.bf16x2 %0, %1, %2;\n" : "=r"(r) : "r"(a), "r"(b));
    return r;
}
__device__ __forceinline__ uint32_t bf2_fma(uint32_t a, uint32_t b, uint32_t c) {
    uint32_t r;
    asm("fma.rn.bf16x2 %0, %1, %2, %3;\n" : "=r"(r) : "r"(a), "r"(b), "r"(c));
    return r;
}
__device__ __forceinline__ uint32_t bf2_add(uint32_t a, uint32_t b) {
    uint32_t r;
    asm("add.rn.bf16x2 %0, %1, %2;\n" : "=r"(r) : "r"(a), "r"(b));
    return r;
}
__device__ __forceinline__ uint32_t h2_mul(uint32_t a, uint32_t b) {
    uint32_t r;
    asm("mul.rn.f16x2 %0, %1, %2;\n" : "=r"(r) : "r"(a), "r"(b));
    return r;
}
__device__ __forceinline__ uint32_t h2_fma(uint32_t a, uint32_t b, uint32_t c) {
    uint32_t r;
    asm("fma.rn.f16x2 %0, %1, %2, %3;\n" : "=r"(r) : "r"(a), "r"(b), "r"(c));
    return r;
}
__device__ __forceinline__ uint32_t pack_f16(float lo, float hi) {
    uint32_t r;
    asm("cvt.rn.f16x2.f32 %0, %1, %2;\n" : "=r"(r) : "f"(hi), "f"(lo));
    return r;
}
__device__ __forceinline__ float h_lo(uint32_t v) { return __low2float(*reinterpret_cast<const __half2*>(&v)); }
__device__ __forceinline__ float h_hi(uint32_t v) { return __high2float(*reinterpret_cast<const __half2*>(&v)); }
__device__ __forceinline__ uint32_t bf2_to_h2(uint32_t v) { return (v & 0x7fff7fffu) * 7u + v; }
__device__ __forceinline__ uint32_t prmt(uint32_t a, uint32_t b, uint32_t sel) {
    uint32_t r;
    asm("prmt.b32 %0, %1, %2, %3;\n" : "=r"(r) : "r"(a), "r"(b), "r"(sel));
    return r;
}
__device__ __forceinline__ uint32_t bitsel(uint32_t a, uint32_t b, uint32_t m) {
    uint32_t r;
    asm("lop3.b32 %0, %1, %2, %3, 0xd8;\n" : "=r"(r) : "r"(a), "r"(b), "r"(m));
    return r;
}
constexpr float KAPPA = 0.3292034911525734f;
constexpr uint32_t GELU_C2 = 0x40d940d9u;
constexpr float HSCALE = 1.0f / (2.0f * KAPPA);
__device__ __forceinline__ float w2_scale(uint32_t m) { return __uint_as_float((257u - max(m >> 23, 16u)) << 23); }
__device__ __forceinline__ void sched_break(int zero) {
    asm volatile("{\n.reg .pred p;\nsetp.ne.s32 p, %0, 0;\nSB_LOOP:\n@p nanosleep.u32 1;\n@p bra SB_LOOP;\n}\n" ::"r"(zero));
}

#define ACC8(d, o) "+r"(d[o + 0]), "+r"(d[o + 1]), "+r"(d[o + 2]), "+r"(d[o + 3]), "+r"(d[o + 4]), "+r"(d[o + 5]), "+r"(d[o + 6]), "+r"(d[o + 7])

__device__ __forceinline__ void mma_rs_n128(uint32_t (&d)[32], const uint32_t (&a)[4], uint64_t desc, int scale_d) {
    asm volatile(
        "{\n.reg .pred p;\nsetp.ne.b32 p, %37, 0;\n"
        "wgmma.mma_async.sync.aligned.m64n128k16.f16.f16.f16 "
        "{%0,%1,%2,%3,%4,%5,%6,%7,%8,%9,%10,%11,%12,%13,%14,%15,"
        "%16,%17,%18,%19,%20,%21,%22,%23,%24,%25,%26,%27,%28,%29,%30,%31},"
        "{%32,%33,%34,%35}, %36, p, 1, 1, 0;\n}\n"
        : ACC8(d, 0), ACC8(d, 8), ACC8(d, 16), ACC8(d, 24)
        : "r"(a[0]), "r"(a[1]), "r"(a[2]), "r"(a[3]), "l"(desc), "r"(scale_d));
}

constexpr int P2_NACC = 48;
#define P2_MMA "wgmma.mma_async.sync.aligned.m64n192k16.f16.f16.f16 " \
        "{%0,%1,%2,%3,%4,%5,%6,%7,%8,%9,%10,%11,%12,%13,%14,%15," \
        "%16,%17,%18,%19,%20,%21,%22,%23,%24,%25,%26,%27,%28,%29,%30,%31," \
        "%32,%33,%34,%35,%36,%37,%38,%39,%40,%41,%42,%43,%44,%45,%46,%47},"
#define P2_ACC(d) ACC8(d, 0), ACC8(d, 8), ACC8(d, 16), ACC8(d, 24), ACC8(d, 32), ACC8(d, 40)
#define P2_RS "{%48,%49,%50,%51}, %52, 1, 1, 1, 0;\n"
#define P2_SS "%48, %49, 0, 1, 1, 0, 0;\n"
__device__ __forceinline__ void mma_rs_n192(uint32_t (&d)[P2_NACC], const uint4& a, uint64_t db) {
    asm volatile(P2_MMA P2_RS : P2_ACC(d) : "r"(a.x), "r"(a.y), "r"(a.z), "r"(a.w), "l"(db));
}
__device__ __forceinline__ void mma_ss_n192_init(uint32_t (&d)[P2_NACC], uint64_t da, uint64_t db) {
    asm volatile(P2_MMA P2_SS : P2_ACC(d) : "l"(da), "l"(db));
}

constexpr int P1_SLOT = LN_TILE / 2, P1_NST = 4;
constexpr int P1_X = 32 * C_DIM * 2;
constexpr int P1_OFF_X = P1_SLOT * P1_NST;
constexpr int P1_OFF_BAR = P1_OFF_X + P1_X;
constexpr int P1_OFF_TILE = P1_OFF_BAR + (2 * P1_NST + 2 + 4 + 4) * 8;
constexpr int P1_OFF_RAW = P1_OFF_TILE + 64;
constexpr int P1_OFF_EX = P1_OFF_RAW + 16;
constexpr int P1_SMEM = P1_OFF_EX + 128 * 4;

__device__ __forceinline__ float rsqrt_fast(float x) {
    float r;
    asm("rsqrt.approx.ftz.f32 %0, %1;\n" : "=f"(r) : "f"(x));
    return r;
}
__device__ __forceinline__ float row_sum(const uint32_t (&c)[4]) {
    const uint32_t u = bf2_add(bf2_add(c[0], c[1]), bf2_add(c[2], c[3]));
    float s = bf_lo(u) + bf_hi(u);
#pragma unroll
    for (int o = 1; o < 8; o <<= 1) s += __shfl_xor_sync(0xffffffffu, s, o);
    return s;
}
__device__ __forceinline__ uint32_t pace(uint32_t bar, uint32_t off, uint32_t val, uint32_t after, int zero) {
    asm volatile(
        "{\n.reg .pred p;\n.reg .b32 par;\n"
        "lop3.b32 par, %4, %2, %3, 0xea;\n"
        "mbarrier.test_wait.parity.shared::cta.b64 p, [%1], par;\n"
        "selp.u32 par, 1, 0, p;\n"
        "mbarrier.try_wait.parity.shared::cta.b64 p, [%1], par, 1000;\n"
        "@p or.b32 %0, %0, %2;\n"
        "}\n" : "+r"(val) : "r"(bar), "r"(zero), "r"(off), "r"(after));
    return val;
}
template <bool PACE>
__device__ __forceinline__ void ln_row(uint32_t (&v)[6][4], const uint32_t (&d)[6][4], uint32_t bar, uint32_t off, int zero,
                                       uint32_t bar_read) {
    uint32_t c[4];
#pragma unroll
    for (int i = 0; i < 6; i++)
#pragma unroll
        for (int k = 0; k < 4; k++) c[k] = bf2_fma(v[i][k], d[i][k], i ? c[k] : 0);
    const float inv = 1.0f / C_DIM;
    const float m = row_sum(c) * inv;
    uint32_t nm = pack_bf16(-m, -m);
    const float e = m + bf_lo(nm);
    if (bar_read) mbar_arrive(bar_read + (nm & zero));
    if (PACE) nm = pace(bar, off, nm, nm, zero);
#pragma unroll
    for (int i = 0; i < 6; i++) {
#pragma unroll
        for (int k = 0; k < 4; k++) {
            v[i][k] = bf2_fma(v[i][k], d[i][k], nm);
            c[k] = i ? bf2_fma(v[i][k], v[i][k], c[k]) : bf2_mul(v[i][k], v[i][k]);
        }
    }
    float r = KAPPA * rsqrt_fast(fmaxf(fmaf(-e, e, row_sum(c) * inv), 0.f) + 1e-5f);
    const float er = -e * r * 0x1p-116f;
    if (__any_sync(0xffffffffu, r < 0x1p-8f)) {
        const uint32_t p2 = __float_as_uint(r) & 0x7f800000u;
        r = __uint_as_float((__float_as_uint(r) & 0x007fffffu) | 0x3f800000u);
#pragma unroll
        for (int i = 0; i < 6; i++)
#pragma unroll
            for (int k = 0; k < 4; k++) v[i][k] = bf2_mul(v[i][k], p2 | p2 >> 16);
    }
    r *= 0x1p-116f;
    uint32_t rs = pack_bf16(r, r);
    const uint32_t sh = pack_bf16(er, er);
    if (PACE) rs = pace(bar, off, rs, sh, zero);
#pragma unroll
    for (int i = 0; i < 6; i++)
#pragma unroll
        for (int k = 0; k < 4; k++) v[i][k] = bf2_to_h2(bf2_fma(v[i][k], rs, sh));
}

template <int R>
__device__ __forceinline__ uint32_t gelu2(uint32_t a, uint32_t sc2) {
    uint32_t y, t;
    if (R) asm("{\n.reg .b16 l, h;\n.reg .b32 f;\nmov.b32 {l, h}, %2;\nmov.b32 f, {h, h};\nmul.rn.f16x2 %0, %1, f;\n}\n" : "=r"(y) : "r"(a), "r"(sc2));
    else asm("{\n.reg .b16 l, h;\n.reg .b32 f;\nmov.b32 {l, h}, %2;\nmov.b32 f, {l, l};\nmul.rn.f16x2 %0, %1, f;\n}\n" : "=r"(y) : "r"(a), "r"(sc2));
    asm("tanh.approx.f16x2 %0, %1;\n" : "=r"(t) : "r"(h2_mul(y, h2_fma(y, y, GELU_C2))));
    return h2_fma(a, t, a);
}
constexpr uint32_t SPARE = 0x40074007u;

__device__ __forceinline__ uint32_t p1_parity(uint32_t sbase) {
    uint32_t v;
    asm volatile("ld.shared.u32 %0, [%1];\n" : "=r"(v) : "r"(sbase + P1_OFF_TILE - 4) : "memory");
    return v;
}
template <int WG>
__device__ __forceinline__ void p1_consumer(const uint32_t (&a)[24][4], uint32_t sc2, uint32_t sbase, int w, int lane, int zero) {
    const uint32_t bar_full = sbase + P1_OFF_BAR, bar_empty = bar_full + P1_NST * 8;
    const uint32_t empty_remote = mapa(bar_empty, lane & 1) + (WG == 0 ? (lane & 2) * 4 : 0);
    const uint32_t bar_pace = bar_empty + P1_NST * 8 + 16 + w * 8;
    const int g = lane >> 2, q = lane & 3, cb = (blockIdx.x % GRP_CTAS) * 2 + WG;
    uint32_t acc[32];
    float ssq[2] = {0.f, 0.f};
    TSTAMP(0, 1);

    uint8_t* hp = reinterpret_cast<uint8_t*>(g_h) + (size_t)(blockIdx.x / GRP_CTAS) * (2 * H_TILE) + ((cb * 2 + (w >> 1)) * H_STEP + (w & 1) * 1536) + g * 64 + (q ^ (g >> 1)) * 16;
    const uint64_t desc_base = make_desc(sbase, 16, 1024) | (1ull << 62);
#pragma unroll 1
    for (int i = 0;; i++) {
        const int s0 = (i & 1) * 16, par = (i >> 1) & 1;
        const uint64_t d0 = desc_base + (uint64_t)((i & 1) * (LN_TILE / 16));
        TRACE(WG, i, 0);
        if (WG == 0) mbar_wait(bar_full + s0, par);
        bar_sync(1 + WG, 256);
        TRACE(WG, i, 1);
        uint32_t step, more;
        wg_fence();
#pragma unroll
        for (int k = 0; k < 24; k++) {
            if (WG == 0 && k == 12) mbar_wait(bar_full + s0 + 8, par);
            mma_rs_n128(acc, a[k], d0 + (uint64_t)((k >> 2) * 1024 + (k & 3) * 2), k != 0);
            if (k == 23) bar_arrive(2 - WG, 256);
            if (k % 12 == 11) wg_commit();
        }
        asm volatile("ld.shared.v2.u32 {%0, %1}, [%2];\n" : "=r"(step), "=r"(more) : "r"(sbase + P1_OFF_TILE + (i & 3) * 16) : "memory");
        TRACE(WG, i, 2);
        if (WG == 1) {
            wg_wait<1>();
            if (lane < 2) mbar_arrive_cluster(empty_remote + s0);
        }
        hp += step;
        TRACE(WG, i, 3);
        wg_wait<0>();
        TRACE(WG, i, 4);
        if (lane < (WG == 0 ? 4 : 2)) mbar_arrive_cluster(empty_remote + s0 + WG * 8);
        uint32_t sq[2];
#pragma unroll
        for (int b = 0; b < 2; b++) {
            uint32_t h[4][4];
#pragma unroll
            for (int c = 0; c < 4; c++)
#pragma unroll
                for (int u = 0; u < 4; u++) {
                    const uint32_t v = acc[16 * b + 8 * (c >> 1) + 2 * u + (c & 1)];
                    h[c][u] = (c & 1) ? gelu2<1>(v, sc2) : gelu2<0>(v, sc2);
                    sq[c & 1] = (b | (c >> 1) | u) ? h2_fma(h[c][u], h[c][u], sq[c & 1]) : h2_mul(h[c][u], h[c][u]);
                }
#pragma unroll
            for (int u = 0; u < 4; u++) {
                const uint32_t v = h[0][u], s = v >> 3;
                h[1][u] = bitsel(h[1][u], prmt(s, v, 0x6240), SPARE);
                h[2][u] = bitsel(h[2][u], prmt(v, v, 0xa381), SPARE);
                h[3][u] = bitsel(h[3][u], prmt(s, v, 0xf3d1), SPARE);
            }
#pragma unroll
            for (int c = 1; c < 4; c++) stg128_cs(hp + b * H_HALF + (c - 1) * 512, h[c][0], h[c][1], h[c][2], h[c][3]);
        }
#pragma unroll
        for (int r = 0; r < 2; r++) ssq[r] += h_lo(sq[r]) + h_hi(sq[r]);
        if (lane == 0) mbar_arrive(bar_pace);
        if (!more) break;
    }
    TSTAMP(0, 21);
    if (WG == 0) bar_sync(1, 256);
#pragma unroll
    for (int r = 0; r < 2; r++) {
        ssq[r] += __shfl_xor_sync(0xffffffffu, ssq[r], 1);
        ssq[r] += __shfl_xor_sync(0xffffffffu, ssq[r], 2);
        float f;
        asm volatile("ld.shared.f32 %0, [%1];\n" : "=f"(f) : "r"(sbase + P1_OFF_EX + (WG * 64 + w * 16 + r * 8 + g) * 4) : "memory");
        if (q == 0) atomicAdd(&g_sums[p1_parity(sbase)][cb * 64 + w * 16 + r * 8 + g], ssq[r] * f * f);
    }
}

__global__ void __cluster_dims__(2, 1, 1) __launch_bounds__(512, 1)
pass1_kernel(const __grid_constant__ CUtensorMap wmap, const __nv_bfloat16* __restrict__ x, const __nv_bfloat16* __restrict__ dw,
             const __nv_bfloat16* __restrict__ w2, const __nv_bfloat16* __restrict__ grn_b, int zero) {
    extern __shared__ __align__(1024) uint8_t smem[];
    const uint32_t sbase = smem_u32(smem);
    const uint32_t bar_full = sbase + P1_OFF_BAR, bar_empty = bar_full + P1_NST * 8, bar_w = bar_empty + P1_NST * 8;
    const int tid = threadIdx.x;
    const int warp = __shfl_sync(0xffffffffu, tid >> 5, 0), lane = tid & 31;
    const uint32_t rank = cluster_rank();
    const int cig = blockIdx.x % GRP_CTAS;
    uint8_t* const ring = reinterpret_cast<uint8_t*>(g_ln);

    TSTAMP(0, 0);
    TRACEW(110 + warp, 0);
    const uint32_t bar_pace = bar_w + 16, bar_xfull = bar_pace + 32, bar_xempty = bar_xfull + 8, bar_done = bar_xfull + 16;
    const uint32_t bar_raw = sbase + P1_OFF_RAW;
    const int ln0 = blockIdx.x >> 2, first = blockIdx.x / GRP_CTAS;
    const uint8_t* xsrc = reinterpret_cast<const uint8_t*>(x) + (size_t)(NGRP * 4 + blockIdx.x) * P1_X;

    if (warp >= 12) {
        reg_dec<40>();
        asm volatile("barrier.cluster.arrive.relaxed.aligned;\n" ::: "memory");
        asm volatile("barrier.cluster.wait.aligned;\n" ::: "memory");
        if (warp == 12) {
            int prev = first - NGRP, t = first, next = t + NGRP;
            const uint32_t rbase = mapa(sbase, lane & 1);
#pragma unroll 1
            for (int i = 1; t < NT_RING; i++) {
                const int s0 = (i & 1) * 2, par = ((i + 1) >> 1 & 1) ^ 1;
                const int round = t / LN_RING, slot = t - round * LN_RING;
                const uint8_t* src = ring + slot * LN_TILE + rank * (P1_SLOT / 2);
                int draw = 0;
                if (rank == 0 && lane == 0) draw = atomicAdd(&g_flag[LN_RING + (cig >> 2)][(cig >> 1) & 1][0], 1u);
                flag_wait<true>(&g_flag[slot][0][0], 4 * round + 4);
                TRACEW(i, 2);
                asm volatile("fence.proxy.async.global;\n" ::: "memory");
                draw = 2 * NGRP + __shfl_sync(0xffffffffu, draw, 0);
#pragma unroll
                for (int h = 0; h < 2; h++) {
                    mbar_wait(bar_empty + (s0 + h) * 8, par);
                    TRACEW(i, 4 + h);
                    if (elect_one()) {
                        mbar_expect_tx(bar_full + (s0 + h) * 8, P1_SLOT + 16 - 16 * h);
                        bulk_g2s_mc(sbase + (s0 + h) * P1_SLOT + rank * (P1_SLOT / 2), src + h * P1_SLOT, P1_SLOT / 2, bar_full + (s0 + h) * 8, (uint16_t)3);
                    }
                    __syncwarp();
                    if (h == 0 && rank == 0 && lane < 2)
                        asm volatile("st.async.shared::cluster.mbarrier::complete_tx::bytes.v4.u32 [%0], {%1, %2, %3, %3}, [%4];\n"
                                     ::"r"(rbase + P1_OFF_TILE + (i & 3) * 16), "r"((t - prev) * (2 * H_TILE)), "r"((int)(next < NT_RING)), "r"(draw),
                                       "r"(rbase + P1_OFF_BAR + s0 * 8) : "memory");
                }
                prev = t;
                t = next;
                next = draw;
                if (rank != 0) {
                    mbar_wait(bar_full + (s0 ^ 2) * 8, ((i - 1) >> 1) & 1);
                    asm volatile("ld.shared.u32 %0, [%1];\n" : "=r"(t) : "r"(sbase + P1_OFF_TILE + ((i - 1) & 3) * 16 + 8) : "memory");
                }
            }
        } else if (warp == 13) {
            int ph = 0;
            unsigned target = 0;
#pragma unroll 1
            for (int i = ln0 + LN_STEP; i < NT_RING; i += LN_STEP, ph ^= 1) {
                target += ph * (GRP_CTAS / 2);
                xsrc += (size_t)NUM_CTAS * P1_X;
                mbar_wait(bar_xempty, ph);
                if (elect_one()) {
                    mbar_expect_tx(bar_xfull, P1_X);
                    bulk_g2s(sbase + P1_OFF_X, xsrc, P1_X, bar_xfull);
                }
                __syncwarp();
                const uint32_t off = flag_wait<false>(&g_flag[ln0 + (ph ^ 1) * LN_STEP][1][0], target);
                mbar_wait(bar_done, ph);
                if (elect_one()) {
                    asm volatile("st.shared.u32 [%0], %1;\n" ::"r"(bar_done + 8), "r"(off) : "memory");
                    mbar_arrive(bar_xfull);
                }
                __syncwarp();
            }
        } else if (warp == 15) {
            if (rank == 1 && lane < 2) mbar_arrive(bar_empty + (2 + lane) * 8);
            const uint32_t par = g_epoch & 1;
            asm volatile("st.shared.u32 [%0], %1;\n" ::"r"(sbase + P1_OFF_TILE - 4), "r"(par) : "memory");
            if (blockIdx.x < 16) reinterpret_cast<float4*>(g_sums[par ^ 1])[blockIdx.x * 32 + lane] = make_float4(0.f, 0.f, 0.f, 0.f);
            {
                bar_sync(4, 288);
                mbar_wait(bar_raw + 8, 0);
                const uint32_t o = lane * 16384 + rank * 8192, peer = mapa(sbase, rank ^ 1);
                if (lane < 6)
                    asm volatile("cp.async.bulk.shared::cluster.shared::cta.mbarrier::complete_tx::bytes [%0], [%1], 8192, [%2];\n"
                                 ::"r"(peer + o), "r"(sbase + o), "r"(peer + P1_OFF_BAR + (lane >= 3 ? 8 : 0)) : "memory");
                __syncwarp();
            }
            int t = first, next = t + NGRP;
            if (rank == 1) {
                mbar_wait(bar_full, 0);
                mbar_wait(bar_full + 8, 0);
                if (lane < 2) mbar_arrive(bar_empty + lane * 8);
            }
#pragma unroll 1
            for (int i = 1; rank == 1 && t < NT_RING; i++) {
                const int s0 = (i & 1) * 16;
                mbar_wait(bar_full + s0, (i >> 1) & 1);
                mbar_wait(bar_full + s0 + 8, (i >> 1) & 1);
                if (lane == 0) asm volatile("red.relaxed.gpu.global.add.u32 [%0], 1;\n" ::"l"(&g_flag[t % LN_RING][1][0]) : "memory");
                t = next;
                asm volatile("ld.shared.u32 %0, [%1];\n" : "=r"(next) : "r"(sbase + P1_OFF_TILE + (i & 3) * 16 + 8) : "memory");
                if (lane < 2) mbar_arrive(bar_empty + s0 + lane * 8);
                TRACEW(i, 3);
            }
            if (rank == 0) {
                mbar_wait(bar_full, 0);
                mbar_wait(bar_full, 1);
                float* sums = g_sums[par] + HID;
                unsigned* flag = reinterpret_cast<unsigned*>(sums + C_DIM);
                float gs = 0.f;
#pragma unroll 1
                for (int pass = 0; pass < 2; pass++) {
                    float mx = 0.f;
#pragma unroll 1
                    for (int it = first; it < 48; it += NGRP) {
                        const int np = (it % 12) * 32 + lane, kb = cig * 2 + it / 12;
                        const __nv_bfloat16* wc = w2 + (size_t)kb * 64 * C_DIM + perm32(np);
                        const uint32_t sc = mapa(sbase + P1_OFF_EX + (kb & 1) * 256, it / 24);
                        float bsum = 0.f;
#pragma unroll 1
                        for (int c = 0; c < 8; c++) {
                            float f[8];
#pragma unroll
                            for (int e = 0; e < 8; e++) f[e] = __bfloat162float(wc[(c * 8 + e) * C_DIM]);
#pragma unroll
                            for (int e = 0; e < 8; e++) {
                                float t;
                                asm volatile("ld.shared::cluster.f32 %0, [%1];\n" : "=f"(t) : "r"(sc + (c * 8 + e) * 4) : "memory");
                                bsum = fmaf(__bfloat162float(grn_b[kb * 64 + c * 8 + e]), f[e], bsum);
                                f[e] *= t;
                                mx = fmaxf(mx, fabsf(f[e]));
                            }
                            if (pass)
                                g_w2img[(((kb * 4 + (c >> 1)) * 48 + (np >> 3)) * 2 + (c & 1)) * 8 + (np & 7)] = make_uint4(
                                    pack_f16(f[0] * gs, f[1] * gs), pack_f16(f[2] * gs, f[3] * gs), pack_f16(f[4] * gs, f[5] * gs), pack_f16(f[6] * gs, f[7] * gs));
                        }
                        if (pass) atomicAdd(&sums[np], bsum);
                    }
                    if (!pass) {
                        const uint32_t m = __reduce_max_sync(0xffffffffu, __float_as_uint(mx));
                        if (lane == 0) {
                            atomicMax(flag, m);
                            asm volatile("red.release.gpu.global.add.u32 [%0], 1;\n" ::"l"(flag + 32) : "memory");
                        }
                        flag_wait<true>(flag + 32, NUM_CTAS / 2);
                        gs = w2_scale(__ldcg(flag));
                    }
                }
            }
        } else if (warp == 14) {
            int ph = 0;
#pragma unroll 1
            for (int i = ln0; i < NT_RING; i += LN_STEP, ph ^= 1) {
                mbar_wait(bar_done, ph);
                TRACEW(i / LN_STEP, 0);
                asm volatile("fence.proxy.async.global;\n" ::: "memory");
                if (elect_one()) asm volatile("red.release.gpu.global.add.u32 [%0], 1;\n" ::"l"(&g_flag[ln0 + ph * LN_STEP][0][0]) : "memory");
                __syncwarp();
                TRACEW(i / LN_STEP, 1);
            }
        }
        __syncwarp();
        cluster_sync();
    } else if (warp >= 8) {
        reg_dec<88>();
        asm volatile("barrier.cluster.arrive.relaxed.aligned;\n" ::: "memory");
        {
            const int l8 = lane & 7, row = (warp - 8) * 4 + (lane >> 3), px = (blockIdx.x & 3) * 32 + row;
            uint32_t d[6][4];
#pragma unroll
            for (int j = 0; j < 6; j++) {
                const uint4 t = reinterpret_cast<const uint4*>(dw)[j * 8 + l8];
                d[j][0] = t.x; d[j][1] = t.y; d[j][2] = t.z; d[j][3] = t.w;
            }
            const int n = (px & 64) + perm32(2 * row + ((px >> 5) & 1));
            uint8_t* const dst0 = ring + ln0 * LN_TILE + n * 128 + ((l8 ^ (n & 7)) << 4);
            const uint32_t src = sbase + P1_OFF_X + ((warp - 8) * 8 + (lane >> 3)) * (C_DIM * 2) + l8 * 16;
            int ph = 0;
            asm volatile("barrier.cluster.wait.aligned;\n" ::: "memory");
#pragma unroll 1
            for (int i = ln0; i < NT_RING; i += LN_STEP, ph ^= 1) {
                TRACE(2, i / LN_STEP, 0);
                mbar_wait(bar_xfull, ph);
                uint32_t off;
                asm volatile("ld.shared.u32 %0, [%1];\n" : "=r"(off) : "r"(bar_done + 8) : "memory");
                TRACE(2, i / LN_STEP, 1);
#pragma unroll 1
                for (int ps = 0; ps < 2; ps++) {
                    uint32_t v[6][4];
#pragma unroll
                    for (int j = 0; j < 6; j++)
                        asm volatile("ld.shared.v4.u32 {%0,%1,%2,%3}, [%4];\n"
                                     : "=r"(v[j][0]), "=r"(v[j][1]), "=r"(v[j][2]), "=r"(v[j][3]) : "r"(src + ps * (4 * C_DIM * 2) + j * 128) : "memory");
                    ln_row<true>(v, d, bar_pace + (warp - 8) * 8, off, zero, ps == 1 && lane == 0 ? bar_xempty : 0);
                    uint8_t* dst = dst0 + ph * (LN_STEP * LN_TILE) + ps * 4096;
#pragma unroll
                    for (int j = 0; j < 6; j++) *reinterpret_cast<uint4*>(dst + j * 16384) = make_uint4(v[j][0], v[j][1], v[j][2], v[j][3]);
                    TRACE(2, i / LN_STEP, 3 + ps);
                }
                asm volatile("fence.proxy.async.global;\nfence.acq_rel.cta;\n" ::: "memory");
                __syncwarp();
                if (lane == 0) mbar_arrive(bar_done);
                TRACE(2, i / LN_STEP, 5);
                TRACE(2, i / LN_STEP, 2);
            }
        }
        __syncwarp();
        cluster_sync();
    } else {
        uint32_t d[6][4];
#pragma unroll
        for (int j = 0; j < 6; j++)
            asm volatile("ld.global.nc.v4.u32 {%0,%1,%2,%3}, [%4];\n" : "=r"(d[j][0]), "=r"(d[j][1]), "=r"(d[j][2]), "=r"(d[j][3])
                         : "l"(reinterpret_cast<const uint4*>(dw) + j * 8 + (lane & 7)) : "memory");
        if (tid == 0) {
            mbar_init(bar_raw, 1);
            mbar_init(bar_raw + 8, 8);
            asm volatile("fence.mbarrier_init.release.cluster;\n" ::: "memory");
            mbar_expect_tx(bar_raw, P1_SLOT);
            for (int i = 0; i < 6; i++)
                bulk_g2s(sbase + i * 16384 + (rank ^ 1) * 8192, x + (size_t)(first * 128 + rank * 64) * C_DIM + i * 4096, 8192, bar_raw);
        }
        if (tid == 32) {
            mbar_init(bar_xfull, 2);
            mbar_init(bar_xempty, 4);
            mbar_init(bar_done, 4);
            asm volatile("fence.mbarrier_init.release.cluster;\n" ::: "memory");
            mbar_expect_tx(bar_xfull, P1_X);
            bulk_g2s(sbase + P1_OFF_X, xsrc, P1_X, bar_xfull);
            asm volatile("st.shared.u32 [%0], 1;\n" ::"r"(bar_done + 8) : "memory");
            mbar_arrive(bar_xfull);
        }
        if (tid == 64) {
            asm volatile("st.shared.v4.u32 [%0], {0, 1, %1, %1};\n" ::"r"(sbase + P1_OFF_TILE), "r"(first + NGRP) : "memory");
            for (int i = 0; i < P1_NST; i++) {
                mbar_init(bar_full + i * 8, 1);
                mbar_init(bar_empty + i * 8, 16 + rank);
                mbar_init(bar_pace + i * 8, 1);
                if (i < 2) mbar_expect_tx(bar_full + i * 8, P1_SLOT / 2);
            }
            asm volatile("fence.mbarrier_init.release.cluster;\n" ::: "memory");
            if (blockIdx.x < 64) (&g_half[0][0])[blockIdx.x] = 0;
            else if (blockIdx.x == 64) g_prog = 0;
        }
        if (tid == 96) {
            for (int i = 0; i < 2; i++) mbar_init(bar_w + i * 8, 1);
            asm volatile("fence.mbarrier_init.release.cluster;\n" ::: "memory");
        }
        __syncwarp();
        asm volatile("barrier.cluster.arrive.relaxed.aligned;\n" ::: "memory");
        if (tid == 96)
            for (int i = 0; i < 2; i++) {
                mbar_expect_tx(bar_w + i * 8, P1_SLOT);
                tma2(sbase + (2 + i) * P1_SLOT, &wmap, cig * 128 + i * 64, 0, bar_w + i * 8);
                tma2(sbase + (2 + i) * P1_SLOT + P1_SLOT / 2, &wmap, cig * 128 + i * 64, 192, bar_w + i * 8);
            }
        __syncwarp();
        reg_inc<192>();
        TRACEW(110 + warp, 1);
        const int wg = warp >> 2, w = warp & 3;
        uint32_t a[24][4];
        {
            const int n = warp * 8 + (lane >> 3), px = (n & 1) * 32 + (n >> 5) * 4 + ((n >> 1) & 1) * 8 + ((n >> 3) & 3);
            if (wg == 1) bar_arrive(1, 256);
            gdc_launch();
            asm volatile("barrier.cluster.wait.aligned;\n" ::: "memory");
#pragma unroll 1
            for (int ps = -1; ps < 2; ps++) {
                if (ps == 0) mbar_wait(bar_raw, 0);
                TRACEW(110 + warp, 2 + (ps == 0));
                uint32_t v[6][4];
#pragma unroll
                for (int j = 0; j < 6; j++) {
                    const uint32_t o = (px + (ps & 1) * 16) * (C_DIM * 2) + j * 128;
                    asm volatile("ld.shared.v4.u32 {%0,%1,%2,%3}, [%4];\n" : "=r"(v[j][0]), "=r"(v[j][1]), "=r"(v[j][2]), "=r"(v[j][3])
                                 : "r"(sbase + (rank ^ 1) * 8192 + (lane & 7) * 16 + o + (o & ~8191u)) : "memory");
                }
                ln_row<false>(v, d, 0, 0, zero, 0);
                const uint32_t p = sbase + (rank * 64 + n + (ps & 1) * 4) * 128 + (((lane ^ n ^ (ps & 1) * 4) & 7) << 4);
#pragma unroll
                for (int j = 0; j < 6; j++)
                    asm volatile("st.shared.v4.u32 [%4], {%0,%1,%2,%3};\n"
                                 ::"r"(v[j][0]), "r"(v[j][1]), "r"(v[j][2]), "r"(v[j][3]), "r"(p + j * 16384) : "memory");
            }
            asm volatile("fence.proxy.async.shared::cta;\n" ::: "memory");
            __syncwarp();
            if (lane == 0) mbar_arrive_cluster(mapa(bar_raw + 8, rank ^ 1));
            bar_arrive(4, 288);
            TRACEW(110 + warp, 4);
            const uint32_t src = sbase + (2 + wg) * P1_SLOT + ((lane >> 4) * 8 + (lane & 7)) * 128 + (((2 * w + ((lane >> 3) & 1)) ^ (lane & 7)) << 4);
            mbar_wait(bar_w + wg * 8, 0);
            TRACEW(110 + warp, 5);
            uint32_t dep = 0;
#pragma unroll
            for (int k = 0; k < 24; k++) {
                ldsm4t(a[k], src + k * 2048);
                dep |= a[k][0];
            }
            __syncwarp();
            if (lane < 4) mbar_arrive_cluster(mapa(bar_empty, lane & 1) + (2 + (lane >> 1)) * 8 + (dep & zero));
        }
        uint32_t ex[2];
#pragma unroll
        for (int r = 0; r < 2; r++) {
            float t = 0.f;
#pragma unroll
            for (int j = 0; j < 6; j++) {
                uint32_t c = bf2_mul(a[4 * j][r], a[4 * j][r]);
#pragma unroll
                for (int k = 1; k < 8; k++) c = bf2_fma(a[4 * j + k / 2][r + (k & 1) * 2], a[4 * j + k / 2][r + (k & 1) * 2], c);
                t += bf_lo(c) + bf_hi(c);
            }
            t += __shfl_xor_sync(0xffffffffu, t, 1);
            t += __shfl_xor_sync(0xffffffffu, t, 2);
            ex[r] = min(max(__float_as_uint(13.9f * __fsqrt_rn(t)) >> 23, 72u), 198u);
            if ((lane & 3) == 0)
                asm volatile("st.shared.u32 [%0], %1;\n" ::"r"(sbase + P1_OFF_EX + (wg * 64 + w * 16 + r * 8 + (lane >> 2)) * 4), "r"(ex[r] << 23) : "memory");
            const uint32_t f = (258u - ex[r]) * 0x00800080u;
#pragma unroll
            for (int k = 0; k < 48; k++) a[k >> 1][r + (k & 1) * 2] = bf2_to_h2(bf2_mul(bf2_mul(a[k >> 1][r + (k & 1) * 2], f), 0x07800780u));
        }
        const uint32_t sc2 = pack_f16(__uint_as_float(min(ex[0], 142u) << 23), __uint_as_float(min(ex[1], 142u) << 23));
        bar_sync(5, 256);
        if (warp < 4) p1_consumer<0>(a, sc2, sbase, w, lane, zero);
        else p1_consumer<1>(a, sc2, sbase, w, lane, zero);
        cluster_sync();
        TSTAMP(0, 30);
    }
}

constexpr int P2_B = 24576, P2_NB = 5;
constexpr int P2_A = 3072, P2_NA = 8;
constexpr int P2_XROW = C_DIM * 2;
constexpr int P2_OFF_A = P2_B * P2_NB;
constexpr int P2_OFF_X = P2_OFF_A + 2 * P2_NA * P2_A;
constexpr int P2_XHALF = 32 * P2_XROW + 64;
constexpr int P2_OFF_BIAS = P2_OFF_X + 64 * P2_XROW + 128;
constexpr int P2_OFF_ONES = P2_OFF_BIAS + 48 * 128;
constexpr int P2_OFF_BAR = P2_OFF_ONES + 256;
constexpr int P2_SMEM = P2_OFF_BAR + (2 * P2_NB + 4 * P2_NA + 5) * 8;
constexpr int P2_LAG = 24;
constexpr int P2_NCL = NUM_CTAS / 2, P2_ITEMS = NT128 / P2_NCL, P2_SHARED = NT128 - P2_ITEMS * P2_NCL;
constexpr int P2_XC = 8 * P2_XROW;
constexpr int P2_DELTA = 9;
__device__ __forceinline__ int p2_tile(int cl, int n) {
    return n == 0 ? NT128 - 1 - cl : n < 0 || n == P2_ITEMS ? NT128 - 1 - P2_NCL - (cl >> 1) : cl + P2_NCL * (n - 1);
}

#define P2_EG 2
__device__ __forceinline__ uint32_t p2_pair(const uint32_t (&acc)[P2_NACC], int i) {
    return pack_bf16(h_lo(acc[i / 2]), h_hi(acc[i / 2]));
}
__device__ __forceinline__ void p2_epilogue(const uint32_t (&acc0)[P2_NACC], const uint32_t (&acc1)[P2_NACC], uint32_t up, uint32_t sx, int zero) {
    uint32_t v[2][P2_EG][4];
    auto load = [&](int c, uint32_t a) {
#pragma unroll
        for (int j = 0; j < P2_EG; j++) {
            const int u = c * P2_EG + j;
            asm volatile("ld.shared.v4.u32 {%0,%1,%2,%3}, [%4];\n" : "=r"(v[c & 1][j][0]), "=r"(v[c & 1][j][1]), "=r"(v[c & 1][j][2]), "=r"(v[c & 1][j][3])
                         : "r"(a + (u >> 1) * 64 + (u & 1) * 4 * P2_XROW) : "memory");
        }
    };
    load(0, sx);
#pragma unroll
    for (int c = 0; c < 24 / P2_EG; c++) {
        if (c + 1 < 24 / P2_EG) load(c + 1, sx + (v[c & 1][P2_EG - 1][0] & zero));
#pragma unroll
        for (int j = 0; j < P2_EG; j++) {
            const int u = c * P2_EG + j, i = 16 * ((u >> 1) % 6) + 2 * (u & 1);
            const uint32_t (&acc)[P2_NACC] = u < 12 ? acc0 : acc1;
            uint32_t (&w)[4] = v[c & 1][j];
#pragma unroll
            for (int e = 0; e < 4; e++) w[e] = bf2_fma(p2_pair(acc, i + 4 * e), up, w[e]);
            asm volatile("st.shared.v4.u32 [%4], {%0,%1,%2,%3};\n" ::"r"(w[0]), "r"(w[1]), "r"(w[2]), "r"(w[3]),
                         "r"(sx + (u >> 1) * 64 + (u & 1) * 4 * P2_XROW) : "memory");
        }
    }
}

__device__ __forceinline__ void p2_unpack(uint32_t (&u)[4], uint32_t o1, uint32_t o2, uint32_t o3) {
    u[2] = bitsel(o1, 0x00040004u, SPARE);
    u[1] = bitsel(o2, 0x00040004u, SPARE);
    u[3] = bitsel(o3, 0x00040004u, SPARE);
    const uint32_t t = bitsel(prmt(o1, o2, 0x6341), prmt(o1, o3, 0x6240) << 3, 0x38383838u);
    u[0] = bitsel(bitsel(t, prmt(o2, o3, 0x7351) << 1, 0x80808080u), 0x00040004u, SPARE);
}
__device__ __forceinline__ void p2_epilogue_add(const uint32_t (&acc)[P2_NACC], uint32_t upf, uint8_t* o) {
    auto up = [&](int i) { return bf2_mul(p2_pair(acc, i), upf); };
#pragma unroll
    for (int t = 0; t < 6; t++)
#pragma unroll
        for (int r = 0; r < 2; r++)
            asm volatile("red.global.add.noftz.v4.bf16x2 [%0], {%1,%2,%3,%4};\n" ::"l"(o + t * 64 + r * 4 * P2_XROW),
                         "r"(up(16 * t + 2 * r)), "r"(up(16 * t + 2 * r + 4)), "r"(up(16 * t + 2 * r + 8)), "r"(up(16 * t + 2 * r + 12)) : "memory");
}

__global__ void __cluster_dims__(2, 1, 1) __launch_bounds__(384, 1)
pass2_kernel(const __nv_bfloat16* __restrict__ x, const __nv_bfloat16* __restrict__ grn_g, __nv_bfloat16* __restrict__ out, int zero) {
    extern __shared__ __align__(1024) uint8_t smem[];
    const uint32_t sbase = smem_u32(smem);
    const uint32_t bar_bfull = sbase + P2_OFF_BAR, bar_bempty = bar_bfull + P2_NB * 8;
    const uint32_t bar_afull = bar_bempty + P2_NB * 8, bar_aempty = bar_afull + 2 * P2_NA * 8;
    const uint32_t bar_xfull = bar_aempty + 2 * P2_NA * 8, bar_oready = bar_xfull + 16;
    int tid;
    asm volatile("mov.u32 %0, %%tid.x;\n" : "=r"(tid));
    const int warp = __shfl_sync(0xffffffffu, tid >> 5, 0), lane = tid & 31;
    const uint32_t rank = cluster_rank();
    const int cl = blockIdx.x >> 1, pair = cl >> 1;
    const int j0 = pair % 12;
    const int head = pair < P2_SHARED && !(cl & 1), tail = pair < P2_SHARED && (cl & 1);

    TSTAMP(1, 0);
    if (tid == 256) {
        for (int i = 0; i < P2_NB; i++) {
            mbar_init(bar_bfull + i * 8, 1);
            mbar_init(bar_bempty + i * 8, 16);
        }
        for (int i = 0; i < 2 * P2_NA; i++) {
            mbar_init(bar_afull + i * 8, 1);
            mbar_init(bar_aempty + i * 8, 4);
        }
        for (int i = 0; i < 2; i++) {
            mbar_init(bar_xfull + i * 8, 2);
            mbar_init(bar_oready + i * 8, 4);
        }
        asm volatile("st.shared.u32 [%0], 0;\n" ::"r"(bar_oready + 16) : "memory");
        asm volatile("fence.mbarrier_init.release.cluster;\n" ::: "memory");
    }
    __syncthreads();
    cluster_sync_relaxed();

    if (warp >= 8) {
        reg_dec<24>();
        if (warp == 8) {
            const uint8_t* wsrc = reinterpret_cast<const uint8_t*>(g_w2img) + rank * (P2_B / 2);
            int st = 0, ph = 1, kb = 4 * j0;
            gdc_wait();
#pragma unroll 1
            for (int p = 0; p < P2_LAG * (P2_ITEMS + 1); p++) {
                mbar_wait(bar_bempty + st * 8, ph);
                if (elect_one()) {
                    mbar_expect_tx(bar_bfull + st * 8, P2_B);
                    bulk_g2s_mc(sbase + st * P2_B + rank * (P2_B / 2), wsrc + kb * P2_B, P2_B / 2, bar_bfull + st * 8, (uint16_t)3);
                    asm volatile("st.volatile.shared.u32 [%0], %1;\n" ::"r"(bar_oready + 16), "r"(p) : "memory");
                    if (rank == 0) asm volatile("red.relaxed.gpu.global.add.u32 [%0], 1;\n" ::"l"(&g_prog) : "memory");
                }
                __syncwarp();
                if (++st == P2_NB) { st = 0; ph ^= 1; }
                if (++kb == 48) kb = 0;
            }
            mbar_wait(bar_bempty + st * 8, ph);
            if (lane == 0) mbar_arrive(bar_bfull + st * 8);
        } else if (warp < 11) {
            const int w = warp - 9;
            int st = 0, ph = 1;
            gdc_wait();
            const uint32_t dst0 = sbase + P2_OFF_A + w * P2_NA * P2_A;
            const uint32_t bf = bar_afull + w * P2_NA * 8, be = bar_aempty + w * P2_NA * 8;
            int u = (4 * j0 + (w && !head ? P2_LAG : 0)) % 48;
#pragma unroll 1
            for (int n = w && head ? -1 : w; n < P2_ITEMS + tail; n += 2) {
                const bool half = n < 0 || n == P2_ITEMS;
                const uint8_t* src = reinterpret_cast<const uint8_t*>(g_h) + (size_t)p2_tile(cl, n) * (2 * H_TILE) + rank * H_HALF + u * H_STEP;
#pragma unroll 1
                for (int p = half ? P2_LAG : 0; p < 48; p++) {
                    mbar_wait(be + st * 8, ph);
                    if (elect_one()) {
                        mbar_expect_tx(bf + st * 8, P2_A);
                        bulk_g2s(dst0 + st * P2_A, src, P2_A, bf + st * 8);
                    }
                    __syncwarp();
                    src += H_STEP;
                    if (++u == 48) { u = 0; src -= 48 * H_STEP; }
                    if (++st == P2_NA) { st = 0; ph ^= 1; }
                }
            }
            mbar_wait(be + st * 8, ph);
            if (lane == 0) mbar_arrive(bf + st * 8);
        } else {
            const uint32_t sx = sbase + P2_OFF_X;
            size_t o = 0;
            auto pace = [&](int target) {
                int v;
                while (true) {
                    asm volatile("ld.volatile.shared.u32 %0, [%1];\n" : "=r"(v) : "r"(bar_oready + 16) : "memory");
                    if (v >= target) break;
                    __nanosleep(100);
                }
            };
#pragma unroll 1
            for (int n = -head; n <= P2_ITEMS; n++) {
                const size_t on = (size_t)(2 * p2_tile(cl, n) + rank) * (64 * C_DIM * 2);
                const uint32_t xf = bar_xfull + (n & 1) * 8;
                const bool st = n + head > 0, ld = n < P2_ITEMS;
                if (st) mbar_wait(bar_oready + (~n & 1) * 8, ((n - 1 + head) >> 1) & 1);
                if (lane == 0) {
                    if (n == 1 && head) {
                        asm volatile("cp.async.bulk.wait_group 0;\nfence.proxy.async.global;\n" ::: "memory");
                        asm volatile("st.release.gpu.global.u32 [%0], 1;\n" ::"l"(&g_half[pair][rank]) : "memory");
                    }
                    if (ld) mbar_expect_tx(xf, 64 * C_DIM * 2);
                    int t = st && ld ? P2_LAG * (n + 1) + 5 : -64;
#pragma unroll 1
                    for (int c = 0; st && c < 64 * P2_XROW; c += P2_XC) {
                        pace(t++);
                        bulk_s2g(reinterpret_cast<uint8_t*>(out) + o + c, sx + c + (c >= 32 * P2_XROW ? 64 : 0), P2_XC);
                    }
                    asm volatile("cp.async.bulk.commit_group;\ncp.async.bulk.wait_group.read 0;\n" ::: "memory");
#pragma unroll 1
                    for (int c = 0; ld && c < 64 * P2_XROW; c += P2_XC) {
                        pace(t++);
                        bulk_g2s(sx + c + (c >= 32 * P2_XROW ? 64 : 0), reinterpret_cast<const uint8_t*>(x) + on + c, P2_XC, xf);
                    }
                    if (rank == 0 && n > 0 && n < P2_ITEMS - 1)
                        flag_wait<false>(&g_prog, P2_NCL * P2_LAG * (n + 2) + (tail ? P2_SHARED - P2_NCL : P2_SHARED) * P2_DELTA);
                    if (ld) mbar_arrive(xf);
                }
                __syncwarp();
                o = on;
            }
            asm volatile("cp.async.bulk.wait_group 0;\n" ::: "memory");
        }
        __syncwarp();
        cluster_sync();
    } else {
        reg_inc<240>();
        const int wg = warp >> 2, w = warp & 3, g = lane >> 2, q = lane & 3;
        const uint32_t sx = sbase + P2_OFF_X + (g & 1) * P2_XHALF + (w * 8 + (g >> 1)) * P2_XROW + q * 16;
        const uint32_t af = bar_afull + wg * P2_NA * 8, ae = bar_aempty + wg * P2_NA * 8;
        const uint32_t s_a = sbase + P2_OFF_A - bar_afull * (P2_A / 8) + (lane >> 3) * 512 + (lane & 7) * 64 +
                             ((w ^ ((lane & 7) >> 1)) << 4);
        uint32_t acc0[P2_NACC], acc1[P2_NACC], up;
        uint4 a0[2], a1[2];
        int st = 0, ph = 0;

        {
            float* s_red = reinterpret_cast<float*>(smem + P2_OFF_ONES);
            float bias[2] = {0.f, 0.f}, gx[6], part = 0.f;
            __nv_bfloat16 gg[6];
#pragma unroll
            for (int i = 0; i < 6; i++) gg[i] = grn_g[tid + 256 * i];
            TSTAMP(1, 27);
            gdc_wait();
            TSTAMP(1, 1);
            if (blockIdx.x == 120 && tid < (LN_RING + 3) * 2) (&g_flag[0][0][0])[tid * 8] = 0;
            if (blockIdx.x == 121 && tid == 0) g_epoch++;
#pragma unroll
            for (int i = 0; i < 6; i++) gx[i] = __ldcg(&g_sums[0][tid + 256 * i]) + __ldcg(&g_sums[1][tid + 256 * i]);
#pragma unroll
            for (int i = 0; i < 2; i++)
                if (i == 0 || tid < 128) bias[i] = __ldcg(&g_sums[0][HID + tid + 256 * i]) + __ldcg(&g_sums[1][HID + tid + 256 * i]);
            const float gs = w2_scale(__float_as_uint(__ldcg(&g_sums[0][HID + C_DIM])) | __float_as_uint(__ldcg(&g_sums[1][HID + C_DIM])));
            float mg = 0.f;
#pragma unroll
            for (int i = 0; i < 6; i++) {
                gx[i] = sqrtf(gx[i] * (HSCALE * HSCALE) + 1e-6f);
                part += gx[i];
                gx[i] *= __bfloat162float(gg[i]);
                mg = fmaxf(mg, fabsf(gx[i]));
            }
#pragma unroll
            for (int o = 16; o > 0; o >>= 1) part += __shfl_xor_sync(0xffffffffu, part, o);
            const uint32_t mgw = __reduce_max_sync(0xffffffffu, __float_as_uint(mg));
            const uint32_t mbw = __reduce_max_sync(0xffffffffu, __float_as_uint(fmaxf(fabsf(bias[0]), fabsf(bias[1]))));
            TSTAMP(1, 26);
            if (lane == 0) *reinterpret_cast<float4*>(s_red + warp * 4) = make_float4(part, __uint_as_float(mgw), __uint_as_float(mbw), 0.f);
            bar_sync(1, 256);
            float tot = 0.f, mb = 0.f;
#pragma unroll
            for (int i = 0; i < 8; i++) {
                const float4 t = *reinterpret_cast<const float4*>(s_red + i * 4);
                tot += t.x;
                mg = fmaxf(mg, t.y);
                mb = fmaxf(mb, t.z);
            }
            const float inv = 1.0f / (tot * (1.0f / HID) + 1e-6f);
            const uint32_t ej = min((__float_as_uint(fmaxf(fmaf(mg, inv, 1.0f) * HSCALE, mb * gs * 0x1p-13f)) >> 23) + 1, 250u);
            const float dn = __uint_as_float((254u - ej) << 23);
            up = min(max(ej + 127u - (__float_as_uint(gs) >> 23), 1u), 254u) * 0x00800080u;
            bar_sync(1, 256);
#pragma unroll
            for (int i = 0; i < 2; i++) {
                if (i == 0 || tid < 128) {
                    const float b = bias[i] * gs * dn;
                    const uint32_t hi = pack_f16(b, 0.f);
                    *reinterpret_cast<uint2*>(smem + P2_OFF_BIAS + (tid + 256 * i) * 16) = make_uint2(pack_f16(b, b - h_lo(hi)), 0u);
                }
            }
#pragma unroll
            for (int i = 0; i < 6; i++) {
                const int k = tid + 256 * i;
                *reinterpret_cast<__half*>(smem + P2_OFF_BIAS + ((k >> 4) * 4 + ((k >> 1) & 3)) * 16 + 8 + ((k >> 3) & 1) * 4 + (k & 1) * 2) =
                    __float2half_rn(fmaf(gx[i], inv, 1.0f) * (HSCALE * dn));
            }
            TSTAMP(1, 25);
            if (tid < 16) reinterpret_cast<uint4*>(smem + P2_OFF_ONES)[tid] = make_uint4(tid < 8 ? 0x3c003c00u : 0u, 0u, 0u, 0u);
            asm volatile("fence.proxy.async.shared::cta;\n" ::: "memory");
            bar_sync(1, 256);
        }
        TSTAMP(1, 28);
        const uint32_t s_t = sbase + P2_OFF_BIAS + q * 16 + 8;
        int kt = (4 * j0 + (wg && !head ? P2_LAG : 0)) % 48;

        int pos = wg && !head ? 24 : 0;
        const int who = __shfl_sync(0xffffffffu, lane == 2 ? 0 : lane < 2 ? 1 : 2, lane);
        const uint32_t rel0 = who ? mapa(bar_bempty, lane & 1) : mapa(ae, rank), rel1 = rel0 + (who ? P2_NB : P2_NA) * 8;
        uint32_t rel = rel1 - 8;
        auto next_rel = [&](bool go) {
            if (go) rel += 8;
            if (rel == rel1) rel = rel0;
        };
        auto release_b = [&]() {
            next_rel(who == 1);
            if (who == 1) mbar_arrive_cluster(rel);
        };
        auto skip = [&]() {
#pragma unroll 1
            for (int p = 0; p < P2_LAG; p++) {
                mbar_wait(bar_bfull + st * 8, ph);
                release_b();
                if (++st == P2_NB) { st = 0; ph ^= 1; }
            }
        };
        auto publish = [&]() {
            asm volatile("fence.proxy.async.shared::cta;\n" ::: "memory");
            __syncwarp();
            if (who == 0) mbar_arrive(bar_oready + wg * 8);
        };
        bool ok_a, pend = false;
        uint32_t abar = af, pa = 0;
        auto fetch = [&](uint4 (&a)[2]) {
            uint32_t u0[4], u1[4];
            const uint32_t src = s_a + abar * (P2_A / 8);
            abar += 8;
            if (abar == af + P2_NA * 8) { abar = af; pa ^= 0x80000000u; }
            uint2 t0, t1;
            asm volatile("ld.shared.v2.u32 {%0,%1}, [%2];\n" : "=r"(t0.x), "=r"(t0.y) : "r"(s_t + kt * 128) : "memory");
            asm volatile("ld.shared.v2.u32 {%0,%1}, [%2];\n" : "=r"(t1.x), "=r"(t1.y) : "r"(s_t + kt * 128 + 64) : "memory");
            const bool ok_b = mbar_test(bar_bfull + st * 8, ph);
            ok_a = mbar_test(abar, pa >> 31);
            uint32_t o[6];
            asm volatile("ldmatrix.sync.aligned.m8n8.x4.trans.shared.b16 {%0,%1,%2,%3}, [%4];\n"
                         : "=r"(o[0]), "=r"(o[1]), "=r"(o[2]), "=r"(o[3]) : "r"(src) : "memory");
            asm volatile("ldmatrix.sync.aligned.m8n8.x2.trans.shared.b16 {%0,%1}, [%2];\n"
                         : "=r"(o[4]), "=r"(o[5]) : "r"(src + 2048) : "memory");
            p2_unpack(u0, o[0], o[1], o[2]);
            p2_unpack(u1, o[3], o[4], o[5]);
            a[0] = make_uint4(h2_mul(u0[0], t0.x), h2_mul(u0[1], t0.x), h2_mul(u0[2], t0.y), h2_mul(u0[3], t0.y));
            a[1] = make_uint4(h2_mul(u1[0], t1.x), h2_mul(u1[1], t1.x), h2_mul(u1[2], t1.y), h2_mul(u1[3], t1.y));
            if (++kt == 48) kt = 0;
            if (!ok_b) mbar_wait(bar_bfull + st * 8, ph);
        };
        auto step = [&](const uint4 (&a)[2], uint4 (&an)[2], int thr) {
            TR2(0);
            const uint64_t db = make_desc(sbase + st * P2_B, 128, 256);
            wg_fence();
            mma_rs_n192(acc0, a[0], db);
            mma_rs_n192(acc1, a[0], db + 384);
            mma_rs_n192(acc0, a[1], db + 768);
            mma_rs_n192(acc1, a[1], db + 768 + 384);
            wg_commit();
            next_rel(who < thr);
            if (++st == P2_NB) { st = 0; ph ^= 1; }
            wg_wait<1>();
            if (!ok_a) {
                if (who < thr) mbar_arrive_cluster(rel);
                if (thr == 1 && pend) publish();
                thr = 0;
                mbar_wait(abar, pa >> 31);
            }
            if (who < thr) mbar_arrive_cluster(rel);
            fetch(an);
            pos++;
        };
        if (wg && !head) skip();
        mbar_wait(af, 0);
        fetch(a0);
#pragma unroll 1
        for (int n = wg && head ? -1 : wg;; n += 2) {
            TSTAMP(1, 2 + n);
            const uint64_t ones = make_desc(sbase + P2_OFF_ONES + (n == P2_ITEMS ? 128 : 0), n == P2_ITEMS ? 0 : 128, 0);
            wg_fence();
            mma_ss_n192_init(acc0, ones, make_desc(sbase + P2_OFF_BIAS, 0, 128));
            mma_ss_n192_init(acc1, ones, make_desc(sbase + P2_OFF_BIAS + 3072, 0, 128));
            wg_commit();
            const int p0 = n < 0 || n == P2_ITEMS ? 12 : 0;
            const bool more = n + 2 < P2_ITEMS + tail;
#pragma unroll 1
            for (int p = p0; p < 24; p++) {
                step(a0, a1, p == p0 ? 1 : 2);
                step(a1, a0, 2);
            }
            if (n == P2_ITEMS) {
                flag_wait<true>(&g_half[pair][rank], 1);
                wg_wait<0>();
                release_b();
                uint8_t* o = reinterpret_cast<uint8_t*>(out) + (size_t)((2 * p2_tile(cl, -1) + rank) * 64 + (g & 1) * 32 + w * 8 + (g >> 1)) * P2_XROW + q * 16;
                p2_epilogue_add(acc0, up, o);
                p2_epilogue_add(acc1, up, o + 384);
                break;
            }
            mbar_wait(bar_xfull + wg * 8, ((n + head) >> 1) & 1);
            TR2(5);
            wg_wait<0>();
            TR2(6);
            release_b();
            __syncwarp();
            p2_epilogue(acc0, acc1, up, sx, zero);
            pend = true;
            ok_a = false;
            if (!more) { publish(); break; }
        }
        TSTAMP(1, 29);
        if (wg && !tail) skip();
        cluster_sync();
        TSTAMP(1, 30);
    }
}

}

extern "C" void kernel_launch(void* const* d_in, const int* in_sizes, int n_in, void* d_out, int out_size) {
    const __nv_bfloat16* x = (const __nv_bfloat16*)d_in[0];
    const __nv_bfloat16* dw = (const __nv_bfloat16*)d_in[1];
    const __nv_bfloat16* w1 = (const __nv_bfloat16*)d_in[2];
    const __nv_bfloat16* w2 = (const __nv_bfloat16*)d_in[3];
    const __nv_bfloat16* grn_g = (const __nv_bfloat16*)d_in[4];
    const __nv_bfloat16* grn_b = (const __nv_bfloat16*)d_in[5];
    __nv_bfloat16* out = (__nv_bfloat16*)d_out;

    cudaFuncSetAttribute(pass1_kernel, cudaFuncAttributeMaxDynamicSharedMemorySize, P1_SMEM);
    cudaFuncSetAttribute(pass2_kernel, cudaFuncAttributeMaxDynamicSharedMemorySize, P2_SMEM);

    typedef CUresult (*EncodeFn)(CUtensorMap*, CUtensorMapDataType, cuuint32_t, void*, const cuuint64_t*, const cuuint64_t*,
                                 const cuuint32_t*, const cuuint32_t*, CUtensorMapInterleave, CUtensorMapSwizzle,
                                 CUtensorMapL2promotion, CUtensorMapFloatOOBfill);
    static EncodeFn encode = nullptr;
    if (!encode) {
        cudaDriverEntryPointQueryResult qres;
        cudaGetDriverEntryPoint("cuTensorMapEncodeTiled", (void**)&encode, cudaEnableDefault, &qres);
    }
    CUtensorMap wmap;
    const cuuint64_t gdim[2] = {HID, C_DIM};
    const cuuint64_t gstr[1] = {HID * 2};
    const cuuint32_t box[2] = {64, 192}, estr[2] = {1, 1};
    CUresult er = encode(&wmap, CU_TENSOR_MAP_DATA_TYPE_BFLOAT16, 2, (void*)w1, gdim, gstr, box, estr, CU_TENSOR_MAP_INTERLEAVE_NONE,
           CU_TENSOR_MAP_SWIZZLE_128B, CU_TENSOR_MAP_L2_PROMOTION_L2_128B, CU_TENSOR_MAP_FLOAT_OOB_FILL_NONE);
    if (er != CUDA_SUCCESS) printf("tensor map encode failed %d\n", (int)er);

    pass1_kernel<<<NUM_CTAS, 512, P1_SMEM>>>(wmap, x, dw, w2, grn_b, 0);

    cudaLaunchAttribute attr[1];
    attr[0].id = cudaLaunchAttributeProgrammaticStreamSerialization;
    attr[0].val.programmaticStreamSerializationAllowed = 1;
    cudaLaunchConfig_t cfg = {};
    cfg.gridDim = dim3(NUM_CTAS);
    cfg.stream = 0;
    cfg.attrs = attr;
    cfg.numAttrs = 1;
    cfg.blockDim = dim3(384);
    cfg.dynamicSmemBytes = P2_SMEM;
    cudaLaunchKernelEx(&cfg, pass2_kernel, x, grn_g, out, 0);
}
```

```cpp
#include <cuda.h>
#include <cuda_runtime.h>
#include <cuda_bf16.h>
#include <cuda_fp16.h>
#include <stdint.h>
#include <stdio.h>

namespace {

constexpr int M_TOTAL = 384 * 384;
constexpr int C_DIM   = 384;
constexpr int HID     = 1536;
constexpr int NT128   = M_TOTAL / 128;
constexpr int NUM_CTAS = 132;

constexpr int NGRP = 11, GRP_CTAS = 12;
constexpr int LN_STEP = NUM_CTAS / 4, LN_RING = 2 * LN_STEP;
constexpr int NT_RING = NT128 - NGRP;
constexpr int LN_TILE = 128 * C_DIM * 2;
constexpr int H_TILE = 64 * HID * 3 / 2;
constexpr int H_HALF = 3072, H_STEP = 6144;

__device__ __align__(1024) uint4 g_h[(size_t)M_TOTAL * HID * 3 / 32];
__device__ __align__(1024) uint4 g_ln[LN_RING * LN_TILE / 16];
__device__ __align__(1024) uint4 g_w2img[2][HID * C_DIM * 2 / 16];
__device__ __align__(16) float g_sums[2][HID + 512];
__device__ unsigned g_epoch;
__device__ __align__(128) unsigned g_prog[2][32];
__device__ __align__(128) unsigned g_half[32][2];
__device__ unsigned g_flag[LN_RING + 3][2][8];
#define TSTAMP(k, i)
#define TRACE(wg, pos, i)
#define TRACEW(pos, i)

#define TR2(i)
__host__ __device__ __forceinline__ int perm32(int n) {
    return (n & ~31) | (((n >> 1) & 3) << 3) | (((n >> 3) & 3) << 1) | (n & 1);
}

__device__ __forceinline__ uint32_t smem_u32(const void* p) { return (uint32_t)__cvta_generic_to_shared(p); }

__device__ __forceinline__ void mbar_init(uint32_t bar, uint32_t count) {
    asm volatile("mbarrier.init.shared::cta.b64 [%0], %1;\n" ::"r"(bar), "r"(count) : "memory");
}
__device__ __forceinline__ void mbar_expect_tx(uint32_t bar, uint32_t bytes) {
    asm volatile("mbarrier.arrive.expect_tx.shared::cta.b64 _, [%0], %1;\n" ::"r"(bar), "r"(bytes) : "memory");
}
__device__ __forceinline__ void mbar_arrive(uint32_t bar) {
    asm volatile("mbarrier.arrive.shared::cta.b64 _, [%0];\n" ::"r"(bar) : "memory");
}
__device__ __forceinline__ void mbar_arrive_cluster(uint32_t bar_cluster_addr) {
    asm volatile("mbarrier.arrive.shared::cluster.b64 _, [%0];\n" ::"r"(bar_cluster_addr) : "memory");
}
#define SAFE_BREAK
__device__ __forceinline__ void mbar_wait(uint32_t bar, uint32_t parity) {
    asm volatile(
        "{\n"
        ".reg .pred p;\n"
        "LAB_WAIT:\n"
        "mbarrier.try_wait.parity.shared::cta.b64 p, [%0], %1;\n"
        "@!p bra LAB_WAIT;\n"
        "}\n" ::"r"(bar), "r"(parity) : "memory");
}
__device__ __forceinline__ bool mbar_test(uint32_t bar, uint32_t parity) {
    uint32_t ok;
    asm volatile("{\n.reg .pred p;\n"
                 "mbarrier.test_wait.parity.shared::cta.b64 p, [%1], %2;\n"
                 "selp.u32 %0, 1, 0, p;\n}\n" : "=r"(ok) : "r"(bar), "r"(parity) : "memory");
    return ok != 0;
}
__device__ __forceinline__ uint32_t mapa(uint32_t addr, uint32_t rank) {
    uint32_t r;
    asm volatile("mapa.shared::cluster.u32 %0, %1, %2;\n" : "=r"(r) : "r"(addr), "r"(rank));
    return r;
}
__device__ __forceinline__ void bulk_g2s(uint32_t dst, const void* src, uint32_t bytes, uint32_t bar) {
    asm volatile("cp.async.bulk.shared::cluster.global.mbarrier::complete_tx::bytes [%0], [%1], %2, [%3];\n"
                 ::"r"(dst), "l"(src), "r"(bytes), "r"(bar) : "memory");
}
__device__ __forceinline__ void bulk_g2s_mc(uint32_t dst, const void* src, uint32_t bytes, uint32_t bar, uint16_t mask) {
    asm volatile("cp.async.bulk.shared::cluster.global.mbarrier::complete_tx::bytes.multicast::cluster [%0], [%1], %2, [%3], %4;\n"
                 ::"r"(dst), "l"(src), "r"(bytes), "r"(bar), "h"(mask) : "memory");
}
__device__ __forceinline__ void tma2(uint32_t dst, const CUtensorMap* map, int c0, int c1, uint32_t bar) {
    asm volatile("cp.async.bulk.tensor.2d.shared::cluster.global.tile.mbarrier::complete_tx::bytes [%0], [%1, {%2, %3}], [%4];\n"
                 ::"r"(dst), "l"(map), "r"(c0), "r"(c1), "r"(bar) : "memory");
}
template <bool ACQ>
__device__ __forceinline__ uint32_t flag_wait(const unsigned* p, unsigned target) {
    unsigned v, n = 0;
    do {
        if (ACQ) asm volatile("ld.acquire.gpu.global.u32 %0, [%1];\n" : "=r"(v) : "l"(p) : "memory");
        else asm volatile("ld.relaxed.gpu.global.u32 %0, [%1];\n" : "=r"(v) : "l"(p) : "memory");
        n++;
    } while (v < target);
    return n == 1;
}
__device__ __forceinline__ void ldsm4t(uint32_t (&r)[4], uint32_t addr) {
    asm volatile("ldmatrix.sync.aligned.m8n8.x4.trans.shared.b16 {%0,%1,%2,%3}, [%4];\n"
                 : "=r"(r[0]), "=r"(r[1]), "=r"(r[2]), "=r"(r[3]) : "r"(addr) : "memory");
}
__device__ __forceinline__ void bulk_s2g(void* dst, uint32_t src, uint32_t bytes) {
    asm volatile("cp.async.bulk.global.shared::cta.bulk_group [%0], [%1], %2;\n" ::"l"(dst), "r"(src), "r"(bytes) : "memory");
}
__device__ __forceinline__ void cluster_sync() {
    asm volatile("barrier.cluster.arrive.aligned;\nbarrier.cluster.wait.aligned;\n" ::: "memory");
}
__device__ __forceinline__ void cluster_sync_relaxed() {
    asm volatile("barrier.cluster.arrive.relaxed.aligned;\nbarrier.cluster.wait.aligned;\n" ::: "memory");
}
__device__ __forceinline__ void gdc_wait() { asm volatile("griddepcontrol.wait;\n" ::: "memory"); }
__device__ __forceinline__ void gdc_launch() { asm volatile("griddepcontrol.launch_dependents;\n" ::: "memory"); }
__device__ __forceinline__ uint32_t cluster_rank() {
    uint32_t r;
    asm volatile("mov.u32 %0, %%cluster_ctarank;\n" : "=r"(r));
    return r;
}
__device__ __forceinline__ bool elect_one() {
    uint32_t pred;
    asm volatile("{\n.reg .pred p;\nelect.sync _|p, 0xffffffff;\nselp.u32 %0, 1, 0, p;\n}\n" : "=r"(pred));
    return pred != 0;
}
__device__ __forceinline__ void wg_fence() { asm volatile("wgmma.fence.sync.aligned;\n" ::: "memory"); }
__device__ __forceinline__ void wg_commit() { asm volatile("wgmma.commit_group.sync.aligned;\n" ::: "memory"); }
template <int N> __device__ __forceinline__ void wg_wait() {
    asm volatile("wgmma.wait_group.sync.aligned %0;\n" ::"n"(N) : "memory");
}
template <int R> __device__ __forceinline__ void reg_inc() { asm volatile("setmaxnreg.inc.sync.aligned.u32 %0;\n" ::"n"(R)); }
template <int R> __device__ __forceinline__ void reg_dec() { asm volatile("setmaxnreg.dec.sync.aligned.u32 %0;\n" ::"n"(R)); }
__device__ __forceinline__ void bar_sync(int id, int n) { asm volatile("bar.sync %0, %1;\n" ::"r"(id), "r"(n) : "memory"); }
__device__ __forceinline__ void bar_arrive(int id, int n) { asm volatile("bar.arrive %0, %1;\n" ::"r"(id), "r"(n) : "memory"); }

__device__ __forceinline__ uint64_t make_desc(uint32_t saddr, uint32_t lbo, uint32_t sbo) {
    return (uint64_t)((saddr & 0x3FFFF) >> 4) | ((uint64_t)(lbo >> 4) << 16) | ((uint64_t)(sbo >> 4) << 32);
}

__device__ __forceinline__ void stg128_cs(void* p, uint32_t a, uint32_t b, uint32_t c, uint32_t d) {
    asm volatile("st.global.cs.v4.u32 [%0], {%1,%2,%3,%4};\n" ::"l"(p), "r"(a), "r"(b), "r"(c), "r"(d) : "memory");
}
__device__ __forceinline__ uint32_t pack_bf16(float lo, float hi) {
    uint32_t r;
    asm("cvt.rn.bf16x2.f32 %0, %1, %2;\n" : "=r"(r) : "f"(hi), "f"(lo));
    return r;
}
__device__ __forceinline__ float bf_lo(uint32_t v) { return __uint_as_float(v << 16); }
__device__ __forceinline__ float bf_hi(uint32_t v) { return __uint_as_float(v & 0xffff0000u); }
__device__ __forceinline__ uint32_t bf2_mul(uint32_t a, uint32_t b) {
    uint32_t r;
    asm("mul.rn.bf16x2 %0, %1, %2;\n" : "=r"(r) : "r"(a), "r"(b));
    return r;
}
__device__ __forceinline__ uint32_t bf2_fma(uint32_t a, uint32_t b, uint32_t c) {
    uint32_t r;
    asm("fma.rn.bf16x2 %0, %1, %2, %3;\n" : "=r"(r) : "r"(a), "r"(b), "r"(c));
    return r;
}
__device__ __forceinline__ uint32_t bf2_add(uint32_t a, uint32_t b) {
    uint32_t r;
    asm("add.rn.bf16x2 %0, %1, %2;\n" : "=r"(r) : "r"(a), "r"(b));
    return r;
}
__device__ __forceinline__ uint32_t h2_mul(uint32_t a, uint32_t b) {
    uint32_t r;
    asm("mul.rn.f16x2 %0, %1, %2;\n" : "=r"(r) : "r"(a), "r"(b));
    return r;
}
__device__ __forceinline__ uint32_t h2_fma(uint32_t a, uint32_t b, uint32_t c) {
    uint32_t r;
    asm("fma.rn.f16x2 %0, %1, %2, %3;\n" : "=r"(r) : "r"(a), "r"(b), "r"(c));
    return r;
}
__device__ __forceinline__ uint32_t pack_f16(float lo, float hi) {
    uint32_t r;
    asm("cvt.rn.f16x2.f32 %0, %1, %2;\n" : "=r"(r) : "f"(hi), "f"(lo));
    return r;
}
__device__ __forceinline__ float h_lo(uint32_t v) { return __low2float(*reinterpret_cast<const __half2*>(&v)); }
__device__ __forceinline__ float h_hi(uint32_t v) { return __high2float(*reinterpret_cast<const __half2*>(&v)); }
__device__ __forceinline__ uint32_t bf2_to_h2(uint32_t v) { return (v & 0x7fff7fffu) * 7u + v; }
__device__ __forceinline__ uint32_t prmt(uint32_t a, uint32_t b, uint32_t sel) {
    uint32_t r;
    asm("prmt.b32 %0, %1, %2, %3;\n" : "=r"(r) : "r"(a), "r"(b), "r"(sel));
    return r;
}
__device__ __forceinline__ uint32_t bitsel(uint32_t a, uint32_t b, uint32_t m) {
    uint32_t r;
    asm("lop3.b32 %0, %1, %2, %3, 0xd8;\n" : "=r"(r) : "r"(a), "r"(b), "r"(m));
    return r;
}
constexpr float KAPPA = 0.3292034911525734f;
constexpr uint32_t GELU_C2 = 0x40d940d9u;
constexpr float HSCALE = 1.0f / (2.0f * KAPPA);
__device__ __forceinline__ float w2_scale(uint32_t m) { return __uint_as_float((257u - max(m >> 23, 16u)) << 23); }
__device__ __forceinline__ void sched_break(int zero) {
    asm volatile("{\n.reg .pred p;\nsetp.ne.s32 p, %0, 0;\nSB_LOOP:\n@p nanosleep.u32 1;\n@p bra SB_LOOP;\n}\n" ::"r"(zero));
}

#define ACC8(d, o) "+r"(d[o + 0]), "+r"(d[o + 1]), "+r"(d[o + 2]), "+r"(d[o + 3]), "+r"(d[o + 4]), "+r"(d[o + 5]), "+r"(d[o + 6]), "+r"(d[o + 7])

__device__ __forceinline__ void mma_rs_n128(uint32_t (&d)[32], const uint32_t (&a)[4], uint64_t desc, int scale_d) {
    asm volatile(
        "{\n.reg .pred p;\nsetp.ne.b32 p, %37, 0;\n"
        "wgmma.mma_async.sync.aligned.m64n128k16.f16.f16.f16 "
        "{%0,%1,%2,%3,%4,%5,%6,%7,%8,%9,%10,%11,%12,%13,%14,%15,"
        "%16,%17,%18,%19,%20,%21,%22,%23,%24,%25,%26,%27,%28,%29,%30,%31},"
        "{%32,%33,%34,%35}, %36, p, 1, 1, 0;\n}\n"
        : ACC8(d, 0), ACC8(d, 8), ACC8(d, 16), ACC8(d, 24)
        : "r"(a[0]), "r"(a[1]), "r"(a[2]), "r"(a[3]), "l"(desc), "r"(scale_d));
}

constexpr int P2_NACC = 48;
#define P2_MMA "wgmma.mma_async.sync.aligned.m64n192k16.f16.f16.f16 " \
        "{%0,%1,%2,%3,%4,%5,%6,%7,%8,%9,%10,%11,%12,%13,%14,%15," \
        "%16,%17,%18,%19,%20,%21,%22,%23,%24,%25,%26,%27,%28,%29,%30,%31," \
        "%32,%33,%34,%35,%36,%37,%38,%39,%40,%41,%42,%43,%44,%45,%46,%47},"
#define P2_ACC(d) ACC8(d, 0), ACC8(d, 8), ACC8(d, 16), ACC8(d, 24), ACC8(d, 32), ACC8(d, 40)
#define P2_RS "{%48,%49,%50,%51}, %52, 1, 1, 1, 0;\n"
#define P2_SS "%48, %49, 0, 1, 1, 0, 0;\n"
__device__ __forceinline__ void mma_rs_n192(uint32_t (&d)[P2_NACC], const uint4& a, uint64_t db) {
    asm volatile(P2_MMA P2_RS : P2_ACC(d) : "r"(a.x), "r"(a.y), "r"(a.z), "r"(a.w), "l"(db));
}
__device__ __forceinline__ void mma_ss_n192_init(uint32_t (&d)[P2_NACC], uint64_t da, uint64_t db) {
    asm volatile(P2_MMA P2_SS : P2_ACC(d) : "l"(da), "l"(db));
}

constexpr int P1_SLOT = LN_TILE / 2, P1_NST = 4;
constexpr int P1_X = 32 * C_DIM * 2;
constexpr int P1_OFF_X = P1_SLOT * P1_NST;
constexpr int P1_OFF_BAR = P1_OFF_X + P1_X;
constexpr int P1_OFF_TILE = P1_OFF_BAR + (2 * P1_NST + 2 + 4 + 4) * 8;
constexpr int P1_OFF_RAW = P1_OFF_TILE + 64;
constexpr int P1_OFF_EX = P1_OFF_RAW + 16;
constexpr int P1_SMEM = P1_OFF_EX + 128 * 4;

__device__ __forceinline__ float rsqrt_fast(float x) {
    float r;
    asm("rsqrt.approx.ftz.f32 %0, %1;\n" : "=f"(r) : "f"(x));
    return r;
}
__device__ __forceinline__ float row_sum(const uint32_t (&c)[4]) {
    const uint32_t u = bf2_add(bf2_add(c[0], c[1]), bf2_add(c[2], c[3]));
    float s = bf_lo(u) + bf_hi(u);
#pragma unroll
    for (int o = 1; o < 8; o <<= 1) s += __shfl_xor_sync(0xffffffffu, s, o);
    return s;
}
__device__ __forceinline__ uint32_t pace(uint32_t bar, uint32_t off, uint32_t val, uint32_t after, int zero) {
    asm volatile(
        "{\n.reg .pred p;\n.reg .b32 par;\n"
        "lop3.b32 par, %4, %2, %3, 0xea;\n"
        "mbarrier.test_wait.parity.shared::cta.b64 p, [%1], par;\n"
        "selp.u32 par, 1, 0, p;\n"
        "mbarrier.try_wait.parity.shared::cta.b64 p, [%1], par, 1000;\n"
        "@p or.b32 %0, %0, %2;\n"
        "}\n" : "+r"(val) : "r"(bar), "r"(zero), "r"(off), "r"(after));
    return val;
}
template <bool PACE>
__device__ __forceinline__ void ln_row(uint32_t (&v)[6][4], const uint32_t (&d)[6][4], uint32_t bar, uint32_t off, int zero,
                                       uint32_t bar_read) {
    uint32_t c[4];
#pragma unroll
    for (int i = 0; i < 6; i++)
#pragma unroll
        for (int k = 0; k < 4; k++) c[k] = bf2_fma(v[i][k], d[i][k], i ? c[k] : 0);
    const float inv = 1.0f / C_DIM;
    const float m = row_sum(c) * inv;
    uint32_t nm = pack_bf16(-m, -m);
    const float e = m + bf_lo(nm);
    if (bar_read) mbar_arrive(bar_read + (nm & zero));
    if (PACE) nm = pace(bar, off, nm, nm, zero);
#pragma unroll
    for (int i = 0; i < 6; i++) {
#pragma unroll
        for (int k = 0; k < 4; k++) {
            v[i][k] = bf2_fma(v[i][k], d[i][k], nm);
            c[k] = i ? bf2_fma(v[i][k], v[i][k], c[k]) : bf2_mul(v[i][k], v[i][k]);
        }
    }
    float r = KAPPA * rsqrt_fast(fmaxf(fmaf(-e, e, row_sum(c) * inv), 0.f) + 1e-5f);
    const float er = -e * r * 0x1p-116f;
    if (__any_sync(0xffffffffu, r < 0x1p-8f)) {
        const uint32_t p2 = __float_as_uint(r) & 0x7f800000u;
        r = __uint_as_float((__float_as_uint(r) & 0x007fffffu) | 0x3f800000u);
#pragma unroll
        for (int i = 0; i < 6; i++)
#pragma unroll
            for (int k = 0; k < 4; k++) v[i][k] = bf2_mul(v[i][k], p2 | p2 >> 16);
    }
    r *= 0x1p-116f;
    uint32_t rs = pack_bf16(r, r);
    const uint32_t sh = pack_bf16(er, er);
    if (PACE) rs = pace(bar, off, rs, sh, zero);
#pragma unroll
    for (int i = 0; i < 6; i++)
#pragma unroll
        for (int k = 0; k < 4; k++) v[i][k] = bf2_to_h2(bf2_fma(v[i][k], rs, sh));
}

template <int R>
__device__ __forceinline__ uint32_t gelu2(uint32_t a, uint32_t sc2) {
    uint32_t y, t;
    if (R) asm("{\n.reg .b16 l, h;\n.reg .b32 f;\nmov.b32 {l, h}, %2;\nmov.b32 f, {h, h};\nmul.rn.f16x2 %0, %1, f;\n}\n" : "=r"(y) : "r"(a), "r"(sc2));
    else asm("{\n.reg .b16 l, h;\n.reg .b32 f;\nmov.b32 {l, h}, %2;\nmov.b32 f, {l, l};\nmul.rn.f16x2 %0, %1, f;\n}\n" : "=r"(y) : "r"(a), "r"(sc2));
    asm("tanh.approx.f16x2 %0, %1;\n" : "=r"(t) : "r"(h2_mul(y, h2_fma(y, y, GELU_C2))));
    return h2_fma(a, t, a);
}
constexpr uint32_t SPARE = 0x40074007u;

__device__ __forceinline__ uint32_t p1_parity(uint32_t sbase) {
    uint32_t v;
    asm volatile("ld.shared.u32 %0, [%1];\n" : "=r"(v) : "r"(sbase + P1_OFF_TILE - 4) : "memory");
    return v;
}
template <int WG>
__device__ __forceinline__ void p1_consumer(const uint32_t (&a)[24][4], uint32_t sc2, uint32_t sbase, int w, int lane, int zero) {
    const uint32_t bar_full = sbase + P1_OFF_BAR, bar_empty = bar_full + P1_NST * 8;
    const uint32_t empty_remote = mapa(bar_empty, lane & 1) + (WG == 0 ? (lane & 2) * 4 : 0);
    const uint32_t bar_pace = bar_empty + P1_NST * 8 + 16 + w * 8;
    const int g = lane >> 2, q = lane & 3, cb = (blockIdx.x % GRP_CTAS) * 2 + WG;
    uint32_t acc[32];
    float ssq[2] = {0.f, 0.f};
    TSTAMP(0, 1);

    uint8_t* hp = reinterpret_cast<uint8_t*>(g_h) + (size_t)(blockIdx.x / GRP_CTAS) * (2 * H_TILE) + ((cb * 2 + (w >> 1)) * H_STEP + (w & 1) * 1536) + g * 64 + (q ^ (g >> 1)) * 16;
    const uint64_t desc_base = make_desc(sbase, 16, 1024) | (1ull << 62);
#pragma unroll 1
    for (int i = 0;; i++) {
        const int s0 = (i & 1) * 16, par = (i >> 1) & 1;
        const uint64_t d0 = desc_base + (uint64_t)((i & 1) * (LN_TILE / 16));
        TRACE(WG, i, 0);
        if (WG == 0) mbar_wait(bar_full + s0, par);
        bar_sync(1 + WG, 256);
        TRACE(WG, i, 1);
        uint32_t step, more;
        wg_fence();
#pragma unroll
        for (int k = 0; k < 24; k++) {
            if (WG == 0 && k == 12) mbar_wait(bar_full + s0 + 8, par);
            mma_rs_n128(acc, a[k], d0 + (uint64_t)((k >> 2) * 1024 + (k & 3) * 2), k != 0);
            if (k == 23) bar_arrive(2 - WG, 256);
            if (k % 12 == 11) wg_commit();
        }
        asm volatile("ld.shared.v2.u32 {%0, %1}, [%2];\n" : "=r"(step), "=r"(more) : "r"(sbase + P1_OFF_TILE + (i & 3) * 16) : "memory");
        TRACE(WG, i, 2);
        if (WG == 1) {
            wg_wait<1>();
            if (lane < 2) mbar_arrive_cluster(empty_remote + s0);
        }
        hp += step;
        TRACE(WG, i, 3);
        wg_wait<0>();
        TRACE(WG, i, 4);
        if (lane < (WG == 0 ? 4 : 2)) mbar_arrive_cluster(empty_remote + s0 + WG * 8);
        uint32_t sq[2];
#pragma unroll
        for (int b = 0; b < 2; b++) {
            uint32_t h[4][4];
#pragma unroll
            for (int c = 0; c < 4; c++)
#pragma unroll
                for (int u = 0; u < 4; u++) {
                    const uint32_t v = acc[16 * b + 8 * (c >> 1) + 2 * u + (c & 1)];
                    h[c][u] = (c & 1) ? gelu2<1>(v, sc2) : gelu2<0>(v, sc2);
                    sq[c & 1] = (b | (c >> 1) | u) ? h2_fma(h[c][u], h[c][u], sq[c & 1]) : h2_mul(h[c][u], h[c][u]);
                }
#pragma unroll
            for (int u = 0; u < 4; u++) {
                const uint32_t v = h[0][u], s = v >> 3;
                h[1][u] = bitsel(h[1][u], prmt(s, v, 0x6240), SPARE);
                h[2][u] = bitsel(h[2][u], prmt(v, v, 0xa381), SPARE);
                h[3][u] = bitsel(h[3][u], prmt(s, v, 0xf3d1), SPARE);
            }
#pragma unroll
            for (int c = 1; c < 4; c++) stg128_cs(hp + b * H_HALF + (c - 1) * 512, h[c][0], h[c][1], h[c][2], h[c][3]);
        }
#pragma unroll
        for (int r = 0; r < 2; r++) ssq[r] += h_lo(sq[r]) + h_hi(sq[r]);
        if (lane == 0) mbar_arrive(bar_pace);
        if (!more) break;
    }
    TSTAMP(0, 21);
    if (WG == 0) bar_sync(1, 256);
#pragma unroll
    for (int r = 0; r < 2; r++) {
        ssq[r] += __shfl_xor_sync(0xffffffffu, ssq[r], 1);
        ssq[r] += __shfl_xor_sync(0xffffffffu, ssq[r], 2);
        float f;
        asm volatile("ld.shared.f32 %0, [%1];\n" : "=f"(f) : "r"(sbase + P1_OFF_EX + (WG * 64 + w * 16 + r * 8 + g) * 4) : "memory");
        if (q == 0) atomicAdd(&g_sums[p1_parity(sbase)][cb * 64 + w * 16 + r * 8 + g], ssq[r] * f * f);
    }
}

__global__ void __cluster_dims__(2, 1, 1) __launch_bounds__(512, 1)
pass1_kernel(const __grid_constant__ CUtensorMap wmap, const __nv_bfloat16* __restrict__ x, const __nv_bfloat16* __restrict__ dw,
             const __nv_bfloat16* __restrict__ w2, const __nv_bfloat16* __restrict__ grn_b, int zero) {
    extern __shared__ __align__(1024) uint8_t smem[];
    const uint32_t sbase = smem_u32(smem);
    const uint32_t bar_full = sbase + P1_OFF_BAR, bar_empty = bar_full + P1_NST * 8, bar_w = bar_empty + P1_NST * 8;
    const int tid = threadIdx.x;
    const int warp = __shfl_sync(0xffffffffu, tid >> 5, 0), lane = tid & 31;
    const uint32_t rank = cluster_rank();
    const int cig = blockIdx.x % GRP_CTAS;
    uint8_t* const ring = reinterpret_cast<uint8_t*>(g_ln);

    TSTAMP(0, 0);
    TRACEW(110 + warp, 0);
    const uint32_t bar_pace = bar_w + 16, bar_xfull = bar_pace + 32, bar_xempty = bar_xfull + 8, bar_done = bar_xfull + 16;
    const uint32_t bar_raw = sbase + P1_OFF_RAW;
    const int ln0 = blockIdx.x >> 2, first = blockIdx.x / GRP_CTAS;
    const uint8_t* xsrc = reinterpret_cast<const uint8_t*>(x) + (size_t)(NGRP * 4 + blockIdx.x) * P1_X;

    if (warp >= 12) {
        reg_dec<40>();
        asm volatile("barrier.cluster.arrive.relaxed.aligned;\n" ::: "memory");
        asm volatile("barrier.cluster.wait.aligned;\n" ::: "memory");
        if (warp == 12) {
            int prev = first - NGRP, t = first, next = t + NGRP;
            const uint32_t rbase = mapa(sbase, lane & 1);
#pragma unroll 1
            for (int i = 1; t < NT_RING; i++) {
                const int s0 = (i & 1) * 2, par = ((i + 1) >> 1 & 1) ^ 1;
                const int round = t / LN_RING, slot = t - round * LN_RING;
                const uint8_t* src = ring + slot * LN_TILE + rank * (P1_SLOT / 2);
                int draw = 0;
                if (rank == 0 && lane == 0) draw = atomicAdd(&g_flag[LN_RING + (cig >> 2)][(cig >> 1) & 1][0], 1u);
                flag_wait<true>(&g_flag[slot][0][0], 4 * round + 4);
                TRACEW(i, 2);
                asm volatile("fence.proxy.async.global;\n" ::: "memory");
                draw = 2 * NGRP + __shfl_sync(0xffffffffu, draw, 0);
#pragma unroll
                for (int h = 0; h < 2; h++) {
                    mbar_wait(bar_empty + (s0 + h) * 8, par);
                    TRACEW(i, 4 + h);
                    if (elect_one()) {
                        mbar_expect_tx(bar_full + (s0 + h) * 8, P1_SLOT + 16 - 16 * h);
                        bulk_g2s_mc(sbase + (s0 + h) * P1_SLOT + rank * (P1_SLOT / 2), src + h * P1_SLOT, P1_SLOT / 2, bar_full + (s0 + h) * 8, (uint16_t)3);
                    }
                    __syncwarp();
                    if (h == 0 && rank == 0 && lane < 2)
                        asm volatile("st.async.shared::cluster.mbarrier::complete_tx::bytes.v4.u32 [%0], {%1, %2, %3, %3}, [%4];\n"
                                     ::"r"(rbase + P1_OFF_TILE + (i & 3) * 16), "r"((t - prev) * (2 * H_TILE)), "r"((int)(next < NT_RING)), "r"(draw),
                                       "r"(rbase + P1_OFF_BAR + s0 * 8) : "memory");
                }
                prev = t;
                t = next;
                next = draw;
                if (rank != 0) {
                    mbar_wait(bar_full + (s0 ^ 2) * 8, ((i - 1) >> 1) & 1);
                    asm volatile("ld.shared.u32 %0, [%1];\n" : "=r"(t) : "r"(sbase + P1_OFF_TILE + ((i - 1) & 3) * 16 + 8) : "memory");
                }
            }
        } else if (warp == 13) {
            int ph = 0;
            unsigned target = 0;
#pragma unroll 1
            for (int i = ln0 + LN_STEP; i < NT_RING; i += LN_STEP, ph ^= 1) {
                target += ph * (GRP_CTAS / 2);
                xsrc += (size_t)NUM_CTAS * P1_X;
                mbar_wait(bar_xempty, ph);
                if (elect_one()) {
                    mbar_expect_tx(bar_xfull, P1_X);
                    bulk_g2s(sbase + P1_OFF_X, xsrc, P1_X, bar_xfull);
                }
                __syncwarp();
                const uint32_t off = flag_wait<false>(&g_flag[ln0 + (ph ^ 1) * LN_STEP][1][0], target);
                mbar_wait(bar_done, ph);
                if (elect_one()) {
                    asm volatile("st.shared.u32 [%0], %1;\n" ::"r"(bar_done + 8), "r"(off) : "memory");
                    mbar_arrive(bar_xfull);
                }
                __syncwarp();
            }
        } else if (warp == 15) {
            if (rank == 1 && lane < 2) mbar_arrive(bar_empty + (2 + lane) * 8);
            const uint32_t par = g_epoch & 1;
            asm volatile("st.shared.u32 [%0], %1;\n" ::"r"(sbase + P1_OFF_TILE - 4), "r"(par) : "memory");
            if (blockIdx.x < 16) reinterpret_cast<float4*>(g_sums[par ^ 1])[blockIdx.x * 32 + lane] = make_float4(0.f, 0.f, 0.f, 0.f);
            {
                bar_sync(4, 288);
                mbar_wait(bar_raw + 8, 0);
                const uint32_t o = lane * 16384 + rank * 8192, peer = mapa(sbase, rank ^ 1);
                if (lane < 6)
                    asm volatile("cp.async.bulk.shared::cluster.shared::cta.mbarrier::complete_tx::bytes [%0], [%1], 8192, [%2];\n"
                                 ::"r"(peer + o), "r"(sbase + o), "r"(peer + P1_OFF_BAR + (lane >= 3 ? 8 : 0)) : "memory");
                __syncwarp();
            }
            int t = first, next = t + NGRP;
            if (rank == 1) {
                mbar_wait(bar_full, 0);
                mbar_wait(bar_full + 8, 0);
                if (lane < 2) mbar_arrive(bar_empty + lane * 8);
            }
#pragma unroll 1
            for (int i = 1; rank == 1 && t < NT_RING; i++) {
                const int s0 = (i & 1) * 16;
                mbar_wait(bar_full + s0, (i >> 1) & 1);
                mbar_wait(bar_full + s0 + 8, (i >> 1) & 1);
                if (lane == 0) asm volatile("red.relaxed.gpu.global.add.u32 [%0], 1;\n" ::"l"(&g_flag[t % LN_RING][1][0]) : "memory");
                t = next;
                asm volatile("ld.shared.u32 %0, [%1];\n" : "=r"(next) : "r"(sbase + P1_OFF_TILE + (i & 3) * 16 + 8) : "memory");
                if (lane < 2) mbar_arrive(bar_empty + s0 + lane * 8);
                TRACEW(i, 3);
            }
            if (rank == 0) {
                mbar_wait(bar_full, 0);
                mbar_wait(bar_full, 1);
                float* sums = g_sums[par] + HID;
                unsigned* flag = reinterpret_cast<unsigned*>(sums + C_DIM);
                float gs = 0.f;
#pragma unroll 1
                for (int pass = 0; pass < 2; pass++) {
                    float mx = 0.f;
#pragma unroll 1
                    for (int it = first; it < 48; it += NGRP) {
                        const int np = (it % 12) * 32 + lane, kb = cig * 2 + it / 12;
                        const __nv_bfloat16* wc = w2 + (size_t)kb * 64 * C_DIM + perm32(np);
                        const uint32_t sc = mapa(sbase + P1_OFF_EX + (kb & 1) * 256, it / 24);
                        float bsum = 0.f;
#pragma unroll 1
                        for (int c = 0; c < 8; c++) {
                            float f[8];
#pragma unroll
                            for (int e = 0; e < 8; e++) f[e] = __bfloat162float(wc[(c * 8 + e) * C_DIM]);
#pragma unroll
                            for (int e = 0; e < 8; e++) {
                                float t;
                                asm volatile("ld.shared::cluster.f32 %0, [%1];\n" : "=f"(t) : "r"(sc + (c * 8 + e) * 4) : "memory");
                                bsum = fmaf(__bfloat162float(grn_b[kb * 64 + c * 8 + e]), f[e], bsum);
                                f[e] *= t;
                                mx = fmaxf(mx, fabsf(f[e]));
                            }
                            if (pass)
                                g_w2img[0][(((kb * 4 + (c >> 1)) * 48 + (np >> 3)) * 2 + (c & 1)) * 8 + (np & 7)] = make_uint4(
                                    pack_f16(f[0] * gs, f[1] * gs), pack_f16(f[2] * gs, f[3] * gs), pack_f16(f[4] * gs, f[5] * gs), pack_f16(f[6] * gs, f[7] * gs));
                        }
                        if (pass) atomicAdd(&sums[np], bsum);
                    }
                    if (!pass) {
                        const uint32_t m = __reduce_max_sync(0xffffffffu, __float_as_uint(mx));
                        if (lane == 0) {
                            atomicMax(flag, m);
                            asm volatile("red.release.gpu.global.add.u32 [%0], 1;\n" ::"l"(flag + 32) : "memory");
                        }
                        flag_wait<true>(flag + 32, NUM_CTAS / 2);
                        gs = w2_scale(__ldcg(flag));
                    }
                }
            }
        } else if (warp == 14) {
            int ph = 0;
#pragma unroll 1
            for (int i = ln0; i < NT_RING; i += LN_STEP, ph ^= 1) {
                mbar_wait(bar_done, ph);
                TRACEW(i / LN_STEP, 0);
                asm volatile("fence.proxy.async.global;\n" ::: "memory");
                if (elect_one()) asm volatile("red.release.gpu.global.add.u32 [%0], 1;\n" ::"l"(&g_flag[ln0 + ph * LN_STEP][0][0]) : "memory");
                __syncwarp();
                TRACEW(i / LN_STEP, 1);
            }
        }
        __syncwarp();
        cluster_sync();
    } else if (warp >= 8) {
        reg_dec<88>();
        asm volatile("barrier.cluster.arrive.relaxed.aligned;\n" ::: "memory");
        {
            const int l8 = lane & 7, row = (warp - 8) * 4 + (lane >> 3), px = (blockIdx.x & 3) * 32 + row;
            uint32_t d[6][4];
#pragma unroll
            for (int j = 0; j < 6; j++) {
                const uint4 t = reinterpret_cast<const uint4*>(dw)[j * 8 + l8];
                d[j][0] = t.x; d[j][1] = t.y; d[j][2] = t.z; d[j][3] = t.w;
            }
            const int n = (px & 64) + perm32(2 * row + ((px >> 5) & 1));
            uint8_t* const dst0 = ring + ln0 * LN_TILE + n * 128 + ((l8 ^ (n & 7)) << 4);
            const uint32_t src = sbase + P1_OFF_X + ((warp - 8) * 8 + (lane >> 3)) * (C_DIM * 2) + l8 * 16;
            int ph = 0;
            asm volatile("barrier.cluster.wait.aligned;\n" ::: "memory");
#pragma unroll 1
            for (int i = ln0; i < NT_RING; i += LN_STEP, ph ^= 1) {
                TRACE(2, i / LN_STEP, 0);
                mbar_wait(bar_xfull, ph);
                uint32_t off;
                asm volatile("ld.shared.u32 %0, [%1];\n" : "=r"(off) : "r"(bar_done + 8) : "memory");
                TRACE(2, i / LN_STEP, 1);
#pragma unroll 1
                for (int ps = 0; ps < 2; ps++) {
                    uint32_t v[6][4];
#pragma unroll
                    for (int j = 0; j < 6; j++)
                        asm volatile("ld.shared.v4.u32 {%0,%1,%2,%3}, [%4];\n"
                                     : "=r"(v[j][0]), "=r"(v[j][1]), "=r"(v[j][2]), "=r"(v[j][3]) : "r"(src + ps * (4 * C_DIM * 2) + j * 128) : "memory");
                    ln_row<true>(v, d, bar_pace + (warp - 8) * 8, off, zero, ps == 1 && lane == 0 ? bar_xempty : 0);
                    uint8_t* dst = dst0 + ph * (LN_STEP * LN_TILE) + ps * 4096;
#pragma unroll
                    for (int j = 0; j < 6; j++) *reinterpret_cast<uint4*>(dst + j * 16384) = make_uint4(v[j][0], v[j][1], v[j][2], v[j][3]);
                    TRACE(2, i / LN_STEP, 3 + ps);
                }
                asm volatile("fence.proxy.async.global;\nfence.acq_rel.cta;\n" ::: "memory");
                __syncwarp();
                if (lane == 0) mbar_arrive(bar_done);
                TRACE(2, i / LN_STEP, 5);
                TRACE(2, i / LN_STEP, 2);
            }
        }
        __syncwarp();
        cluster_sync();
    } else {
        uint32_t d[6][4];
#pragma unroll
        for (int j = 0; j < 6; j++)
            asm volatile("ld.global.nc.v4.u32 {%0,%1,%2,%3}, [%4];\n" : "=r"(d[j][0]), "=r"(d[j][1]), "=r"(d[j][2]), "=r"(d[j][3])
                         : "l"(reinterpret_cast<const uint4*>(dw) + j * 8 + (lane & 7)) : "memory");
        if (tid == 0) {
            mbar_init(bar_raw, 1);
            mbar_init(bar_raw + 8, 8);
            asm volatile("fence.mbarrier_init.release.cluster;\n" ::: "memory");
            mbar_expect_tx(bar_raw, P1_SLOT);
            for (int i = 0; i < 6; i++)
                bulk_g2s(sbase + i * 16384 + (rank ^ 1) * 8192, x + (size_t)(first * 128 + rank * 64) * C_DIM + i * 4096, 8192, bar_raw);
        }
        if (tid == 32) {
            mbar_init(bar_xfull, 2);
            mbar_init(bar_xempty, 4);
            mbar_init(bar_done, 4);
            asm volatile("fence.mbarrier_init.release.cluster;\n" ::: "memory");
            mbar_expect_tx(bar_xfull, P1_X);
            bulk_g2s(sbase + P1_OFF_X, xsrc, P1_X, bar_xfull);
            asm volatile("st.shared.u32 [%0], 1;\n" ::"r"(bar_done + 8) : "memory");
            mbar_arrive(bar_xfull);
        }
        if (tid == 64) {
            asm volatile("st.shared.v4.u32 [%0], {0, 1, %1, %1};\n" ::"r"(sbase + P1_OFF_TILE), "r"(first + NGRP) : "memory");
            for (int i = 0; i < P1_NST; i++) {
                mbar_init(bar_full + i * 8, 1);
                mbar_init(bar_empty + i * 8, 16 + rank);
                mbar_init(bar_pace + i * 8, 1);
                if (i < 2) mbar_expect_tx(bar_full + i * 8, P1_SLOT / 2);
            }
            asm volatile("fence.mbarrier_init.release.cluster;\n" ::: "memory");
            if (blockIdx.x < 64) (&g_half[0][0])[blockIdx.x] = 0;
            else if (blockIdx.x < 66) g_prog[blockIdx.x - 64][0] = 0;
        }
        if (tid == 96) {
            for (int i = 0; i < 2; i++) mbar_init(bar_w + i * 8, 1);
            asm volatile("fence.mbarrier_init.release.cluster;\n" ::: "memory");
        }
        __syncwarp();
        asm volatile("barrier.cluster.arrive.relaxed.aligned;\n" ::: "memory");
        if (tid == 96)
            for (int i = 0; i < 2; i++) {
                mbar_expect_tx(bar_w + i * 8, P1_SLOT);
                tma2(sbase + (2 + i) * P1_SLOT, &wmap, cig * 128 + i * 64, 0, bar_w + i * 8);
                tma2(sbase + (2 + i) * P1_SLOT + P1_SLOT / 2, &wmap, cig * 128 + i * 64, 192, bar_w + i * 8);
            }
        __syncwarp();
        reg_inc<192>();
        TRACEW(110 + warp, 1);
        const int wg = warp >> 2, w = warp & 3;
        uint32_t a[24][4];
        {
            const int n = warp * 8 + (lane >> 3), px = (n & 1) * 32 + (n >> 5) * 4 + ((n >> 1) & 1) * 8 + ((n >> 3) & 3);
            if (wg == 1) bar_arrive(1, 256);
            gdc_launch();
            asm volatile("barrier.cluster.wait.aligned;\n" ::: "memory");
#pragma unroll 1
            for (int ps = -1; ps < 2; ps++) {
                if (ps == 0) mbar_wait(bar_raw, 0);
                TRACEW(110 + warp, 2 + (ps == 0));
                uint32_t v[6][4];
#pragma unroll
                for (int j = 0; j < 6; j++) {
                    const uint32_t o = (px + (ps & 1) * 16) * (C_DIM * 2) + j * 128;
                    asm volatile("ld.shared.v4.u32 {%0,%1,%2,%3}, [%4];\n" : "=r"(v[j][0]), "=r"(v[j][1]), "=r"(v[j][2]), "=r"(v[j][3])
                                 : "r"(sbase + (rank ^ 1) * 8192 + (lane & 7) * 16 + o + (o & ~8191u)) : "memory");
                }
                ln_row<false>(v, d, 0, 0, zero, 0);
                const uint32_t p = sbase + (rank * 64 + n + (ps & 1) * 4) * 128 + (((lane ^ n ^ (ps & 1) * 4) & 7) << 4);
#pragma unroll
                for (int j = 0; j < 6; j++)
                    asm volatile("st.shared.v4.u32 [%4], {%0,%1,%2,%3};\n"
                                 ::"r"(v[j][0]), "r"(v[j][1]), "r"(v[j][2]), "r"(v[j][3]), "r"(p + j * 16384) : "memory");
            }
            asm volatile("fence.proxy.async.shared::cta;\n" ::: "memory");
            __syncwarp();
            if (lane == 0) mbar_arrive_cluster(mapa(bar_raw + 8, rank ^ 1));
            bar_arrive(4, 288);
            TRACEW(110 + warp, 4);
            const uint32_t src = sbase + (2 + wg) * P1_SLOT + ((lane >> 4) * 8 + (lane & 7)) * 128 + (((2 * w + ((lane >> 3) & 1)) ^ (lane & 7)) << 4);
            mbar_wait(bar_w + wg * 8, 0);
            TRACEW(110 + warp, 5);
            uint32_t dep = 0;
#pragma unroll
            for (int k = 0; k < 24; k++) {
                ldsm4t(a[k], src + k * 2048);
                dep |= a[k][0];
            }
            __syncwarp();
            if (lane < 4) mbar_arrive_cluster(mapa(bar_empty, lane & 1) + (2 + (lane >> 1)) * 8 + (dep & zero));
        }
        uint32_t ex[2];
#pragma unroll
        for (int r = 0; r < 2; r++) {
            float t = 0.f;
#pragma unroll
            for (int j = 0; j < 6; j++) {
                uint32_t c = bf2_mul(a[4 * j][r], a[4 * j][r]);
#pragma unroll
                for (int k = 1; k < 8; k++) c = bf2_fma(a[4 * j + k / 2][r + (k & 1) * 2], a[4 * j + k / 2][r + (k & 1) * 2], c);
                t += bf_lo(c) + bf_hi(c);
            }
            t += __shfl_xor_sync(0xffffffffu, t, 1);
            t += __shfl_xor_sync(0xffffffffu, t, 2);
            ex[r] = min(max(__float_as_uint(13.9f * __fsqrt_rn(t)) >> 23, 72u), 198u);
            if ((lane & 3) == 0)
                asm volatile("st.shared.u32 [%0], %1;\n" ::"r"(sbase + P1_OFF_EX + (wg * 64 + w * 16 + r * 8 + (lane >> 2)) * 4), "r"(ex[r] << 23) : "memory");
            const uint32_t f = (258u - ex[r]) * 0x00800080u;
#pragma unroll
            for (int k = 0; k < 48; k++) a[k >> 1][r + (k & 1) * 2] = bf2_to_h2(bf2_mul(bf2_mul(a[k >> 1][r + (k & 1) * 2], f), 0x07800780u));
        }
        const uint32_t sc2 = pack_f16(__uint_as_float(min(ex[0], 142u) << 23), __uint_as_float(min(ex[1], 142u) << 23));
        bar_sync(5, 256);
        if (warp < 4) p1_consumer<0>(a, sc2, sbase, w, lane, zero);
        else p1_consumer<1>(a, sc2, sbase, w, lane, zero);
        cluster_sync();
        TSTAMP(0, 30);
    }
}

constexpr int P2_B = 24576, P2_NB = 4;
constexpr int P2_A = 3072, P2_NA = 8;
constexpr int P2_XROW = C_DIM * 2;
constexpr int P2_OFF_A = P2_B * P2_NB;
constexpr int P2_OFF_X = P2_OFF_A + 3 * P2_NA * P2_A;
constexpr int P2_XHALF = 32 * P2_XROW + 64;
constexpr int P2_OFF_BIAS = P2_OFF_X + 64 * P2_XROW + 128;
constexpr int P2_OFF_ONES = P2_OFF_BIAS + 48 * 128;
constexpr int P2_OFF_BAR = P2_OFF_ONES + 256;
constexpr int P2_SMEM = P2_OFF_BAR + (2 * P2_NB + 6 * P2_NA + 7) * 8;
constexpr int P2_LAG = 16;
constexpr int P2_NCL = NUM_CTAS / 2, P2_ITEMS = NT128 / P2_NCL, P2_SHARED = NT128 - P2_ITEMS * P2_NCL;
constexpr int P2_NPOS = P2_LAG * (P2_ITEMS - 1) + 48;
constexpr int P2_RAW = 24;
constexpr int P2_XC = 8 * P2_XROW;
#define P2_DELTA 7
#define P2_T0 4
#define P2_SLACK 0
__device__ __forceinline__ int p2_start(int n) { return n < 0 ? 0 : n == P2_ITEMS ? P2_NPOS - 24 : P2_LAG * n; }
__device__ __forceinline__ int p2_tile(int cl, int n) {
    return n == 0 ? NT128 - 1 - cl : n < 0 || n == P2_ITEMS ? NT128 - 1 - P2_NCL - (cl >> 1) : cl + P2_NCL * (n - 1);
}

#define P2_EG 2
__device__ __forceinline__ uint32_t p2_pair(const uint32_t (&acc)[P2_NACC], int i) {
    return pack_bf16(h_lo(acc[i / 2]), h_hi(acc[i / 2]));
}
__device__ __forceinline__ void p2_epilogue(const uint32_t (&acc0)[P2_NACC], const uint32_t (&acc1)[P2_NACC], uint32_t up, uint32_t sx, int zero) {
    uint32_t v[2][P2_EG][4];
    auto load = [&](int c, uint32_t a) {
#pragma unroll
        for (int j = 0; j < P2_EG; j++) {
            const int u = c * P2_EG + j;
            asm volatile("ld.shared.v4.u32 {%0,%1,%2,%3}, [%4];\n" : "=r"(v[c & 1][j][0]), "=r"(v[c & 1][j][1]), "=r"(v[c & 1][j][2]), "=r"(v[c & 1][j][3])
                         : "r"(a + (u >> 1) * 64 + (u & 1) * 4 * P2_XROW) : "memory");
        }
    };
    load(0, sx);
#pragma unroll
    for (int c = 0; c < 24 / P2_EG; c++) {
        if (c + 1 < 24 / P2_EG) load(c + 1, sx + (v[c & 1][P2_EG - 1][0] & zero));
#pragma unroll
        for (int j = 0; j < P2_EG; j++) {
            const int u = c * P2_EG + j, i = 16 * ((u >> 1) % 6) + 2 * (u & 1);
            const uint32_t (&acc)[P2_NACC] = u < 12 ? acc0 : acc1;
            uint32_t (&w)[4] = v[c & 1][j];
#pragma unroll
            for (int e = 0; e < 4; e++) w[e] = bf2_fma(p2_pair(acc, i + 4 * e), up, w[e]);
            asm volatile("st.shared.v4.u32 [%4], {%0,%1,%2,%3};\n" ::"r"(w[0]), "r"(w[1]), "r"(w[2]), "r"(w[3]),
                         "r"(sx + (u >> 1) * 64 + (u & 1) * 4 * P2_XROW) : "memory");
        }
    }
}

__device__ __forceinline__ void p2_unpack(uint32_t (&u)[4], uint32_t o1, uint32_t o2, uint32_t o3) {
    u[2] = bitsel(o1, 0x00040004u, SPARE);
    u[1] = bitsel(o2, 0x00040004u, SPARE);
    u[3] = bitsel(o3, 0x00040004u, SPARE);
    const uint32_t t = bitsel(prmt(o1, o2, 0x6341), prmt(o1, o3, 0x6240) << 3, 0x38383838u);
    u[0] = bitsel(bitsel(t, prmt(o2, o3, 0x7351) << 1, 0x80808080u), 0x00040004u, SPARE);
}
__device__ __forceinline__ void p2_epilogue_add(const uint32_t (&acc)[P2_NACC], uint32_t upf, uint8_t* o) {
    auto up = [&](int i) { return bf2_mul(p2_pair(acc, i), upf); };
#pragma unroll
    for (int t = 0; t < 6; t++)
#pragma unroll
        for (int r = 0; r < 2; r++)
            asm volatile("red.global.add.noftz.v4.bf16x2 [%0], {%1,%2,%3,%4};\n" ::"l"(o + t * 64 + r * 4 * P2_XROW),
                         "r"(up(16 * t + 2 * r)), "r"(up(16 * t + 2 * r + 4)), "r"(up(16 * t + 2 * r + 8)), "r"(up(16 * t + 2 * r + 12)) : "memory");
}

__global__ void __cluster_dims__(2, 1, 1) __launch_bounds__(512, 1)
pass2_kernel(const __nv_bfloat16* __restrict__ x, const __nv_bfloat16* __restrict__ grn_g, __nv_bfloat16* __restrict__ out, int zero) {
    extern __shared__ __align__(1024) uint8_t smem[];
    const uint32_t sbase = smem_u32(smem);
    const uint32_t bar_bfull = sbase + P2_OFF_BAR, bar_bempty = bar_bfull + P2_NB * 8;
    const uint32_t bar_afull = bar_bempty + P2_NB * 8, bar_aempty = bar_afull + 3 * P2_NA * 8;
    const uint32_t bar_xfull = bar_aempty + 3 * P2_NA * 8, bar_oready = bar_xfull + 24, s_pos = bar_oready + 24;
    int tid;
    asm volatile("mov.u32 %0, %%tid.x;\n" : "=r"(tid));
    const int warp = __shfl_sync(0xffffffffu, tid >> 5, 0), lane = tid & 31;
    const uint32_t rank = cluster_rank();
    const int cl = blockIdx.x >> 1, pair = cl >> 1;
    const int head = pair < P2_SHARED && !(cl & 1), tail = pair < P2_SHARED && (cl & 1);
    const int k0 = (pair + 4 * (cl & 1)) % 6 * 8;
    auto wait_pos = [&](int target) {
        int v;
        while (true) {
            asm volatile("ld.volatile.shared.u32 %0, [%1];\n" : "=r"(v) : "r"(s_pos) : "memory");
            if (v >= target) break;
            SAFE_BREAK;
            __nanosleep(100);
        }
    };

    TSTAMP(1, 0);
    if (tid == 384) {
        for (int i = 0; i < P2_NB; i++) {
            mbar_init(bar_bfull + i * 8, 1);
            mbar_init(bar_bempty + i * 8, 24);
        }
        for (int i = 0; i < 3 * P2_NA; i++) {
            mbar_init(bar_afull + i * 8, 1);
            mbar_init(bar_aempty + i * 8, 4);
        }
        for (int i = 0; i < 3; i++) {
            mbar_init(bar_xfull + i * 8, 2);
            mbar_init(bar_oready + i * 8, 4);
        }
        asm volatile("st.shared.u32 [%0], 0;\n" ::"r"(s_pos) : "memory");
        asm volatile("fence.mbarrier_init.release.cluster;\n" ::: "memory");
    }
    __syncthreads();
    cluster_sync_relaxed();

    if (warp >= 12) {
        reg_dec<24>();
        if (warp == 12) {
            const uint8_t* wsrc = reinterpret_cast<const uint8_t*>(g_w2img) + rank * (P2_B / 2);
            int kb = k0;
            gdc_wait();
#pragma unroll 1
            for (int p = 0; p < P2_NPOS; p++) {
                const int st = p & 3;
                if (p == P2_RAW) {
                    flag_wait<true>(&g_prog[1][0], NUM_CTAS);
                    asm volatile("fence.proxy.async.global;\n" ::: "memory");
                    wsrc += sizeof(g_w2img[0]);
                }
                const int idle = (p < P2_LAG || p >= P2_NPOS - P2_LAG) + (p < 2 * P2_LAG ? !head || p >= 24 : p >= P2_NPOS - 2 * P2_LAG && (!tail || p < P2_NPOS - 24));
                mbar_wait(bar_bempty + st * 8, (~p >> 2) & 1);
                if (elect_one()) {
                    mbar_expect_tx(bar_bfull + st * 8, P2_B);
                    bulk_g2s_mc(sbase + st * P2_B + rank * (P2_B / 2), wsrc + kb * P2_B, P2_B / 2, bar_bfull + st * 8, (uint16_t)3);
                    asm volatile("st.volatile.shared.u32 [%0], %1;\n" ::"r"(s_pos), "r"(p) : "memory");
                    if (rank == 0) asm volatile("red.relaxed.gpu.global.add.u32 [%0], 1;\n" ::"l"(&g_prog[0][0]) : "memory");
                    if (idle) asm volatile("mbarrier.arrive.shared::cta.b64 _, [%0], %1;\n" ::"r"(bar_bempty + st * 8), "r"(8 * idle) : "memory");
                }
                __syncwarp();
                if (++kb == 48) kb = 0;
            }
            mbar_wait(bar_bempty, 1);
            if (lane == 0) mbar_arrive(bar_bfull);
        } else if (warp == 13) {
            const int w = lane < 3 ? lane : 0;
            const uint32_t dst0 = sbase + P2_OFF_A + w * P2_NA * P2_A;
            const uint32_t bf = bar_afull + w * P2_NA * 8, be = bar_aempty + w * P2_NA * 8;
            int n = (w == 2 && head ? -1 : w) - 3, left = 0, u = 0, c = 0;
            const uint8_t* src = nullptr;
            bool act = lane < 3;
            gdc_wait();
            while (__any_sync(0xffffffffu, act)) {
                if (left == 0) {
                    n += 3;
                    left = n >= P2_ITEMS + tail ? -1 : n < 0 || n == P2_ITEMS ? 24 : 48;
                    u = (k0 + p2_start(n)) % 48;
                    src = reinterpret_cast<const uint8_t*>(g_h) + (size_t)p2_tile(cl, n) * (2 * H_TILE) + rank * H_HALF + u * H_STEP;
                }
                const bool ok = act && mbar_test(be + ((c - 1) & 7) * 8, (~c >> 3) & 1);
                if (ok) {
                    const int st = c & 7;
                    if (left > 0) {
                        mbar_expect_tx(bf + st * 8, P2_A);
                        bulk_g2s(dst0 + st * P2_A, src, P2_A, bf + st * 8);
                    } else {
                        mbar_arrive(bf + st * 8);
                        act = false;
                    }
                    src += H_STEP;
                    if (++u == 48) { u = 0; src -= 48 * H_STEP; }
                    c++;
                    left--;
                }
                SAFE_BREAK;
                if (!__any_sync(0xffffffffu, ok)) __nanosleep(100);
            }
        } else if (warp == 14) {
            const uint32_t sx = sbase + P2_OFF_X;
            size_t o = 0;
            int w = head ? 2 : 0, wp = 0;
            uint32_t par = 0;
#pragma unroll 1
            for (int n = -head; n <= P2_ITEMS; n++) {
                const size_t on = (size_t)(2 * p2_tile(cl, n) + rank) * (64 * C_DIM * 2);
                const uint32_t xf = bar_xfull + w * 8;
                const bool st = n + head > 0, ld = n < P2_ITEMS;
                if (st) {
                    mbar_wait(bar_oready + wp * 8, (par >> wp) & 1);
                    par ^= 1u << wp;
                }
                if (lane == 0) {
                    if (n == 1 && head) {
                        asm volatile("cp.async.bulk.wait_group 0;\nfence.proxy.async.global;\n" ::: "memory");
                        asm volatile("st.release.gpu.global.u32 [%0], 1;\n" ::"l"(&g_half[pair][rank]) : "memory");
                    }
                    if (ld) mbar_expect_tx(xf, 64 * C_DIM * 2);
                    int t = st && ld ? 4 * (P2_LAG * n + 32 + P2_T0) : -256;
#pragma unroll 1
                    for (int c = 0; st && c < 64 * P2_XROW; c += P2_XC, t += 3) {
                        wait_pos(min(t >> 2, P2_NPOS - 1));
                        bulk_s2g(reinterpret_cast<uint8_t*>(out) + o + c, sx + c + (c >= 32 * P2_XROW ? 64 : 0), P2_XC);
                    }
                    asm volatile("cp.async.bulk.commit_group;\ncp.async.bulk.wait_group.read 0;\n" ::: "memory");
#pragma unroll 1
                    for (int c = 0; ld && c < 64 * P2_XROW; c += P2_XC, t += 3) {
                        wait_pos(min(t >> 2, P2_NPOS - 1));
                        bulk_g2s(sx + c + (c >= 32 * P2_XROW ? 64 : 0), reinterpret_cast<const uint8_t*>(x) + on + c, P2_XC, xf);
                    }
                    if (rank == 0 && n > 0 && n < P2_ITEMS - 1)
                        flag_wait<false>(&g_prog[0][0], P2_NCL * (P2_LAG * n + 48 + P2_SLACK) + (tail ? P2_SHARED - P2_NCL : P2_SHARED) * P2_DELTA);
                    if (ld) mbar_arrive(xf);
                }
                __syncwarp();
                o = on;
                wp = w;
                w = w == 2 ? 0 : w + 1;
            }
            asm volatile("cp.async.bulk.wait_group 0;\n" ::: "memory");
        }
        __syncwarp();
        cluster_sync();
    } else {
        reg_inc<160>();
        const int wg = warp >> 2, w = warp & 3, g = lane >> 2, q = lane & 3;
        const uint32_t sx = sbase + P2_OFF_X + (g & 1) * P2_XHALF + (w * 8 + (g >> 1)) * P2_XROW + q * 16;
        const uint32_t af = bar_afull + wg * P2_NA * 8;
        const uint32_t s_a = sbase + P2_OFF_A + wg * P2_NA * P2_A + (lane >> 3) * 512 + (lane & 7) * 64 + ((w ^ ((lane & 7) >> 1)) << 4);
        uint32_t acc0[P2_NACC], acc1[P2_NACC], up;
        uint4 a[2][2];

        {
            float* s_red = reinterpret_cast<float*>(smem + P2_OFF_ONES);
            float gx[4], part = 0.f;
            __nv_bfloat16 gg[4];
#pragma unroll
            for (int i = 0; i < 4; i++) gg[i] = grn_g[tid + 384 * i];
            TSTAMP(1, 27);
            gdc_wait();
            TSTAMP(1, 1);
            if (blockIdx.x == 120 && tid < (LN_RING + 3) * 2) (&g_flag[0][0][0])[tid * 8] = 0;
            if (blockIdx.x == 121 && tid == 0) g_epoch++;
#pragma unroll
            for (int i = 0; i < 4; i++) gx[i] = __ldcg(&g_sums[0][tid + 384 * i]) + __ldcg(&g_sums[1][tid + 384 * i]);
            const float bias = __ldcg(&g_sums[0][HID + tid]) + __ldcg(&g_sums[1][HID + tid]);
            const float gs = w2_scale(__float_as_uint(__ldcg(&g_sums[0][HID + C_DIM])) | __float_as_uint(__ldcg(&g_sums[1][HID + C_DIM])));
            float mg = 0.f;
#pragma unroll
            for (int i = 0; i < 4; i++) {
                gx[i] = sqrtf(gx[i] * (HSCALE * HSCALE) + 1e-6f);
                part += gx[i];
                gx[i] *= __bfloat162float(gg[i]);
                mg = fmaxf(mg, fabsf(gx[i]));
            }
#pragma unroll
            for (int o = 16; o > 0; o >>= 1) part += __shfl_xor_sync(0xffffffffu, part, o);
            const uint32_t mgw = __reduce_max_sync(0xffffffffu, __float_as_uint(mg));
            const uint32_t mbw = __reduce_max_sync(0xffffffffu, __float_as_uint(fabsf(bias)));
            TSTAMP(1, 26);
            if (lane == 0) *reinterpret_cast<float4*>(s_red + warp * 4) = make_float4(part, __uint_as_float(mgw), __uint_as_float(mbw), 0.f);
            bar_sync(1, 384);
            float tot = 0.f, mb = 0.f;
#pragma unroll
            for (int i = 0; i < 12; i++) {
                const float4 t = *reinterpret_cast<const float4*>(s_red + i * 4);
                tot += t.x;
                mg = fmaxf(mg, t.y);
                mb = fmaxf(mb, t.z);
            }
            const float inv = 1.0f / (tot * (1.0f / HID) + 1e-6f);
            const uint32_t ej = min((__float_as_uint(fmaxf(fmaf(mg, inv, 1.0f) * HSCALE, mb * gs * 0x1p-13f)) >> 23) + 1, 250u);
            const float dn = __uint_as_float((254u - ej) << 23);
            up = min(ej + 127u - (__float_as_uint(gs) >> 23), 254u) * 0x00800080u;
            bar_sync(1, 384);
            {
                const float b = bias * gs * dn;
                const uint32_t hi = pack_f16(b, 0.f);
                *reinterpret_cast<uint2*>(smem + P2_OFF_BIAS + tid * 16) = make_uint2(pack_f16(b, b - h_lo(hi)), 0u);
            }
#pragma unroll
            for (int i = 0; i < 4; i++) {
                const int k = tid + 384 * i;
                *reinterpret_cast<__half*>(smem + P2_OFF_BIAS + ((k >> 4) * 4 + ((k >> 1) & 3)) * 16 + 8 + ((k >> 3) & 1) * 4 + (k & 1) * 2) =
                    __float2half_rn(fmaf(gx[i], inv, 1.0f) * (HSCALE * dn));
            }
            TSTAMP(1, 25);
            if (tid < 16) reinterpret_cast<uint4*>(smem + P2_OFF_ONES)[tid] = make_uint4(tid < 8 ? 0x3c003c00u : 0u, 0u, 0u, 0u);
            asm volatile("fence.proxy.async.shared::cta;\n" ::: "memory");
            bar_sync(1, 384);
        }
        TSTAMP(1, 28);
        if (wg == 1) {
            constexpr int N = sizeof(g_w2img[0]) / 16, PER = (N + NUM_CTAS - 1) / NUM_CTAS;
            uint4 v[5];
#pragma unroll
            for (int i = 0; i < 5; i++) v[i] = __ldcg(&g_w2img[0][min(blockIdx.x * PER + (tid & 127) + 128 * i, N - 1)]);
#pragma unroll
            for (int i = 0; i < 5; i++) {
                const int j = min(blockIdx.x * PER + (tid & 127) + 128 * i, N - 1);
                const uint32_t* t = reinterpret_cast<const uint32_t*>(smem + P2_OFF_BIAS + (j / 768) * 64 + 8 + (j & 8) / 2);
                auto sc = [&](uint32_t u, int e) { return (h2_mul(u, t[4 * e]) + 0x00040004u) & 0xfff8fff8u; };
                g_w2img[1][j] = make_uint4(sc(v[i].x, 0), sc(v[i].y, 1), sc(v[i].z, 2), sc(v[i].w, 3));
            }
            asm volatile("fence.proxy.async.global;\n" ::: "memory");
            bar_sync(2, 128);
            if (tid == 128) asm volatile("fence.acq_rel.gpu;\nred.release.gpu.global.add.u32 [%0], 1;\n" ::"l"(&g_prog[1][0]) : "memory");
        }

        const int who = __shfl_sync(0xffffffffu, lane == 2 ? 0 : lane < 2 ? 1 : 2, lane);
        const uint32_t rel0 = who ? mapa(bar_bempty, lane & 1) : mapa(bar_aempty + wg * P2_NA * 8, rank), rel1 = rel0 + (who ? 0 : 32);
        auto publish = [&]() {
            asm volatile("fence.proxy.async.shared::cta;\n" ::: "memory");
            __syncwarp();
            if (who == 0) mbar_arrive(bar_oready + wg * 8);
        };
        bool ok_a, pend = false;
        uint32_t pa = 0, s_t;
        auto fetch = [&](int j, bool raw) {
            uint32_t o[6], u0[4], u1[4];
            uint2 t0, t1;
            if (raw) {
                asm volatile("ld.shared.v2.u32 {%0,%1}, [%2];\n" : "=r"(t0.x), "=r"(t0.y) : "r"(s_t + j * 128) : "memory");
                asm volatile("ld.shared.v2.u32 {%0,%1}, [%2];\n" : "=r"(t1.x), "=r"(t1.y) : "r"(s_t + j * 128 + 64) : "memory");
            }
            const bool ok_b = mbar_test(bar_bfull + (j & 3) * 8, j >> 2);
            if (j == 7) pa ^= 1;
            ok_a = mbar_test(af + ((j + 1) & 7) * 8, pa);
            asm volatile("ldmatrix.sync.aligned.m8n8.x4.trans.shared.b16 {%0,%1,%2,%3}, [%4];\n"
                         : "=r"(o[0]), "=r"(o[1]), "=r"(o[2]), "=r"(o[3]) : "r"(s_a + j * P2_A) : "memory");
            asm volatile("ldmatrix.sync.aligned.m8n8.x2.trans.shared.b16 {%0,%1}, [%2];\n"
                         : "=r"(o[4]), "=r"(o[5]) : "r"(s_a + j * P2_A + 2048) : "memory");
            p2_unpack(u0, o[0], o[1], o[2]);
            p2_unpack(u1, o[3], o[4], o[5]);
            if (raw) {
                u0[0] = h2_mul(u0[0], t0.x); u0[1] = h2_mul(u0[1], t0.x); u0[2] = h2_mul(u0[2], t0.y); u0[3] = h2_mul(u0[3], t0.y);
                u1[0] = h2_mul(u1[0], t1.x); u1[1] = h2_mul(u1[1], t1.x); u1[2] = h2_mul(u1[2], t1.y); u1[3] = h2_mul(u1[3], t1.y);
            }
            a[j & 1][0] = make_uint4(u0[0], u0[1], u0[2], u0[3]);
            a[j & 1][1] = make_uint4(u1[0], u1[1], u1[2], u1[3]);
            if (!ok_b) mbar_wait(bar_bfull + (j & 3) * 8, j >> 2);
        };
        auto table = [&](int pos) { s_t = sbase + P2_OFF_BIAS + q * 16 + 8 + (k0 + pos) % 48 * 128; };
        const uint64_t db0 = make_desc(sbase, 128, 256);
        auto block8 = [&](bool raw, int pos, int thr0) {
#pragma unroll
            for (int j = 0; j < 8; j++) {
                const uint64_t db = db0 + (j & 3) * (P2_B / 16);
                wg_fence();
                mma_rs_n192(acc0, a[j & 1][0], db);
                mma_rs_n192(acc1, a[j & 1][0], db + 384);
                mma_rs_n192(acc0, a[j & 1][1], db + 768);
                mma_rs_n192(acc1, a[j & 1][1], db + 768 + 384);
                wg_commit();
                const uint32_t rel = ((j - 1) & 4 ? rel1 : rel0) + ((j - 1) & 3) * 8;
                wg_wait<1>();
                if (who < (j ? 2 : thr0)) mbar_arrive_cluster(rel);
                if (!ok_a) {
                    if (j == 0 && pend) { publish(); pend = false; }
                    mbar_wait(af + ((j + 1) & 7) * 8, pa);
                }
                if (raw && j == 7) table(pos + 8);
                fetch((j + 1) & 7, raw && (j < 7 || pos + 8 < P2_RAW));
            }
        };
        int n = wg == 2 && head ? -1 : wg, pos = p2_start(n);
        uint32_t px = 0;
        wait_pos(pos);
        mbar_wait(af, 0);
        table(pos);
        fetch(0, pos < P2_RAW);
#pragma unroll 1
        for (;; n += 3) {
            TSTAMP(1, 2 + n);
            const uint64_t ones = make_desc(sbase + P2_OFF_ONES + (n == P2_ITEMS ? 128 : 0), n == P2_ITEMS ? 0 : 128, 0);
            wg_fence();
            mma_ss_n192_init(acc0, ones, make_desc(sbase + P2_OFF_BIAS, 0, 128));
            mma_ss_n192_init(acc1, ones, make_desc(sbase + P2_OFF_BIAS + 3072, 0, 128));
            wg_commit();
            const int end = pos + (n < 0 || n == P2_ITEMS ? 24 : 48);
            int thr = 1;
#pragma unroll 1
            for (; pos < P2_RAW; pos += 8, thr = 2) block8(true, pos, thr);
#pragma unroll 1
            for (; pos < end; pos += 8, thr = 2) block8(false, pos, thr);
            if (n == P2_ITEMS) {
                flag_wait<true>(&g_half[pair][rank], 1);
                wg_wait<0>();
                if (who == 1) mbar_arrive_cluster(rel0 + 24);
                uint8_t* o = reinterpret_cast<uint8_t*>(out) + (size_t)((2 * p2_tile(cl, -1) + rank) * 64 + (g & 1) * 32 + w * 8 + (g >> 1)) * P2_XROW + q * 16;
                p2_epilogue_add(acc0, up, o);
                p2_epilogue_add(acc1, up, o + 384);
                break;
            }
            wg_wait<0>();
            if (who == 1) mbar_arrive_cluster(rel0 + 24);
            mbar_wait(bar_xfull + wg * 8, px);
            px ^= 1;
            __syncwarp();
            p2_epilogue(acc0, acc1, up, sx, zero);
            if (n + 3 >= P2_ITEMS + tail) { publish(); break; }
            if (pos != p2_start(n + 3)) {
                publish();
                pos += 8;
                wait_pos(pos);
                mbar_wait(bar_bfull, 0);
            } else {
                pend = true;
                ok_a = false;
            }
        }
        TSTAMP(1, 29);
        cluster_sync();
        TSTAMP(1, 30);
    }
}

}

extern "C" void kernel_launch(void* const* d_in, const int* in_sizes, int n_in, void* d_out, int out_size) {
    const __nv_bfloat16* x = (const __nv_bfloat16*)d_in[0];
    const __nv_bfloat16* dw = (const __nv_bfloat16*)d_in[1];
    const __nv_bfloat16* w1 = (const __nv_bfloat16*)d_in[2];
    const __nv_bfloat16* w2 = (const __nv_bfloat16*)d_in[3];
    const __nv_bfloat16* grn_g = (const __nv_bfloat16*)d_in[4];
    const __nv_bfloat16* grn_b = (const __nv_bfloat16*)d_in[5];
    __nv_bfloat16* out = (__nv_bfloat16*)d_out;

    cudaFuncSetAttribute(pass1_kernel, cudaFuncAttributeMaxDynamicSharedMemorySize, P1_SMEM);
    cudaFuncSetAttribute(pass2_kernel, cudaFuncAttributeMaxDynamicSharedMemorySize, P2_SMEM);

    typedef CUresult (*EncodeFn)(CUtensorMap*, CUtensorMapDataType, cuuint32_t, void*, const cuuint64_t*, const cuuint64_t*,
                                 const cuuint32_t*, const cuuint32_t*, CUtensorMapInterleave, CUtensorMapSwizzle,
                                 CUtensorMapL2promotion, CUtensorMapFloatOOBfill);
    static EncodeFn encode = nullptr;
    if (!encode) {
        cudaDriverEntryPointQueryResult qres;
        cudaGetDriverEntryPoint("cuTensorMapEncodeTiled", (void**)&encode, cudaEnableDefault, &qres);
    }
    CUtensorMap wmap;
    const cuuint64_t gdim[2] = {HID, C_DIM};
    const cuuint64_t gstr[1] = {HID * 2};
    const cuuint32_t box[2] = {64, 192}, estr[2] = {1, 1};
    CUresult er = encode(&wmap, CU_TENSOR_MAP_DATA_TYPE_BFLOAT16, 2, (void*)w1, gdim, gstr, box, estr, CU_TENSOR_MAP_INTERLEAVE_NONE,
           CU_TENSOR_MAP_SWIZZLE_128B, CU_TENSOR_MAP_L2_PROMOTION_L2_128B, CU_TENSOR_MAP_FLOAT_OOB_FILL_NONE);
    if (er != CUDA_SUCCESS) printf("tensor map encode failed %d\n", (int)er);

    pass1_kernel<<<NUM_CTAS, 512, P1_SMEM>>>(wmap, x, dw, w2, grn_b, 0);

    cudaLaunchAttribute attr[1];
    attr[0].id = cudaLaunchAttributeProgrammaticStreamSerialization;
    attr[0].val.programmaticStreamSerializationAllowed = 1;
    cudaLaunchConfig_t cfg = {};
    cfg.gridDim = dim3(NUM_CTAS);
    cfg.stream = 0;
    cfg.attrs = attr;
    cfg.numAttrs = 1;
    cfg.blockDim = dim3(512);
    cfg.dynamicSmemBytes = P2_SMEM;
    cudaLaunchKernelEx(&cfg, pass2_kernel, x, grn_g, out, 0);
}
```

```cpp
#include <cuda.h>
#include <cuda_runtime.h>
#include <cuda_bf16.h>
#include <cuda_fp16.h>
#include <stdint.h>
#include <stdio.h>

namespace {

constexpr int M_TOTAL = 384 * 384;
constexpr int C_DIM   = 384;
constexpr int HID     = 1536;
constexpr int NT128   = M_TOTAL / 128;
constexpr int NUM_CTAS = 132;

constexpr int NGRP = 11, GRP_CTAS = 12;
constexpr int LN_STEP = NUM_CTAS / 4, LN_RING = 2 * LN_STEP;
constexpr int NT_RING = NT128 - NGRP;
constexpr int LN_TILE = 128 * C_DIM * 2;
constexpr int H_TILE = 64 * HID * 3 / 2;
constexpr int H_HALF = 3072, H_STEP = 6144;

__device__ __align__(1024) uint4 g_h[(size_t)M_TOTAL * HID * 3 / 32];
__device__ __align__(1024) uint4 g_ln[LN_RING * LN_TILE / 16];
__device__ __align__(1024) uint4 g_w2img[2][HID * C_DIM * 2 / 16];
__device__ __align__(16) float g_sums[2][HID + 512];
__device__ unsigned g_epoch;
__device__ __align__(128) unsigned g_prog[2][32];
__device__ __align__(128) unsigned g_half[32][2];
__device__ unsigned g_flag[LN_RING + 3][2][8];
#define TSTAMP(k, i)
#define TRACE(wg, pos, i)
#define TRACEW(pos, i)

#define TR2(i)
__host__ __device__ __forceinline__ int perm32(int n) {
    return (n & ~31) | (((n >> 1) & 3) << 3) | (((n >> 3) & 3) << 1) | (n & 1);
}

__device__ __forceinline__ uint32_t smem_u32(const void* p) { return (uint32_t)__cvta_generic_to_shared(p); }

__device__ __forceinline__ void mbar_init(uint32_t bar, uint32_t count) {
    asm volatile("mbarrier.init.shared::cta.b64 [%0], %1;\n" ::"r"(bar), "r"(count) : "memory");
}
__device__ __forceinline__ void mbar_expect_tx(uint32_t bar, uint32_t bytes) {
    asm volatile("mbarrier.arrive.expect_tx.shared::cta.b64 _, [%0], %1;\n" ::"r"(bar), "r"(bytes) : "memory");
}
__device__ __forceinline__ void mbar_arrive(uint32_t bar) {
    asm volatile("mbarrier.arrive.shared::cta.b64 _, [%0];\n" ::"r"(bar) : "memory");
}
__device__ __forceinline__ void mbar_arrive_cluster(uint32_t bar_cluster_addr) {
    asm volatile("mbarrier.arrive.shared::cluster.b64 _, [%0];\n" ::"r"(bar_cluster_addr) : "memory");
}
#define SAFE_BREAK
__device__ __forceinline__ void mbar_wait(uint32_t bar, uint32_t parity) {
    asm volatile(
        "{\n"
        ".reg .pred p;\n"
        "LAB_WAIT:\n"
        "mbarrier.try_wait.parity.shared::cta.b64 p, [%0], %1;\n"
        "@!p bra LAB_WAIT;\n"
        "}\n" ::"r"(bar), "r"(parity) : "memory");
}
__device__ __forceinline__ bool mbar_test(uint32_t bar, uint32_t parity) {
    uint32_t ok;
    asm volatile("{\n.reg .pred p;\n"
                 "mbarrier.test_wait.parity.shared::cta.b64 p, [%1], %2;\n"
                 "selp.u32 %0, 1, 0, p;\n}\n" : "=r"(ok) : "r"(bar), "r"(parity) : "memory");
    return ok != 0;
}
__device__ __forceinline__ uint32_t mapa(uint32_t addr, uint32_t rank) {
    uint32_t r;
    asm volatile("mapa.shared::cluster.u32 %0, %1, %2;\n" : "=r"(r) : "r"(addr), "r"(rank));
    return r;
}
__device__ __forceinline__ void bulk_g2s(uint32_t dst, const void* src, uint32_t bytes, uint32_t bar) {
    asm volatile("cp.async.bulk.shared::cluster.global.mbarrier::complete_tx::bytes [%0], [%1], %2, [%3];\n"
                 ::"r"(dst), "l"(src), "r"(bytes), "r"(bar) : "memory");
}
__device__ __forceinline__ void bulk_g2s_mc(uint32_t dst, const void* src, uint32_t bytes, uint32_t bar, uint16_t mask) {
    asm volatile("cp.async.bulk.shared::cluster.global.mbarrier::complete_tx::bytes.multicast::cluster [%0], [%1], %2, [%3], %4;\n"
                 ::"r"(dst), "l"(src), "r"(bytes), "r"(bar), "h"(mask) : "memory");
}
__device__ __forceinline__ void tma2(uint32_t dst, const CUtensorMap* map, int c0, int c1, uint32_t bar) {
    asm volatile("cp.async.bulk.tensor.2d.shared::cluster.global.tile.mbarrier::complete_tx::bytes [%0], [%1, {%2, %3}], [%4];\n"
                 ::"r"(dst), "l"(map), "r"(c0), "r"(c1), "r"(bar) : "memory");
}
template <bool ACQ>
__device__ __forceinline__ uint32_t flag_wait(const unsigned* p, unsigned target) {
    unsigned v, n = 0;
    do {
        if (ACQ) asm volatile("ld.acquire.gpu.global.u32 %0, [%1];\n" : "=r"(v) : "l"(p) : "memory");
        else asm volatile("ld.relaxed.gpu.global.u32 %0, [%1];\n" : "=r"(v) : "l"(p) : "memory");
        n++;
    } while (v < target);
    return n == 1;
}
__device__ __forceinline__ void ldsm4t(uint32_t (&r)[4], uint32_t addr) {
    asm volatile("ldmatrix.sync.aligned.m8n8.x4.trans.shared.b16 {%0,%1,%2,%3}, [%4];\n"
                 : "=r"(r[0]), "=r"(r[1]), "=r"(r[2]), "=r"(r[3]) : "r"(addr) : "memory");
}
__device__ __forceinline__ void bulk_s2g(void* dst, uint32_t src, uint32_t bytes) {
    asm volatile("cp.async.bulk.global.shared::cta.bulk_group [%0], [%1], %2;\n" ::"l"(dst), "r"(src), "r"(bytes) : "memory");
}
__device__ __forceinline__ void cluster_sync() {
    asm volatile("barrier.cluster.arrive.aligned;\nbarrier.cluster.wait.aligned;\n" ::: "memory");
}
__device__ __forceinline__ void cluster_sync_relaxed() {
    asm volatile("barrier.cluster.arrive.relaxed.aligned;\nbarrier.cluster.wait.aligned;\n" ::: "memory");
}
__device__ __forceinline__ void gdc_wait() { asm volatile("griddepcontrol.wait;\n" ::: "memory"); }
__device__ __forceinline__ void gdc_launch() { asm volatile("griddepcontrol.launch_dependents;\n" ::: "memory"); }
__device__ __forceinline__ uint32_t cluster_rank() {
    uint32_t r;
    asm volatile("mov.u32 %0, %%cluster_ctarank;\n" : "=r"(r));
    return r;
}
__device__ __forceinline__ bool elect_one() {
    uint32_t pred;
    asm volatile("{\n.reg .pred p;\nelect.sync _|p, 0xffffffff;\nselp.u32 %0, 1, 0, p;\n}\n" : "=r"(pred));
    return pred != 0;
}
__device__ __forceinline__ void wg_fence() { asm volatile("wgmma.fence.sync.aligned;\n" ::: "memory"); }
__device__ __forceinline__ void wg_commit() { asm volatile("wgmma.commit_group.sync.aligned;\n" ::: "memory"); }
template <int N> __device__ __forceinline__ void wg_wait() {
    asm volatile("wgmma.wait_group.sync.aligned %0;\n" ::"n"(N) : "memory");
}
template <int R> __device__ __forceinline__ void reg_inc() { asm volatile("setmaxnreg.inc.sync.aligned.u32 %0;\n" ::"n"(R)); }
template <int R> __device__ __forceinline__ void reg_dec() { asm volatile("setmaxnreg.dec.sync.aligned.u32 %0;\n" ::"n"(R)); }
__device__ __forceinline__ void bar_sync(int id, int n) { asm volatile("bar.sync %0, %1;\n" ::"r"(id), "r"(n) : "memory"); }
__device__ __forceinline__ void bar_arrive(int id, int n) { asm volatile("bar.arrive %0, %1;\n" ::"r"(id), "r"(n) : "memory"); }

__device__ __forceinline__ uint64_t make_desc(uint32_t saddr, uint32_t lbo, uint32_t sbo) {
    return (uint64_t)((saddr & 0x3FFFF) >> 4) | ((uint64_t)(lbo >> 4) << 16) | ((uint64_t)(sbo >> 4) << 32);
}

__device__ __forceinline__ void stg128_cs(void* p, uint32_t a, uint32_t b, uint32_t c, uint32_t d) {
    asm volatile("st.global.cs.v4.u32 [%0], {%1,%2,%3,%4};\n" ::"l"(p), "r"(a), "r"(b), "r"(c), "r"(d) : "memory");
}
__device__ __forceinline__ uint32_t pack_bf16(float lo, float hi) {
    uint32_t r;
    asm("cvt.rn.bf16x2.f32 %0, %1, %2;\n" : "=r"(r) : "f"(hi), "f"(lo));
    return r;
}
__device__ __forceinline__ float bf_lo(uint32_t v) { return __uint_as_float(v << 16); }
__device__ __forceinline__ float bf_hi(uint32_t v) { return __uint_as_float(v & 0xffff0000u); }
__device__ __forceinline__ uint32_t bf2_mul(uint32_t a, uint32_t b) {
    uint32_t r;
    asm("mul.rn.bf16x2 %0, %1, %2;\n" : "=r"(r) : "r"(a), "r"(b));
    return r;
}
__device__ __forceinline__ uint32_t bf2_fma(uint32_t a, uint32_t b, uint32_t c) {
    uint32_t r;
    asm("fma.rn.bf16x2 %0, %1, %2, %3;\n" : "=r"(r) : "r"(a), "r"(b), "r"(c));
    return r;
}
__device__ __forceinline__ uint32_t bf2_add(uint32_t a, uint32_t b) {
    uint32_t r;
    asm("add.rn.bf16x2 %0, %1, %2;\n" : "=r"(r) : "r"(a), "r"(b));
    return r;
}
__device__ __forceinline__ uint32_t h2_mul(uint32_t a, uint32_t b) {
    uint32_t r;
    asm("mul.rn.f16x2 %0, %1, %2;\n" : "=r"(r) : "r"(a), "r"(b));
    return r;
}
__device__ __forceinline__ uint32_t h2_fma(uint32_t a, uint32_t b, uint32_t c) {
    uint32_t r;
    asm("fma.rn.f16x2 %0, %1, %2, %3;\n" : "=r"(r) : "r"(a), "r"(b), "r"(c));
    return r;
}
__device__ __forceinline__ uint32_t pack_f16(float lo, float hi) {
    uint32_t r;
    asm("cvt.rn.f16x2.f32 %0, %1, %2;\n" : "=r"(r) : "f"(hi), "f"(lo));
    return r;
}
__device__ __forceinline__ float h_lo(uint32_t v) { return __low2float(*reinterpret_cast<const __half2*>(&v)); }
__device__ __forceinline__ float h_hi(uint32_t v) { return __high2float(*reinterpret_cast<const __half2*>(&v)); }
__device__ __forceinline__ uint32_t bf2_to_h2(uint32_t v) { return (v & 0x7fff7fffu) * 7u + v; }
__device__ __forceinline__ uint32_t prmt(uint32_t a, uint32_t b, uint32_t sel) {
    uint32_t r;
    asm("prmt.b32 %0, %1, %2, %3;\n" : "=r"(r) : "r"(a), "r"(b), "r"(sel));
    return r;
}
__device__ __forceinline__ uint32_t bitsel(uint32_t a, uint32_t b, uint32_t m) {
    uint32_t r;
    asm("lop3.b32 %0, %1, %2, %3, 0xd8;\n" : "=r"(r) : "r"(a), "r"(b), "r"(m));
    return r;
}
constexpr float KAPPA = 0.3292034911525734f;
constexpr uint32_t GELU_C2 = 0x40d940d9u;
constexpr float HSCALE = 1.0f / (2.0f * KAPPA);
__device__ __forceinline__ float w2_scale(uint32_t m) { return __uint_as_float((257u - max(m >> 23, 16u)) << 23); }
__device__ __forceinline__ void sched_break(int zero) {
    asm volatile("{\n.reg .pred p;\nsetp.ne.s32 p, %0, 0;\nSB_LOOP:\n@p nanosleep.u32 1;\n@p bra SB_LOOP;\n}\n" ::"r"(zero));
}

#define ACC8(d, o) "+r"(d[o + 0]), "+r"(d[o + 1]), "+r"(d[o + 2]), "+r"(d[o + 3]), "+r"(d[o + 4]), "+r"(d[o + 5]), "+r"(d[o + 6]), "+r"(d[o + 7])

__device__ __forceinline__ void mma_rs_n128(uint32_t (&d)[32], const uint32_t (&a)[4], uint64_t desc, int scale_d) {
    asm volatile(
        "{\n.reg .pred p;\nsetp.ne.b32 p, %37, 0;\n"
        "wgmma.mma_async.sync.aligned.m64n128k16.f16.f16.f16 "
        "{%0,%1,%2,%3,%4,%5,%6,%7,%8,%9,%10,%11,%12,%13,%14,%15,"
        "%16,%17,%18,%19,%20,%21,%22,%23,%24,%25,%26,%27,%28,%29,%30,%31},"
        "{%32,%33,%34,%35}, %36, p, 1, 1, 0;\n}\n"
        : ACC8(d, 0), ACC8(d, 8), ACC8(d, 16), ACC8(d, 24)
        : "r"(a[0]), "r"(a[1]), "r"(a[2]), "r"(a[3]), "l"(desc), "r"(scale_d));
}

constexpr int P2_NACC = 48;
#define P2_MMA "wgmma.mma_async.sync.aligned.m64n192k16.f16.f16.f16 " \
        "{%0,%1,%2,%3,%4,%5,%6,%7,%8,%9,%10,%11,%12,%13,%14,%15," \
        "%16,%17,%18,%19,%20,%21,%22,%23,%24,%25,%26,%27,%28,%29,%30,%31," \
        "%32,%33,%34,%35,%36,%37,%38,%39,%40,%41,%42,%43,%44,%45,%46,%47},"
#define P2_ACC(d) ACC8(d, 0), ACC8(d, 8), ACC8(d, 16), ACC8(d, 24), ACC8(d, 32), ACC8(d, 40)
#define P2_RS "{%48,%49,%50,%51}, %52, 1, 1, 1, 0;\n"
#define P2_SS "%48, %49, 0, 1, 1, 0, 0;\n"
__device__ __forceinline__ void mma_rs_n192(uint32_t (&d)[P2_NACC], const uint4& a, uint64_t db) {
    asm volatile(P2_MMA P2_RS : P2_ACC(d) : "r"(a.x), "r"(a.y), "r"(a.z), "r"(a.w), "l"(db));
}
__device__ __forceinline__ void mma_ss_n192_init(uint32_t (&d)[P2_NACC], uint64_t da, uint64_t db) {
    asm volatile(P2_MMA P2_SS : P2_ACC(d) : "l"(da), "l"(db));
}

#define P1_PACE true
constexpr int P1_SLOT = LN_TILE / 2, P1_NST = 4;
constexpr int P1_X = 32 * C_DIM * 2;
constexpr int P1_OFF_X = P1_SLOT * P1_NST;
constexpr int P1_OFF_BAR = P1_OFF_X + P1_X;
constexpr int P1_OFF_TILE = P1_OFF_BAR + (2 * P1_NST + 2 + 4 + 4) * 8;
constexpr int P1_OFF_RAW = P1_OFF_TILE + 64;
constexpr int P1_OFF_EX = P1_OFF_RAW + 16;
constexpr int P1_SMEM = P1_OFF_EX + 128 * 4;

__device__ __forceinline__ float rsqrt_fast(float x) {
    float r;
    asm("rsqrt.approx.ftz.f32 %0, %1;\n" : "=f"(r) : "f"(x));
    return r;
}
__device__ __forceinline__ float row_sum(const uint32_t (&c)[4]) {
    const uint32_t u = bf2_add(bf2_add(c[0], c[1]), bf2_add(c[2], c[3]));
    float s = bf_lo(u) + bf_hi(u);
#pragma unroll
    for (int o = 1; o < 8; o <<= 1) s += __shfl_xor_sync(0xffffffffu, s, o);
    return s;
}
__device__ __forceinline__ uint32_t pace(uint32_t bar, uint32_t off, uint32_t val, uint32_t after, int zero) {
    asm volatile(
        "{\n.reg .pred p;\n.reg .b32 par;\n"
        "lop3.b32 par, %4, %2, %3, 0xea;\n"
        "mbarrier.test_wait.parity.shared::cta.b64 p, [%1], par;\n"
        "selp.u32 par, 1, 0, p;\n"
        "mbarrier.try_wait.parity.shared::cta.b64 p, [%1], par, 1000;\n"
        "@p or.b32 %0, %0, %2;\n"
        "}\n" : "+r"(val) : "r"(bar), "r"(zero), "r"(off), "r"(after));
    return val;
}
template <bool PACE>
__device__ __forceinline__ void ln_row(uint32_t (&v)[6][4], const uint32_t (&d)[6][4], uint32_t bar, uint32_t off, int zero,
                                       uint32_t bar_read) {
    uint32_t c[4];
#pragma unroll
    for (int i = 0; i < 6; i++)
#pragma unroll
        for (int k = 0; k < 4; k++) c[k] = bf2_fma(v[i][k], d[i][k], i ? c[k] : 0);
    const float inv = 1.0f / C_DIM;
    const float m = row_sum(c) * inv;
    uint32_t nm = pack_bf16(-m, -m);
    const float e = m + bf_lo(nm);
    if (bar_read) mbar_arrive(bar_read + (nm & zero));
    if (PACE) nm = pace(bar, off, nm, nm, zero);
#pragma unroll
    for (int i = 0; i < 6; i++) {
#pragma unroll
        for (int k = 0; k < 4; k++) {
            v[i][k] = bf2_fma(v[i][k], d[i][k], nm);
            c[k] = i ? bf2_fma(v[i][k], v[i][k], c[k]) : bf2_mul(v[i][k], v[i][k]);
        }
    }
    float r = KAPPA * rsqrt_fast(fmaxf(fmaf(-e, e, row_sum(c) * inv), 0.f) + 1e-5f);
    const float er = -e * r * 0x1p-116f;
    if (__any_sync(0xffffffffu, r < 0x1p-8f)) {
        const uint32_t p2 = __float_as_uint(r) & 0x7f800000u;
        r = __uint_as_float((__float_as_uint(r) & 0x007fffffu) | 0x3f800000u);
#pragma unroll
        for (int i = 0; i < 6; i++)
#pragma unroll
            for (int k = 0; k < 4; k++) v[i][k] = bf2_mul(v[i][k], p2 | p2 >> 16);
    }
    r *= 0x1p-116f;
    uint32_t rs = pack_bf16(r, r);
    const uint32_t sh = pack_bf16(er, er);
    if (PACE) rs = pace(bar, off, rs, sh, zero);
#pragma unroll
    for (int i = 0; i < 6; i++)
#pragma unroll
        for (int k = 0; k < 4; k++) v[i][k] = bf2_to_h2(bf2_fma(v[i][k], rs, sh));
}

template <int R>
__device__ __forceinline__ uint32_t gelu2(uint32_t a, uint32_t sc2) {
    uint32_t y, t;
    if (R) asm("{\n.reg .b16 l, h;\n.reg .b32 f;\nmov.b32 {l, h}, %2;\nmov.b32 f, {h, h};\nmul.rn.f16x2 %0, %1, f;\n}\n" : "=r"(y) : "r"(a), "r"(sc2));
    else asm("{\n.reg .b16 l, h;\n.reg .b32 f;\nmov.b32 {l, h}, %2;\nmov.b32 f, {l, l};\nmul.rn.f16x2 %0, %1, f;\n}\n" : "=r"(y) : "r"(a), "r"(sc2));
    asm("tanh.approx.f16x2 %0, %1;\n" : "=r"(t) : "r"(h2_mul(y, h2_fma(y, y, GELU_C2))));
    return h2_fma(a, t, a);
}
constexpr uint32_t SPARE = 0x40074007u;

__device__ __forceinline__ uint32_t p1_parity(uint32_t sbase) {
    uint32_t v;
    asm volatile("ld.shared.u32 %0, [%1];\n" : "=r"(v) : "r"(sbase + P1_OFF_TILE - 4) : "memory");
    return v;
}
template <int WG>
__device__ __forceinline__ void p1_consumer(const uint32_t (&a)[24][4], uint32_t sc2, uint32_t sbase, int w, int lane, int zero) {
    const uint32_t bar_full = sbase + P1_OFF_BAR, bar_empty = bar_full + P1_NST * 8;
    const uint32_t empty_remote = mapa(bar_empty, lane & 1) + (WG == 0 ? (lane & 2) * 4 : 0);
    const uint32_t bar_pace = bar_empty + P1_NST * 8 + 16 + w * 8;
    const int g = lane >> 2, q = lane & 3, cb = (blockIdx.x % GRP_CTAS) * 2 + WG;
    uint32_t acc[32], st[6][4] = {};
    float ssq[2] = {0.f, 0.f};
    TSTAMP(0, 1);

    uint8_t* hp = reinterpret_cast<uint8_t*>(g_h) + (size_t)(blockIdx.x / GRP_CTAS) * (2 * H_TILE) + ((cb * 2 + (w >> 1)) * H_STEP + (w & 1) * 1536) + g * 64 + (q ^ (g >> 1)) * 16;
    const uint64_t desc_base = make_desc(sbase, 16, 1024) | (1ull << 62);
#pragma unroll 1
    for (int i = 0;; i++) {
        const int s0 = (i & 1) * 16, par = (i >> 1) & 1;
        const uint64_t d0 = desc_base + (uint64_t)((i & 1) * (LN_TILE / 16));
        TRACE(WG, i, 0);
        if (WG == 0) mbar_wait(bar_full + s0, par);
        bar_sync(1 + WG, 256);
        TRACE(WG, i, 1);
        uint32_t step, more;
        wg_fence();
#pragma unroll
        for (int k = 0; k < 24; k++) {
            if (WG == 0 && k == 12) mbar_wait(bar_full + s0 + 8, par);
            mma_rs_n128(acc, a[k], d0 + (uint64_t)((k >> 2) * 1024 + (k & 3) * 2), k != 0);
            if (k == 23) bar_arrive(2 - WG, 256);
            if (k % 12 == 11) wg_commit();
        }
        asm volatile("ld.shared.v2.u32 {%0, %1}, [%2];\n" : "=r"(step), "=r"(more) : "r"(sbase + P1_OFF_TILE + (i & 3) * 16) : "memory");
        TRACE(WG, i, 2);
        if (WG == 1) {
            wg_wait<1>();
            if (lane < 2) mbar_arrive_cluster(empty_remote + s0);
        }
        hp += step;
        TRACE(WG, i, 3);
        if (zero) {
#pragma unroll
            for (int c = 0; c < 6; c++) stg128_cs(hp + c * 512, st[c][0], st[c][1], st[c][2], st[c][3]);
        }
        wg_wait<0>();
        TRACE(WG, i, 4);
        if (lane < (WG == 0 ? 4 : 2)) mbar_arrive_cluster(empty_remote + s0 + WG * 8);
        uint32_t sq[2], h[8][4];
#pragma unroll
        for (int i2 = 0; i2 < 5; i2++) {
#pragma unroll
            for (int c = 2 * i2 - 2; c < 2 * i2; c++) {
                if (c < 0) continue;
                if (c & 3) {
                    uint32_t (&o)[4] = st[c - 1 - (c >> 2)];
#pragma unroll
                    for (int u = 0; u < 4; u++) {
                        const uint32_t v = h[c & 4][u];
                        o[u] = bitsel(h[c][u], (c & 3) == 2 ? prmt(v, v, 0xa381) : prmt(v >> 3, v, (c & 3) == 1 ? 0x6240 : 0xf3d1), SPARE);
                    }
                    stg128_cs(hp + (c >> 2) * H_HALF + ((c & 3) - 1) * 512, o[0], o[1], o[2], o[3]);
                }
            }
            if (i2 < 4) {
#pragma unroll
                for (int u = 0; u < 4; u++) {
                    h[2 * i2][u] = gelu2<0>(acc[8 * i2 + 2 * u], sc2);
                    h[2 * i2 + 1][u] = gelu2<1>(acc[8 * i2 + 2 * u + 1], sc2);
#pragma unroll
                    for (int r = 0; r < 2; r++) sq[r] = (i2 | u) ? h2_fma(h[2 * i2 + r][u], h[2 * i2 + r][u], sq[r]) : h2_mul(h[r][u], h[r][u]);
                }
                sched_break(zero);
            }
        }
#pragma unroll
        for (int r = 0; r < 2; r++) ssq[r] += h_lo(sq[r]) + h_hi(sq[r]);
        if (lane == 0) mbar_arrive(bar_pace);
        if (!more) break;
    }
    TSTAMP(0, 21);
    if (WG == 0) bar_sync(1, 256);
#pragma unroll
    for (int r = 0; r < 2; r++) {
        ssq[r] += __shfl_xor_sync(0xffffffffu, ssq[r], 1);
        ssq[r] += __shfl_xor_sync(0xffffffffu, ssq[r], 2);
        float f;
        asm volatile("ld.shared.f32 %0, [%1];\n" : "=f"(f) : "r"(sbase + P1_OFF_EX + (WG * 64 + w * 16 + r * 8 + g) * 4) : "memory");
        if (q == 0) atomicAdd(&g_sums[p1_parity(sbase)][cb * 64 + w * 16 + r * 8 + g], ssq[r] * f * f);
    }
}

__global__ void __cluster_dims__(2, 1, 1) __launch_bounds__(512, 1)
pass1_kernel(const __grid_constant__ CUtensorMap wmap, const __nv_bfloat16* __restrict__ x, const __nv_bfloat16* __restrict__ dw,
             const __nv_bfloat16* __restrict__ w2, const __nv_bfloat16* __restrict__ grn_b, int zero) {
    extern __shared__ __align__(1024) uint8_t smem[];
    const uint32_t sbase = smem_u32(smem);
    const uint32_t bar_full = sbase + P1_OFF_BAR, bar_empty = bar_full + P1_NST * 8, bar_w = bar_empty + P1_NST * 8;
    const int tid = threadIdx.x;
    const int warp = __shfl_sync(0xffffffffu, tid >> 5, 0), lane = tid & 31;
    const uint32_t rank = cluster_rank();
    const int cig = blockIdx.x % GRP_CTAS;
    uint8_t* const ring = reinterpret_cast<uint8_t*>(g_ln);

    TSTAMP(0, 0);
    TRACEW(110 + warp, 0);
    const uint32_t bar_pace = bar_w + 16, bar_xfull = bar_pace + 32, bar_xempty = bar_xfull + 8, bar_done = bar_xfull + 16;
    const uint32_t bar_raw = sbase + P1_OFF_RAW;
    const int ln0 = blockIdx.x >> 2, first = blockIdx.x / GRP_CTAS;
    const uint8_t* xsrc = reinterpret_cast<const uint8_t*>(x) + (size_t)(NGRP * 4 + blockIdx.x) * P1_X;

    if (warp >= 12) {
        reg_dec<40>();
        asm volatile("barrier.cluster.arrive.relaxed.aligned;\n" ::: "memory");
        asm volatile("barrier.cluster.wait.aligned;\n" ::: "memory");
        if (warp == 12) {
            int prev = first - NGRP, t = first, next = t + NGRP;
            const uint32_t rbase = mapa(sbase, lane & 1);
#pragma unroll 1
            for (int i = 1; t < NT_RING; i++) {
                const int s0 = (i & 1) * 2, par = ((i + 1) >> 1 & 1) ^ 1;
                const int round = t / LN_RING, slot = t - round * LN_RING;
                const uint8_t* src = ring + slot * LN_TILE + rank * (P1_SLOT / 2);
                int draw = 0;
                if (rank == 0 && lane == 0) draw = atomicAdd(&g_flag[LN_RING + (cig >> 2)][(cig >> 1) & 1][0], 1u);
                flag_wait<true>(&g_flag[slot][0][0], 4 * round + 4);
                TRACEW(i, 2);
                asm volatile("fence.proxy.async.global;\n" ::: "memory");
                draw = 2 * NGRP + __shfl_sync(0xffffffffu, draw, 0);
#pragma unroll
                for (int h = 0; h < 2; h++) {
                    mbar_wait(bar_empty + (s0 + h) * 8, par);
                    TRACEW(i, 4 + h);
                    if (elect_one()) {
                        const int len = P1_SLOT / 2;
                        mbar_expect_tx(bar_full + (s0 + h) * 8, 2 * len + 16 - 16 * h);
                        bulk_g2s_mc(sbase + (s0 + h) * P1_SLOT + rank * (P1_SLOT / 2), src + h * P1_SLOT, len, bar_full + (s0 + h) * 8, (uint16_t)3);
                    }
                    __syncwarp();
                    if (h == 0 && rank == 0 && lane < 2)
                        asm volatile("st.async.shared::cluster.mbarrier::complete_tx::bytes.v4.u32 [%0], {%1, %2, %3, %3}, [%4];\n"
                                     ::"r"(rbase + P1_OFF_TILE + (i & 3) * 16), "r"((t - prev) * (2 * H_TILE)), "r"((int)(next < NT_RING)), "r"(draw),
                                       "r"(rbase + P1_OFF_BAR + s0 * 8) : "memory");
                }
                prev = t;
                t = next;
                next = draw;
                if (rank != 0) {
                    mbar_wait(bar_full + (s0 ^ 2) * 8, ((i - 1) >> 1) & 1);
                    asm volatile("ld.shared.u32 %0, [%1];\n" : "=r"(t) : "r"(sbase + P1_OFF_TILE + ((i - 1) & 3) * 16 + 8) : "memory");
                }
            }
        } else if (warp == 13) {
            int ph = 0;
            unsigned target = 0;
#pragma unroll 1
            for (int i = ln0 + LN_STEP; i < NT_RING; i += LN_STEP, ph ^= 1) {
                target += ph * (GRP_CTAS / 2);
                xsrc += (size_t)NUM_CTAS * P1_X;
                mbar_wait(bar_xempty, ph);
                if (elect_one()) {
                    mbar_expect_tx(bar_xfull, P1_X);
                    bulk_g2s(sbase + P1_OFF_X, xsrc, P1_X, bar_xfull);
                }
                __syncwarp();
                const uint32_t off = flag_wait<false>(&g_flag[ln0 + (ph ^ 1) * LN_STEP][1][0], target);
                mbar_wait(bar_done, ph);
                if (elect_one()) {
                    asm volatile("st.shared.u32 [%0], %1;\n" ::"r"(bar_done + 8), "r"(off) : "memory");
                    mbar_arrive(bar_xfull);
                }
                __syncwarp();
            }
        } else if (warp == 15) {
            if (rank == 1 && lane < 2) mbar_arrive(bar_empty + (2 + lane) * 8);
            const uint32_t par = g_epoch & 1;
            asm volatile("st.shared.u32 [%0], %1;\n" ::"r"(sbase + P1_OFF_TILE - 4), "r"(par) : "memory");
            if (blockIdx.x < 16) reinterpret_cast<float4*>(g_sums[par ^ 1])[blockIdx.x * 32 + lane] = make_float4(0.f, 0.f, 0.f, 0.f);
            {
                bar_sync(4, 288);
                TRACEW(110 + warp, 1);
                mbar_wait(bar_raw + 8, 0);
                TRACEW(110 + warp, 2);
                const uint32_t o = lane * 16384 + rank * 8192, peer = mapa(sbase, rank ^ 1);
                if (lane < 6)
                    asm volatile("cp.async.bulk.shared::cluster.shared::cta.mbarrier::complete_tx::bytes [%0], [%1], 8192, [%2];\n"
                                 ::"r"(peer + o), "r"(sbase + o), "r"(peer + P1_OFF_BAR + (lane >= 3 ? 8 : 0)) : "memory");
                __syncwarp();
            }
            int t = first, next = t + NGRP;
            if (rank == 1) {
                mbar_wait(bar_full, 0);
                mbar_wait(bar_full + 8, 0);
                if (lane < 2) mbar_arrive(bar_empty + lane * 8);
            }
#pragma unroll 1
            for (int i = 1; rank == 1 && t < NT_RING; i++) {
                const int s0 = (i & 1) * 16;
                mbar_wait(bar_full + s0, (i >> 1) & 1);
                mbar_wait(bar_full + s0 + 8, (i >> 1) & 1);
                if (lane == 0) asm volatile("red.relaxed.gpu.global.add.u32 [%0], 1;\n" ::"l"(&g_flag[t % LN_RING][1][0]) : "memory");
                t = next;
                asm volatile("ld.shared.u32 %0, [%1];\n" : "=r"(next) : "r"(sbase + P1_OFF_TILE + (i & 3) * 16 + 8) : "memory");
                if (lane < 2) mbar_arrive(bar_empty + s0 + lane * 8);
                TRACEW(i, 3);
            }
            if (rank == 0) {
                mbar_wait(bar_full, 0);
                TRACEW(110 + warp, 3);
                mbar_wait(bar_full, 1);
                float* sums = g_sums[par] + HID;
                unsigned* flag = reinterpret_cast<unsigned*>(sums + C_DIM);
                float gs = 0.f;
#pragma unroll 1
                for (int pass = 0; pass < 2; pass++) {
                    float mx = 0.f;
#pragma unroll 1
                    for (int it = first; it < 48; it += NGRP) {
                        const int np = (it % 12) * 32 + lane, kb = cig * 2 + it / 12;
                        const __nv_bfloat16* wc = w2 + (size_t)kb * 64 * C_DIM + perm32(np);
                        const uint32_t sc = mapa(sbase + P1_OFF_EX + (kb & 1) * 256, it / 24);
                        float bsum = 0.f;
#pragma unroll 1
                        for (int c = 0; c < 8; c++) {
                            float f[8];
#pragma unroll
                            for (int e = 0; e < 8; e++) f[e] = __bfloat162float(wc[(c * 8 + e) * C_DIM]);
#pragma unroll
                            for (int e = 0; e < 8; e++) {
                                float t;
                                asm volatile("ld.shared::cluster.f32 %0, [%1];\n" : "=f"(t) : "r"(sc + (c * 8 + e) * 4) : "memory");
                                bsum = fmaf(__bfloat162float(grn_b[kb * 64 + c * 8 + e]), f[e], bsum);
                                f[e] *= t;
                                mx = fmaxf(mx, fabsf(f[e]));
                            }
                            if (pass)
                                g_w2img[0][(((kb * 4 + (c >> 1)) * 48 + (np >> 3)) * 2 + (c & 1)) * 8 + (np & 7)] = make_uint4(
                                    pack_f16(f[0] * gs, f[1] * gs), pack_f16(f[2] * gs, f[3] * gs), pack_f16(f[4] * gs, f[5] * gs), pack_f16(f[6] * gs, f[7] * gs));
                        }
                        if (pass) atomicAdd(&sums[np], bsum);
                    }
                    if (!pass) {
                        const uint32_t m = __reduce_max_sync(0xffffffffu, __float_as_uint(mx));
                        if (lane == 0) {
                            atomicMax(flag, m);
                            asm volatile("red.release.gpu.global.add.u32 [%0], 1;\n" ::"l"(flag + 32) : "memory");
                        }
                        flag_wait<true>(flag + 32, NUM_CTAS / 2);
                        gs = w2_scale(__ldcg(flag));
                    }
                }
            }
        } else if (warp == 14) {
            int ph = 0;
#pragma unroll 1
            for (int i = ln0; i < NT_RING; i += LN_STEP, ph ^= 1) {
                mbar_wait(bar_done, ph);
                TRACEW(i / LN_STEP, 0);
                asm volatile("fence.proxy.async.global;\n" ::: "memory");
                if (elect_one()) asm volatile("red.release.gpu.global.add.u32 [%0], 1;\n" ::"l"(&g_flag[ln0 + ph * LN_STEP][0][0]) : "memory");
                __syncwarp();
                TRACEW(i / LN_STEP, 1);
            }
        }
        __syncwarp();
        cluster_sync();
    } else if (warp >= 8) {
        reg_dec<88>();
        asm volatile("barrier.cluster.arrive.relaxed.aligned;\n" ::: "memory");
        {
            const int l8 = lane & 7, row = (warp - 8) * 4 + (lane >> 3), px = (blockIdx.x & 3) * 32 + row;
            uint32_t d[6][4];
#pragma unroll
            for (int j = 0; j < 6; j++) {
                const uint4 t = reinterpret_cast<const uint4*>(dw)[j * 8 + l8];
                d[j][0] = t.x; d[j][1] = t.y; d[j][2] = t.z; d[j][3] = t.w;
            }
            const int n = (px & 64) + perm32(2 * row + ((px >> 5) & 1));
            uint8_t* const dst0 = ring + ln0 * LN_TILE + n * 128 + ((l8 ^ (n & 7)) << 4);
            const uint32_t src = sbase + P1_OFF_X + ((warp - 8) * 8 + (lane >> 3)) * (C_DIM * 2) + l8 * 16;
            int ph = 0;
            asm volatile("barrier.cluster.wait.aligned;\n" ::: "memory");
#pragma unroll 1
            for (int i = ln0; i < NT_RING; i += LN_STEP, ph ^= 1) {
                TRACE(2, i / LN_STEP, 0);
                mbar_wait(bar_xfull, ph);
                uint32_t off;
                asm volatile("ld.shared.u32 %0, [%1];\n" : "=r"(off) : "r"(bar_done + 8) : "memory");
                TRACE(2, i / LN_STEP, 1);
#pragma unroll 1
                for (int ps = 0; ps < 2; ps++) {
                    uint32_t v[6][4];
#pragma unroll
                    for (int j = 0; j < 6; j++)
                        asm volatile("ld.shared.v4.u32 {%0,%1,%2,%3}, [%4];\n"
                                     : "=r"(v[j][0]), "=r"(v[j][1]), "=r"(v[j][2]), "=r"(v[j][3]) : "r"(src + ps * (4 * C_DIM * 2) + j * 128) : "memory");
                    ln_row<P1_PACE>(v, d, bar_pace + (warp - 8) * 8, off, zero, ps == 1 && lane == 0 ? bar_xempty : 0);
                    uint8_t* dst = dst0 + ph * (LN_STEP * LN_TILE) + ps * 4096;
#pragma unroll
                    for (int j = 0; j < 6; j++) *reinterpret_cast<uint4*>(dst + j * 16384) = make_uint4(v[j][0], v[j][1], v[j][2], v[j][3]);
                    TRACE(2, i / LN_STEP, 3 + ps);
                }
                asm volatile("fence.proxy.async.global;\nfence.acq_rel.cta;\n" ::: "memory");
                __syncwarp();
                if (lane == 0) mbar_arrive(bar_done);
                TRACE(2, i / LN_STEP, 5);
                TRACE(2, i / LN_STEP, 2);
            }
        }
        __syncwarp();
        cluster_sync();
    } else {
        uint32_t d[6][4];
#pragma unroll
        for (int j = 0; j < 6; j++)
            asm volatile("ld.global.nc.v4.u32 {%0,%1,%2,%3}, [%4];\n" : "=r"(d[j][0]), "=r"(d[j][1]), "=r"(d[j][2]), "=r"(d[j][3])
                         : "l"(reinterpret_cast<const uint4*>(dw) + j * 8 + (lane & 7)) : "memory");
        if (tid == 0) {
            mbar_init(bar_raw, 1);
            mbar_init(bar_raw + 8, 8);
            asm volatile("fence.mbarrier_init.release.cluster;\n" ::: "memory");
            mbar_expect_tx(bar_raw, P1_SLOT);
            for (int i = 0; i < 6; i++)
                bulk_g2s(sbase + i * 16384 + (rank ^ 1) * 8192, x + (size_t)(first * 128 + rank * 64) * C_DIM + i * 4096, 8192, bar_raw);
        }
        if (tid == 32) {
            mbar_init(bar_xfull, 2);
            mbar_init(bar_xempty, 4);
            mbar_init(bar_done, 4);
            asm volatile("fence.mbarrier_init.release.cluster;\n" ::: "memory");
            mbar_expect_tx(bar_xfull, P1_X);
            bulk_g2s(sbase + P1_OFF_X, xsrc, P1_X, bar_xfull);
            asm volatile("st.shared.u32 [%0], 1;\n" ::"r"(bar_done + 8) : "memory");
            mbar_arrive(bar_xfull);
        }
        if (tid == 64) {
            asm volatile("st.shared.v4.u32 [%0], {0, 1, %1, %1};\n" ::"r"(sbase + P1_OFF_TILE), "r"(first + NGRP) : "memory");
            for (int i = 0; i < P1_NST; i++) {
                mbar_init(bar_full + i * 8, 1);
                mbar_init(bar_empty + i * 8, 16 + rank);
                mbar_init(bar_pace + i * 8, 1);
                if (i < 2) mbar_expect_tx(bar_full + i * 8, P1_SLOT / 2);
            }
            asm volatile("fence.mbarrier_init.release.cluster;\n" ::: "memory");
            if (blockIdx.x < 64) (&g_half[0][0])[blockIdx.x] = 0;
            else if (blockIdx.x < 66) g_prog[blockIdx.x - 64][0] = 0;
        }
        if (tid == 96) {
            for (int i = 0; i < 2; i++) mbar_init(bar_w + i * 8, 1);
            asm volatile("fence.mbarrier_init.release.cluster;\n" ::: "memory");
        }
        __syncwarp();
        asm volatile("barrier.cluster.arrive.relaxed.aligned;\n" ::: "memory");
        if (tid == 96)
            for (int i = 0; i < 2; i++) {
                mbar_expect_tx(bar_w + i * 8, P1_SLOT);
                tma2(sbase + (2 + i) * P1_SLOT, &wmap, cig * 128 + i * 64, 0, bar_w + i * 8);
                tma2(sbase + (2 + i) * P1_SLOT + P1_SLOT / 2, &wmap, cig * 128 + i * 64, 192, bar_w + i * 8);
            }
        __syncwarp();
        reg_inc<192>();
        TRACEW(110 + warp, 1);
        const int wg = warp >> 2, w = warp & 3;
        uint32_t a[24][4];
        {
            const int n = warp * 8 + (lane >> 3), px = (n & 1) * 32 + (n >> 5) * 4 + ((n >> 1) & 1) * 8 + ((n >> 3) & 3);
            if (wg == 1) bar_arrive(1, 256);
            gdc_launch();
            asm volatile("barrier.cluster.wait.aligned;\n" ::: "memory");
#pragma unroll 1
            for (int ps = -1; ps < 2; ps++) {
                if (ps == 0) mbar_wait(bar_raw, 0);
                TRACEW(110 + warp, 2 + (ps == 0));
                uint32_t v[6][4];
#pragma unroll
                for (int j = 0; j < 6; j++) {
                    const uint32_t o = (px + (ps & 1) * 16) * (C_DIM * 2) + j * 128;
                    asm volatile("ld.shared.v4.u32 {%0,%1,%2,%3}, [%4];\n" : "=r"(v[j][0]), "=r"(v[j][1]), "=r"(v[j][2]), "=r"(v[j][3])
                                 : "r"(sbase + (rank ^ 1) * 8192 + (lane & 7) * 16 + o + (o & ~8191u)) : "memory");
                }
                ln_row<false>(v, d, 0, 0, zero, 0);
                const uint32_t p = sbase + (rank * 64 + n + (ps & 1) * 4) * 128 + (((lane ^ n ^ (ps & 1) * 4) & 7) << 4);
#pragma unroll
                for (int j = 0; j < 6; j++)
                    asm volatile("st.shared.v4.u32 [%4], {%0,%1,%2,%3};\n"
                                 ::"r"(v[j][0]), "r"(v[j][1]), "r"(v[j][2]), "r"(v[j][3]), "r"(p + j * 16384) : "memory");
            }
            asm volatile("fence.proxy.async.shared::cta;\n" ::: "memory");
            __syncwarp();
            if (lane == 0) mbar_arrive_cluster(mapa(bar_raw + 8, rank ^ 1));
            bar_arrive(4, 288);
            TRACEW(110 + warp, 4);
            const uint32_t src = sbase + (2 + wg) * P1_SLOT + ((lane >> 4) * 8 + (lane & 7)) * 128 + (((2 * w + ((lane >> 3) & 1)) ^ (lane & 7)) << 4);
            mbar_wait(bar_w + wg * 8, 0);
            TRACEW(110 + warp, 5);
            uint32_t dep = 0;
#pragma unroll
            for (int k = 0; k < 24; k++) {
                ldsm4t(a[k], src + k * 2048);
                dep |= a[k][0];
            }
            __syncwarp();
            if (lane < 4) mbar_arrive_cluster(mapa(bar_empty, lane & 1) + (2 + (lane >> 1)) * 8 + (dep & zero));
        }
        TRACEW(110 + warp, 6);
        uint32_t ex[2];
#pragma unroll
        for (int r = 0; r < 2; r++) {
            float t = 0.f;
#pragma unroll
            for (int j = 0; j < 6; j++) {
                uint32_t c = bf2_mul(a[4 * j][r], a[4 * j][r]);
#pragma unroll
                for (int k = 1; k < 8; k++) c = bf2_fma(a[4 * j + k / 2][r + (k & 1) * 2], a[4 * j + k / 2][r + (k & 1) * 2], c);
                t += bf_lo(c) + bf_hi(c);
            }
            t += __shfl_xor_sync(0xffffffffu, t, 1);
            t += __shfl_xor_sync(0xffffffffu, t, 2);
            ex[r] = min(max(__float_as_uint(13.9f * __fsqrt_rn(t)) >> 23, 72u), 198u);
            if ((lane & 3) == 0)
                asm volatile("st.shared.u32 [%0], %1;\n" ::"r"(sbase + P1_OFF_EX + (wg * 64 + w * 16 + r * 8 + (lane >> 2)) * 4), "r"(ex[r] << 23) : "memory");
            const uint32_t f = (258u - ex[r]) * 0x00800080u;
#pragma unroll
            for (int k = 0; k < 48; k++) a[k >> 1][r + (k & 1) * 2] = bf2_to_h2(bf2_mul(bf2_mul(a[k >> 1][r + (k & 1) * 2], f), 0x07800780u));
        }
        const uint32_t sc2 = pack_f16(__uint_as_float(min(ex[0], 142u) << 23), __uint_as_float(min(ex[1], 142u) << 23));
        TRACEW(110 + warp, 7);
        bar_sync(5, 256);
        if (warp < 4) p1_consumer<0>(a, sc2, sbase, w, lane, zero);
        else p1_consumer<1>(a, sc2, sbase, w, lane, zero);
        cluster_sync();
        TSTAMP(0, 30);
    }
}

constexpr int P2_B = 24576, P2_NB = 4;
constexpr int P2_A = 3072, P2_NA = 8;
constexpr int P2_XROW = C_DIM * 2;
constexpr int P2_OFF_A = P2_B * P2_NB;
constexpr int P2_OFF_X = P2_OFF_A + 3 * P2_NA * P2_A;
constexpr int P2_XHALF = 32 * P2_XROW + 64;
constexpr int P2_OFF_BIAS = P2_OFF_X + 64 * P2_XROW + 128;
constexpr int P2_OFF_ONES = P2_OFF_BIAS + 48 * 128;
constexpr int P2_OFF_BAR = P2_OFF_ONES + 256;
constexpr int P2_SMEM = P2_OFF_BAR + (2 * P2_NB + 6 * P2_NA + 7) * 8;
constexpr int P2_LAG = 16;
constexpr int P2_NCL = NUM_CTAS / 2, P2_ITEMS = NT128 / P2_NCL, P2_SHARED = NT128 - P2_ITEMS * P2_NCL;
constexpr int P2_NPOS = P2_LAG * (P2_ITEMS - 1) + 48;
constexpr int P2_RAW = 24;
constexpr int P2_XC = 8 * P2_XROW;
#define P2_DELTA 7
#define P2_T0 4
#define P2_SLACK 0
__device__ __forceinline__ int p2_start(int n) { return n < 0 ? 0 : n == P2_ITEMS ? P2_NPOS - 24 : P2_LAG * n; }
__device__ __forceinline__ int p2_tile(int cl, int n) {
    return n == 0 ? NT128 - 1 - cl : n < 0 || n == P2_ITEMS ? NT128 - 1 - P2_NCL - (cl >> 1) : cl + P2_NCL * (n - 1);
}

#define P2_EG 2
__device__ __forceinline__ uint32_t p2_pair(const uint32_t (&acc)[P2_NACC], int i) {
    return pack_bf16(h_lo(acc[i / 2]), h_hi(acc[i / 2]));
}
__device__ __forceinline__ void p2_epilogue(const uint32_t (&acc0)[P2_NACC], const uint32_t (&acc1)[P2_NACC], uint32_t up, uint32_t sx, int zero) {
    uint32_t v[2][P2_EG][4];
    auto load = [&](int c, uint32_t a) {
#pragma unroll
        for (int j = 0; j < P2_EG; j++) {
            const int u = c * P2_EG + j;
            asm volatile("ld.shared.v4.u32 {%0,%1,%2,%3}, [%4];\n" : "=r"(v[c & 1][j][0]), "=r"(v[c & 1][j][1]), "=r"(v[c & 1][j][2]), "=r"(v[c & 1][j][3])
                         : "r"(a + (u >> 1) * 64 + (u & 1) * 4 * P2_XROW) : "memory");
        }
    };
    load(0, sx);
#pragma unroll
    for (int c = 0; c < 24 / P2_EG; c++) {
        if (c + 1 < 24 / P2_EG) load(c + 1, sx + (v[c & 1][P2_EG - 1][0] & zero));
#pragma unroll
        for (int j = 0; j < P2_EG; j++) {
            const int u = c * P2_EG + j, i = 16 * ((u >> 1) % 6) + 2 * (u & 1);
            const uint32_t (&acc)[P2_NACC] = u < 12 ? acc0 : acc1;
            uint32_t (&w)[4] = v[c & 1][j];
#pragma unroll
            for (int e = 0; e < 4; e++) w[e] = bf2_fma(p2_pair(acc, i + 4 * e), up, w[e]);
            asm volatile("st.shared.v4.u32 [%4], {%0,%1,%2,%3};\n" ::"r"(w[0]), "r"(w[1]), "r"(w[2]), "r"(w[3]),
                         "r"(sx + (u >> 1) * 64 + (u & 1) * 4 * P2_XROW) : "memory");
        }
    }
}

__device__ __forceinline__ void p2_unpack(uint32_t (&u)[4], uint32_t o1, uint32_t o2, uint32_t o3) {
    u[2] = bitsel(o1, 0x00040004u, SPARE);
    u[1] = bitsel(o2, 0x00040004u, SPARE);
    u[3] = bitsel(o3, 0x00040004u, SPARE);
    const uint32_t t = bitsel(prmt(o1, o2, 0x6341), prmt(o1, o3, 0x6240) << 3, 0x38383838u);
    u[0] = bitsel(bitsel(t, prmt(o2, o3, 0x7351) << 1, 0x80808080u), 0x00040004u, SPARE);
}
__device__ __forceinline__ void p2_epilogue_add(const uint32_t (&acc)[P2_NACC], uint32_t upf, uint8_t* o) {
    auto up = [&](int i) { return bf2_mul(p2_pair(acc, i), upf); };
#pragma unroll
    for (int t = 0; t < 6; t++)
#pragma unroll
        for (int r = 0; r < 2; r++)
            asm volatile("red.global.add.noftz.v4.bf16x2 [%0], {%1,%2,%3,%4};\n" ::"l"(o + t * 64 + r * 4 * P2_XROW),
                         "r"(up(16 * t + 2 * r)), "r"(up(16 * t + 2 * r + 4)), "r"(up(16 * t + 2 * r + 8)), "r"(up(16 * t + 2 * r + 12)) : "memory");
}

__global__ void __cluster_dims__(2, 1, 1) __launch_bounds__(512, 1)
pass2_kernel(const __nv_bfloat16* __restrict__ x, const __nv_bfloat16* __restrict__ grn_g, __nv_bfloat16* __restrict__ out, int zero) {
    extern __shared__ __align__(1024) uint8_t smem[];
    const uint32_t sbase = smem_u32(smem);
    const uint32_t bar_bfull = sbase + P2_OFF_BAR, bar_bempty = bar_bfull + P2_NB * 8;
    const uint32_t bar_afull = bar_bempty + P2_NB * 8, bar_aempty = bar_afull + 3 * P2_NA * 8;
    const uint32_t bar_xfull = bar_aempty + 3 * P2_NA * 8, bar_oready = bar_xfull + 24, s_pos = bar_oready + 24;
    int tid;
    asm volatile("mov.u32 %0, %%tid.x;\n" : "=r"(tid));
    const int warp = __shfl_sync(0xffffffffu, tid >> 5, 0), lane = tid & 31;
    const uint32_t rank = cluster_rank();
    const int cl = blockIdx.x >> 1, pair = cl >> 1;
    const int head = pair < P2_SHARED && !(cl & 1), tail = pair < P2_SHARED && (cl & 1);
    const int k0 = (pair + 4 * (cl & 1)) % 6 * 8;
    auto wait_pos = [&](int target) {
        int v;
        while (true) {
            asm volatile("ld.volatile.shared.u32 %0, [%1];\n" : "=r"(v) : "r"(s_pos) : "memory");
            if (v >= target) break;
            SAFE_BREAK;
            __nanosleep(100);
        }
    };

    TSTAMP(1, 0);
    if (tid == 384) {
        for (int i = 0; i < P2_NB; i++) {
            mbar_init(bar_bfull + i * 8, 1);
            mbar_init(bar_bempty + i * 8, 24);
        }
        for (int i = 0; i < 3 * P2_NA; i++) {
            mbar_init(bar_afull + i * 8, 1);
            mbar_init(bar_aempty + i * 8, 4);
        }
        for (int i = 0; i < 3; i++) {
            mbar_init(bar_xfull + i * 8, 2);
            mbar_init(bar_oready + i * 8, 4);
        }
        asm volatile("st.shared.u32 [%0], 0;\n" ::"r"(s_pos) : "memory");
        asm volatile("fence.mbarrier_init.release.cluster;\n" ::: "memory");
    }
    __syncthreads();
    cluster_sync_relaxed();

    if (warp >= 12) {
        reg_dec<24>();
        if (warp == 12) {
            const uint8_t* wsrc = reinterpret_cast<const uint8_t*>(g_w2img) + rank * (P2_B / 2);
            int kb = k0;
            gdc_wait();
#pragma unroll 1
            for (int p = 0; p < P2_NPOS; p++) {
                const int st = p & 3;
                if (p == P2_RAW) {
                    flag_wait<true>(&g_prog[1][0], NUM_CTAS);
                    asm volatile("fence.proxy.async.global;\n" ::: "memory");
                    wsrc += sizeof(g_w2img[0]);
                }
                const int idle = (p < P2_LAG || p >= P2_NPOS - P2_LAG) + (p < 2 * P2_LAG ? !head || p >= 24 : p >= P2_NPOS - 2 * P2_LAG && (!tail || p < P2_NPOS - 24));
                mbar_wait(bar_bempty + st * 8, (~p >> 2) & 1);
                if (elect_one()) {
                    mbar_expect_tx(bar_bfull + st * 8, P2_B);
                    bulk_g2s_mc(sbase + st * P2_B + rank * (P2_B / 2), wsrc + kb * P2_B, P2_B / 2, bar_bfull + st * 8, (uint16_t)3);
                    asm volatile("st.volatile.shared.u32 [%0], %1;\n" ::"r"(s_pos), "r"(p) : "memory");
                    if (rank == 0) asm volatile("red.relaxed.gpu.global.add.u32 [%0], 1;\n" ::"l"(&g_prog[0][0]) : "memory");
                    if (idle) asm volatile("mbarrier.arrive.shared::cta.b64 _, [%0], %1;\n" ::"r"(bar_bempty + st * 8), "r"(8 * idle) : "memory");
                }
                __syncwarp();
                if (++kb == 48) kb = 0;
            }
            mbar_wait(bar_bempty, 1);
            if (lane == 0) mbar_arrive(bar_bfull);
        } else if (warp == 13) {
            const int w = lane < 3 ? lane : 0;
            const uint32_t dst0 = sbase + P2_OFF_A + w * P2_NA * P2_A;
            const uint32_t bf = bar_afull + w * P2_NA * 8, be = bar_aempty + w * P2_NA * 8;
            int n = (w == 2 && head ? -1 : w) - 3, left = 0, u = 0, c = 0;
            const uint8_t* src = nullptr;
            bool act = lane < 3;
            gdc_wait();
            while (__any_sync(0xffffffffu, act)) {
                if (left == 0) {
                    n += 3;
                    left = n >= P2_ITEMS + tail ? -1 : n < 0 || n == P2_ITEMS ? 24 : 48;
                    u = (k0 + p2_start(n)) % 48;
                    src = reinterpret_cast<const uint8_t*>(g_h) + (size_t)p2_tile(cl, n) * (2 * H_TILE) + rank * H_HALF + u * H_STEP;
                }
                const bool ok = act && mbar_test(be + ((c - 1) & 7) * 8, (~c >> 3) & 1);
                if (ok) {
                    const int st = c & 7;
                    if (left > 0) {
                        mbar_expect_tx(bf + st * 8, P2_A);
                        bulk_g2s(dst0 + st * P2_A, src, P2_A, bf + st * 8);
                    } else {
                        mbar_arrive(bf + st * 8);
                        act = false;
                    }
                    src += H_STEP;
                    if (++u == 48) { u = 0; src -= 48 * H_STEP; }
                    c++;
                    left--;
                }
                SAFE_BREAK;
                if (!__any_sync(0xffffffffu, ok)) __nanosleep(100);
            }
        } else if (warp == 14) {
            const uint32_t sx = sbase + P2_OFF_X;
            size_t o = 0;
            int w = head ? 2 : 0, wp = 0;
            uint32_t par = 0;
#pragma unroll 1
            for (int n = -head; n <= P2_ITEMS; n++) {
                const size_t on = (size_t)(2 * p2_tile(cl, n) + rank) * (64 * C_DIM * 2);
                const uint32_t xf = bar_xfull + w * 8;
                const bool st = n + head > 0, ld = n < P2_ITEMS;
                if (st) {
                    mbar_wait(bar_oready + wp * 8, (par >> wp) & 1);
                    par ^= 1u << wp;
                }
                if (lane == 0) {
                    if (n == 1 && head) {
                        asm volatile("cp.async.bulk.wait_group 0;\nfence.proxy.async.global;\n" ::: "memory");
                        asm volatile("st.release.gpu.global.u32 [%0], 1;\n" ::"l"(&g_half[pair][rank]) : "memory");
                    }
                    if (ld) mbar_expect_tx(xf, 64 * C_DIM * 2);
                    int t = st && ld ? 4 * (P2_LAG * n + 32 + P2_T0) : -256;
#pragma unroll 1
                    for (int c = 0; st && c < 64 * P2_XROW; c += P2_XC, t += 3) {
                        wait_pos(min(t >> 2, P2_NPOS - 1));
                        bulk_s2g(reinterpret_cast<uint8_t*>(out) + o + c, sx + c + (c >= 32 * P2_XROW ? 64 : 0), P2_XC);
                    }
                    asm volatile("cp.async.bulk.commit_group;\ncp.async.bulk.wait_group.read 0;\n" ::: "memory");
#pragma unroll 1
                    for (int c = 0; ld && c < 64 * P2_XROW; c += P2_XC, t += 3) {
                        wait_pos(min(t >> 2, P2_NPOS - 1));
                        bulk_g2s(sx + c + (c >= 32 * P2_XROW ? 64 : 0), reinterpret_cast<const uint8_t*>(x) + on + c, P2_XC, xf);
                    }
                    if (rank == 0 && n > 0 && n < P2_ITEMS - 1)
                        flag_wait<false>(&g_prog[0][0], P2_NCL * (P2_LAG * n + 48 + P2_SLACK) + (tail ? P2_SHARED - P2_NCL : P2_SHARED) * P2_DELTA);
                    if (ld) mbar_arrive(xf);
                }
                __syncwarp();
                o = on;
                wp = w;
                w = w == 2 ? 0 : w + 1;
            }
            asm volatile("cp.async.bulk.wait_group 0;\n" ::: "memory");
        }
        __syncwarp();
        cluster_sync();
    } else {
        reg_inc<160>();
        const int wg = warp >> 2, w = warp & 3, g = lane >> 2, q = lane & 3;
        const uint32_t sx = sbase + P2_OFF_X + (g & 1) * P2_XHALF + (w * 8 + (g >> 1)) * P2_XROW + q * 16;
        const uint32_t af = bar_afull + wg * P2_NA * 8;
        const uint32_t s_a = sbase + P2_OFF_A + wg * P2_NA * P2_A + (lane >> 3) * 512 + (lane & 7) * 64 + ((w ^ ((lane & 7) >> 1)) << 4);
        uint32_t acc0[P2_NACC], acc1[P2_NACC], up;
        uint4 a[2][2];

        {
            float* s_red = reinterpret_cast<float*>(smem + P2_OFF_ONES);
            float gx[4], part = 0.f;
            __nv_bfloat16 gg[4];
#pragma unroll
            for (int i = 0; i < 4; i++) gg[i] = grn_g[tid + 384 * i];
            TSTAMP(1, 27);
            gdc_wait();
            TSTAMP(1, 1);
            if (blockIdx.x == 120 && tid < (LN_RING + 3) * 2) (&g_flag[0][0][0])[tid * 8] = 0;
            if (blockIdx.x == 121 && tid == 0) g_epoch++;
#pragma unroll
            for (int i = 0; i < 4; i++) gx[i] = __ldcg(&g_sums[0][tid + 384 * i]) + __ldcg(&g_sums[1][tid + 384 * i]);
            const float bias = __ldcg(&g_sums[0][HID + tid]) + __ldcg(&g_sums[1][HID + tid]);
            const float gs = w2_scale(__float_as_uint(__ldcg(&g_sums[0][HID + C_DIM])) | __float_as_uint(__ldcg(&g_sums[1][HID + C_DIM])));
            float mg = 0.f;
#pragma unroll
            for (int i = 0; i < 4; i++) {
                gx[i] = sqrtf(gx[i] * (HSCALE * HSCALE) + 1e-6f);
                part += gx[i];
                gx[i] *= __bfloat162float(gg[i]);
                mg = fmaxf(mg, fabsf(gx[i]));
            }
#pragma unroll
            for (int o = 16; o > 0; o >>= 1) part += __shfl_xor_sync(0xffffffffu, part, o);
            const uint32_t mgw = __reduce_max_sync(0xffffffffu, __float_as_uint(mg));
            const uint32_t mbw = __reduce_max_sync(0xffffffffu, __float_as_uint(fabsf(bias)));
            TSTAMP(1, 26);
            if (lane == 0) *reinterpret_cast<float4*>(s_red + warp * 4) = make_float4(part, __uint_as_float(mgw), __uint_as_float(mbw), 0.f);
            bar_sync(1, 384);
            float tot = 0.f, mb = 0.f;
#pragma unroll
            for (int i = 0; i < 12; i++) {
                const float4 t = *reinterpret_cast<const float4*>(s_red + i * 4);
                tot += t.x;
                mg = fmaxf(mg, t.y);
                mb = fmaxf(mb, t.z);
            }
            const float inv = 1.0f / (tot * (1.0f / HID) + 1e-6f);
            const uint32_t ej = min((__float_as_uint(fmaxf(fmaf(mg, inv, 1.0f) * HSCALE, mb * gs * 0x1p-13f)) >> 23) + 1, 250u);
            const float dn = __uint_as_float((254u - ej) << 23);
            up = min(ej + 127u - (__float_as_uint(gs) >> 23), 254u) * 0x00800080u;
            bar_sync(1, 384);
            {
                const float b = bias * gs * dn;
                const uint32_t hi = pack_f16(b, 0.f);
                *reinterpret_cast<uint2*>(smem + P2_OFF_BIAS + tid * 16) = make_uint2(pack_f16(b, b - h_lo(hi)), 0u);
            }
#pragma unroll
            for (int i = 0; i < 4; i++) {
                const int k = tid + 384 * i;
                *reinterpret_cast<__half*>(smem + P2_OFF_BIAS + ((k >> 4) * 4 + ((k >> 1) & 3)) * 16 + 8 + ((k >> 3) & 1) * 4 + (k & 1) * 2) =
                    __float2half_rn(fmaf(gx[i], inv, 1.0f) * (HSCALE * dn));
            }
            TSTAMP(1, 25);
            if (tid < 16) reinterpret_cast<uint4*>(smem + P2_OFF_ONES)[tid] = make_uint4(tid < 8 ? 0x3c003c00u : 0u, 0u, 0u, 0u);
            asm volatile("fence.proxy.async.shared::cta;\n" ::: "memory");
            bar_sync(1, 384);
        }
        TSTAMP(1, 28);
        if (wg == 1) {
            constexpr int N = sizeof(g_w2img[0]) / 16, PER = (N + NUM_CTAS - 1) / NUM_CTAS;
            uint4 v[5];
#pragma unroll
            for (int i = 0; i < 5; i++) v[i] = __ldcg(&g_w2img[0][min(blockIdx.x * PER + (tid & 127) + 128 * i, N - 1)]);
#pragma unroll
            for (int i = 0; i < 5; i++) {
                const int j = min(blockIdx.x * PER + (tid & 127) + 128 * i, N - 1);
                const uint32_t* t = reinterpret_cast<const uint32_t*>(smem + P2_OFF_BIAS + (j / 768) * 64 + 8 + (j & 8) / 2);
                auto sc = [&](uint32_t u, int e) { return (h2_mul(u, t[4 * e]) + 0x00040004u) & 0xfff8fff8u; };
                g_w2img[1][j] = make_uint4(sc(v[i].x, 0), sc(v[i].y, 1), sc(v[i].z, 2), sc(v[i].w, 3));
            }
            asm volatile("fence.proxy.async.global;\n" ::: "memory");
            bar_sync(2, 128);
            if (tid == 128) asm volatile("fence.acq_rel.gpu;\nred.release.gpu.global.add.u32 [%0], 1;\n" ::"l"(&g_prog[1][0]) : "memory");
        }

        const int who = __shfl_sync(0xffffffffu, lane == 2 ? 0 : lane < 2 ? 1 : 2, lane);
        const uint32_t rel0 = who ? mapa(bar_bempty, lane & 1) : mapa(bar_aempty + wg * P2_NA * 8, rank), rel1 = rel0 + (who ? 0 : 32);
        auto publish = [&]() {
            asm volatile("fence.proxy.async.shared::cta;\n" ::: "memory");
            __syncwarp();
            if (who == 0) mbar_arrive(bar_oready + wg * 8);
        };
        bool ok_a, pend = false;
        uint32_t pa = 0, s_t;
        auto fetch = [&](int j, bool raw) {
            uint32_t o[6], u0[4], u1[4];
            uint2 t0, t1;
            if (raw) {
                asm volatile("ld.shared.v2.u32 {%0,%1}, [%2];\n" : "=r"(t0.x), "=r"(t0.y) : "r"(s_t + j * 128) : "memory");
                asm volatile("ld.shared.v2.u32 {%0,%1}, [%2];\n" : "=r"(t1.x), "=r"(t1.y) : "r"(s_t + j * 128 + 64) : "memory");
            }
            const bool ok_b = mbar_test(bar_bfull + (j & 3) * 8, j >> 2);
            if (j == 7) pa ^= 1;
            ok_a = mbar_test(af + ((j + 1) & 7) * 8, pa);
            asm volatile("ldmatrix.sync.aligned.m8n8.x4.trans.shared.b16 {%0,%1,%2,%3}, [%4];\n"
                         : "=r"(o[0]), "=r"(o[1]), "=r"(o[2]), "=r"(o[3]) : "r"(s_a + j * P2_A) : "memory");
            asm volatile("ldmatrix.sync.aligned.m8n8.x2.trans.shared.b16 {%0,%1}, [%2];\n"
                         : "=r"(o[4]), "=r"(o[5]) : "r"(s_a + j * P2_A + 2048) : "memory");
            p2_unpack(u0, o[0], o[1], o[2]);
            p2_unpack(u1, o[3], o[4], o[5]);
            if (raw) {
                u0[0] = h2_mul(u0[0], t0.x); u0[1] = h2_mul(u0[1], t0.x); u0[2] = h2_mul(u0[2], t0.y); u0[3] = h2_mul(u0[3], t0.y);
                u1[0] = h2_mul(u1[0], t1.x); u1[1] = h2_mul(u1[1], t1.x); u1[2] = h2_mul(u1[2], t1.y); u1[3] = h2_mul(u1[3], t1.y);
            }
            a[j & 1][0] = make_uint4(u0[0], u0[1], u0[2], u0[3]);
            a[j & 1][1] = make_uint4(u1[0], u1[1], u1[2], u1[3]);
            if (!ok_b) mbar_wait(bar_bfull + (j & 3) * 8, j >> 2);
        };
        auto table = [&](int pos) { s_t = sbase + P2_OFF_BIAS + q * 16 + 8 + (k0 + pos) % 48 * 128; };
        const uint64_t db0 = make_desc(sbase, 128, 256);
        auto block8 = [&](bool raw, int pos, int thr0) {
#pragma unroll
            for (int j = 0; j < 8; j++) {
                const uint64_t db = db0 + (j & 3) * (P2_B / 16);
                wg_fence();
                mma_rs_n192(acc0, a[j & 1][0], db);
                mma_rs_n192(acc1, a[j & 1][0], db + 384);
                mma_rs_n192(acc0, a[j & 1][1], db + 768);
                mma_rs_n192(acc1, a[j & 1][1], db + 768 + 384);
                wg_commit();
                const uint32_t rel = ((j - 1) & 4 ? rel1 : rel0) + ((j - 1) & 3) * 8;
                wg_wait<1>();
                if (who < (j ? 2 : thr0)) mbar_arrive_cluster(rel);
                if (!ok_a) {
                    if (j == 0 && pend) { publish(); pend = false; }
                    mbar_wait(af + ((j + 1) & 7) * 8, pa);
                }
                if (raw && j == 7) table(pos + 8);
                fetch((j + 1) & 7, raw && (j < 7 || pos + 8 < P2_RAW));
            }
        };
        int n = wg == 2 && head ? -1 : wg, pos = p2_start(n);
        uint32_t px = 0;
        wait_pos(pos);
        mbar_wait(af, 0);
        table(pos);
        fetch(0, pos < P2_RAW);
#pragma unroll 1
        for (;; n += 3) {
            TSTAMP(1, 2 + n);
            const uint64_t ones = make_desc(sbase + P2_OFF_ONES + (n == P2_ITEMS ? 128 : 0), n == P2_ITEMS ? 0 : 128, 0);
            wg_fence();
            mma_ss_n192_init(acc0, ones, make_desc(sbase + P2_OFF_BIAS, 0, 128));
            mma_ss_n192_init(acc1, ones, make_desc(sbase + P2_OFF_BIAS + 3072, 0, 128));
            wg_commit();
            const int end = pos + (n < 0 || n == P2_ITEMS ? 24 : 48);
            int thr = 1;
#pragma unroll 1
            for (; pos < P2_RAW; pos += 8, thr = 2) block8(true, pos, thr);
#pragma unroll 1
            for (; pos < end; pos += 8, thr = 2) block8(false, pos, thr);
            if (n == P2_ITEMS) {
                flag_wait<true>(&g_half[pair][rank], 1);
                wg_wait<0>();
                if (who == 1) mbar_arrive_cluster(rel0 + 24);
                uint8_t* o = reinterpret_cast<uint8_t*>(out) + (size_t)((2 * p2_tile(cl, -1) + rank) * 64 + (g & 1) * 32 + w * 8 + (g >> 1)) * P2_XROW + q * 16;
                p2_epilogue_add(acc0, up, o);
                p2_epilogue_add(acc1, up, o + 384);
                break;
            }
            wg_wait<0>();
            if (who == 1) mbar_arrive_cluster(rel0 + 24);
            mbar_wait(bar_xfull + wg * 8, px);
            px ^= 1;
            __syncwarp();
            p2_epilogue(acc0, acc1, up, sx, zero);
            if (n + 3 >= P2_ITEMS + tail) { publish(); break; }
            if (pos != p2_start(n + 3)) {
                publish();
                pos += 8;
                wait_pos(pos);
                mbar_wait(bar_bfull, 0);
            } else {
                pend = true;
                ok_a = false;
            }
        }
        TSTAMP(1, 29);
        cluster_sync();
        TSTAMP(1, 30);
    }
}

}

extern "C" void kernel_launch(void* const* d_in, const int* in_sizes, int n_in, void* d_out, int out_size) {
    const __nv_bfloat16* x = (const __nv_bfloat16*)d_in[0];
    const __nv_bfloat16* dw = (const __nv_bfloat16*)d_in[1];
    const __nv_bfloat16* w1 = (const __nv_bfloat16*)d_in[2];
    const __nv_bfloat16* w2 = (const __nv_bfloat16*)d_in[3];
    const __nv_bfloat16* grn_g = (const __nv_bfloat16*)d_in[4];
    const __nv_bfloat16* grn_b = (const __nv_bfloat16*)d_in[5];
    __nv_bfloat16* out = (__nv_bfloat16*)d_out;

    cudaFuncSetAttribute(pass1_kernel, cudaFuncAttributeMaxDynamicSharedMemorySize, P1_SMEM);
    cudaFuncSetAttribute(pass2_kernel, cudaFuncAttributeMaxDynamicSharedMemorySize, P2_SMEM);

    typedef CUresult (*EncodeFn)(CUtensorMap*, CUtensorMapDataType, cuuint32_t, void*, const cuuint64_t*, const cuuint64_t*,
                                 const cuuint32_t*, const cuuint32_t*, CUtensorMapInterleave, CUtensorMapSwizzle,
                                 CUtensorMapL2promotion, CUtensorMapFloatOOBfill);
    static EncodeFn encode = nullptr;
    if (!encode) {
        cudaDriverEntryPointQueryResult qres;
        cudaGetDriverEntryPoint("cuTensorMapEncodeTiled", (void**)&encode, cudaEnableDefault, &qres);
    }
    CUtensorMap wmap;
    const cuuint64_t gdim[2] = {HID, C_DIM};
    const cuuint64_t gstr[1] = {HID * 2};
    const cuuint32_t box[2] = {64, 192}, estr[2] = {1, 1};
    CUresult er = encode(&wmap, CU_TENSOR_MAP_DATA_TYPE_BFLOAT16, 2, (void*)w1, gdim, gstr, box, estr, CU_TENSOR_MAP_INTERLEAVE_NONE,
           CU_TENSOR_MAP_SWIZZLE_128B, CU_TENSOR_MAP_L2_PROMOTION_L2_128B, CU_TENSOR_MAP_FLOAT_OOB_FILL_NONE);
    if (er != CUDA_SUCCESS) printf("tensor map encode failed %d\n", (int)er);

    pass1_kernel<<<NUM_CTAS, 512, P1_SMEM>>>(wmap, x, dw, w2, grn_b, 0);

    cudaLaunchAttribute attr[1];
    attr[0].id = cudaLaunchAttributeProgrammaticStreamSerialization;
    attr[0].val.programmaticStreamSerializationAllowed = 1;
    cudaLaunchConfig_t cfg = {};
    cfg.gridDim = dim3(NUM_CTAS);
    cfg.stream = 0;
    cfg.attrs = attr;
    cfg.numAttrs = 1;
    cfg.blockDim = dim3(512);
    cfg.dynamicSmemBytes = P2_SMEM;
    cudaLaunchKernelEx(&cfg, pass2_kernel, x, grn_g, out, 0);
}
```

```cpp
#include <cuda.h>
#include <cuda_runtime.h>
#include <cuda_bf16.h>
#include <cuda_fp16.h>
#include <stdint.h>
#include <stdio.h>

namespace {

constexpr int M_TOTAL = 384 * 384;
constexpr int C_DIM   = 384;
constexpr int HID     = 1536;
constexpr int NT128   = M_TOTAL / 128;
constexpr int NUM_CTAS = 132;

constexpr int NGRP = 11, GRP_CTAS = 12;
constexpr int LN_STEP = NUM_CTAS / 4, LN_RING = 2 * LN_STEP;
constexpr int NT_RING = NT128 - NGRP;
constexpr int LN_TILE = 128 * C_DIM * 2;
constexpr int H_TILE = 64 * HID * 3 / 2;
constexpr int H_HALF = 3072, H_STEP = 6144;

__device__ __align__(1024) uint4 g_h[(size_t)M_TOTAL * HID * 3 / 32];
__device__ __align__(1024) uint4 g_ln[LN_RING * LN_TILE / 16];
__device__ __align__(1024) uint4 g_w2img[2][HID * C_DIM * 2 / 16];
__device__ __align__(16) float g_sums[2][HID + 512];
__device__ unsigned g_epoch;
__device__ __align__(128) unsigned g_prog[2][32];
__device__ __align__(128) unsigned g_half[32][2];
__device__ unsigned g_flag[LN_RING + 3][2][8];
#define TSTAMP(k, i)
#define TRACE(wg, pos, i)
#define TRACEW(pos, i)

#define TR2(wg, pos, i)
__host__ __device__ __forceinline__ int perm32(int n) {
    return (n & ~31) | (((n >> 1) & 3) << 3) | (((n >> 3) & 3) << 1) | (n & 1);
}

__device__ __forceinline__ uint32_t smem_u32(const void* p) { return (uint32_t)__cvta_generic_to_shared(p); }

__device__ __forceinline__ void mbar_init(uint32_t bar, uint32_t count) {
    asm volatile("mbarrier.init.shared::cta.b64 [%0], %1;\n" ::"r"(bar), "r"(count) : "memory");
}
__device__ __forceinline__ void mbar_expect_tx(uint32_t bar, uint32_t bytes) {
    asm volatile("mbarrier.arrive.expect_tx.shared::cta.b64 _, [%0], %1;\n" ::"r"(bar), "r"(bytes) : "memory");
}
__device__ __forceinline__ void mbar_arrive(uint32_t bar) {
    asm volatile("mbarrier.arrive.shared::cta.b64 _, [%0];\n" ::"r"(bar) : "memory");
}
__device__ __forceinline__ void mbar_arrive_cluster(uint32_t bar_cluster_addr) {
    asm volatile("mbarrier.arrive.shared::cluster.b64 _, [%0];\n" ::"r"(bar_cluster_addr) : "memory");
}
#define SAFE_BREAK
__device__ __forceinline__ void mbar_wait(uint32_t bar, uint32_t parity) {
    asm volatile(
        "{\n"
        ".reg .pred p;\n"
        "LAB_WAIT:\n"
        "mbarrier.try_wait.parity.shared::cta.b64 p, [%0], %1;\n"
        "@!p bra LAB_WAIT;\n"
        "}\n" ::"r"(bar), "r"(parity) : "memory");
}
__device__ __forceinline__ bool mbar_test(uint32_t bar, uint32_t parity) {
    uint32_t ok;
    asm volatile("{\n.reg .pred p;\n"
                 "mbarrier.test_wait.parity.shared::cta.b64 p, [%1], %2;\n"
                 "selp.u32 %0, 1, 0, p;\n}\n" : "=r"(ok) : "r"(bar), "r"(parity) : "memory");
    return ok != 0;
}
__device__ __forceinline__ uint32_t mapa(uint32_t addr, uint32_t rank) {
    uint32_t r;
    asm volatile("mapa.shared::cluster.u32 %0, %1, %2;\n" : "=r"(r) : "r"(addr), "r"(rank));
    return r;
}
__device__ __forceinline__ void bulk_g2s(uint32_t dst, const void* src, uint32_t bytes, uint32_t bar) {
    asm volatile("cp.async.bulk.shared::cluster.global.mbarrier::complete_tx::bytes [%0], [%1], %2, [%3];\n"
                 ::"r"(dst), "l"(src), "r"(bytes), "r"(bar) : "memory");
}
__device__ __forceinline__ void bulk_g2s_mc(uint32_t dst, const void* src, uint32_t bytes, uint32_t bar, uint16_t mask) {
    asm volatile("cp.async.bulk.shared::cluster.global.mbarrier::complete_tx::bytes.multicast::cluster [%0], [%1], %2, [%3], %4;\n"
                 ::"r"(dst), "l"(src), "r"(bytes), "r"(bar), "h"(mask) : "memory");
}
__device__ __forceinline__ void tma2(uint32_t dst, const CUtensorMap* map, int c0, int c1, uint32_t bar) {
    asm volatile("cp.async.bulk.tensor.2d.shared::cluster.global.tile.mbarrier::complete_tx::bytes [%0], [%1, {%2, %3}], [%4];\n"
                 ::"r"(dst), "l"(map), "r"(c0), "r"(c1), "r"(bar) : "memory");
}
template <bool ACQ>
__device__ __forceinline__ uint32_t flag_wait(const unsigned* p, unsigned target) {
    unsigned v, n = 0;
    do {
        if (ACQ) asm volatile("ld.acquire.gpu.global.u32 %0, [%1];\n" : "=r"(v) : "l"(p) : "memory");
        else asm volatile("ld.relaxed.gpu.global.u32 %0, [%1];\n" : "=r"(v) : "l"(p) : "memory");
        n++;
    } while (v < target);
    return n == 1;
}
__device__ __forceinline__ void ldsm4t(uint32_t (&r)[4], uint32_t addr) {
    asm volatile("ldmatrix.sync.aligned.m8n8.x4.trans.shared.b16 {%0,%1,%2,%3}, [%4];\n"
                 : "=r"(r[0]), "=r"(r[1]), "=r"(r[2]), "=r"(r[3]) : "r"(addr) : "memory");
}
__device__ __forceinline__ void bulk_s2g(void* dst, uint32_t src, uint32_t bytes) {
    asm volatile("cp.async.bulk.global.shared::cta.bulk_group [%0], [%1], %2;\n" ::"l"(dst), "r"(src), "r"(bytes) : "memory");
}
__device__ __forceinline__ void cluster_sync() {
    asm volatile("barrier.cluster.arrive.aligned;\nbarrier.cluster.wait.aligned;\n" ::: "memory");
}
__device__ __forceinline__ void cluster_sync_relaxed() {
    asm volatile("barrier.cluster.arrive.relaxed.aligned;\nbarrier.cluster.wait.aligned;\n" ::: "memory");
}
__device__ __forceinline__ void gdc_wait() { asm volatile("griddepcontrol.wait;\n" ::: "memory"); }
__device__ __forceinline__ void gdc_launch() { asm volatile("griddepcontrol.launch_dependents;\n" ::: "memory"); }
__device__ __forceinline__ uint32_t cluster_rank() {
    uint32_t r;
    asm volatile("mov.u32 %0, %%cluster_ctarank;\n" : "=r"(r));
    return r;
}
__device__ __forceinline__ bool elect_one() {
    uint32_t pred;
    asm volatile("{\n.reg .pred p;\nelect.sync _|p, 0xffffffff;\nselp.u32 %0, 1, 0, p;\n}\n" : "=r"(pred));
    return pred != 0;
}
__device__ __forceinline__ void wg_fence() { asm volatile("wgmma.fence.sync.aligned;\n" ::: "memory"); }
__device__ __forceinline__ void wg_commit() { asm volatile("wgmma.commit_group.sync.aligned;\n" ::: "memory"); }
template <int N> __device__ __forceinline__ void wg_wait() {
    asm volatile("wgmma.wait_group.sync.aligned %0;\n" ::"n"(N) : "memory");
}
template <int R> __device__ __forceinline__ void reg_inc() { asm volatile("setmaxnreg.inc.sync.aligned.u32 %0;\n" ::"n"(R)); }
template <int R> __device__ __forceinline__ void reg_dec() { asm volatile("setmaxnreg.dec.sync.aligned.u32 %0;\n" ::"n"(R)); }
__device__ __forceinline__ void bar_sync(int id, int n) { asm volatile("bar.sync %0, %1;\n" ::"r"(id), "r"(n) : "memory"); }
__device__ __forceinline__ void bar_arrive(int id, int n) { asm volatile("bar.arrive %0, %1;\n" ::"r"(id), "r"(n) : "memory"); }

__device__ __forceinline__ uint64_t make_desc(uint32_t saddr, uint32_t lbo, uint32_t sbo) {
    return (uint64_t)((saddr & 0x3FFFF) >> 4) | ((uint64_t)(lbo >> 4) << 16) | ((uint64_t)(sbo >> 4) << 32);
}

__device__ __forceinline__ void stg128_cs(void* p, uint32_t a, uint32_t b, uint32_t c, uint32_t d) {
    asm volatile("st.global.cs.v4.u32 [%0], {%1,%2,%3,%4};\n" ::"l"(p), "r"(a), "r"(b), "r"(c), "r"(d) : "memory");
}
__device__ __forceinline__ uint32_t pack_bf16(float lo, float hi) {
    uint32_t r;
    asm("cvt.rn.bf16x2.f32 %0, %1, %2;\n" : "=r"(r) : "f"(hi), "f"(lo));
    return r;
}
__device__ __forceinline__ float bf_lo(uint32_t v) { return __uint_as_float(v << 16); }
__device__ __forceinline__ float bf_hi(uint32_t v) { return __uint_as_float(v & 0xffff0000u); }
__device__ __forceinline__ uint32_t bf2_mul(uint32_t a, uint32_t b) {
    uint32_t r;
    asm("mul.rn.bf16x2 %0, %1, %2;\n" : "=r"(r) : "r"(a), "r"(b));
    return r;
}
__device__ __forceinline__ uint32_t bf2_fma(uint32_t a, uint32_t b, uint32_t c) {
    uint32_t r;
    asm("fma.rn.bf16x2 %0, %1, %2, %3;\n" : "=r"(r) : "r"(a), "r"(b), "r"(c));
    return r;
}
__device__ __forceinline__ uint32_t bf2_add(uint32_t a, uint32_t b) {
    uint32_t r;
    asm("add.rn.bf16x2 %0, %1, %2;\n" : "=r"(r) : "r"(a), "r"(b));
    return r;
}
__device__ __forceinline__ uint32_t h2_mul(uint32_t a, uint32_t b) {
    uint32_t r;
    asm("mul.rn.f16x2 %0, %1, %2;\n" : "=r"(r) : "r"(a), "r"(b));
    return r;
}
__device__ __forceinline__ uint32_t h2_fma(uint32_t a, uint32_t b, uint32_t c) {
    uint32_t r;
    asm("fma.rn.f16x2 %0, %1, %2, %3;\n" : "=r"(r) : "r"(a), "r"(b), "r"(c));
    return r;
}
__device__ __forceinline__ uint32_t h2_add(uint32_t a, uint32_t b) {
    uint32_t r;
    asm("add.rn.f16x2 %0, %1, %2;\n" : "=r"(r) : "r"(a), "r"(b));
    return r;
}
__device__ __forceinline__ uint32_t pack_f16(float lo, float hi) {
    uint32_t r;
    asm("cvt.rn.f16x2.f32 %0, %1, %2;\n" : "=r"(r) : "f"(hi), "f"(lo));
    return r;
}
__device__ __forceinline__ float h_lo(uint32_t v) { return __low2float(*reinterpret_cast<const __half2*>(&v)); }
__device__ __forceinline__ float h_hi(uint32_t v) { return __high2float(*reinterpret_cast<const __half2*>(&v)); }
__device__ __forceinline__ uint32_t bf2_to_h2(uint32_t v) { return (v & 0x7fff7fffu) * 7u + v; }
__device__ __forceinline__ uint32_t prmt(uint32_t a, uint32_t b, uint32_t sel) {
    uint32_t r;
    asm("prmt.b32 %0, %1, %2, %3;\n" : "=r"(r) : "r"(a), "r"(b), "r"(sel));
    return r;
}
__device__ __forceinline__ uint32_t bitsel(uint32_t a, uint32_t b, uint32_t m) {
    uint32_t r;
    asm("lop3.b32 %0, %1, %2, %3, 0xd8;\n" : "=r"(r) : "r"(a), "r"(b), "r"(m));
    return r;
}
constexpr float KAPPA = 0.3292034911525734f;
constexpr uint32_t GELU_C2 = 0x40d940d9u;
constexpr float HSCALE = 1.0f / (2.0f * KAPPA);
__device__ __forceinline__ float w2_scale(uint32_t m) { return __uint_as_float((257u - max(m >> 23, 16u)) << 23); }
__device__ __forceinline__ void sched_break(int zero) {
    asm volatile("{\n.reg .pred p;\nsetp.ne.s32 p, %0, 0;\nSB_LOOP:\n@p nanosleep.u32 1;\n@p bra SB_LOOP;\n}\n" ::"r"(zero));
}

#define ACC8(d, o) "+r"(d[o + 0]), "+r"(d[o + 1]), "+r"(d[o + 2]), "+r"(d[o + 3]), "+r"(d[o + 4]), "+r"(d[o + 5]), "+r"(d[o + 6]), "+r"(d[o + 7])

__device__ __forceinline__ void mma_rs_n128(uint32_t (&d)[32], const uint32_t (&a)[4], uint64_t desc, int scale_d) {
    asm volatile(
        "{\n.reg .pred p;\nsetp.ne.b32 p, %37, 0;\n"
        "wgmma.mma_async.sync.aligned.m64n128k16.f16.f16.f16 "
        "{%0,%1,%2,%3,%4,%5,%6,%7,%8,%9,%10,%11,%12,%13,%14,%15,"
        "%16,%17,%18,%19,%20,%21,%22,%23,%24,%25,%26,%27,%28,%29,%30,%31},"
        "{%32,%33,%34,%35}, %36, p, 1, 1, 0;\n}\n"
        : ACC8(d, 0), ACC8(d, 8), ACC8(d, 16), ACC8(d, 24)
        : "r"(a[0]), "r"(a[1]), "r"(a[2]), "r"(a[3]), "l"(desc), "r"(scale_d));
}

__device__ __forceinline__ void mma_rs_n192(uint32_t (&d)[48], const uint4& a, uint64_t db) {
    asm volatile(
        "wgmma.mma_async.sync.aligned.m64n192k16.f16.f16.f16 "
        "{%0,%1,%2,%3,%4,%5,%6,%7,%8,%9,%10,%11,%12,%13,%14,%15,"
        "%16,%17,%18,%19,%20,%21,%22,%23,%24,%25,%26,%27,%28,%29,%30,%31,"
        "%32,%33,%34,%35,%36,%37,%38,%39,%40,%41,%42,%43,%44,%45,%46,%47},"
        "{%48,%49,%50,%51}, %52, 1, 1, 1, 0;\n"
        : ACC8(d, 0), ACC8(d, 8), ACC8(d, 16), ACC8(d, 24), ACC8(d, 32), ACC8(d, 40)
        : "r"(a.x), "r"(a.y), "r"(a.z), "r"(a.w), "l"(db));
}

#define P1_WPF 30
#define P1_PACE true
constexpr int P1_SLOT = LN_TILE / 2, P1_NST = 4;
constexpr int P1_X = 32 * C_DIM * 2;
constexpr int P1_OFF_X = P1_SLOT * P1_NST;
constexpr int P1_OFF_BAR = P1_OFF_X + P1_X;
constexpr int P1_OFF_TILE = P1_OFF_BAR + (2 * P1_NST + 2 + 4 + 4) * 8;
constexpr int P1_OFF_RAW = P1_OFF_TILE + 64;
constexpr int P1_OFF_EX = P1_OFF_RAW + 16;
constexpr int P1_SMEM = P1_OFF_EX + 128 * 4;

__device__ __forceinline__ float rsqrt_fast(float x) {
    float r;
    asm("rsqrt.approx.ftz.f32 %0, %1;\n" : "=f"(r) : "f"(x));
    return r;
}
__device__ __forceinline__ float row_sum(const uint32_t (&c)[4]) {
    const uint32_t u = bf2_add(bf2_add(c[0], c[1]), bf2_add(c[2], c[3]));
    float s = bf_lo(u) + bf_hi(u);
#pragma unroll
    for (int o = 1; o < 8; o <<= 1) s += __shfl_xor_sync(0xffffffffu, s, o);
    return s;
}
__device__ __forceinline__ uint32_t pace(uint32_t bar, uint32_t off, uint32_t val, uint32_t after, int zero) {
    asm volatile(
        "{\n.reg .pred p;\n.reg .b32 par;\n"
        "lop3.b32 par, %4, %2, %3, 0xea;\n"
        "mbarrier.test_wait.parity.shared::cta.b64 p, [%1], par;\n"
        "selp.u32 par, 1, 0, p;\n"
        "mbarrier.try_wait.parity.shared::cta.b64 p, [%1], par, 1000;\n"
        "@p or.b32 %0, %0, %2;\n"
        "}\n" : "+r"(val) : "r"(bar), "r"(zero), "r"(off), "r"(after));
    return val;
}
template <bool PACE>
__device__ __forceinline__ void ln_row(uint32_t (&v)[6][4], const uint32_t (&d)[6][4], uint32_t bar, uint32_t off, int zero,
                                       uint32_t bar_read) {
    uint32_t c[4];
#pragma unroll
    for (int i = 0; i < 6; i++)
#pragma unroll
        for (int k = 0; k < 4; k++) c[k] = bf2_fma(v[i][k], d[i][k], i ? c[k] : 0);
    const float inv = 1.0f / C_DIM;
    const float m = row_sum(c) * inv;
    uint32_t nm = pack_bf16(-m, -m);
    const float e = m + bf_lo(nm);
    if (bar_read) mbar_arrive(bar_read + (nm & zero));
    if (PACE) nm = pace(bar, off, nm, nm, zero);
#pragma unroll
    for (int i = 0; i < 6; i++) {
#pragma unroll
        for (int k = 0; k < 4; k++) {
            v[i][k] = bf2_fma(v[i][k], d[i][k], nm);
            c[k] = i ? bf2_fma(v[i][k], v[i][k], c[k]) : bf2_mul(v[i][k], v[i][k]);
        }
    }
    float r = KAPPA * rsqrt_fast(fmaxf(fmaf(-e, e, row_sum(c) * inv), 0.f) + 1e-5f);
    const float er = -e * r * 0x1p-116f;
    if (__any_sync(0xffffffffu, r < 0x1p-8f)) {
        const uint32_t p2 = __float_as_uint(r) & 0x7f800000u;
        r = __uint_as_float((__float_as_uint(r) & 0x007fffffu) | 0x3f800000u);
#pragma unroll
        for (int i = 0; i < 6; i++)
#pragma unroll
            for (int k = 0; k < 4; k++) v[i][k] = bf2_mul(v[i][k], p2 | p2 >> 16);
    }
    r *= 0x1p-116f;
    uint32_t rs = pack_bf16(r, r);
    const uint32_t sh = pack_bf16(er, er);
    if (PACE) rs = pace(bar, off, rs, sh, zero);
#pragma unroll
    for (int i = 0; i < 6; i++)
#pragma unroll
        for (int k = 0; k < 4; k++) v[i][k] = bf2_to_h2(bf2_fma(v[i][k], rs, sh));
}

template <int R>
__device__ __forceinline__ uint32_t gelu2(uint32_t a, uint32_t sc2) {
    uint32_t y, t;
    if (R) asm("{\n.reg .b16 l, h;\n.reg .b32 f;\nmov.b32 {l, h}, %2;\nmov.b32 f, {h, h};\nmul.rn.f16x2 %0, %1, f;\n}\n" : "=r"(y) : "r"(a), "r"(sc2));
    else asm("{\n.reg .b16 l, h;\n.reg .b32 f;\nmov.b32 {l, h}, %2;\nmov.b32 f, {l, l};\nmul.rn.f16x2 %0, %1, f;\n}\n" : "=r"(y) : "r"(a), "r"(sc2));
    asm("tanh.approx.f16x2 %0, %1;\n" : "=r"(t) : "r"(h2_mul(y, h2_fma(y, y, GELU_C2))));
    return h2_fma(a, t, a);
}
constexpr uint32_t SPARE = 0x40074007u;

__device__ __forceinline__ uint32_t p1_parity(uint32_t sbase) {
    uint32_t v;
    asm volatile("ld.shared.u32 %0, [%1];\n" : "=r"(v) : "r"(sbase + P1_OFF_TILE - 4) : "memory");
    return v;
}
template <int WG>
__device__ __forceinline__ void p1_consumer(const uint32_t (&a)[24][4], uint32_t sc2, uint32_t sbase, int w, int lane, int zero) {
    const uint32_t bar_full = sbase + P1_OFF_BAR, bar_empty = bar_full + P1_NST * 8;
    const uint32_t empty_remote = mapa(bar_empty, lane & 1) + (WG == 0 ? (lane & 2) * 4 : 0);
    const uint32_t bar_pace = bar_empty + P1_NST * 8 + 16 + w * 8;
    const int g = lane >> 2, q = lane & 3, cb = (blockIdx.x % GRP_CTAS) * 2 + WG;
    uint32_t acc[32], st[6][4] = {};
    float ssq[2] = {0.f, 0.f};
    TSTAMP(0, 1);

    uint8_t* hp = reinterpret_cast<uint8_t*>(g_h) + (size_t)(blockIdx.x / GRP_CTAS) * (2 * H_TILE) + ((cb * 2 + (w >> 1)) * H_STEP + (w & 1) * 1536) + g * 64 + (q ^ (g >> 1)) * 16;
    const uint64_t desc_base = make_desc(sbase, 16, 1024) | (1ull << 62);
#pragma unroll 1
    for (int i = 0;; i++) {
        const int s0 = (i & 1) * 16, par = (i >> 1) & 1;
        const uint64_t d0 = desc_base + (uint64_t)((i & 1) * (LN_TILE / 16));
        TRACE(WG, i, 0);
        if (WG == 0) mbar_wait(bar_full + s0, par);
        bar_sync(1 + WG, 256);
        TRACE(WG, i, 1);
        uint32_t step, more;
        wg_fence();
#pragma unroll
        for (int k = 0; k < 24; k++) {
            if (WG == 0 && k == 12) mbar_wait(bar_full + s0 + 8, par);
            mma_rs_n128(acc, a[k], d0 + (uint64_t)((k >> 2) * 1024 + (k & 3) * 2), k != 0);
            if (k == 23) bar_arrive(2 - WG, 256);
            if (k % 12 == 11) wg_commit();
        }
        asm volatile("ld.shared.v2.u32 {%0, %1}, [%2];\n" : "=r"(step), "=r"(more) : "r"(sbase + P1_OFF_TILE + (i & 3) * 16) : "memory");
        TRACE(WG, i, 2);
        if (WG == 1) {
            wg_wait<1>();
            if (lane < 2) mbar_arrive_cluster(empty_remote + s0);
        }
        hp += step;
        TRACE(WG, i, 3);
        if (zero) {
#pragma unroll
            for (int c = 0; c < 6; c++) stg128_cs(hp + c * 512, st[c][0], st[c][1], st[c][2], st[c][3]);
        }
        wg_wait<0>();
        TRACE(WG, i, 4);
        if (lane < (WG == 0 ? 4 : 2)) mbar_arrive_cluster(empty_remote + s0 + WG * 8);
        uint32_t sq[2], h[8][4];
#pragma unroll
        for (int i2 = 0; i2 < 5; i2++) {
#pragma unroll
            for (int c = 2 * i2 - 2; c < 2 * i2; c++) {
                if (c < 0) continue;
                if (c & 3) {
                    uint32_t (&o)[4] = st[c - 1 - (c >> 2)];
#pragma unroll
                    for (int u = 0; u < 4; u++) {
                        const uint32_t v = h[c & 4][u];
                        o[u] = bitsel(h[c][u], (c & 3) == 2 ? prmt(v, v, 0xa381) : prmt(v >> 3, v, (c & 3) == 1 ? 0x6240 : 0xf3d1), SPARE);
                    }
                    stg128_cs(hp + (c >> 2) * H_HALF + ((c & 3) - 1) * 512, o[0], o[1], o[2], o[3]);
                }
            }
            if (i2 < 4) {
#pragma unroll
                for (int u = 0; u < 4; u++) {
                    h[2 * i2][u] = gelu2<0>(acc[8 * i2 + 2 * u], sc2);
                    h[2 * i2 + 1][u] = gelu2<1>(acc[8 * i2 + 2 * u + 1], sc2);
#pragma unroll
                    for (int r = 0; r < 2; r++) sq[r] = (i2 | u) ? h2_fma(h[2 * i2 + r][u], h[2 * i2 + r][u], sq[r]) : h2_mul(h[r][u], h[r][u]);
                }
                sched_break(zero);
            }
        }
#pragma unroll
        for (int r = 0; r < 2; r++) ssq[r] += h_lo(sq[r]) + h_hi(sq[r]);
        if (lane == 0) mbar_arrive(bar_pace);
        if (!more) break;
    }
    TSTAMP(0, 21);
    if (WG == 0) bar_sync(1, 256);
#pragma unroll
    for (int r = 0; r < 2; r++) {
        ssq[r] += __shfl_xor_sync(0xffffffffu, ssq[r], 1);
        ssq[r] += __shfl_xor_sync(0xffffffffu, ssq[r], 2);
        float f;
        asm volatile("ld.shared.f32 %0, [%1];\n" : "=f"(f) : "r"(sbase + P1_OFF_EX + (WG * 64 + w * 16 + r * 8 + g) * 4) : "memory");
        if (q == 0) atomicAdd(&g_sums[p1_parity(sbase)][cb * 64 + w * 16 + r * 8 + g], ssq[r] * f * f);
    }
}

__global__ void __cluster_dims__(2, 1, 1) __launch_bounds__(512, 1)
pass1_kernel(const __grid_constant__ CUtensorMap wmap, const __nv_bfloat16* __restrict__ x, const __nv_bfloat16* __restrict__ dw,
             const __nv_bfloat16* __restrict__ w2, const __nv_bfloat16* __restrict__ grn_b, int zero) {
    extern __shared__ __align__(1024) uint8_t smem[];
    const uint32_t sbase = smem_u32(smem);
    const uint32_t bar_full = sbase + P1_OFF_BAR, bar_empty = bar_full + P1_NST * 8, bar_w = bar_empty + P1_NST * 8;
    const int tid = threadIdx.x;
    const int warp = __shfl_sync(0xffffffffu, tid >> 5, 0), lane = tid & 31;
    const uint32_t rank = cluster_rank();
    const int cig = blockIdx.x % GRP_CTAS;
    uint8_t* const ring = reinterpret_cast<uint8_t*>(g_ln);

    TSTAMP(0, 0);
    TRACEW(110 + warp, 0);
    const uint32_t bar_pace = bar_w + 16, bar_xfull = bar_pace + 32, bar_xempty = bar_xfull + 8, bar_done = bar_xfull + 16;
    const uint32_t bar_raw = sbase + P1_OFF_RAW;
    const int ln0 = blockIdx.x >> 2, first = blockIdx.x / GRP_CTAS;
    const uint8_t* xsrc = reinterpret_cast<const uint8_t*>(x) + (size_t)(NGRP * 4 + blockIdx.x) * P1_X;

    if (warp >= 12) {
        reg_dec<40>();
        asm volatile("barrier.cluster.arrive.relaxed.aligned;\n" ::: "memory");
        asm volatile("barrier.cluster.wait.aligned;\n" ::: "memory");
        if (warp == 12) {
            int prev = first - NGRP, t = first, next = t + NGRP;
            const uint32_t rbase = mapa(sbase, lane & 1);
#pragma unroll 1
            for (int i = 1; t < NT_RING; i++) {
                const int s0 = (i & 1) * 2, par = ((i + 1) >> 1 & 1) ^ 1;
                const int round = t / LN_RING, slot = t - round * LN_RING;
                const uint8_t* src = ring + slot * LN_TILE + rank * (P1_SLOT / 2);
                int draw = 0;
                if (rank == 0 && lane == 0) draw = atomicAdd(&g_flag[LN_RING + (cig >> 2)][(cig >> 1) & 1][0], 1u);
                flag_wait<true>(&g_flag[slot][0][0], 4 * round + 4);
                TRACEW(i, 2);
                asm volatile("fence.proxy.async.global;\n" ::: "memory");
                draw = 2 * NGRP + __shfl_sync(0xffffffffu, draw, 0);
#pragma unroll
                for (int h = 0; h < 2; h++) {
                    mbar_wait(bar_empty + (s0 + h) * 8, par);
                    TRACEW(i, 4 + h);
                    if (elect_one()) {
                        const int len = P1_SLOT / 2;
                        mbar_expect_tx(bar_full + (s0 + h) * 8, 2 * len + 16 - 16 * h);
                        bulk_g2s_mc(sbase + (s0 + h) * P1_SLOT + rank * (P1_SLOT / 2), src + h * P1_SLOT, len, bar_full + (s0 + h) * 8, (uint16_t)3);
                    }
                    __syncwarp();
                    if (h == 0 && rank == 0 && lane < 2)
                        asm volatile("st.async.shared::cluster.mbarrier::complete_tx::bytes.v4.u32 [%0], {%1, %2, %3, %3}, [%4];\n"
                                     ::"r"(rbase + P1_OFF_TILE + (i & 3) * 16), "r"((t - prev) * (2 * H_TILE)), "r"((int)(next < NT_RING)), "r"(draw),
                                       "r"(rbase + P1_OFF_BAR + s0 * 8) : "memory");
                }
                prev = t;
                t = next;
                next = draw;
                if (rank != 0) {
                    mbar_wait(bar_full + (s0 ^ 2) * 8, ((i - 1) >> 1) & 1);
                    asm volatile("ld.shared.u32 %0, [%1];\n" : "=r"(t) : "r"(sbase + P1_OFF_TILE + ((i - 1) & 3) * 16 + 8) : "memory");
                }
            }
        } else if (warp == 13) {
            int ph = 0;
            unsigned target = 0;
#pragma unroll 1
            for (int i = ln0 + LN_STEP; i < NT_RING; i += LN_STEP, ph ^= 1) {
                target += ph * (GRP_CTAS / 2);
                xsrc += (size_t)NUM_CTAS * P1_X;
                mbar_wait(bar_xempty, ph);
                if (elect_one()) {
                    mbar_expect_tx(bar_xfull, P1_X);
                    bulk_g2s(sbase + P1_OFF_X, xsrc, P1_X, bar_xfull);
                }
                __syncwarp();
                const uint32_t off = flag_wait<false>(&g_flag[ln0 + (ph ^ 1) * LN_STEP][1][0], target);
                mbar_wait(bar_done, ph);
                if (elect_one()) {
                    asm volatile("st.shared.u32 [%0], %1;\n" ::"r"(bar_done + 8), "r"(off) : "memory");
                    mbar_arrive(bar_xfull);
                }
                __syncwarp();
            }
        } else if (warp == 15) {
            if (rank == 1 && lane < 2) mbar_arrive(bar_empty + (2 + lane) * 8);
            const uint32_t par = g_epoch & 1;
            asm volatile("st.shared.u32 [%0], %1;\n" ::"r"(sbase + P1_OFF_TILE - 4), "r"(par) : "memory");
            if (blockIdx.x < 16) reinterpret_cast<float4*>(g_sums[par ^ 1])[blockIdx.x * 32 + lane] = make_float4(0.f, 0.f, 0.f, 0.f);
            {
                bar_sync(4, 288);
                TRACEW(110 + warp, 1);
                mbar_wait(bar_raw + 8, 0);
                TRACEW(110 + warp, 2);
                const uint32_t o = lane * 16384 + rank * 8192, peer = mapa(sbase, rank ^ 1);
                if (lane < 6)
                    asm volatile("cp.async.bulk.shared::cluster.shared::cta.mbarrier::complete_tx::bytes [%0], [%1], 8192, [%2];\n"
                                 ::"r"(peer + o), "r"(sbase + o), "r"(peer + P1_OFF_BAR + (lane >= 3 ? 8 : 0)) : "memory");
                __syncwarp();
            }
            int t = first, next = t + NGRP;
            if (rank == 1) {
                mbar_wait(bar_full, 0);
                mbar_wait(bar_full + 8, 0);
                if (lane < 2) mbar_arrive(bar_empty + lane * 8);
            }
#pragma unroll 1
            for (int i = 1; rank == 1 && t < NT_RING; i++) {
                const int s0 = (i & 1) * 16;
                mbar_wait(bar_full + s0, (i >> 1) & 1);
                mbar_wait(bar_full + s0 + 8, (i >> 1) & 1);
                if (lane == 0) asm volatile("red.relaxed.gpu.global.add.u32 [%0], 1;\n" ::"l"(&g_flag[t % LN_RING][1][0]) : "memory");
                t = next;
                asm volatile("ld.shared.u32 %0, [%1];\n" : "=r"(next) : "r"(sbase + P1_OFF_TILE + (i & 3) * 16 + 8) : "memory");
                if (lane < 2) mbar_arrive(bar_empty + s0 + lane * 8);
                TRACEW(i, 3);
            }
            if (rank == 0) {
                mbar_wait(bar_full, 0);
                TRACEW(110 + warp, 3);
                mbar_wait(bar_full, 1);
                float* sums = g_sums[par] + HID;
                unsigned* flag = reinterpret_cast<unsigned*>(sums + C_DIM);
                float gs = 0.f;
#pragma unroll 1
                for (int pass = 0; pass < 2; pass++) {
                    float mx = 0.f;
#pragma unroll 1
                    for (int it = first; it < 48; it += NGRP) {
                        const int np = (it % 12) * 32 + lane, kb = cig * 2 + it / 12;
                        const __nv_bfloat16* wc = w2 + (size_t)kb * 64 * C_DIM + perm32(np);
                        const uint32_t sc = mapa(sbase + P1_OFF_EX + (kb & 1) * 256, it / 24);
                        float bsum = 0.f;
#pragma unroll 1
                        for (int c = 0; c < 8; c++) {
                            float f[8];
#pragma unroll
                            for (int e = 0; e < 8; e++) f[e] = __bfloat162float(wc[(c * 8 + e) * C_DIM]);
#pragma unroll
                            for (int e = 0; e < 8; e++) {
                                float t;
                                asm volatile("ld.shared::cluster.f32 %0, [%1];\n" : "=f"(t) : "r"(sc + (c * 8 + e) * 4) : "memory");
                                bsum = fmaf(__bfloat162float(grn_b[kb * 64 + c * 8 + e]), f[e], bsum);
                                f[e] *= t;
                                mx = fmaxf(mx, fabsf(f[e]));
                            }
                            if (pass)
                                g_w2img[0][(((kb * 4 + (c >> 1)) * 48 + (np >> 3)) * 2 + (c & 1)) * 8 + (np & 7)] = make_uint4(
                                    pack_f16(f[0] * gs, f[1] * gs), pack_f16(f[2] * gs, f[3] * gs), pack_f16(f[4] * gs, f[5] * gs), pack_f16(f[6] * gs, f[7] * gs));
                        }
                        if (pass) atomicAdd(&sums[np], bsum);
                    }
                    if (!pass) {
                        const uint32_t m = __reduce_max_sync(0xffffffffu, __float_as_uint(mx));
                        if (lane == 0) {
                            atomicMax(flag, m);
                            asm volatile("red.release.gpu.global.add.u32 [%0], 1;\n" ::"l"(flag + 32) : "memory");
                        }
                        flag_wait<true>(flag + 32, NUM_CTAS / 2);
                        gs = w2_scale(__ldcg(flag));
                    }
                }
                do {
                    __nanosleep(1000);
                    asm volatile("ld.volatile.shared.u32 %0, [%1];\n" : "=r"(t) : "r"(sbase + P1_OFF_TILE + (lane & 3) * 16 + 8) : "memory");
                    SAFE_BREAK;
                } while (__all_sync(0xffffffffu, t < NT_RING - P1_WPF));
                if (lane == 0 && blockIdx.x < 128)
                    asm volatile("cp.async.bulk.prefetch.L2.global [%0], %1;\n" ::"l"(g_w2img[0] + blockIdx.x * 576), "r"(18432) : "memory");
            }
        } else if (warp == 14) {
            int ph = 0;
#pragma unroll 1
            for (int i = ln0; i < NT_RING; i += LN_STEP, ph ^= 1) {
                mbar_wait(bar_done, ph);
                TRACEW(i / LN_STEP, 0);
                asm volatile("fence.proxy.async.global;\n" ::: "memory");
                if (elect_one()) asm volatile("red.release.gpu.global.add.u32 [%0], 1;\n" ::"l"(&g_flag[ln0 + ph * LN_STEP][0][0]) : "memory");
                __syncwarp();
                TRACEW(i / LN_STEP, 1);
            }
        }
        __syncwarp();
        cluster_sync();
    } else if (warp >= 8) {
        reg_dec<88>();
        asm volatile("barrier.cluster.arrive.relaxed.aligned;\n" ::: "memory");
        {
            const int l8 = lane & 7, row = (warp - 8) * 4 + (lane >> 3), px = (blockIdx.x & 3) * 32 + row;
            uint32_t d[6][4];
#pragma unroll
            for (int j = 0; j < 6; j++) {
                const uint4 t = reinterpret_cast<const uint4*>(dw)[j * 8 + l8];
                d[j][0] = t.x; d[j][1] = t.y; d[j][2] = t.z; d[j][3] = t.w;
            }
            const int n = (px & 64) + perm32(2 * row + ((px >> 5) & 1));
            uint8_t* const dst0 = ring + ln0 * LN_TILE + n * 128 + ((l8 ^ (n & 7)) << 4);
            const uint32_t src = sbase + P1_OFF_X + ((warp - 8) * 8 + (lane >> 3)) * (C_DIM * 2) + l8 * 16;
            int ph = 0;
            asm volatile("barrier.cluster.wait.aligned;\n" ::: "memory");
#pragma unroll 1
            for (int i = ln0; i < NT_RING; i += LN_STEP, ph ^= 1) {
                TRACE(2, i / LN_STEP, 0);
                mbar_wait(bar_xfull, ph);
                uint32_t off;
                asm volatile("ld.shared.u32 %0, [%1];\n" : "=r"(off) : "r"(bar_done + 8) : "memory");
                TRACE(2, i / LN_STEP, 1);
#pragma unroll 1
                for (int ps = 0; ps < 2; ps++) {
                    uint32_t v[6][4];
#pragma unroll
                    for (int j = 0; j < 6; j++)
                        asm volatile("ld.shared.v4.u32 {%0,%1,%2,%3}, [%4];\n"
                                     : "=r"(v[j][0]), "=r"(v[j][1]), "=r"(v[j][2]), "=r"(v[j][3]) : "r"(src + ps * (4 * C_DIM * 2) + j * 128) : "memory");
                    ln_row<P1_PACE>(v, d, bar_pace + (warp - 8) * 8, off, zero, ps == 1 && lane == 0 ? bar_xempty : 0);
                    uint8_t* dst = dst0 + ph * (LN_STEP * LN_TILE) + ps * 4096;
#pragma unroll
                    for (int j = 0; j < 6; j++) *reinterpret_cast<uint4*>(dst + j * 16384) = make_uint4(v[j][0], v[j][1], v[j][2], v[j][3]);
                    TRACE(2, i / LN_STEP, 3 + ps);
                }
                asm volatile("fence.proxy.async.global;\nfence.acq_rel.cta;\n" ::: "memory");
                __syncwarp();
                if (lane == 0) mbar_arrive(bar_done);
                TRACE(2, i / LN_STEP, 5);
                TRACE(2, i / LN_STEP, 2);
            }
        }
        __syncwarp();
        cluster_sync();
    } else {
        uint32_t d[6][4];
#pragma unroll
        for (int j = 0; j < 6; j++)
            asm volatile("ld.global.nc.v4.u32 {%0,%1,%2,%3}, [%4];\n" : "=r"(d[j][0]), "=r"(d[j][1]), "=r"(d[j][2]), "=r"(d[j][3])
                         : "l"(reinterpret_cast<const uint4*>(dw) + j * 8 + (lane & 7)) : "memory");
        if (tid == 0) {
            mbar_init(bar_raw, 1);
            mbar_init(bar_raw + 8, 8);
            asm volatile("fence.mbarrier_init.release.cluster;\n" ::: "memory");
            mbar_expect_tx(bar_raw, P1_SLOT);
            for (int i = 0; i < 6; i++)
                bulk_g2s(sbase + i * 16384 + (rank ^ 1) * 8192, x + (size_t)(first * 128 + rank * 64) * C_DIM + i * 4096, 8192, bar_raw);
        }
        if (tid == 32) {
            mbar_init(bar_xfull, 2);
            mbar_init(bar_xempty, 4);
            mbar_init(bar_done, 4);
            asm volatile("fence.mbarrier_init.release.cluster;\n" ::: "memory");
            mbar_expect_tx(bar_xfull, P1_X);
            bulk_g2s(sbase + P1_OFF_X, xsrc, P1_X, bar_xfull);
            asm volatile("st.shared.u32 [%0], 1;\n" ::"r"(bar_done + 8) : "memory");
            mbar_arrive(bar_xfull);
        }
        if (tid == 64) {
            asm volatile("st.shared.v4.u32 [%0], {0, 1, %1, %1};\n" ::"r"(sbase + P1_OFF_TILE), "r"(first + NGRP) : "memory");
            for (int i = 0; i < P1_NST; i++) {
                mbar_init(bar_full + i * 8, 1);
                mbar_init(bar_empty + i * 8, 16 + rank);
                mbar_init(bar_pace + i * 8, 1);
                if (i < 2) mbar_expect_tx(bar_full + i * 8, P1_SLOT / 2);
            }
            asm volatile("fence.mbarrier_init.release.cluster;\n" ::: "memory");
            if (blockIdx.x < 64) (&g_half[0][0])[blockIdx.x] = 0;
            else if (blockIdx.x < 66) g_prog[blockIdx.x - 64][0] = 0;
        }
        if (tid == 96) {
            for (int i = 0; i < 2; i++) mbar_init(bar_w + i * 8, 1);
            asm volatile("fence.mbarrier_init.release.cluster;\n" ::: "memory");
        }
        __syncwarp();
        asm volatile("barrier.cluster.arrive.relaxed.aligned;\n" ::: "memory");
        if (tid == 96)
            for (int i = 0; i < 2; i++) {
                mbar_expect_tx(bar_w + i * 8, P1_SLOT);
                tma2(sbase + (2 + i) * P1_SLOT, &wmap, cig * 128 + i * 64, 0, bar_w + i * 8);
                tma2(sbase + (2 + i) * P1_SLOT + P1_SLOT / 2, &wmap, cig * 128 + i * 64, 192, bar_w + i * 8);
            }
        __syncwarp();
        reg_inc<192>();
        TRACEW(110 + warp, 1);
        const int wg = warp >> 2, w = warp & 3;
        uint32_t a[24][4];
        {
            const int n = warp * 8 + (lane >> 3), px = (n & 1) * 32 + (n >> 5) * 4 + ((n >> 1) & 1) * 8 + ((n >> 3) & 3);
            if (wg == 1) bar_arrive(1, 256);
            gdc_launch();
            asm volatile("barrier.cluster.wait.aligned;\n" ::: "memory");
#pragma unroll 1
            for (int ps = -1; ps < 2; ps++) {
                if (ps == 0) mbar_wait(bar_raw, 0);
                TRACEW(110 + warp, 2 + (ps == 0));
                uint32_t v[6][4];
#pragma unroll
                for (int j = 0; j < 6; j++) {
                    const uint32_t o = (px + (ps & 1) * 16) * (C_DIM * 2) + j * 128;
                    asm volatile("ld.shared.v4.u32 {%0,%1,%2,%3}, [%4];\n" : "=r"(v[j][0]), "=r"(v[j][1]), "=r"(v[j][2]), "=r"(v[j][3])
                                 : "r"(sbase + (rank ^ 1) * 8192 + (lane & 7) * 16 + o + (o & ~8191u)) : "memory");
                }
                ln_row<false>(v, d, 0, 0, zero, 0);
                const uint32_t p = sbase + (rank * 64 + n + (ps & 1) * 4) * 128 + (((lane ^ n ^ (ps & 1) * 4) & 7) << 4);
#pragma unroll
                for (int j = 0; j < 6; j++)
                    asm volatile("st.shared.v4.u32 [%4], {%0,%1,%2,%3};\n"
                                 ::"r"(v[j][0]), "r"(v[j][1]), "r"(v[j][2]), "r"(v[j][3]), "r"(p + j * 16384) : "memory");
            }
            asm volatile("fence.proxy.async.shared::cta;\n" ::: "memory");
            __syncwarp();
            if (lane == 0) mbar_arrive_cluster(mapa(bar_raw + 8, rank ^ 1));
            bar_arrive(4, 288);
            TRACEW(110 + warp, 4);
            const uint32_t src = sbase + (2 + wg) * P1_SLOT + ((lane >> 4) * 8 + (lane & 7)) * 128 + (((2 * w + ((lane >> 3) & 1)) ^ (lane & 7)) << 4);
            mbar_wait(bar_w + wg * 8, 0);
            TRACEW(110 + warp, 5);
            uint32_t dep = 0;
#pragma unroll
            for (int k = 0; k < 24; k++) {
                ldsm4t(a[k], src + k * 2048);
                dep |= a[k][0];
            }
            __syncwarp();
            if (lane < 4) mbar_arrive_cluster(mapa(bar_empty, lane & 1) + (2 + (lane >> 1)) * 8 + (dep & zero));
        }
        TRACEW(110 + warp, 6);
        uint32_t ex[2];
#pragma unroll
        for (int r = 0; r < 2; r++) {
            float t = 0.f;
#pragma unroll
            for (int j = 0; j < 6; j++) {
                uint32_t c = bf2_mul(a[4 * j][r], a[4 * j][r]);
#pragma unroll
                for (int k = 1; k < 8; k++) c = bf2_fma(a[4 * j + k / 2][r + (k & 1) * 2], a[4 * j + k / 2][r + (k & 1) * 2], c);
                t += bf_lo(c) + bf_hi(c);
            }
            t += __shfl_xor_sync(0xffffffffu, t, 1);
            t += __shfl_xor_sync(0xffffffffu, t, 2);
            ex[r] = min(max(__float_as_uint(13.9f * __fsqrt_rn(t)) >> 23, 72u), 198u);
            if ((lane & 3) == 0)
                asm volatile("st.shared.u32 [%0], %1;\n" ::"r"(sbase + P1_OFF_EX + (wg * 64 + w * 16 + r * 8 + (lane >> 2)) * 4), "r"(ex[r] << 23) : "memory");
            const uint32_t f = (258u - ex[r]) * 0x00800080u;
#pragma unroll
            for (int k = 0; k < 48; k++) a[k >> 1][r + (k & 1) * 2] = bf2_to_h2(bf2_mul(bf2_mul(a[k >> 1][r + (k & 1) * 2], f), 0x07800780u));
        }
        const uint32_t sc2 = pack_f16(__uint_as_float(min(ex[0], 142u) << 23), __uint_as_float(min(ex[1], 142u) << 23));
        TRACEW(110 + warp, 7);
        bar_sync(5, 256);
        if (warp < 4) p1_consumer<0>(a, sc2, sbase, w, lane, zero);
        else p1_consumer<1>(a, sc2, sbase, w, lane, zero);
        cluster_sync();
        TSTAMP(0, 30);
    }
}

constexpr int P2_B = 24576, P2_NB = 4;
constexpr int P2_A = 3072, P2_NA = 8;
constexpr int P2_XROW = C_DIM * 2;
constexpr int P2_OFF_A = P2_B * P2_NB;
constexpr int P2_OFF_X = P2_OFF_A + 3 * P2_NA * P2_A;
constexpr int P2_XHALF = 32 * P2_XROW + 64;
constexpr int P2_OFF_GRN = P2_OFF_X + 64 * P2_XROW + 128;
constexpr int P2_OFF_BIAS = P2_OFF_GRN + HID * 2;
constexpr int P2_OFF_RED = P2_OFF_BIAS + C_DIM * 4;
constexpr int P2_OFF_BAR = P2_OFF_RED + 192;
constexpr int P2_SMEM = P2_OFF_BAR + (2 * P2_NB + 6 * P2_NA + 7) * 8;
#define P2_S1 16
constexpr int P2_S2 = 32;
constexpr int P2_NCL = NUM_CTAS / 2, P2_ITEMS = NT128 / P2_NCL, P2_SHARED = NT128 - P2_ITEMS * P2_NCL;
constexpr int P2_NPOS = 6 * 48 + P2_S1;
constexpr int P2_RAW = 24;
constexpr int P2_XC = 8 * P2_XROW;
#define P2_T0 4
#define P2_SLACK 0
#define P2_AH 2
__device__ __forceinline__ int p2_start(int n) { return n < 0 ? 0 : n / 3 * 48 + (n % 3 == 1 ? P2_S1 : n % 3 * (P2_S2 / 2)); }
__device__ __forceinline__ int p2_tile(int cl, int n) {
    return n == 0 ? NT128 - 1 - cl : n < 0 ? NT128 - 1 - P2_NCL - (cl >> 1) : cl + P2_NCL * (n - 1);
}

#define P2_EB 2
#define P2_EX 1
__device__ __forceinline__ void p2_epilogue(uint32_t (&acc0)[48], uint32_t (&acc1)[48], uint32_t up, uint32_t sx, uint32_t sb, int zero) {
    uint32_t v[12][3][4];
    auto load = [&](int t, int j) {
        if (t >= 12) return;
        uint32_t (&w)[4] = v[t][j];
        asm volatile("ld.shared.v4.u32 {%0,%1,%2,%3}, [%4];\n" : "=r"(w[0]), "=r"(w[1]), "=r"(w[2]), "=r"(w[3])
                     : "r"((j ? sx + (j - 1) * 4 * P2_XROW : sb) + t * 64) : "memory");
    };
    auto store = [&](int t, int r) {
        const uint32_t* w = (t < 6 ? acc0 : acc1) + 8 * (t % 6) + 4 * r;
        asm volatile("st.shared.v4.u32 [%4], {%0,%1,%2,%3};\n" ::"r"(w[0]), "r"(w[1]), "r"(w[2]), "r"(w[3]), "r"(sx + t * 64 + r * 4 * P2_XROW) : "memory");
    };
#pragma unroll
    for (int t = 0; t < P2_EB; t++) load(t, 0);
#pragma unroll
    for (int t = 0; t < 2 * P2_EX; t++) load(t >> 1, 1 + (t & 1));
#pragma unroll
    for (int t = 0; t < 12; t++) {
        load(t + P2_EX, 1);
        load(t + P2_EX, 2);
        load(t + P2_EB, 0);
        uint32_t* acc = (t < 6 ? acc0 : acc1) + 8 * (t % 6);
        uint32_t y[8];
#pragma unroll
        for (int e = 0; e < 8; e++) {
            y[e] = h2_add(acc[e], v[t][0][e >> 1]);
            y[e] = pack_bf16(h_lo(y[e]), h_hi(y[e]));
        }
#pragma unroll
        for (int e = 0; e < 8; e++) acc[(e & 1) * 4 + (e >> 1)] = bf2_fma(y[e], up, v[t][1 + (e & 1)][e >> 1]);
        store(t, 0);
        store(t, 1);
        sched_break(zero);
    }
    if (zero) {
#pragma unroll
        for (int t = 0; t < 24; t++) store(t >> 1, t & 1);
    }
}

__device__ __forceinline__ void p2_unpack(uint32_t (&u)[4], uint32_t o1, uint32_t o2, uint32_t o3) {
    u[2] = bitsel(o1, 0x00040004u, SPARE);
    u[1] = bitsel(o2, 0x00040004u, SPARE);
    u[3] = bitsel(o3, 0x00040004u, SPARE);
    const uint32_t t = bitsel(prmt(o1, o2, 0x6341), prmt(o1, o3, 0x6240) << 3, 0x38383838u);
    u[0] = bitsel(bitsel(t, prmt(o2, o3, 0x7351) << 1, 0x80808080u), 0x00040004u, SPARE);
}

__global__ void __cluster_dims__(2, 1, 1) __launch_bounds__(512, 1)
pass2_kernel(const __nv_bfloat16* __restrict__ x, const __nv_bfloat16* __restrict__ grn_g, __nv_bfloat16* __restrict__ out, int zero) {
    extern __shared__ __align__(1024) uint8_t smem[];
    const uint32_t sbase = smem_u32(smem);
    const uint32_t bar_bfull = sbase + P2_OFF_BAR, bar_bempty = bar_bfull + P2_NB * 8;
    const uint32_t bar_afull = bar_bempty + P2_NB * 8, bar_aempty = bar_afull + 3 * P2_NA * 8;
    const uint32_t bar_xfull = bar_aempty + 3 * P2_NA * 8, bar_oready = bar_xfull + 24, s_pos = bar_oready + 24;
    int tid;
    asm volatile("mov.u32 %0, %%tid.x;\n" : "=r"(tid));
    const int warp = __shfl_sync(0xffffffffu, tid >> 5, 0), lane = tid & 31;
    const uint32_t rank = cluster_rank();
    const int cl = blockIdx.x >> 1, pair = cl >> 1;
    const int half = pair < P2_SHARED, fin = half && (cl & 1);
    const int k0 = (pair + 3 * (cl & 1)) % 6 * 8;
    auto wait_pos = [&](int target) {
        int v;
        while (true) {
            asm volatile("ld.volatile.shared.u32 %0, [%1];\n" : "=r"(v) : "r"(s_pos) : "memory");
            if (v >= target) break;
            SAFE_BREAK;
            __nanosleep(100);
        }
    };

    TSTAMP(1, 0);
    if (tid == 384) {
        for (int i = 0; i < P2_NB; i++) {
            mbar_init(bar_bfull + i * 8, 1);
            mbar_init(bar_bempty + i * 8, 24);
        }
        for (int i = 0; i < 3 * P2_NA; i++) {
            mbar_init(bar_afull + i * 8, 1);
            mbar_init(bar_aempty + i * 8, 4);
        }
        for (int i = 0; i < 3; i++) {
            mbar_init(bar_xfull + i * 8, 2);
            mbar_init(bar_oready + i * 8, 4);
        }
        asm volatile("st.shared.u32 [%0], 0;\n" ::"r"(s_pos) : "memory");
        asm volatile("fence.mbarrier_init.release.cluster;\n" ::: "memory");
    }
    __syncthreads();
    cluster_sync_relaxed();

    if (warp >= 12) {
        reg_dec<32>();
        if (warp == 12) {
            const uint8_t* wsrc = reinterpret_cast<const uint8_t*>(g_w2img) + rank * (P2_B / 2);
            int kb = k0;
            gdc_wait();
#pragma unroll 1
            for (int p = 0; p < P2_NPOS; p++) {
                const int st = p & 3;
                if (p == P2_RAW) {
                    flag_wait<true>(&g_prog[1][0], NUM_CTAS);
                    asm volatile("fence.proxy.async.global;\n" ::: "memory");
                    wsrc += sizeof(g_w2img[0]);
                }
                const int idle = (p < P2_S1 || p >= 6 * 48) + (p < P2_S2 ? !half || p >= 24 : p >= 5 * 48 + P2_S2);
                mbar_wait(bar_bempty + st * 8, (~p >> 2) & 1);
                TR2(3, p, 0);
                if (elect_one()) {
                    mbar_expect_tx(bar_bfull + st * 8, P2_B);
                    bulk_g2s_mc(sbase + st * P2_B + rank * (P2_B / 2), wsrc + kb * P2_B, P2_B / 2, bar_bfull + st * 8, (uint16_t)3);
                    asm volatile("st.volatile.shared.u32 [%0], %1;\n" ::"r"(s_pos), "r"(p) : "memory");
                    if (rank == 0) asm volatile("red.relaxed.gpu.global.add.u32 [%0], 1;\n" ::"l"(&g_prog[0][0]) : "memory");
                    if (idle) asm volatile("mbarrier.arrive.shared::cta.b64 _, [%0], %1;\n" ::"r"(bar_bempty + st * 8), "r"(8 * idle) : "memory");
                }
                __syncwarp();
                if (++kb == 48) kb = 0;
            }
            mbar_wait(bar_bempty, 1);
            if (lane == 0) mbar_arrive(bar_bfull);
        } else if (warp == 13) {
            const int w = lane < 3 ? lane : 0;
            const uint32_t dst0 = sbase + P2_OFF_A + w * P2_NA * P2_A;
            const uint32_t bf = bar_afull + w * P2_NA * 8, be = bar_aempty + w * P2_NA * 8;
            int n = (w == 2 && half ? -1 : w) - 3, left = 0, u = 0, c = 0;
            const uint8_t* src = nullptr;
            bool act = lane < 3;
            gdc_wait();
            while (__any_sync(0xffffffffu, act)) {
                if (left == 0) {
                    n += 3;
                    left = n >= P2_ITEMS ? -1 : n < 0 ? 24 : 48;
                    u = (k0 + p2_start(n)) % 48;
                    src = reinterpret_cast<const uint8_t*>(g_h) + (size_t)p2_tile(cl, n) * (2 * H_TILE) + rank * H_HALF + u * H_STEP;
                }
                const bool ok = act && mbar_test(be + ((c - 1) & 7) * 8, (~c >> 3) & 1);
                if (ok) {
                    const int st = c & 7;
                    if (left > 0) {
                        mbar_expect_tx(bf + st * 8, P2_A);
                        bulk_g2s(dst0 + st * P2_A, src, P2_A, bf + st * 8);
                    } else {
                        mbar_arrive(bf + st * 8);
                        act = false;
                    }
                    src += H_STEP;
                    if (++u == 48) { u = 0; src -= 48 * H_STEP; }
                    c++;
                    left--;
                }
                SAFE_BREAK;
                if (!__any_sync(0xffffffffu, ok)) __nanosleep(100);
            }
        } else if (warp == 14) {
            const uint32_t sx = sbase + P2_OFF_X;
            size_t o = 0;
            int wp = 0;
            uint32_t par = 0;
            if (fin) {
#pragma unroll 1
                for (int c = lane * 16; c < 64 * P2_XROW + 128; c += 512) asm volatile("st.shared.v4.u32 [%0], {0, 0, 0, 0};\n" ::"r"(sx + c) : "memory");
                __syncwarp();
            }
#pragma unroll 1
            for (int n = -half; n <= P2_ITEMS; n++) {
                const int w = (n + 3) % 3, end = p2_start(n) + 48;
                const size_t on = (size_t)(2 * p2_tile(cl, n) + rank) * (64 * C_DIM * 2);
                const uint32_t xf = bar_xfull + w * 8;
                bool st = n + half > 0;
                const bool ld = n < P2_ITEMS && !(n < 0 && fin);
                if (n == P2_ITEMS - 1 && lane == 0)
                    asm volatile("cp.async.bulk.prefetch.L2.global [%0], %1;\n" ::"l"(reinterpret_cast<const uint8_t*>(x) + on), "r"(64 * P2_XROW) : "memory");
                if (st) {
                    mbar_wait(bar_oready + wp * 8, (par >> wp) & 1);
                    par ^= 1u << wp;
                }
                if (lane == 0) {
                    if (n < P2_ITEMS) mbar_expect_tx(xf, ld ? 64 * C_DIM * 2 : 0);
                    const int t0 = (n ? p2_start(n - 1) + 48 : P2_S2) + P2_T0, dt = end - t0;
                    int t = st && n < P2_ITEMS - 1 ? 16 * t0 : -4096;
                    if ((n == 0 && half) || n >= P2_ITEMS - 1) {
                        if (fin && n == 0) {
                            flag_wait<true>(&g_half[pair][rank], 1);
                            asm volatile("fence.proxy.async.global;\n" ::: "memory");
                        }
#pragma unroll 1
                        for (int c = 0; c < 2; c++) {
                            uint8_t* dst = reinterpret_cast<uint8_t*>(out) + o + c * 32 * P2_XROW;
                            if (!fin || n) bulk_s2g(dst, sx + c * P2_XHALF, 32 * P2_XROW);
                            else asm volatile("cp.reduce.async.bulk.global.shared::cta.bulk_group.add.noftz.bf16 [%0], [%1], %2;\n"
                                              ::"l"(dst), "r"(sx + c * P2_XHALF), "r"(32 * P2_XROW) : "memory");
                        }
                        asm volatile("cp.async.bulk.commit_group;\n" ::: "memory");
                        if (!fin && n == 0) {
                            asm volatile("cp.async.bulk.wait_group 0;\nfence.proxy.async.global;\n" ::: "memory");
                            asm volatile("st.release.gpu.global.u32 [%0], 1;\n" ::"l"(&g_half[pair][rank]) : "memory");
                        }
                        st = false;
                    }
#pragma unroll 1
                    for (int c = 0; c < 64 * P2_XROW; c += P2_XC, t += 2 * dt) {
                        const uint32_t sp = sx + c + (c >= 32 * P2_XROW ? 64 : 0);
                        wait_pos(t >> 4);
                        if (st) bulk_s2g(reinterpret_cast<uint8_t*>(out) + o + c, sp, P2_XC);
                        asm volatile("cp.async.bulk.commit_group;\n" ::: "memory");
                        if (ld) {
                            wait_pos((t + dt) >> 4);
                            asm volatile("cp.async.bulk.wait_group.read 0;\n" ::: "memory");
                            bulk_g2s(sp, reinterpret_cast<const uint8_t*>(x) + on + c, P2_XC, xf);
                        }
                    }
                    if (rank == 0 && n > 0 && n < P2_ITEMS - 1) flag_wait<false>(&g_prog[0][0], P2_NCL * (end + P2_SLACK));
                    if (n < P2_ITEMS) mbar_arrive(xf);
                }
                __syncwarp();
                o = on;
                wp = w;
            }
            asm volatile("cp.async.bulk.wait_group 0;\n" ::: "memory");
        }
        __syncwarp();
        cluster_sync();
    } else {
        reg_inc<160>();
        const int wg = warp >> 2, w = warp & 3, g = lane >> 2, q = lane & 3;
        const uint32_t sx = sbase + P2_OFF_X + (g & 1) * P2_XHALF + (w * 8 + (g >> 1)) * P2_XROW + q * 16;
        const uint32_t af = bar_afull + wg * P2_NA * 8;
        const uint32_t s_a = sbase + P2_OFF_A + wg * P2_NA * P2_A + (lane >> 3) * 512 + (lane & 7) * 64 + ((w ^ ((lane & 7) >> 1)) << 4);
        uint32_t acc0[48], acc1[48], up;
        uint4 a[2][2];

        {
            float* s_red = reinterpret_cast<float*>(smem + P2_OFF_RED);
            float gx[4], part = 0.f;
            __nv_bfloat16 gg[4];
#pragma unroll
            for (int i = 0; i < 4; i++) gg[i] = grn_g[tid + 384 * i];
            TSTAMP(1, 27);
            gdc_wait();
            TSTAMP(1, 1);
            if (blockIdx.x == 120 && tid < (LN_RING + 3) * 2) (&g_flag[0][0][0])[tid * 8] = 0;
            if (blockIdx.x == 121 && tid == 0) g_epoch++;
#pragma unroll
            for (int i = 0; i < 4; i++) gx[i] = __ldcg(&g_sums[0][tid + 384 * i]) + __ldcg(&g_sums[1][tid + 384 * i]);
            const float bias = __ldcg(&g_sums[0][HID + tid]) + __ldcg(&g_sums[1][HID + tid]);
            const float gs = w2_scale(__float_as_uint(__ldcg(&g_sums[0][HID + C_DIM])) | __float_as_uint(__ldcg(&g_sums[1][HID + C_DIM])));
            float mg = 0.f;
#pragma unroll
            for (int i = 0; i < 4; i++) {
                gx[i] = sqrtf(gx[i] * (HSCALE * HSCALE) + 1e-6f);
                part += gx[i];
                gx[i] *= __bfloat162float(gg[i]);
                mg = fmaxf(mg, fabsf(gx[i]));
            }
#pragma unroll
            for (int o = 16; o > 0; o >>= 1) part += __shfl_xor_sync(0xffffffffu, part, o);
            const uint32_t mgw = __reduce_max_sync(0xffffffffu, __float_as_uint(mg));
            const uint32_t mbw = __reduce_max_sync(0xffffffffu, __float_as_uint(fabsf(bias)));
            TSTAMP(1, 26);
            if (lane == 0) *reinterpret_cast<float4*>(s_red + warp * 4) = make_float4(part, __uint_as_float(mgw), __uint_as_float(mbw), 0.f);
            bar_sync(1, 384);
            float tot = 0.f, mb = 0.f;
#pragma unroll
            for (int i = 0; i < 12; i++) {
                const float4 t = *reinterpret_cast<const float4*>(s_red + i * 4);
                tot += t.x;
                mg = fmaxf(mg, t.y);
                mb = fmaxf(mb, t.z);
            }
            const float inv = 1.0f / (tot * (1.0f / HID) + 1e-6f);
            const uint32_t ej = min((__float_as_uint(fmaxf(fmaf(mg, inv, 1.0f) * HSCALE, mb * gs * 0x1p-13f)) >> 23) + 1, 250u);
            const float dn = __uint_as_float((254u - ej) << 23);
            up = min(ej + 127u - (__float_as_uint(gs) >> 23), 254u) * 0x00800080u;
            reinterpret_cast<uint16_t*>(smem + P2_OFF_BIAS + C_DIM * 2)[tid] = 0;
            *reinterpret_cast<__half*>(smem + P2_OFF_BIAS + (tid >> 5) * 64 + (tid & 6) * 8 + (tid & 24) / 2 + (tid & 1) * 2) = __float2half_rn(bias * gs * dn);
#pragma unroll
            for (int i = 0; i < 4; i++) {
                const int k = tid + 384 * i;
                *reinterpret_cast<__half*>(smem + P2_OFF_GRN + (k >> 4) * 32 + (k & 6) * 4 + (k & 8) / 2 + (k & 1) * 2) =
                    __float2half_rn(fmaf(gx[i], inv, 1.0f) * (HSCALE * dn));
            }
            TSTAMP(1, 25);
            bar_sync(1, 384);
        }
        TSTAMP(1, 28);
        if (wg == 1) {
            constexpr int N = sizeof(g_w2img[0]) / 16, PER = (N + NUM_CTAS - 1) / NUM_CTAS;
            uint4 v[5];
#pragma unroll
            for (int i = 0; i < 5; i++) v[i] = __ldcg(&g_w2img[0][min(blockIdx.x * PER + (tid & 127) + 128 * i, N - 1)]);
#pragma unroll
            for (int i = 0; i < 5; i++) {
                const int j = min(blockIdx.x * PER + (tid & 127) + 128 * i, N - 1);
                const uint32_t* t = reinterpret_cast<const uint32_t*>(smem + P2_OFF_GRN + (j / 768) * 32 + (j & 8) / 2);
                auto sc = [&](uint32_t u, int e) { return (h2_mul(u, t[2 * e]) + 0x00040004u) & 0xfff8fff8u; };
                g_w2img[1][j] = make_uint4(sc(v[i].x, 0), sc(v[i].y, 1), sc(v[i].z, 2), sc(v[i].w, 3));
            }
            asm volatile("fence.proxy.async.global;\n" ::: "memory");
            bar_sync(2, 128);
            if (tid == 128) asm volatile("fence.acq_rel.gpu;\nred.release.gpu.global.add.u32 [%0], 1;\n" ::"l"(&g_prog[1][0]) : "memory");
        }

        const int who = __shfl_sync(0xffffffffu, lane == 2 ? 0 : lane < 2 ? 1 : 2, lane);
        const uint32_t rel0 = who ? mapa(bar_bempty, lane & 1) : mapa(bar_aempty + wg * P2_NA * 8, rank), rel1 = rel0 + (who ? 0 : 32);
        auto publish = [&]() {
            asm volatile("fence.proxy.async.shared::cta;\n" ::: "memory");
            __syncwarp();
            if (who == 0) mbar_arrive(bar_oready + wg * 8);
        };
        bool ok_a, pend = false;
        uint32_t pa = 0, s_t;
        auto fetch = [&](int j, bool raw) {
            uint32_t o[6], u0[4], u1[4];
            uint2 t0 = make_uint2(0, 0), t1 = t0;
            if (raw) {
                asm volatile("ld.shared.v2.u32 {%0,%1}, [%2];\n" : "=r"(t0.x), "=r"(t0.y) : "r"(s_t + j * 64) : "memory");
                asm volatile("ld.shared.v2.u32 {%0,%1}, [%2];\n" : "=r"(t1.x), "=r"(t1.y) : "r"(s_t + j * 64 + 32) : "memory");
            }
            const bool ok_b = mbar_test(bar_bfull + (j & 3) * 8, j >> 2);
            if (j == 7) pa ^= 1;
            ok_a = mbar_test(af + ((j + 1) & 7) * 8, pa);
            asm volatile("ldmatrix.sync.aligned.m8n8.x4.trans.shared.b16 {%0,%1,%2,%3}, [%4];\n"
                         : "=r"(o[0]), "=r"(o[1]), "=r"(o[2]), "=r"(o[3]) : "r"(s_a + j * P2_A) : "memory");
            asm volatile("ldmatrix.sync.aligned.m8n8.x2.trans.shared.b16 {%0,%1}, [%2];\n"
                         : "=r"(o[4]), "=r"(o[5]) : "r"(s_a + j * P2_A + 2048) : "memory");
            p2_unpack(u0, o[0], o[1], o[2]);
            p2_unpack(u1, o[3], o[4], o[5]);
            if (raw) {
                u0[0] = h2_mul(u0[0], t0.x); u0[1] = h2_mul(u0[1], t0.x); u0[2] = h2_mul(u0[2], t0.y); u0[3] = h2_mul(u0[3], t0.y);
                u1[0] = h2_mul(u1[0], t1.x); u1[1] = h2_mul(u1[1], t1.x); u1[2] = h2_mul(u1[2], t1.y); u1[3] = h2_mul(u1[3], t1.y);
            }
            a[j & 1][0] = make_uint4(u0[0], u0[1], u0[2], u0[3]);
            a[j & 1][1] = make_uint4(u1[0], u1[1], u1[2], u1[3]);
            if (!ok_b) mbar_wait(bar_bfull + (j & 3) * 8, j >> 2);
        };
        auto table = [&](int pos) { s_t = sbase + P2_OFF_GRN + q * 8 + (k0 + pos) % 48 * 64; };
        const uint64_t db0 = make_desc(sbase, 128, 256);
        auto block8 = [&](bool raw, int pos, int thr0, int mode) {
#pragma unroll
            for (int j = 0; j < 8; j++) {
                const uint64_t db = db0 + (j & 3) * (P2_B / 16);
                if (j == 8 - P2_AH && mode == 1) bar_sync(4, 384);
                TR2(wg, pos + j, 0);
                wg_fence();
                mma_rs_n192(acc0, a[j & 1][0], db);
                mma_rs_n192(acc1, a[j & 1][0], db + 384);
                mma_rs_n192(acc0, a[j & 1][1], db + 768);
                mma_rs_n192(acc1, a[j & 1][1], db + 768 + 384);
                wg_commit();
                if (j == 7 && mode == 2) bar_arrive(4, 384);
                const uint32_t rel = ((j - 1) & 4 ? rel1 : rel0) + ((j - 1) & 3) * 8;
                TR2(wg, pos + j, 1);
                wg_wait<1>();
                TR2(wg, pos + j, 2);
                if (who < (j ? 2 : thr0)) mbar_arrive_cluster(rel);
                if (!ok_a) {
                    if (j == 0 && pend) { publish(); pend = false; }
                    mbar_wait(af + ((j + 1) & 7) * 8, pa);
                }
                TR2(wg, pos + j, 3);
                if (raw && j == 7) table(pos + 8);
                fetch((j + 1) & 7, raw && (j < 7 || pos + 8 < P2_RAW));
            }
        };
        int n = wg == 2 && half ? -1 : wg, pos = p2_start(n);
        uint32_t px = 0;
        wait_pos(pos);
        mbar_wait(af, 0);
        table(pos);
        fetch(0, pos < P2_RAW);
#pragma unroll 1
        for (;; n += 3) {
            TSTAMP(1, 2 + n);
            const int end = pos + (n < 0 ? 24 : 48);
#pragma unroll
            for (int i = 0; i < 48; i += 2) {
                asm volatile("mov.b64 {%0, %1}, 0;\n" : "=r"(acc0[i]), "=r"(acc0[i + 1]));
                asm volatile("mov.b64 {%0, %1}, 0;\n" : "=r"(acc1[i]), "=r"(acc1[i + 1]));
            }
            int thr = 1;
#pragma unroll 1
            for (; pos < P2_RAW; pos += 8, thr = 2) block8(true, pos, thr, 0);
#pragma unroll 1
            for (; pos < end; pos += 8, thr = 2) {
                const int e = pos + 8, r = e % 48;
                block8(false, pos, thr, e < 48 || e > 256 || (r != 0 && r != P2_S1 && r != P2_S2) ? 0 : e == end ? 2 : 1);
            }
            TR2(wg, pos - 1, 4);
            wg_wait<0>();
            TR2(wg, pos - 1, 5);
            if (who == 1) mbar_arrive_cluster(rel0 + 24);
            mbar_wait(bar_xfull + wg * 8, px);
            TR2(wg, pos - 1, 6);
            px ^= 1;
            __syncwarp();
            p2_epilogue(acc0, acc1, up, sx, sbase + P2_OFF_BIAS + q * 16 + (n < 0 && fin ? C_DIM * 2 : 0), zero);
            TR2(wg, pos - 1, 7);
            if (n + 3 >= P2_ITEMS) { publish(); break; }
            if (n < 0) {
                publish();
                pos = P2_S2;
                wait_pos(pos);
                mbar_wait(bar_bfull, 0);
            } else {
                pend = true;
                ok_a = false;
            }
        }
        TSTAMP(1, 29);
        cluster_sync();
        TSTAMP(1, 30);
    }
}

}

extern "C" void kernel_launch(void* const* d_in, const int* in_sizes, int n_in, void* d_out, int out_size) {
    const __nv_bfloat16* x = (const __nv_bfloat16*)d_in[0];
    const __nv_bfloat16* dw = (const __nv_bfloat16*)d_in[1];
    const __nv_bfloat16* w1 = (const __nv_bfloat16*)d_in[2];
    const __nv_bfloat16* w2 = (const __nv_bfloat16*)d_in[3];
    const __nv_bfloat16* grn_g = (const __nv_bfloat16*)d_in[4];
    const __nv_bfloat16* grn_b = (const __nv_bfloat16*)d_in[5];
    __nv_bfloat16* out = (__nv_bfloat16*)d_out;

    cudaFuncSetAttribute(pass1_kernel, cudaFuncAttributeMaxDynamicSharedMemorySize, P1_SMEM);
    cudaFuncSetAttribute(pass2_kernel, cudaFuncAttributeMaxDynamicSharedMemorySize, P2_SMEM);

    typedef CUresult (*EncodeFn)(CUtensorMap*, CUtensorMapDataType, cuuint32_t, void*, const cuuint64_t*, const cuuint64_t*,
                                 const cuuint32_t*, const cuuint32_t*, CUtensorMapInterleave, CUtensorMapSwizzle,
                                 CUtensorMapL2promotion, CUtensorMapFloatOOBfill);
    static EncodeFn encode = nullptr;
    if (!encode) {
        cudaDriverEntryPointQueryResult qres;
        cudaGetDriverEntryPoint("cuTensorMapEncodeTiled", (void**)&encode, cudaEnableDefault, &qres);
    }
    CUtensorMap wmap;
    const cuuint64_t gdim[2] = {HID, C_DIM};
    const cuuint64_t gstr[1] = {HID * 2};
    const cuuint32_t box[2] = {64, 192}, estr[2] = {1, 1};
    CUresult er = encode(&wmap, CU_TENSOR_MAP_DATA_TYPE_BFLOAT16, 2, (void*)w1, gdim, gstr, box, estr, CU_TENSOR_MAP_INTERLEAVE_NONE,
           CU_TENSOR_MAP_SWIZZLE_128B, CU_TENSOR_MAP_L2_PROMOTION_L2_128B, CU_TENSOR_MAP_FLOAT_OOB_FILL_NONE);
    if (er != CUDA_SUCCESS) printf("tensor map encode failed %d\n", (int)er);

    pass1_kernel<<<NUM_CTAS, 512, P1_SMEM>>>(wmap, x, dw, w2, grn_b, 0);

    cudaLaunchAttribute attr[1];
    attr[0].id = cudaLaunchAttributeProgrammaticStreamSerialization;
    attr[0].val.programmaticStreamSerializationAllowed = 1;
    cudaLaunchConfig_t cfg = {};
    cfg.gridDim = dim3(NUM_CTAS);
    cfg.stream = 0;
    cfg.attrs = attr;
    cfg.numAttrs = 1;
    cfg.blockDim = dim3(512);
    cfg.dynamicSmemBytes = P2_SMEM;
    cudaLaunchKernelEx(&cfg, pass2_kernel, x, grn_g, out, 0);
}
```

```cpp
#include <cuda.h>
#include <cuda_runtime.h>
#include <cuda_bf16.h>
#include <cuda_fp16.h>
#include <stdint.h>
#include <stdio.h>

namespace {

constexpr int M_TOTAL = 384 * 384;
constexpr int C_DIM   = 384;
constexpr int HID     = 1536;
constexpr int NT128   = M_TOTAL / 128;
constexpr int NUM_CTAS = 132;

constexpr int NGRP = 11, GRP_CTAS = 12;
constexpr int LN_STEP = NUM_CTAS / 4, LN_RING = 2 * LN_STEP;
constexpr int NT_RING = NT128 - NGRP;
constexpr int LN_TILE = 128 * C_DIM * 2;
constexpr int H_TILE = 64 * HID * 3 / 2;
constexpr int H_HALF = 3072, H_STEP = 6144;

__device__ __align__(1024) uint4 g_h[(size_t)M_TOTAL * HID * 3 / 32];
__device__ __align__(1024) uint4 g_ln[LN_RING * LN_TILE / 16];
__device__ __align__(1024) uint4 g_w2img[2][HID * C_DIM * 2 / 16];
__device__ __align__(16) float g_sums[2][HID + 512];
__device__ unsigned g_epoch;
__device__ __align__(128) unsigned g_prog[2][32];
__device__ __align__(128) unsigned g_half[32][2];
__device__ unsigned g_flag[LN_RING + 3][2][8];
#define TSTAMP(k, i)
#define TRACE(wg, pos, i)
#define TRACEW(pos, i)

#define TR2(wg, pos, i)
__host__ __device__ __forceinline__ int perm32(int n) {
    return (n & ~31) | (((n >> 1) & 3) << 3) | (((n >> 3) & 3) << 1) | (n & 1);
}

__device__ __forceinline__ uint32_t smem_u32(const void* p) { return (uint32_t)__cvta_generic_to_shared(p); }

__device__ __forceinline__ void mbar_init(uint32_t bar, uint32_t count) {
    asm volatile("mbarrier.init.shared::cta.b64 [%0], %1;\n" ::"r"(bar), "r"(count) : "memory");
}
__device__ __forceinline__ void mbar_expect_tx(uint32_t bar, uint32_t bytes) {
    asm volatile("mbarrier.arrive.expect_tx.shared::cta.b64 _, [%0], %1;\n" ::"r"(bar), "r"(bytes) : "memory");
}
__device__ __forceinline__ void mbar_arrive(uint32_t bar) {
    asm volatile("mbarrier.arrive.shared::cta.b64 _, [%0];\n" ::"r"(bar) : "memory");
}
__device__ __forceinline__ void mbar_arrive_cluster(uint32_t bar_cluster_addr) {
    asm volatile("mbarrier.arrive.shared::cluster.b64 _, [%0];\n" ::"r"(bar_cluster_addr) : "memory");
}
#define SAFE_BREAK
__device__ __forceinline__ void mbar_wait(uint32_t bar, uint32_t parity) {
    asm volatile(
        "{\n"
        ".reg .pred p;\n"
        "LAB_WAIT:\n"
        "mbarrier.try_wait.parity.shared::cta.b64 p, [%0], %1;\n"
        "@!p bra LAB_WAIT;\n"
        "}\n" ::"r"(bar), "r"(parity) : "memory");
}
__device__ __forceinline__ bool mbar_test(uint32_t bar, uint32_t parity) {
    uint32_t ok;
    asm volatile("{\n.reg .pred p;\n"
                 "mbarrier.test_wait.parity.shared::cta.b64 p, [%1], %2;\n"
                 "selp.u32 %0, 1, 0, p;\n}\n" : "=r"(ok) : "r"(bar), "r"(parity) : "memory");
    return ok != 0;
}
__device__ __forceinline__ uint32_t mapa(uint32_t addr, uint32_t rank) {
    uint32_t r;
    asm volatile("mapa.shared::cluster.u32 %0, %1, %2;\n" : "=r"(r) : "r"(addr), "r"(rank));
    return r;
}
__device__ __forceinline__ void bulk_g2s(uint32_t dst, const void* src, uint32_t bytes, uint32_t bar) {
    asm volatile("cp.async.bulk.shared::cluster.global.mbarrier::complete_tx::bytes [%0], [%1], %2, [%3];\n"
                 ::"r"(dst), "l"(src), "r"(bytes), "r"(bar) : "memory");
}
__device__ __forceinline__ void bulk_g2s_mc(uint32_t dst, const void* src, uint32_t bytes, uint32_t bar, uint16_t mask) {
    asm volatile("cp.async.bulk.shared::cluster.global.mbarrier::complete_tx::bytes.multicast::cluster [%0], [%1], %2, [%3], %4;\n"
                 ::"r"(dst), "l"(src), "r"(bytes), "r"(bar), "h"(mask) : "memory");
}
__device__ __forceinline__ void tma2(uint32_t dst, const CUtensorMap* map, int c0, int c1, uint32_t bar) {
    asm volatile("cp.async.bulk.tensor.2d.shared::cluster.global.tile.mbarrier::complete_tx::bytes [%0], [%1, {%2, %3}], [%4];\n"
                 ::"r"(dst), "l"(map), "r"(c0), "r"(c1), "r"(bar) : "memory");
}
template <bool ACQ>
__device__ __forceinline__ uint32_t flag_wait(const unsigned* p, unsigned target) {
    unsigned v, n = 0;
    do {
        if (ACQ) asm volatile("ld.acquire.gpu.global.u32 %0, [%1];\n" : "=r"(v) : "l"(p) : "memory");
        else asm volatile("ld.relaxed.gpu.global.u32 %0, [%1];\n" : "=r"(v) : "l"(p) : "memory");
        n++;
    } while (v < target);
    return n == 1;
}
__device__ __forceinline__ void ldsm4t(uint32_t (&r)[4], uint32_t addr) {
    asm volatile("ldmatrix.sync.aligned.m8n8.x4.trans.shared.b16 {%0,%1,%2,%3}, [%4];\n"
                 : "=r"(r[0]), "=r"(r[1]), "=r"(r[2]), "=r"(r[3]) : "r"(addr) : "memory");
}
__device__ __forceinline__ void bulk_s2g(void* dst, uint32_t src, uint32_t bytes) {
    asm volatile("cp.async.bulk.global.shared::cta.bulk_group [%0], [%1], %2;\n" ::"l"(dst), "r"(src), "r"(bytes) : "memory");
}
__device__ __forceinline__ void cluster_sync() {
    asm volatile("barrier.cluster.arrive.aligned;\nbarrier.cluster.wait.aligned;\n" ::: "memory");
}
__device__ __forceinline__ void cluster_sync_relaxed() {
    asm volatile("barrier.cluster.arrive.relaxed.aligned;\nbarrier.cluster.wait.aligned;\n" ::: "memory");
}
__device__ __forceinline__ void gdc_wait() { asm volatile("griddepcontrol.wait;\n" ::: "memory"); }
__device__ __forceinline__ void gdc_launch() { asm volatile("griddepcontrol.launch_dependents;\n" ::: "memory"); }
__device__ __forceinline__ uint32_t cluster_rank() {
    uint32_t r;
    asm volatile("mov.u32 %0, %%cluster_ctarank;\n" : "=r"(r));
    return r;
}
__device__ __forceinline__ bool elect_one() {
    uint32_t pred;
    asm volatile("{\n.reg .pred p;\nelect.sync _|p, 0xffffffff;\nselp.u32 %0, 1, 0, p;\n}\n" : "=r"(pred));
    return pred != 0;
}
__device__ __forceinline__ void wg_fence() { asm volatile("wgmma.fence.sync.aligned;\n" ::: "memory"); }
__device__ __forceinline__ void wg_commit() { asm volatile("wgmma.commit_group.sync.aligned;\n" ::: "memory"); }
template <int N> __device__ __forceinline__ void wg_wait() {
    asm volatile("wgmma.wait_group.sync.aligned %0;\n" ::"n"(N) : "memory");
}
template <int R> __device__ __forceinline__ void reg_inc() { asm volatile("setmaxnreg.inc.sync.aligned.u32 %0;\n" ::"n"(R)); }
template <int R> __device__ __forceinline__ void reg_dec() { asm volatile("setmaxnreg.dec.sync.aligned.u32 %0;\n" ::"n"(R)); }
__device__ __forceinline__ void bar_sync(int id, int n) { asm volatile("bar.sync %0, %1;\n" ::"r"(id), "r"(n) : "memory"); }
__device__ __forceinline__ void bar_arrive(int id, int n) { asm volatile("bar.arrive %0, %1;\n" ::"r"(id), "r"(n) : "memory"); }

__device__ __forceinline__ uint64_t make_desc(uint32_t saddr, uint32_t lbo, uint32_t sbo) {
    return (uint64_t)((saddr & 0x3FFFF) >> 4) | ((uint64_t)(lbo >> 4) << 16) | ((uint64_t)(sbo >> 4) << 32);
}

__device__ __forceinline__ void stg128_cs(void* p, uint32_t a, uint32_t b, uint32_t c, uint32_t d) {
    asm volatile("st.global.cs.v4.u32 [%0], {%1,%2,%3,%4};\n" ::"l"(p), "r"(a), "r"(b), "r"(c), "r"(d) : "memory");
}
__device__ __forceinline__ uint32_t pack_bf16(float lo, float hi) {
    uint32_t r;
    asm("cvt.rn.bf16x2.f32 %0, %1, %2;\n" : "=r"(r) : "f"(hi), "f"(lo));
    return r;
}
__device__ __forceinline__ float bf_lo(uint32_t v) { return __uint_as_float(v << 16); }
__device__ __forceinline__ float bf_hi(uint32_t v) { return __uint_as_float(v & 0xffff0000u); }
__device__ __forceinline__ uint32_t bf2_mul(uint32_t a, uint32_t b) {
    uint32_t r;
    asm("mul.rn.bf16x2 %0, %1, %2;\n" : "=r"(r) : "r"(a), "r"(b));
    return r;
}
__device__ __forceinline__ uint32_t bf2_fma(uint32_t a, uint32_t b, uint32_t c) {
    uint32_t r;
    asm("fma.rn.bf16x2 %0, %1, %2, %3;\n" : "=r"(r) : "r"(a), "r"(b), "r"(c));
    return r;
}
__device__ __forceinline__ uint32_t bf2_add(uint32_t a, uint32_t b) {
    uint32_t r;
    asm("add.rn.bf16x2 %0, %1, %2;\n" : "=r"(r) : "r"(a), "r"(b));
    return r;
}
__device__ __forceinline__ uint32_t h2_mul(uint32_t a, uint32_t b) {
    uint32_t r;
    asm("mul.rn.f16x2 %0, %1, %2;\n" : "=r"(r) : "r"(a), "r"(b));
    return r;
}
__device__ __forceinline__ uint32_t h2_fma(uint32_t a, uint32_t b, uint32_t c) {
    uint32_t r;
    asm("fma.rn.f16x2 %0, %1, %2, %3;\n" : "=r"(r) : "r"(a), "r"(b), "r"(c));
    return r;
}
__device__ __forceinline__ uint32_t h2_add(uint32_t a, uint32_t b) {
    uint32_t r;
    asm("add.rn.f16x2 %0, %1, %2;\n" : "=r"(r) : "r"(a), "r"(b));
    return r;
}
__device__ __forceinline__ uint32_t pack_f16(float lo, float hi) {
    uint32_t r;
    asm("cvt.rn.f16x2.f32 %0, %1, %2;\n" : "=r"(r) : "f"(hi), "f"(lo));
    return r;
}
__device__ __forceinline__ float h_lo(uint32_t v) { return __low2float(*reinterpret_cast<const __half2*>(&v)); }
__device__ __forceinline__ float h_hi(uint32_t v) { return __high2float(*reinterpret_cast<const __half2*>(&v)); }
__device__ __forceinline__ uint32_t bf2_to_h2(uint32_t v) { return (v & 0x7fff7fffu) * 7u + v; }
__device__ __forceinline__ uint32_t prmt(uint32_t a, uint32_t b, uint32_t sel) {
    uint32_t r;
    asm("prmt.b32 %0, %1, %2, %3;\n" : "=r"(r) : "r"(a), "r"(b), "r"(sel));
    return r;
}
__device__ __forceinline__ uint32_t bitsel(uint32_t a, uint32_t b, uint32_t m) {
    uint32_t r;
    asm("lop3.b32 %0, %1, %2, %3, 0xd8;\n" : "=r"(r) : "r"(a), "r"(b), "r"(m));
    return r;
}
constexpr float KAPPA = 0.3292034911525734f;
constexpr uint32_t GELU_C2 = 0x40d940d9u;
constexpr float HSCALE = 1.0f / (2.0f * KAPPA);
__device__ __forceinline__ float w2_scale(uint32_t m) { return __uint_as_float((257u - max(m >> 23, 16u)) << 23); }
__device__ __forceinline__ void sched_break(int zero) {
    asm volatile("{\n.reg .pred p;\nsetp.ne.s32 p, %0, 0;\nSB_LOOP:\n@p nanosleep.u32 1;\n@p bra SB_LOOP;\n}\n" ::"r"(zero));
}

#define ACC8(d, o) "+r"(d[o + 0]), "+r"(d[o + 1]), "+r"(d[o + 2]), "+r"(d[o + 3]), "+r"(d[o + 4]), "+r"(d[o + 5]), "+r"(d[o + 6]), "+r"(d[o + 7])

__device__ __forceinline__ void mma_rs_n128(uint32_t (&d)[32], const uint32_t (&a)[4], uint64_t desc, int scale_d) {
    asm volatile(
        "{\n.reg .pred p;\nsetp.ne.b32 p, %37, 0;\n"
        "wgmma.mma_async.sync.aligned.m64n128k16.f16.f16.f16 "
        "{%0,%1,%2,%3,%4,%5,%6,%7,%8,%9,%10,%11,%12,%13,%14,%15,"
        "%16,%17,%18,%19,%20,%21,%22,%23,%24,%25,%26,%27,%28,%29,%30,%31},"
        "{%32,%33,%34,%35}, %36, p, 1, 1, 0;\n}\n"
        : ACC8(d, 0), ACC8(d, 8), ACC8(d, 16), ACC8(d, 24)
        : "r"(a[0]), "r"(a[1]), "r"(a[2]), "r"(a[3]), "l"(desc), "r"(scale_d));
}

__device__ __forceinline__ void mma_rs_n192(uint32_t (&d)[48], const uint4& a, uint64_t db) {
    asm volatile(
        "wgmma.mma_async.sync.aligned.m64n192k16.f16.f16.f16 "
        "{%0,%1,%2,%3,%4,%5,%6,%7,%8,%9,%10,%11,%12,%13,%14,%15,"
        "%16,%17,%18,%19,%20,%21,%22,%23,%24,%25,%26,%27,%28,%29,%30,%31,"
        "%32,%33,%34,%35,%36,%37,%38,%39,%40,%41,%42,%43,%44,%45,%46,%47},"
        "{%48,%49,%50,%51}, %52, 1, 1, 1, 0;\n"
        : ACC8(d, 0), ACC8(d, 8), ACC8(d, 16), ACC8(d, 24), ACC8(d, 32), ACC8(d, 40)
        : "r"(a.x), "r"(a.y), "r"(a.z), "r"(a.w), "l"(db));
}

#define P1_WPF 30
#define P1_PACE true
constexpr int P1_SLOT = LN_TILE / 2, P1_NST = 4;
constexpr int P1_X = 32 * C_DIM * 2;
constexpr int P1_OFF_X = P1_SLOT * P1_NST;
constexpr int P1_OFF_BAR = P1_OFF_X + P1_X;
constexpr int P1_OFF_TILE = P1_OFF_BAR + (2 * P1_NST + 2 + 4 + 4) * 8;
constexpr int P1_OFF_RAW = P1_OFF_TILE + 64;
constexpr int P1_OFF_EX = P1_OFF_RAW + 16;
constexpr int P1_SMEM = P1_OFF_EX + 128 * 4;

__device__ __forceinline__ float rsqrt_fast(float x) {
    float r;
    asm("rsqrt.approx.ftz.f32 %0, %1;\n" : "=f"(r) : "f"(x));
    return r;
}
__device__ __forceinline__ float row_sum(const uint32_t (&c)[4]) {
    const uint32_t u = bf2_add(bf2_add(c[0], c[1]), bf2_add(c[2], c[3]));
    float s = bf_lo(u) + bf_hi(u);
#pragma unroll
    for (int o = 1; o < 8; o <<= 1) s += __shfl_xor_sync(0xffffffffu, s, o);
    return s;
}
__device__ __forceinline__ uint32_t pace(uint32_t bar, uint32_t off, uint32_t val, uint32_t after, int zero) {
    asm volatile(
        "{\n.reg .pred p;\n.reg .b32 par;\n"
        "lop3.b32 par, %4, %2, %3, 0xea;\n"
        "mbarrier.test_wait.parity.shared::cta.b64 p, [%1], par;\n"
        "selp.u32 par, 1, 0, p;\n"
        "mbarrier.try_wait.parity.shared::cta.b64 p, [%1], par, 1000;\n"
        "@p or.b32 %0, %0, %2;\n"
        "}\n" : "+r"(val) : "r"(bar), "r"(zero), "r"(off), "r"(after));
    return val;
}
template <bool PACE>
__device__ __forceinline__ void ln_row(uint32_t (&v)[6][4], const uint32_t (&d)[6][4], uint32_t bar, uint32_t off, int zero,
                                       uint32_t bar_read) {
    uint32_t c[4];
#pragma unroll
    for (int i = 0; i < 6; i++)
#pragma unroll
        for (int k = 0; k < 4; k++) c[k] = bf2_fma(v[i][k], d[i][k], i ? c[k] : 0);
    const float inv = 1.0f / C_DIM;
    const float m = row_sum(c) * inv;
    uint32_t nm = pack_bf16(-m, -m);
    const float e = m + bf_lo(nm);
    if (bar_read) mbar_arrive(bar_read + (nm & zero));
    if (PACE) nm = pace(bar, off, nm, nm, zero);
#pragma unroll
    for (int i = 0; i < 6; i++) {
#pragma unroll
        for (int k = 0; k < 4; k++) {
            v[i][k] = bf2_fma(v[i][k], d[i][k], nm);
            c[k] = i ? bf2_fma(v[i][k], v[i][k], c[k]) : bf2_mul(v[i][k], v[i][k]);
        }
    }
    float r = KAPPA * rsqrt_fast(fmaxf(fmaf(-e, e, row_sum(c) * inv), 0.f) + 1e-5f);
    const float er = -e * r * 0x1p-116f;
    if (__any_sync(0xffffffffu, r < 0x1p-8f)) {
        const uint32_t p2 = __float_as_uint(r) & 0x7f800000u;
        r = __uint_as_float((__float_as_uint(r) & 0x007fffffu) | 0x3f800000u);
#pragma unroll
        for (int i = 0; i < 6; i++)
#pragma unroll
            for (int k = 0; k < 4; k++) v[i][k] = bf2_mul(v[i][k], p2 | p2 >> 16);
    }
    r *= 0x1p-116f;
    uint32_t rs = pack_bf16(r, r);
    const uint32_t sh = pack_bf16(er, er);
    if (PACE) rs = pace(bar, off, rs, sh, zero);
#pragma unroll
    for (int i = 0; i < 6; i++)
#pragma unroll
        for (int k = 0; k < 4; k++) v[i][k] = bf2_to_h2(bf2_fma(v[i][k], rs, sh));
}

template <int R>
__device__ __forceinline__ uint32_t gelu2(uint32_t a, uint32_t sc2) {
    uint32_t y, t;
    if (R) asm("{\n.reg .b16 l, h;\n.reg .b32 f;\nmov.b32 {l, h}, %2;\nmov.b32 f, {h, h};\nmul.rn.f16x2 %0, %1, f;\n}\n" : "=r"(y) : "r"(a), "r"(sc2));
    else asm("{\n.reg .b16 l, h;\n.reg .b32 f;\nmov.b32 {l, h}, %2;\nmov.b32 f, {l, l};\nmul.rn.f16x2 %0, %1, f;\n}\n" : "=r"(y) : "r"(a), "r"(sc2));
    asm("tanh.approx.f16x2 %0, %1;\n" : "=r"(t) : "r"(h2_mul(y, h2_fma(y, y, GELU_C2))));
    return h2_fma(a, t, a);
}
constexpr uint32_t SPARE = 0x40074007u;

__device__ __forceinline__ uint32_t p1_parity(uint32_t sbase) {
    uint32_t v;
    asm volatile("ld.shared.u32 %0, [%1];\n" : "=r"(v) : "r"(sbase + P1_OFF_TILE - 4) : "memory");
    return v;
}
template <int WG>
__device__ __forceinline__ void p1_consumer(const uint32_t (&a)[24][4], uint32_t sc2, uint32_t sbase, int w, int lane, int zero) {
    const uint32_t bar_full = sbase + P1_OFF_BAR, bar_empty = bar_full + P1_NST * 8;
    const uint32_t empty_remote = mapa(bar_empty, lane & 1) + (WG == 0 ? (lane & 2) * 4 : 0);
    const uint32_t bar_pace = bar_empty + P1_NST * 8 + 16 + w * 8;
    const int g = lane >> 2, q = lane & 3, cb = (blockIdx.x % GRP_CTAS) * 2 + WG;
    uint32_t acc[32], st[6][4] = {};
    float ssq[2] = {0.f, 0.f};
    TSTAMP(0, 1);

    uint8_t* hp = reinterpret_cast<uint8_t*>(g_h) + (size_t)(blockIdx.x / GRP_CTAS) * (2 * H_TILE) + ((cb * 2 + (w >> 1)) * H_STEP + (w & 1) * 1536) + g * 64 + (q ^ (g >> 1)) * 16;
    const uint64_t desc_base = make_desc(sbase, 16, 1024) | (1ull << 62);
#pragma unroll 1
    for (int i = 0;; i++) {
        const int s0 = (i & 1) * 16, par = (i >> 1) & 1;
        const uint64_t d0 = desc_base + (uint64_t)((i & 1) * (LN_TILE / 16));
        TRACE(WG, i, 0);
        if (WG == 0) mbar_wait(bar_full + s0, par);
        bar_sync(1 + WG, 256);
        TRACE(WG, i, 1);
        uint32_t step, more;
        wg_fence();
#pragma unroll
        for (int k = 0; k < 24; k++) {
            if (WG == 0 && k == 12) mbar_wait(bar_full + s0 + 8, par);
            mma_rs_n128(acc, a[k], d0 + (uint64_t)((k >> 2) * 1024 + (k & 3) * 2), k != 0);
            if (k == 23) bar_arrive(2 - WG, 256);
            if (k % 12 == 11) wg_commit();
        }
        asm volatile("ld.shared.v2.u32 {%0, %1}, [%2];\n" : "=r"(step), "=r"(more) : "r"(sbase + P1_OFF_TILE + (i & 3) * 16) : "memory");
        TRACE(WG, i, 2);
        if (WG == 1) {
            wg_wait<1>();
            if (lane < 2) mbar_arrive_cluster(empty_remote + s0);
        }
        hp += step;
        TRACE(WG, i, 3);
        if (zero) {
#pragma unroll
            for (int c = 0; c < 6; c++) stg128_cs(hp + c * 512, st[c][0], st[c][1], st[c][2], st[c][3]);
        }
        wg_wait<0>();
        TRACE(WG, i, 4);
        if (lane < (WG == 0 ? 4 : 2)) mbar_arrive_cluster(empty_remote + s0 + WG * 8);
        uint32_t sq[2], h[8][4];
#pragma unroll
        for (int i2 = 0; i2 < 5; i2++) {
#pragma unroll
            for (int c = 2 * i2 - 2; c < 2 * i2; c++) {
                if (c < 0) continue;
                if (c & 3) {
                    uint32_t (&o)[4] = st[c - 1 - (c >> 2)];
#pragma unroll
                    for (int u = 0; u < 4; u++) {
                        const uint32_t v = h[c & 4][u];
                        o[u] = bitsel(h[c][u], (c & 3) == 2 ? prmt(v, v, 0xa381) : prmt(v >> 3, v, (c & 3) == 1 ? 0x6240 : 0xf3d1), SPARE);
                    }
                    stg128_cs(hp + (c >> 2) * H_HALF + ((c & 3) - 1) * 512, o[0], o[1], o[2], o[3]);
                }
            }
            if (i2 < 4) {
#pragma unroll
                for (int u = 0; u < 4; u++) {
                    h[2 * i2][u] = gelu2<0>(acc[8 * i2 + 2 * u], sc2);
                    h[2 * i2 + 1][u] = gelu2<1>(acc[8 * i2 + 2 * u + 1], sc2);
#pragma unroll
                    for (int r = 0; r < 2; r++) sq[r] = (i2 | u) ? h2_fma(h[2 * i2 + r][u], h[2 * i2 + r][u], sq[r]) : h2_mul(h[r][u], h[r][u]);
                }
                sched_break(zero);
            }
        }
#pragma unroll
        for (int r = 0; r < 2; r++) ssq[r] += h_lo(sq[r]) + h_hi(sq[r]);
        if (lane == 0) mbar_arrive(bar_pace);
        if (!more) break;
    }
    TSTAMP(0, 21);
    if (WG == 0) bar_sync(1, 256);
#pragma unroll
    for (int r = 0; r < 2; r++) {
        ssq[r] += __shfl_xor_sync(0xffffffffu, ssq[r], 1);
        ssq[r] += __shfl_xor_sync(0xffffffffu, ssq[r], 2);
        float f;
        asm volatile("ld.shared.f32 %0, [%1];\n" : "=f"(f) : "r"(sbase + P1_OFF_EX + (WG * 64 + w * 16 + r * 8 + g) * 4) : "memory");
        if (q == 0) atomicAdd(&g_sums[p1_parity(sbase)][cb * 64 + w * 16 + r * 8 + g], ssq[r] * f * f);
    }
}

__global__ void __cluster_dims__(2, 1, 1) __launch_bounds__(512, 1)
pass1_kernel(const __grid_constant__ CUtensorMap wmap, const __nv_bfloat16* __restrict__ x, const __nv_bfloat16* __restrict__ dw,
             const __nv_bfloat16* __restrict__ w2, const __nv_bfloat16* __restrict__ grn_b, int zero) {
    extern __shared__ __align__(1024) uint8_t smem[];
    const uint32_t sbase = smem_u32(smem);
    const uint32_t bar_full = sbase + P1_OFF_BAR, bar_empty = bar_full + P1_NST * 8, bar_w = bar_empty + P1_NST * 8;
    const int tid = threadIdx.x;
    const int warp = __shfl_sync(0xffffffffu, tid >> 5, 0), lane = tid & 31;
    const uint32_t rank = cluster_rank();
    const int cig = blockIdx.x % GRP_CTAS;
    uint8_t* const ring = reinterpret_cast<uint8_t*>(g_ln);

    TSTAMP(0, 0);
    TRACEW(110 + warp, 0);
    const uint32_t bar_pace = bar_w + 16, bar_xfull = bar_pace + 32, bar_xempty = bar_xfull + 8, bar_done = bar_xfull + 16;
    const uint32_t bar_raw = sbase + P1_OFF_RAW;
    const int ln0 = blockIdx.x >> 2, first = blockIdx.x / GRP_CTAS;
    const uint8_t* xsrc = reinterpret_cast<const uint8_t*>(x) + (size_t)(NGRP * 4 + blockIdx.x) * P1_X;

    if (warp >= 12) {
        reg_dec<40>();
        asm volatile("barrier.cluster.arrive.relaxed.aligned;\n" ::: "memory");
        asm volatile("barrier.cluster.wait.aligned;\n" ::: "memory");
        if (warp == 12) {
            int prev = first - NGRP, t = first, next = t + NGRP;
            const uint32_t rbase = mapa(sbase, lane & 1);
#pragma unroll 1
            for (int i = 1; t < NT_RING; i++) {
                const int s0 = (i & 1) * 2, par = ((i + 1) >> 1 & 1) ^ 1;
                const int round = t / LN_RING, slot = t - round * LN_RING;
                const uint8_t* src = ring + slot * LN_TILE + rank * (P1_SLOT / 2);
                int draw = 0;
                if (rank == 0 && lane == 0) draw = atomicAdd(&g_flag[LN_RING + (cig >> 2)][(cig >> 1) & 1][0], 1u);
                flag_wait<true>(&g_flag[slot][0][0], 4 * round + 4);
                TRACEW(i, 2);
                asm volatile("fence.proxy.async.global;\n" ::: "memory");
                draw = 2 * NGRP + __shfl_sync(0xffffffffu, draw, 0);
#pragma unroll
                for (int h = 0; h < 2; h++) {
                    mbar_wait(bar_empty + (s0 + h) * 8, par);
                    TRACEW(i, 4 + h);
                    if (elect_one()) {
                        const int len = P1_SLOT / 2;
                        mbar_expect_tx(bar_full + (s0 + h) * 8, 2 * len + 16 - 16 * h);
                        bulk_g2s_mc(sbase + (s0 + h) * P1_SLOT + rank * (P1_SLOT / 2), src + h * P1_SLOT, len, bar_full + (s0 + h) * 8, (uint16_t)3);
                    }
                    __syncwarp();
                    if (h == 0 && rank == 0 && lane < 2)
                        asm volatile("st.async.shared::cluster.mbarrier::complete_tx::bytes.v4.u32 [%0], {%1, %2, %3, %3}, [%4];\n"
                                     ::"r"(rbase + P1_OFF_TILE + (i & 3) * 16), "r"((t - prev) * (2 * H_TILE)), "r"((int)(next < NT_RING)), "r"(draw),
                                       "r"(rbase + P1_OFF_BAR + s0 * 8) : "memory");
                }
                prev = t;
                t = next;
                next = draw;
                if (rank != 0) {
                    mbar_wait(bar_full + (s0 ^ 2) * 8, ((i - 1) >> 1) & 1);
                    asm volatile("ld.shared.u32 %0, [%1];\n" : "=r"(t) : "r"(sbase + P1_OFF_TILE + ((i - 1) & 3) * 16 + 8) : "memory");
                }
            }
        } else if (warp == 13) {
            int ph = 0;
            unsigned target = 0;
#pragma unroll 1
            for (int i = ln0 + LN_STEP; i < NT_RING; i += LN_STEP, ph ^= 1) {
                target += ph * (GRP_CTAS / 2);
                xsrc += (size_t)NUM_CTAS * P1_X;
                mbar_wait(bar_xempty, ph);
                if (elect_one()) {
                    mbar_expect_tx(bar_xfull, P1_X);
                    bulk_g2s(sbase + P1_OFF_X, xsrc, P1_X, bar_xfull);
                }
                __syncwarp();
                const uint32_t off = flag_wait<false>(&g_flag[ln0 + (ph ^ 1) * LN_STEP][1][0], target);
                mbar_wait(bar_done, ph);
                if (elect_one()) {
                    asm volatile("st.shared.u32 [%0], %1;\n" ::"r"(bar_done + 8), "r"(off) : "memory");
                    mbar_arrive(bar_xfull);
                }
                __syncwarp();
            }
        } else if (warp == 15) {
            if (rank == 1 && lane < 2) mbar_arrive(bar_empty + (2 + lane) * 8);
            const uint32_t par = g_epoch & 1;
            asm volatile("st.shared.u32 [%0], %1;\n" ::"r"(sbase + P1_OFF_TILE - 4), "r"(par) : "memory");
            if (blockIdx.x < 16) reinterpret_cast<float4*>(g_sums[par ^ 1])[blockIdx.x * 32 + lane] = make_float4(0.f, 0.f, 0.f, 0.f);
            {
                bar_sync(4, 288);
                TRACEW(110 + warp, 1);
                mbar_wait(bar_raw + 8, 0);
                TRACEW(110 + warp, 2);
                const uint32_t o = lane * 16384 + rank * 8192, peer = mapa(sbase, rank ^ 1);
                if (lane < 6)
                    asm volatile("cp.async.bulk.shared::cluster.shared::cta.mbarrier::complete_tx::bytes [%0], [%1], 8192, [%2];\n"
                                 ::"r"(peer + o), "r"(sbase + o), "r"(peer + P1_OFF_BAR + (lane >= 3 ? 8 : 0)) : "memory");
                __syncwarp();
            }
            int t = first, next = t + NGRP;
            if (rank == 1) {
                mbar_wait(bar_full, 0);
                mbar_wait(bar_full + 8, 0);
                if (lane < 2) mbar_arrive(bar_empty + lane * 8);
            }
#pragma unroll 1
            for (int i = 1; rank == 1 && t < NT_RING; i++) {
                const int s0 = (i & 1) * 16;
                mbar_wait(bar_full + s0, (i >> 1) & 1);
                mbar_wait(bar_full + s0 + 8, (i >> 1) & 1);
                if (lane == 0) asm volatile("red.relaxed.gpu.global.add.u32 [%0], 1;\n" ::"l"(&g_flag[t % LN_RING][1][0]) : "memory");
                t = next;
                asm volatile("ld.shared.u32 %0, [%1];\n" : "=r"(next) : "r"(sbase + P1_OFF_TILE + (i & 3) * 16 + 8) : "memory");
                if (lane < 2) mbar_arrive(bar_empty + s0 + lane * 8);
                TRACEW(i, 3);
            }
            if (rank == 0) {
                mbar_wait(bar_full, 0);
                TRACEW(110 + warp, 3);
                mbar_wait(bar_full, 1);
                float* sums = g_sums[par] + HID;
                unsigned* flag = reinterpret_cast<unsigned*>(sums + C_DIM);
                float gs = 0.f;
#pragma unroll 1
                for (int pass = 0; pass < 2; pass++) {
                    float mx = 0.f;
#pragma unroll 1
                    for (int it = first; it < 48; it += NGRP) {
                        const int np = (it % 12) * 32 + lane, kb = cig * 2 + it / 12;
                        const __nv_bfloat16* wc = w2 + (size_t)kb * 64 * C_DIM + perm32(np);
                        const uint32_t sc = mapa(sbase + P1_OFF_EX + (kb & 1) * 256, it / 24);
                        float bsum = 0.f;
#pragma unroll 1
                        for (int c = 0; c < 8; c++) {
                            float f[8];
#pragma unroll
                            for (int e = 0; e < 8; e++) f[e] = __bfloat162float(wc[(c * 8 + e) * C_DIM]);
#pragma unroll
                            for (int e = 0; e < 8; e++) {
                                float t;
                                asm volatile("ld.shared::cluster.f32 %0, [%1];\n" : "=f"(t) : "r"(sc + (c * 8 + e) * 4) : "memory");
                                bsum = fmaf(__bfloat162float(grn_b[kb * 64 + c * 8 + e]), f[e], bsum);
                                f[e] *= t;
                                mx = fmaxf(mx, fabsf(f[e]));
                            }
                            if (pass)
                                g_w2img[0][(((kb * 4 + (c >> 1)) * 48 + (np >> 3)) * 2 + (c & 1)) * 8 + (np & 7)] = make_uint4(
                                    pack_f16(f[0] * gs, f[1] * gs), pack_f16(f[2] * gs, f[3] * gs), pack_f16(f[4] * gs, f[5] * gs), pack_f16(f[6] * gs, f[7] * gs));
                        }
                        if (pass) atomicAdd(&sums[np], bsum);
                    }
                    if (!pass) {
                        const uint32_t m = __reduce_max_sync(0xffffffffu, __float_as_uint(mx));
                        if (lane == 0) {
                            atomicMax(flag, m);
                            asm volatile("red.release.gpu.global.add.u32 [%0], 1;\n" ::"l"(flag + 32) : "memory");
                        }
                        flag_wait<true>(flag + 32, NUM_CTAS / 2);
                        gs = w2_scale(__ldcg(flag));
                    }
                }
                do {
                    __nanosleep(1000);
                    asm volatile("ld.volatile.shared.u32 %0, [%1];\n" : "=r"(t) : "r"(sbase + P1_OFF_TILE + (lane & 3) * 16 + 8) : "memory");
                    SAFE_BREAK;
                } while (__all_sync(0xffffffffu, t < NT_RING - P1_WPF));
                if (lane == 0 && blockIdx.x < 128)
                    asm volatile("cp.async.bulk.prefetch.L2.global [%0], %1;\n" ::"l"(g_w2img[0] + blockIdx.x * 576), "r"(18432) : "memory");
            }
        } else if (warp == 14) {
            int ph = 0;
#pragma unroll 1
            for (int i = ln0; i < NT_RING; i += LN_STEP, ph ^= 1) {
                mbar_wait(bar_done, ph);
                TRACEW(i / LN_STEP, 0);
                asm volatile("fence.proxy.async.global;\n" ::: "memory");
                if (elect_one()) asm volatile("red.release.gpu.global.add.u32 [%0], 1;\n" ::"l"(&g_flag[ln0 + ph * LN_STEP][0][0]) : "memory");
                __syncwarp();
                TRACEW(i / LN_STEP, 1);
            }
        }
        __syncwarp();
        cluster_sync();
    } else if (warp >= 8) {
        reg_dec<88>();
        asm volatile("barrier.cluster.arrive.relaxed.aligned;\n" ::: "memory");
        {
            const int l8 = lane & 7, row = (warp - 8) * 4 + (lane >> 3), px = (blockIdx.x & 3) * 32 + row;
            uint32_t d[6][4];
#pragma unroll
            for (int j = 0; j < 6; j++) {
                const uint4 t = reinterpret_cast<const uint4*>(dw)[j * 8 + l8];
                d[j][0] = t.x; d[j][1] = t.y; d[j][2] = t.z; d[j][3] = t.w;
            }
            const int n = (px & 64) + perm32(2 * row + ((px >> 5) & 1));
            uint8_t* const dst0 = ring + ln0 * LN_TILE + n * 128 + ((l8 ^ (n & 7)) << 4);
            const uint32_t src = sbase + P1_OFF_X + ((warp - 8) * 8 + (lane >> 3)) * (C_DIM * 2) + l8 * 16;
            int ph = 0;
            asm volatile("barrier.cluster.wait.aligned;\n" ::: "memory");
#pragma unroll 1
            for (int i = ln0; i < NT_RING; i += LN_STEP, ph ^= 1) {
                TRACE(2, i / LN_STEP, 0);
                mbar_wait(bar_xfull, ph);
                uint32_t off;
                asm volatile("ld.shared.u32 %0, [%1];\n" : "=r"(off) : "r"(bar_done + 8) : "memory");
                TRACE(2, i / LN_STEP, 1);
#pragma unroll 1
                for (int ps = 0; ps < 2; ps++) {
                    uint32_t v[6][4];
#pragma unroll
                    for (int j = 0; j < 6; j++)
                        asm volatile("ld.shared.v4.u32 {%0,%1,%2,%3}, [%4];\n"
                                     : "=r"(v[j][0]), "=r"(v[j][1]), "=r"(v[j][2]), "=r"(v[j][3]) : "r"(src + ps * (4 * C_DIM * 2) + j * 128) : "memory");
                    ln_row<P1_PACE>(v, d, bar_pace + (warp - 8) * 8, off, zero, ps == 1 && lane == 0 ? bar_xempty : 0);
                    uint8_t* dst = dst0 + ph * (LN_STEP * LN_TILE) + ps * 4096;
#pragma unroll
                    for (int j = 0; j < 6; j++) *reinterpret_cast<uint4*>(dst + j * 16384) = make_uint4(v[j][0], v[j][1], v[j][2], v[j][3]);
                    TRACE(2, i / LN_STEP, 3 + ps);
                }
                asm volatile("fence.proxy.async.global;\nfence.acq_rel.cta;\n" ::: "memory");
                __syncwarp();
                if (lane == 0) mbar_arrive(bar_done);
                TRACE(2, i / LN_STEP, 5);
                TRACE(2, i / LN_STEP, 2);
            }
        }
        __syncwarp();
        cluster_sync();
    } else {
        uint32_t d[6][4];
#pragma unroll
        for (int j = 0; j < 6; j++)
            asm volatile("ld.global.nc.v4.u32 {%0,%1,%2,%3}, [%4];\n" : "=r"(d[j][0]), "=r"(d[j][1]), "=r"(d[j][2]), "=r"(d[j][3])
                         : "l"(reinterpret_cast<const uint4*>(dw) + j * 8 + (lane & 7)) : "memory");
        if (tid == 0) {
            mbar_init(bar_raw, 1);
            mbar_init(bar_raw + 8, 8);
            asm volatile("fence.mbarrier_init.release.cluster;\n" ::: "memory");
            mbar_expect_tx(bar_raw, P1_SLOT);
            for (int i = 0; i < 6; i++)
                bulk_g2s(sbase + i * 16384 + (rank ^ 1) * 8192, x + (size_t)(first * 128 + rank * 64) * C_DIM + i * 4096, 8192, bar_raw);
        }
        if (tid == 32) {
            mbar_init(bar_xfull, 2);
            mbar_init(bar_xempty, 4);
            mbar_init(bar_done, 4);
            asm volatile("fence.mbarrier_init.release.cluster;\n" ::: "memory");
            mbar_expect_tx(bar_xfull, P1_X);
            bulk_g2s(sbase + P1_OFF_X, xsrc, P1_X, bar_xfull);
            asm volatile("st.shared.u32 [%0], 1;\n" ::"r"(bar_done + 8) : "memory");
            mbar_arrive(bar_xfull);
        }
        if (tid == 64) {
            asm volatile("st.shared.v4.u32 [%0], {0, 1, %1, %1};\n" ::"r"(sbase + P1_OFF_TILE), "r"(first + NGRP) : "memory");
            for (int i = 0; i < P1_NST; i++) {
                mbar_init(bar_full + i * 8, 1);
                mbar_init(bar_empty + i * 8, 16 + rank);
                mbar_init(bar_pace + i * 8, 1);
                if (i < 2) mbar_expect_tx(bar_full + i * 8, P1_SLOT / 2);
            }
            asm volatile("fence.mbarrier_init.release.cluster;\n" ::: "memory");
            if (blockIdx.x < 64) (&g_half[0][0])[blockIdx.x] = 0;
            else if (blockIdx.x < 66) g_prog[blockIdx.x - 64][0] = 0;
        }
        if (tid == 96) {
            for (int i = 0; i < 2; i++) mbar_init(bar_w + i * 8, 1);
            asm volatile("fence.mbarrier_init.release.cluster;\n" ::: "memory");
        }
        __syncwarp();
        asm volatile("barrier.cluster.arrive.relaxed.aligned;\n" ::: "memory");
        if (tid == 96)
            for (int i = 0; i < 2; i++) {
                mbar_expect_tx(bar_w + i * 8, P1_SLOT);
                tma2(sbase + (2 + i) * P1_SLOT, &wmap, cig * 128 + i * 64, 0, bar_w + i * 8);
                tma2(sbase + (2 + i) * P1_SLOT + P1_SLOT / 2, &wmap, cig * 128 + i * 64, 192, bar_w + i * 8);
            }
        __syncwarp();
        reg_inc<192>();
        TRACEW(110 + warp, 1);
        const int wg = warp >> 2, w = warp & 3;
        uint32_t a[24][4];
        {
            const int n = warp * 8 + (lane >> 3), px = (n & 1) * 32 + (n >> 5) * 4 + ((n >> 1) & 1) * 8 + ((n >> 3) & 3);
            if (wg == 1) bar_arrive(1, 256);
            gdc_launch();
            asm volatile("barrier.cluster.wait.aligned;\n" ::: "memory");
#pragma unroll 1
            for (int ps = -1; ps < 2; ps++) {
                if (ps == 0) mbar_wait(bar_raw, 0);
                TRACEW(110 + warp, 2 + (ps == 0));
                uint32_t v[6][4];
#pragma unroll
                for (int j = 0; j < 6; j++) {
                    const uint32_t o = (px + (ps & 1) * 16) * (C_DIM * 2) + j * 128;
                    asm volatile("ld.shared.v4.u32 {%0,%1,%2,%3}, [%4];\n" : "=r"(v[j][0]), "=r"(v[j][1]), "=r"(v[j][2]), "=r"(v[j][3])
                                 : "r"(sbase + (rank ^ 1) * 8192 + (lane & 7) * 16 + o + (o & ~8191u)) : "memory");
                }
                ln_row<false>(v, d, 0, 0, zero, 0);
                const uint32_t p = sbase + (rank * 64 + n + (ps & 1) * 4) * 128 + (((lane ^ n ^ (ps & 1) * 4) & 7) << 4);
#pragma unroll
                for (int j = 0; j < 6; j++)
                    asm volatile("st.shared.v4.u32 [%4], {%0,%1,%2,%3};\n"
                                 ::"r"(v[j][0]), "r"(v[j][1]), "r"(v[j][2]), "r"(v[j][3]), "r"(p + j * 16384) : "memory");
            }
            asm volatile("fence.proxy.async.shared::cta;\n" ::: "memory");
            __syncwarp();
            if (lane == 0) mbar_arrive_cluster(mapa(bar_raw + 8, rank ^ 1));
            bar_arrive(4, 288);
            TRACEW(110 + warp, 4);
            const uint32_t src = sbase + (2 + wg) * P1_SLOT + ((lane >> 4) * 8 + (lane & 7)) * 128 + (((2 * w + ((lane >> 3) & 1)) ^ (lane & 7)) << 4);
            mbar_wait(bar_w + wg * 8, 0);
            TRACEW(110 + warp, 5);
            uint32_t dep = 0;
#pragma unroll
            for (int k = 0; k < 24; k++) {
                ldsm4t(a[k], src + k * 2048);
                dep |= a[k][0];
            }
            __syncwarp();
            if (lane < 4) mbar_arrive_cluster(mapa(bar_empty, lane & 1) + (2 + (lane >> 1)) * 8 + (dep & zero));
        }
        TRACEW(110 + warp, 6);
        uint32_t ex[2];
#pragma unroll
        for (int r = 0; r < 2; r++) {
            float t = 0.f;
#pragma unroll
            for (int j = 0; j < 6; j++) {
                uint32_t c = bf2_mul(a[4 * j][r], a[4 * j][r]);
#pragma unroll
                for (int k = 1; k < 8; k++) c = bf2_fma(a[4 * j + k / 2][r + (k & 1) * 2], a[4 * j + k / 2][r + (k & 1) * 2], c);
                t += bf_lo(c) + bf_hi(c);
            }
            t += __shfl_xor_sync(0xffffffffu, t, 1);
            t += __shfl_xor_sync(0xffffffffu, t, 2);
            ex[r] = min(max(__float_as_uint(13.9f * __fsqrt_rn(t)) >> 23, 72u), 198u);
            if ((lane & 3) == 0)
                asm volatile("st.shared.u32 [%0], %1;\n" ::"r"(sbase + P1_OFF_EX + (wg * 64 + w * 16 + r * 8 + (lane >> 2)) * 4), "r"(ex[r] << 23) : "memory");
            const uint32_t f = (258u - ex[r]) * 0x00800080u;
#pragma unroll
            for (int k = 0; k < 48; k++) a[k >> 1][r + (k & 1) * 2] = bf2_to_h2(bf2_mul(bf2_mul(a[k >> 1][r + (k & 1) * 2], f), 0x07800780u));
        }
        const uint32_t sc2 = pack_f16(__uint_as_float(min(ex[0], 142u) << 23), __uint_as_float(min(ex[1], 142u) << 23));
        TRACEW(110 + warp, 7);
        bar_sync(5, 256);
        if (warp < 4) p1_consumer<0>(a, sc2, sbase, w, lane, zero);
        else p1_consumer<1>(a, sc2, sbase, w, lane, zero);
        cluster_sync();
        TSTAMP(0, 30);
    }
}

constexpr int P2_B = 24576, P2_NB = 4;
constexpr int P2_A = 3072, P2_NA = 8;
constexpr int P2_XROW = C_DIM * 2;
constexpr int P2_OFF_A = P2_B * P2_NB;
constexpr int P2_OFF_X = P2_OFF_A + 3 * P2_NA * P2_A;
constexpr int P2_XHALF = 32 * P2_XROW + 64;
constexpr int P2_OFF_GRN = P2_OFF_X + 64 * P2_XROW + 128;
constexpr int P2_OFF_BIAS = P2_OFF_GRN + HID * 2;
constexpr int P2_OFF_RED = P2_OFF_BIAS + C_DIM * 4;
constexpr int P2_OFF_BAR = P2_OFF_RED + 192;
constexpr int P2_SMEM = P2_OFF_BAR + (2 * P2_NB + 6 * P2_NA + 7) * 8;
#define P2_S1 16
constexpr int P2_S2 = 32;
constexpr int P2_NCL = NUM_CTAS / 2, P2_ITEMS = NT128 / P2_NCL, P2_SHARED = NT128 - P2_ITEMS * P2_NCL;
constexpr int P2_NPOS = 6 * 48 + P2_S1;
constexpr int P2_RAW = 24;
constexpr int P2_XC = 8 * P2_XROW;
#define P2_T0 4
#define P2_SLACK 0
#define P2_RAMP 2
#define P2_AH 2
__device__ __forceinline__ int p2_start(int n) { return n < 0 ? 0 : n / 3 * 48 + (n % 3 == 1 ? P2_S1 : n % 3 * (P2_S2 / 2)); }
__device__ __forceinline__ int p2_tile(int cl, int n) {
    return n == 0 ? NT128 - 1 - cl : n < 0 ? NT128 - 1 - P2_NCL - (cl >> 1) : cl + P2_NCL * (n - 1);
}

#define P2_EB 2
#define P2_EX 1
__device__ __forceinline__ void p2_epilogue(uint32_t (&acc0)[48], uint32_t (&acc1)[48], uint32_t up, uint32_t sx, uint32_t sb, int zero) {
    uint32_t v[12][3][4];
    auto load = [&](int t, int j) {
        if (t >= 12) return;
        uint32_t (&w)[4] = v[t][j];
        asm volatile("ld.shared.v4.u32 {%0,%1,%2,%3}, [%4];\n" : "=r"(w[0]), "=r"(w[1]), "=r"(w[2]), "=r"(w[3])
                     : "r"((j ? sx + (j - 1) * 4 * P2_XROW : sb) + t * 64) : "memory");
    };
    auto store = [&](int t, int r) {
        const uint32_t* w = (t < 6 ? acc0 : acc1) + 8 * (t % 6) + 4 * r;
        asm volatile("st.shared.v4.u32 [%4], {%0,%1,%2,%3};\n" ::"r"(w[0]), "r"(w[1]), "r"(w[2]), "r"(w[3]), "r"(sx + t * 64 + r * 4 * P2_XROW) : "memory");
    };
#pragma unroll
    for (int t = 0; t < P2_EB; t++) load(t, 0);
#pragma unroll
    for (int t = 0; t < 2 * P2_EX; t++) load(t >> 1, 1 + (t & 1));
#pragma unroll
    for (int t = 0; t < 12; t++) {
        load(t + P2_EX, 1);
        load(t + P2_EX, 2);
        load(t + P2_EB, 0);
        uint32_t* acc = (t < 6 ? acc0 : acc1) + 8 * (t % 6);
        uint32_t y[8];
#pragma unroll
        for (int e = 0; e < 8; e++) {
            y[e] = h2_add(acc[e], v[t][0][e >> 1]);
            y[e] = pack_bf16(h_lo(y[e]), h_hi(y[e]));
        }
#pragma unroll
        for (int e = 0; e < 8; e++) acc[(e & 1) * 4 + (e >> 1)] = bf2_fma(y[e], up, v[t][1 + (e & 1)][e >> 1]);
        store(t, 0);
        store(t, 1);
        sched_break(zero);
    }
    if (zero) {
#pragma unroll
        for (int t = 0; t < 24; t++) store(t >> 1, t & 1);
    }
}

__device__ __forceinline__ void p2_unpack(uint32_t (&u)[4], uint32_t o1, uint32_t o2, uint32_t o3) {
    u[2] = bitsel(o1, 0x00040004u, SPARE);
    u[1] = bitsel(o2, 0x00040004u, SPARE);
    u[3] = bitsel(o3, 0x00040004u, SPARE);
    const uint32_t t = bitsel(prmt(o1, o2, 0x6341), prmt(o1, o3, 0x6240) << 3, 0x38383838u);
    u[0] = bitsel(bitsel(t, prmt(o2, o3, 0x7351) << 1, 0x80808080u), 0x00040004u, SPARE);
}

__global__ void __cluster_dims__(2, 1, 1) __launch_bounds__(512, 1)
pass2_kernel(const __nv_bfloat16* __restrict__ x, const __nv_bfloat16* __restrict__ grn_g, __nv_bfloat16* __restrict__ out, int zero) {
    extern __shared__ __align__(1024) uint8_t smem[];
    const uint32_t sbase = smem_u32(smem);
    const uint32_t bar_bfull = sbase + P2_OFF_BAR, bar_bempty = bar_bfull + P2_NB * 8;
    const uint32_t bar_afull = bar_bempty + P2_NB * 8, bar_aempty = bar_afull + 3 * P2_NA * 8;
    const uint32_t bar_xfull = bar_aempty + 3 * P2_NA * 8, bar_oready = bar_xfull + 24, s_pos = bar_oready + 24;
    int tid;
    asm volatile("mov.u32 %0, %%tid.x;\n" : "=r"(tid));
    const int warp = __shfl_sync(0xffffffffu, tid >> 5, 0), lane = tid & 31;
    const uint32_t rank = cluster_rank();
    const int cl = blockIdx.x >> 1, pair = cl >> 1;
    const int half = pair < P2_SHARED, fin = half && (cl & 1);
    const int k0 = (pair + 3 * (cl & 1)) % 6 * 8;
    auto wait_pos = [&](int target) {
        int v;
        while (true) {
            asm volatile("ld.volatile.shared.u32 %0, [%1];\n" : "=r"(v) : "r"(s_pos) : "memory");
            if (v >= target) break;
            SAFE_BREAK;
            __nanosleep(100);
        }
    };

    TSTAMP(1, 0);
    if (tid == 384) {
        for (int i = 0; i < P2_NB; i++) {
            mbar_init(bar_bfull + i * 8, 1);
            mbar_init(bar_bempty + i * 8, 24);
        }
        for (int i = 0; i < 3 * P2_NA; i++) {
            mbar_init(bar_afull + i * 8, 1);
            mbar_init(bar_aempty + i * 8, 4);
        }
        for (int i = 0; i < 3; i++) {
            mbar_init(bar_xfull + i * 8, 2);
            mbar_init(bar_oready + i * 8, 4);
        }
        asm volatile("st.shared.u32 [%0], 0;\n" ::"r"(s_pos) : "memory");
        asm volatile("fence.mbarrier_init.release.cluster;\n" ::: "memory");
    }
    __syncthreads();
    cluster_sync_relaxed();

    if (warp >= 12) {
        reg_dec<32>();
        if (warp == 12) {
            const uint8_t* wsrc = reinterpret_cast<const uint8_t*>(g_w2img) + rank * (P2_B / 2);
            int kb = k0;
            gdc_wait();
#pragma unroll 1
            for (int p = 0; p < P2_NPOS; p++) {
                const int st = p & 3;
                if (p == P2_RAW) {
                    flag_wait<true>(&g_prog[1][0], NUM_CTAS);
                    asm volatile("fence.proxy.async.global;\n" ::: "memory");
                    wsrc += sizeof(g_w2img[0]);
                }
                const int idle = (p < P2_S1 || p >= 6 * 48) + (p < P2_S2 ? !half || p >= 24 : p >= 5 * 48 + P2_S2);
                mbar_wait(bar_bempty + st * 8, (~p >> 2) & 1);
                TR2(3, p, 0);
                if (elect_one()) {
                    const int len = P2_B / 2;
                    mbar_expect_tx(bar_bfull + st * 8, 2 * len);
                    bulk_g2s_mc(sbase + st * P2_B + rank * (P2_B / 2), wsrc + kb * P2_B, len, bar_bfull + st * 8, (uint16_t)3);
                    asm volatile("st.volatile.shared.u32 [%0], %1;\n" ::"r"(s_pos), "r"(p) : "memory");
                    if (rank == 0) asm volatile("red.relaxed.gpu.global.add.u32 [%0], 1;\n" ::"l"(&g_prog[0][0]) : "memory");
                    if (idle) asm volatile("mbarrier.arrive.shared::cta.b64 _, [%0], %1;\n" ::"r"(bar_bempty + st * 8), "r"(8 * idle) : "memory");
                }
                __syncwarp();
                if (++kb == 48) kb = 0;
            }
            mbar_wait(bar_bempty, 1);
            if (lane == 0) mbar_arrive(bar_bfull);
        } else if (warp == 13) {
            const int w = lane < 3 ? lane : 0;
            const uint32_t dst0 = sbase + P2_OFF_A + w * P2_NA * P2_A;
            const uint32_t bf = bar_afull + w * P2_NA * 8, be = bar_aempty + w * P2_NA * 8;
            int n = (w == 2 && half ? -1 : w) - 3, left = 0, u = 0, c = 0;
            const uint8_t* src = nullptr;
            bool act = lane < 3;
            gdc_wait();
            while (__any_sync(0xffffffffu, act)) {
                if (left == 0) {
                    n += 3;
                    left = n >= P2_ITEMS ? -1 : n < 0 ? 24 : 48;
                    u = (k0 + p2_start(n)) % 48;
                    src = reinterpret_cast<const uint8_t*>(g_h) + (size_t)p2_tile(cl, n) * (2 * H_TILE) + rank * H_HALF + u * H_STEP;
                }
                bool ok = act && mbar_test(be + ((c - 1) & 7) * 8, (~c >> 3) & 1);
                if (__any_sync(0xffffffffu, act && c < 16)) {
                    int v;
                    asm volatile("ld.volatile.shared.u32 %0, [%1];\n" : "=r"(v) : "r"(s_pos) : "memory");
                    ok = ok && c <= (n <= 0 ? 2 * v - P2_RAMP : c >= 16 ? c : v - p2_start(n) + 8);
                }
                if (ok) {
                    const int st = c & 7;
                    if (left > 0) {
                        mbar_expect_tx(bf + st * 8, P2_A);
                        bulk_g2s(dst0 + st * P2_A, src, P2_A, bf + st * 8);
                    } else {
                        mbar_arrive(bf + st * 8);
                        act = false;
                    }
                    src += H_STEP;
                    if (++u == 48) { u = 0; src -= 48 * H_STEP; }
                    c++;
                    left--;
                }
                SAFE_BREAK;
                if (!__any_sync(0xffffffffu, ok)) __nanosleep(100);
            }
        } else if (warp == 14) {
            const uint32_t sx = sbase + P2_OFF_X;
            size_t o = 0;
            int wp = 0;
            uint32_t par = 0;
            if (fin) {
#pragma unroll 1
                for (int c = lane * 16; c < 64 * P2_XROW + 128; c += 512) asm volatile("st.shared.v4.u32 [%0], {0, 0, 0, 0};\n" ::"r"(sx + c) : "memory");
                __syncwarp();
            }
#pragma unroll 1
            for (int n = -half; n <= P2_ITEMS; n++) {
                const int w = (n + 3) % 3, end = p2_start(n) + 48;
                const size_t on = (size_t)(2 * p2_tile(cl, n) + rank) * (64 * C_DIM * 2);
                const uint32_t xf = bar_xfull + w * 8;
                bool st = n + half > 0;
                const bool ld = n < P2_ITEMS && !(n < 0 && fin);
                if (n == P2_ITEMS - 1 && lane == 0)
                    asm volatile("cp.async.bulk.prefetch.L2.global [%0], %1;\n" ::"l"(reinterpret_cast<const uint8_t*>(x) + on), "r"(64 * P2_XROW) : "memory");
                if (st) {
                    mbar_wait(bar_oready + wp * 8, (par >> wp) & 1);
                    par ^= 1u << wp;
                }
                if (lane == 0) {
                    if (n < P2_ITEMS) mbar_expect_tx(xf, ld ? 64 * C_DIM * 2 : 0);
                    const int t0 = (n ? p2_start(n - 1) + 48 : P2_S2) + P2_T0, dt = end - t0;
                    int t = st && n < P2_ITEMS - 1 ? 16 * t0 : -4096;
                    if ((n == 0 && half) || n >= P2_ITEMS - 1) {
                        if (fin && n == 0) {
                            flag_wait<true>(&g_half[pair][rank], 1);
                            asm volatile("fence.proxy.async.global;\n" ::: "memory");
                        }
#pragma unroll 1
                        for (int c = 0; c < 2; c++) {
                            uint8_t* dst = reinterpret_cast<uint8_t*>(out) + o + c * 32 * P2_XROW;
                            if (!fin || n) bulk_s2g(dst, sx + c * P2_XHALF, 32 * P2_XROW);
                            else asm volatile("cp.reduce.async.bulk.global.shared::cta.bulk_group.add.noftz.bf16 [%0], [%1], %2;\n"
                                              ::"l"(dst), "r"(sx + c * P2_XHALF), "r"(32 * P2_XROW) : "memory");
                        }
                        asm volatile("cp.async.bulk.commit_group;\n" ::: "memory");
                        if (!fin && n == 0) {
                            asm volatile("cp.async.bulk.wait_group 0;\nfence.proxy.async.global;\n" ::: "memory");
                            asm volatile("st.release.gpu.global.u32 [%0], 1;\n" ::"l"(&g_half[pair][rank]) : "memory");
                        }
                        st = false;
                    }
#pragma unroll 1
                    for (int c = 0; c < 64 * P2_XROW; c += P2_XC, t += 2 * dt) {
                        const uint32_t sp = sx + c + (c >= 32 * P2_XROW ? 64 : 0);
                        wait_pos(t >> 4);
                        if (st) bulk_s2g(reinterpret_cast<uint8_t*>(out) + o + c, sp, P2_XC);
                        asm volatile("cp.async.bulk.commit_group;\n" ::: "memory");
                        if (ld) {
                            wait_pos((t + dt) >> 4);
                            asm volatile("cp.async.bulk.wait_group.read 0;\n" ::: "memory");
                            bulk_g2s(sp, reinterpret_cast<const uint8_t*>(x) + on + c, P2_XC, xf);
                        }
                    }
                    if (rank == 0 && n > 0 && n < P2_ITEMS - 1) flag_wait<false>(&g_prog[0][0], P2_NCL * (end + P2_SLACK));
                    if (n < P2_ITEMS) mbar_arrive(xf);
                }
                __syncwarp();
                o = on;
                wp = w;
            }
            asm volatile("cp.async.bulk.wait_group 0;\n" ::: "memory");
        }
        __syncwarp();
        cluster_sync();
    } else {
        reg_inc<160>();
        const int wg = warp >> 2, w = warp & 3, g = lane >> 2, q = lane & 3;
        const uint32_t sx = sbase + P2_OFF_X + (g & 1) * P2_XHALF + (w * 8 + (g >> 1)) * P2_XROW + q * 16;
        const uint32_t af = bar_afull + wg * P2_NA * 8;
        const uint32_t s_a = sbase + P2_OFF_A + wg * P2_NA * P2_A + (lane >> 3) * 512 + (lane & 7) * 64 + ((w ^ ((lane & 7) >> 1)) << 4);
        uint32_t acc0[48], acc1[48], up;
        uint4 a[2][2];

        {
            float* s_red = reinterpret_cast<float*>(smem + P2_OFF_RED);
            float gx[4], part = 0.f;
            __nv_bfloat16 gg[4];
#pragma unroll
            for (int i = 0; i < 4; i++) gg[i] = grn_g[tid + 384 * i];
            TSTAMP(1, 27);
            gdc_wait();
            TSTAMP(1, 1);
            if (blockIdx.x == 120 && tid < (LN_RING + 3) * 2) (&g_flag[0][0][0])[tid * 8] = 0;
            if (blockIdx.x == 121 && tid == 0) g_epoch++;
#pragma unroll
            for (int i = 0; i < 4; i++) gx[i] = __ldcg(&g_sums[0][tid + 384 * i]) + __ldcg(&g_sums[1][tid + 384 * i]);
            const float bias = __ldcg(&g_sums[0][HID + tid]) + __ldcg(&g_sums[1][HID + tid]);
            const float gs = w2_scale(__float_as_uint(__ldcg(&g_sums[0][HID + C_DIM])) | __float_as_uint(__ldcg(&g_sums[1][HID + C_DIM])));
            float mg = 0.f;
#pragma unroll
            for (int i = 0; i < 4; i++) {
                gx[i] = sqrtf(gx[i] * (HSCALE * HSCALE) + 1e-6f);
                part += gx[i];
                gx[i] *= __bfloat162float(gg[i]);
                mg = fmaxf(mg, fabsf(gx[i]));
            }
#pragma unroll
            for (int o = 16; o > 0; o >>= 1) part += __shfl_xor_sync(0xffffffffu, part, o);
            const uint32_t mgw = __reduce_max_sync(0xffffffffu, __float_as_uint(mg));
            const uint32_t mbw = __reduce_max_sync(0xffffffffu, __float_as_uint(fabsf(bias)));
            TSTAMP(1, 26);
            if (lane == 0) *reinterpret_cast<float4*>(s_red + warp * 4) = make_float4(part, __uint_as_float(mgw), __uint_as_float(mbw), 0.f);
            bar_sync(1, 384);
            float tot = 0.f, mb = 0.f;
#pragma unroll
            for (int i = 0; i < 12; i++) {
                const float4 t = *reinterpret_cast<const float4*>(s_red + i * 4);
                tot += t.x;
                mg = fmaxf(mg, t.y);
                mb = fmaxf(mb, t.z);
            }
            const float inv = 1.0f / (tot * (1.0f / HID) + 1e-6f);
            const uint32_t ej = min((__float_as_uint(fmaxf(fmaf(mg, inv, 1.0f) * HSCALE, mb * gs * 0x1p-13f)) >> 23) + 1, 250u);
            const float dn = __uint_as_float((254u - ej) << 23);
            up = min(ej + 127u - (__float_as_uint(gs) >> 23), 254u) * 0x00800080u;
            reinterpret_cast<uint16_t*>(smem + P2_OFF_BIAS + C_DIM * 2)[tid] = 0;
            *reinterpret_cast<__half*>(smem + P2_OFF_BIAS + (tid >> 5) * 64 + (tid & 6) * 8 + (tid & 24) / 2 + (tid & 1) * 2) = __float2half_rn(bias * gs * dn);
#pragma unroll
            for (int i = 0; i < 4; i++) {
                const int k = tid + 384 * i;
                *reinterpret_cast<__half*>(smem + P2_OFF_GRN + (k >> 4) * 32 + (k & 6) * 4 + (k & 8) / 2 + (k & 1) * 2) =
                    __float2half_rn(fmaf(gx[i], inv, 1.0f) * (HSCALE * dn));
            }
            TSTAMP(1, 25);
            bar_sync(1, 384);
        }
        TSTAMP(1, 28);
        if (wg == 1) {
            constexpr int N = sizeof(g_w2img[0]) / 16, PER = (N + NUM_CTAS - 1) / NUM_CTAS;
            uint4 v[5];
#pragma unroll
            for (int i = 0; i < 5; i++) v[i] = __ldcg(&g_w2img[0][min(blockIdx.x * PER + (tid & 127) + 128 * i, N - 1)]);
#pragma unroll
            for (int i = 0; i < 5; i++) {
                const int j = min(blockIdx.x * PER + (tid & 127) + 128 * i, N - 1);
                const uint32_t* t = reinterpret_cast<const uint32_t*>(smem + P2_OFF_GRN + (j / 768) * 32 + (j & 8) / 2);
                auto sc = [&](uint32_t u, int e) { return (h2_mul(u, t[2 * e]) + 0x00040004u) & 0xfff8fff8u; };
                g_w2img[1][j] = make_uint4(sc(v[i].x, 0), sc(v[i].y, 1), sc(v[i].z, 2), sc(v[i].w, 3));
            }
            asm volatile("fence.proxy.async.global;\n" ::: "memory");
            bar_sync(2, 128);
            if (tid == 128) asm volatile("fence.acq_rel.gpu;\nred.release.gpu.global.add.u32 [%0], 1;\n" ::"l"(&g_prog[1][0]) : "memory");
        }

        const int who = __shfl_sync(0xffffffffu, lane == 2 ? 0 : lane < 2 ? 1 : 2, lane);
        const uint32_t rel0 = who ? mapa(bar_bempty, lane & 1) : mapa(bar_aempty + wg * P2_NA * 8, rank), rel1 = rel0 + (who ? 0 : 32);
        auto publish = [&]() {
            asm volatile("fence.proxy.async.shared::cta;\n" ::: "memory");
            __syncwarp();
            if (who == 0) mbar_arrive(bar_oready + wg * 8);
        };
        bool ok_a, pend = false;
        uint32_t pa = 0, s_t;
        auto fetch = [&](int j, bool raw) {
            uint32_t o[6], u0[4], u1[4];
            uint2 t0 = make_uint2(0, 0), t1 = t0;
            if (raw) {
                asm volatile("ld.shared.v2.u32 {%0,%1}, [%2];\n" : "=r"(t0.x), "=r"(t0.y) : "r"(s_t + j * 64) : "memory");
                asm volatile("ld.shared.v2.u32 {%0,%1}, [%2];\n" : "=r"(t1.x), "=r"(t1.y) : "r"(s_t + j * 64 + 32) : "memory");
            }
            const bool ok_b = mbar_test(bar_bfull + (j & 3) * 8, j >> 2);
            if (j == 7) pa ^= 1;
            ok_a = mbar_test(af + ((j + 1) & 7) * 8, pa);
            asm volatile("ldmatrix.sync.aligned.m8n8.x4.trans.shared.b16 {%0,%1,%2,%3}, [%4];\n"
                         : "=r"(o[0]), "=r"(o[1]), "=r"(o[2]), "=r"(o[3]) : "r"(s_a + j * P2_A) : "memory");
            asm volatile("ldmatrix.sync.aligned.m8n8.x2.trans.shared.b16 {%0,%1}, [%2];\n"
                         : "=r"(o[4]), "=r"(o[5]) : "r"(s_a + j * P2_A + 2048) : "memory");
            p2_unpack(u0, o[0], o[1], o[2]);
            p2_unpack(u1, o[3], o[4], o[5]);
            if (raw) {
                u0[0] = h2_mul(u0[0], t0.x); u0[1] = h2_mul(u0[1], t0.x); u0[2] = h2_mul(u0[2], t0.y); u0[3] = h2_mul(u0[3], t0.y);
                u1[0] = h2_mul(u1[0], t1.x); u1[1] = h2_mul(u1[1], t1.x); u1[2] = h2_mul(u1[2], t1.y); u1[3] = h2_mul(u1[3], t1.y);
            }
            a[j & 1][0] = make_uint4(u0[0], u0[1], u0[2], u0[3]);
            a[j & 1][1] = make_uint4(u1[0], u1[1], u1[2], u1[3]);
            if (!ok_b) mbar_wait(bar_bfull + (j & 3) * 8, j >> 2);
        };
        auto table = [&](int pos) { s_t = sbase + P2_OFF_GRN + q * 8 + (k0 + pos) % 48 * 64; };
        const uint64_t db0 = make_desc(sbase, 128, 256);
        auto block8 = [&](bool raw, int pos, int thr0, int mode) {
#pragma unroll
            for (int j = 0; j < 8; j++) {
                const uint64_t db = db0 + (j & 3) * (P2_B / 16);
                if (j == 8 - P2_AH && mode == 1) bar_sync(4, 384);
                TR2(wg, pos + j, 0);
                wg_fence();
                mma_rs_n192(acc0, a[j & 1][0], db);
                mma_rs_n192(acc1, a[j & 1][0], db + 384);
                mma_rs_n192(acc0, a[j & 1][1], db + 768);
                mma_rs_n192(acc1, a[j & 1][1], db + 768 + 384);
                wg_commit();
                if (j == 7 && mode == 2) bar_arrive(4, 384);
                const uint32_t rel = ((j - 1) & 4 ? rel1 : rel0) + ((j - 1) & 3) * 8;
                TR2(wg, pos + j, 1);
                wg_wait<1>();
                TR2(wg, pos + j, 2);
                if (who < (j ? 2 : thr0)) mbar_arrive_cluster(rel);
                if (!ok_a) {
                    if (j == 0 && pend) { publish(); pend = false; }
                    mbar_wait(af + ((j + 1) & 7) * 8, pa);
                }
                TR2(wg, pos + j, 3);
                if (raw && j == 7) table(pos + 8);
                fetch((j + 1) & 7, raw && (j < 7 || pos + 8 < P2_RAW));
            }
        };
        int n = wg == 2 && half ? -1 : wg, pos = p2_start(n);
        uint32_t px = 0;
        wait_pos(pos);
        mbar_wait(af, 0);
        table(pos);
        fetch(0, pos < P2_RAW);
#pragma unroll 1
        for (;; n += 3) {
            TSTAMP(1, 2 + n);
            const int end = pos + (n < 0 ? 24 : 48);
#pragma unroll
            for (int i = 0; i < 48; i += 2) {
                asm volatile("mov.b64 {%0, %1}, 0;\n" : "=r"(acc0[i]), "=r"(acc0[i + 1]));
                asm volatile("mov.b64 {%0, %1}, 0;\n" : "=r"(acc1[i]), "=r"(acc1[i + 1]));
            }
            int thr = 1;
#pragma unroll 1
            for (; pos < P2_RAW; pos += 8, thr = 2) block8(true, pos, thr, 0);
#pragma unroll 1
            for (; pos < end; pos += 8, thr = 2) {
                const int e = pos + 8, r = e % 48;
                block8(false, pos, thr, e < 48 || e > 256 || (r != 0 && r != P2_S1 && r != P2_S2) ? 0 : e == end ? 2 : 1);
            }
            TR2(wg, pos - 1, 4);
            wg_wait<0>();
            TR2(wg, pos - 1, 5);
            if (who == 1) mbar_arrive_cluster(rel0 + 24);
            mbar_wait(bar_xfull + wg * 8, px);
            TR2(wg, pos - 1, 6);
            px ^= 1;
            __syncwarp();
            p2_epilogue(acc0, acc1, up, sx, sbase + P2_OFF_BIAS + q * 16 + (n < 0 && fin ? C_DIM * 2 : 0), zero);
            TR2(wg, pos - 1, 7);
            if (n + 3 >= P2_ITEMS) { publish(); break; }
            if (n < 0) {
                publish();
                pos = P2_S2;
                wait_pos(pos);
                mbar_wait(bar_bfull, 0);
            } else {
                pend = true;
                ok_a = false;
            }
        }
        TSTAMP(1, 29);
        cluster_sync();
        TSTAMP(1, 30);
    }
}

}

extern "C" void kernel_launch(void* const* d_in, const int* in_sizes, int n_in, void* d_out, int out_size) {
    const __nv_bfloat16* x = (const __nv_bfloat16*)d_in[0];
    const __nv_bfloat16* dw = (const __nv_bfloat16*)d_in[1];
    const __nv_bfloat16* w1 = (const __nv_bfloat16*)d_in[2];
    const __nv_bfloat16* w2 = (const __nv_bfloat16*)d_in[3];
    const __nv_bfloat16* grn_g = (const __nv_bfloat16*)d_in[4];
    const __nv_bfloat16* grn_b = (const __nv_bfloat16*)d_in[5];
    __nv_bfloat16* out = (__nv_bfloat16*)d_out;

    cudaFuncSetAttribute(pass1_kernel, cudaFuncAttributeMaxDynamicSharedMemorySize, P1_SMEM);
    cudaFuncSetAttribute(pass2_kernel, cudaFuncAttributeMaxDynamicSharedMemorySize, P2_SMEM);

    typedef CUresult (*EncodeFn)(CUtensorMap*, CUtensorMapDataType, cuuint32_t, void*, const cuuint64_t*, const cuuint64_t*,
                                 const cuuint32_t*, const cuuint32_t*, CUtensorMapInterleave, CUtensorMapSwizzle,
                                 CUtensorMapL2promotion, CUtensorMapFloatOOBfill);
    static EncodeFn encode = nullptr;
    if (!encode) {
        cudaDriverEntryPointQueryResult qres;
        cudaGetDriverEntryPoint("cuTensorMapEncodeTiled", (void**)&encode, cudaEnableDefault, &qres);
    }
    CUtensorMap wmap;
    const cuuint64_t gdim[2] = {HID, C_DIM};
    const cuuint64_t gstr[1] = {HID * 2};
    const cuuint32_t box[2] = {64, 192}, estr[2] = {1, 1};
    CUresult er = encode(&wmap, CU_TENSOR_MAP_DATA_TYPE_BFLOAT16, 2, (void*)w1, gdim, gstr, box, estr, CU_TENSOR_MAP_INTERLEAVE_NONE,
           CU_TENSOR_MAP_SWIZZLE_128B, CU_TENSOR_MAP_L2_PROMOTION_L2_128B, CU_TENSOR_MAP_FLOAT_OOB_FILL_NONE);
    if (er != CUDA_SUCCESS) printf("tensor map encode failed %d\n", (int)er);

    pass1_kernel<<<NUM_CTAS, 512, P1_SMEM>>>(wmap, x, dw, w2, grn_b, 0);

    cudaLaunchAttribute attr[1];
    attr[0].id = cudaLaunchAttributeProgrammaticStreamSerialization;
    attr[0].val.programmaticStreamSerializationAllowed = 1;
    cudaLaunchConfig_t cfg = {};
    cfg.gridDim = dim3(NUM_CTAS);
    cfg.stream = 0;
    cfg.attrs = attr;
    cfg.numAttrs = 1;
    cfg.blockDim = dim3(512);
    cfg.dynamicSmemBytes = P2_SMEM;
    cudaLaunchKernelEx(&cfg, pass2_kernel, x, grn_g, out, 0);
}
```

```cpp
#include <cuda.h>
#include <cuda_runtime.h>
#include <cuda_bf16.h>
#include <cuda_fp16.h>
#include <stdint.h>
#include <stdio.h>

namespace {

constexpr int M_TOTAL = 384 * 384;
constexpr int C_DIM   = 384;
constexpr int HID     = 1536;
constexpr int NT128   = M_TOTAL / 128;
constexpr int NUM_CTAS = 132;

constexpr int NGRP = 22, GRP_CTAS = 6;
constexpr int LN_STEP = NUM_CTAS / 4, LN_RING = 2 * LN_STEP;
constexpr int NT_RING = NT128 - NGRP;
constexpr int LN_TILE = 128 * C_DIM * 2;
constexpr int H_TILE = 64 * HID * 3 / 2;
constexpr int H_HALF = 3072, H_STEP = 6144;

__device__ __align__(1024) uint4 g_h[(size_t)M_TOTAL * HID * 3 / 32];
__device__ __align__(1024) uint4 g_ln[LN_RING * LN_TILE / 16];
__device__ __align__(1024) uint4 g_w2img[2][HID * C_DIM * 2 / 16];
__device__ __align__(16) float g_sums[2][HID + 512];
__device__ unsigned g_epoch;
__device__ __align__(128) unsigned g_prog[2][32];
__device__ __align__(128) unsigned g_half[32][2];
__device__ unsigned g_flag[LN_RING + 3][2][8];
#define TSTAMP(k, i)
#define TRACE(wg, pos, i)
#define TRACEW(pos, i)

#define TR2(wg, pos, i)
__host__ __device__ __forceinline__ int perm32(int n) {
    return (n & ~31) | (((n >> 1) & 3) << 3) | (((n >> 3) & 3) << 1) | (n & 1);
}

__device__ __forceinline__ uint32_t smem_u32(const void* p) { return (uint32_t)__cvta_generic_to_shared(p); }

__device__ __forceinline__ void mbar_init(uint32_t bar, uint32_t count) {
    asm volatile("mbarrier.init.shared::cta.b64 [%0], %1;\n" ::"r"(bar), "r"(count) : "memory");
}
__device__ __forceinline__ void mbar_expect_tx(uint32_t bar, uint32_t bytes) {
    asm volatile("mbarrier.arrive.expect_tx.shared::cta.b64 _, [%0], %1;\n" ::"r"(bar), "r"(bytes) : "memory");
}
__device__ __forceinline__ void mbar_arrive(uint32_t bar) {
    asm volatile("mbarrier.arrive.shared::cta.b64 _, [%0];\n" ::"r"(bar) : "memory");
}
__device__ __forceinline__ void mbar_arrive_cluster(uint32_t bar_cluster_addr) {
    asm volatile("mbarrier.arrive.shared::cluster.b64 _, [%0];\n" ::"r"(bar_cluster_addr) : "memory");
}
#define SAFE_BREAK
__device__ __forceinline__ void mbar_wait(uint32_t bar, uint32_t parity) {
    asm volatile(
        "{\n"
        ".reg .pred p;\n"
        "LAB_WAIT:\n"
        "mbarrier.try_wait.parity.shared::cta.b64 p, [%0], %1;\n"
        "@!p bra LAB_WAIT;\n"
        "}\n" ::"r"(bar), "r"(parity) : "memory");
}
__device__ __forceinline__ bool mbar_test(uint32_t bar, uint32_t parity) {
    uint32_t ok;
    asm volatile("{\n.reg .pred p;\n"
                 "mbarrier.test_wait.parity.shared::cta.b64 p, [%1], %2;\n"
                 "selp.u32 %0, 1, 0, p;\n}\n" : "=r"(ok) : "r"(bar), "r"(parity) : "memory");
    return ok != 0;
}
__device__ __forceinline__ uint32_t mapa(uint32_t addr, uint32_t rank) {
    uint32_t r;
    asm volatile("mapa.shared::cluster.u32 %0, %1, %2;\n" : "=r"(r) : "r"(addr), "r"(rank));
    return r;
}
__device__ __forceinline__ void bulk_g2s(uint32_t dst, const void* src, uint32_t bytes, uint32_t bar) {
    asm volatile("cp.async.bulk.shared::cluster.global.mbarrier::complete_tx::bytes [%0], [%1], %2, [%3];\n"
                 ::"r"(dst), "l"(src), "r"(bytes), "r"(bar) : "memory");
}
__device__ __forceinline__ void bulk_g2s_mc(uint32_t dst, const void* src, uint32_t bytes, uint32_t bar, uint16_t mask) {
    asm volatile("cp.async.bulk.shared::cluster.global.mbarrier::complete_tx::bytes.multicast::cluster [%0], [%1], %2, [%3], %4;\n"
                 ::"r"(dst), "l"(src), "r"(bytes), "r"(bar), "h"(mask) : "memory");
}
__device__ __forceinline__ void tma2(uint32_t dst, const CUtensorMap* map, int c0, int c1, uint32_t bar) {
    asm volatile("cp.async.bulk.tensor.2d.shared::cluster.global.tile.mbarrier::complete_tx::bytes [%0], [%1, {%2, %3}], [%4];\n"
                 ::"r"(dst), "l"(map), "r"(c0), "r"(c1), "r"(bar) : "memory");
}
template <bool ACQ>
__device__ __forceinline__ uint32_t flag_wait(const unsigned* p, unsigned target) {
    unsigned v, n = 0;
    do {
        if (ACQ) asm volatile("ld.acquire.gpu.global.u32 %0, [%1];\n" : "=r"(v) : "l"(p) : "memory");
        else asm volatile("ld.relaxed.gpu.global.u32 %0, [%1];\n" : "=r"(v) : "l"(p) : "memory");
        n++;
    } while (v < target);
    return n == 1;
}
__device__ __forceinline__ void ldsm4t(uint32_t (&r)[4], uint32_t addr) {
    asm volatile("ldmatrix.sync.aligned.m8n8.x4.trans.shared.b16 {%0,%1,%2,%3}, [%4];\n"
                 : "=r"(r[0]), "=r"(r[1]), "=r"(r[2]), "=r"(r[3]) : "r"(addr) : "memory");
}
__device__ __forceinline__ void bulk_s2g(void* dst, uint32_t src, uint32_t bytes) {
    asm volatile("cp.async.bulk.global.shared::cta.bulk_group [%0], [%1], %2;\n" ::"l"(dst), "r"(src), "r"(bytes) : "memory");
}
__device__ __forceinline__ void cluster_sync() {
    asm volatile("barrier.cluster.arrive.aligned;\nbarrier.cluster.wait.aligned;\n" ::: "memory");
}
__device__ __forceinline__ void cluster_sync_relaxed() {
    asm volatile("barrier.cluster.arrive.relaxed.aligned;\nbarrier.cluster.wait.aligned;\n" ::: "memory");
}
__device__ __forceinline__ void gdc_wait() { asm volatile("griddepcontrol.wait;\n" ::: "memory"); }
__device__ __forceinline__ void gdc_launch() { asm volatile("griddepcontrol.launch_dependents;\n" ::: "memory"); }
__device__ __forceinline__ uint32_t cluster_rank() {
    uint32_t r;
    asm volatile("mov.u32 %0, %%cluster_ctarank;\n" : "=r"(r));
    return r;
}
__device__ __forceinline__ bool elect_one() {
    uint32_t pred;
    asm volatile("{\n.reg .pred p;\nelect.sync _|p, 0xffffffff;\nselp.u32 %0, 1, 0, p;\n}\n" : "=r"(pred));
    return pred != 0;
}
__device__ __forceinline__ void wg_fence() { asm volatile("wgmma.fence.sync.aligned;\n" ::: "memory"); }
__device__ __forceinline__ void wg_commit() { asm volatile("wgmma.commit_group.sync.aligned;\n" ::: "memory"); }
template <int N> __device__ __forceinline__ void wg_wait() {
    asm volatile("wgmma.wait_group.sync.aligned %0;\n" ::"n"(N) : "memory");
}
template <int R> __device__ __forceinline__ void reg_inc() { asm volatile("setmaxnreg.inc.sync.aligned.u32 %0;\n" ::"n"(R)); }
template <int R> __device__ __forceinline__ void reg_dec() { asm volatile("setmaxnreg.dec.sync.aligned.u32 %0;\n" ::"n"(R)); }
__device__ __forceinline__ void bar_sync(int id, int n) { asm volatile("bar.sync %0, %1;\n" ::"r"(id), "r"(n) : "memory"); }
__device__ __forceinline__ void bar_arrive(int id, int n) { asm volatile("bar.arrive %0, %1;\n" ::"r"(id), "r"(n) : "memory"); }

__device__ __forceinline__ uint64_t make_desc(uint32_t saddr, uint32_t lbo, uint32_t sbo) {
    return (uint64_t)((saddr & 0x3FFFF) >> 4) | ((uint64_t)(lbo >> 4) << 16) | ((uint64_t)(sbo >> 4) << 32);
}

__device__ __forceinline__ void stg128_cs(void* p, uint32_t a, uint32_t b, uint32_t c, uint32_t d) {
    asm volatile("st.global.cs.v4.u32 [%0], {%1,%2,%3,%4};\n" ::"l"(p), "r"(a), "r"(b), "r"(c), "r"(d) : "memory");
}
__device__ __forceinline__ uint32_t pack_bf16(float lo, float hi) {
    uint32_t r;
    asm("cvt.rn.bf16x2.f32 %0, %1, %2;\n" : "=r"(r) : "f"(hi), "f"(lo));
    return r;
}
__device__ __forceinline__ float bf_lo(uint32_t v) { return __uint_as_float(v << 16); }
__device__ __forceinline__ float bf_hi(uint32_t v) { return __uint_as_float(v & 0xffff0000u); }
__device__ __forceinline__ uint32_t bf2_mul(uint32_t a, uint32_t b) {
    uint32_t r;
    asm("mul.rn.bf16x2 %0, %1, %2;\n" : "=r"(r) : "r"(a), "r"(b));
    return r;
}
__device__ __forceinline__ uint32_t bf2_fma(uint32_t a, uint32_t b, uint32_t c) {
    uint32_t r;
    asm("fma.rn.bf16x2 %0, %1, %2, %3;\n" : "=r"(r) : "r"(a), "r"(b), "r"(c));
    return r;
}
__device__ __forceinline__ uint32_t bf2_add(uint32_t a, uint32_t b) {
    uint32_t r;
    asm("add.rn.bf16x2 %0, %1, %2;\n" : "=r"(r) : "r"(a), "r"(b));
    return r;
}
__device__ __forceinline__ uint32_t h2_mul(uint32_t a, uint32_t b) {
    uint32_t r;
    asm("mul.rn.f16x2 %0, %1, %2;\n" : "=r"(r) : "r"(a), "r"(b));
    return r;
}
__device__ __forceinline__ uint32_t h2_fma(uint32_t a, uint32_t b, uint32_t c) {
    uint32_t r;
    asm("fma.rn.f16x2 %0, %1, %2, %3;\n" : "=r"(r) : "r"(a), "r"(b), "r"(c));
    return r;
}
__device__ __forceinline__ uint32_t h2_add(uint32_t a, uint32_t b) {
    uint32_t r;
    asm("add.rn.f16x2 %0, %1, %2;\n" : "=r"(r) : "r"(a), "r"(b));
    return r;
}
__device__ __forceinline__ uint32_t pack_f16(float lo, float hi) {
    uint32_t r;
    asm("cvt.rn.f16x2.f32 %0, %1, %2;\n" : "=r"(r) : "f"(hi), "f"(lo));
    return r;
}
__device__ __forceinline__ float h_lo(uint32_t v) { return __low2float(*reinterpret_cast<const __half2*>(&v)); }
__device__ __forceinline__ float h_hi(uint32_t v) { return __high2float(*reinterpret_cast<const __half2*>(&v)); }
__device__ __forceinline__ uint32_t bf2_to_h2(uint32_t v) { return (v & 0x7fff7fffu) * 7u + v; }
__device__ __forceinline__ uint32_t prmt(uint32_t a, uint32_t b, uint32_t sel) {
    uint32_t r;
    asm("prmt.b32 %0, %1, %2, %3;\n" : "=r"(r) : "r"(a), "r"(b), "r"(sel));
    return r;
}
__device__ __forceinline__ uint32_t bitsel(uint32_t a, uint32_t b, uint32_t m) {
    uint32_t r;
    asm("lop3.b32 %0, %1, %2, %3, 0xd8;\n" : "=r"(r) : "r"(a), "r"(b), "r"(m));
    return r;
}
constexpr float KAPPA = 0.3292034911525734f;
constexpr uint32_t GELU_C2 = 0x40d940d9u;
constexpr float HSCALE = 1.0f / (2.0f * KAPPA);
__device__ __forceinline__ float w2_scale(uint32_t m) { return __uint_as_float((257u - max(m >> 23, 16u)) << 23); }
__device__ __forceinline__ void sched_break(int zero) {
    asm volatile("{\n.reg .pred p;\nsetp.ne.s32 p, %0, 0;\nSB_LOOP:\n@p nanosleep.u32 1;\n@p bra SB_LOOP;\n}\n" ::"r"(zero));
}

#define ACC8(d, o) "+r"(d[o + 0]), "+r"(d[o + 1]), "+r"(d[o + 2]), "+r"(d[o + 3]), "+r"(d[o + 4]), "+r"(d[o + 5]), "+r"(d[o + 6]), "+r"(d[o + 7])

__device__ __forceinline__ void mma_rs_n128(uint32_t (&d)[32], const uint32_t (&a)[4], uint64_t desc, int scale_d) {
    asm volatile(
        "{\n.reg .pred p;\nsetp.ne.b32 p, %37, 0;\n"
        "wgmma.mma_async.sync.aligned.m64n128k16.f16.f16.f16 "
        "{%0,%1,%2,%3,%4,%5,%6,%7,%8,%9,%10,%11,%12,%13,%14,%15,"
        "%16,%17,%18,%19,%20,%21,%22,%23,%24,%25,%26,%27,%28,%29,%30,%31},"
        "{%32,%33,%34,%35}, %36, p, 1, 1, 0;\n}\n"
        : ACC8(d, 0), ACC8(d, 8), ACC8(d, 16), ACC8(d, 24)
        : "r"(a[0]), "r"(a[1]), "r"(a[2]), "r"(a[3]), "l"(desc), "r"(scale_d));
}

__device__ __forceinline__ void mma_ss_n128(uint32_t (&d)[32], uint64_t da, uint64_t db, int scale_d) {
    asm volatile(
        "{\n.reg .pred p;\nsetp.ne.b32 p, %34, 0;\n"
        "wgmma.mma_async.sync.aligned.m64n128k16.f16.f16.f16 "
        "{%0,%1,%2,%3,%4,%5,%6,%7,%8,%9,%10,%11,%12,%13,%14,%15,"
        "%16,%17,%18,%19,%20,%21,%22,%23,%24,%25,%26,%27,%28,%29,%30,%31},"
        "%32, %33, p, 1, 1, 1, 0;\n}\n"
        : ACC8(d, 0), ACC8(d, 8), ACC8(d, 16), ACC8(d, 24)
        : "l"(da), "l"(db), "r"(scale_d));
}

__device__ __forceinline__ void mma_rs_n192(uint32_t (&d)[48], const uint4& a, uint64_t db) {
    asm volatile(
        "wgmma.mma_async.sync.aligned.m64n192k16.f16.f16.f16 "
        "{%0,%1,%2,%3,%4,%5,%6,%7,%8,%9,%10,%11,%12,%13,%14,%15,"
        "%16,%17,%18,%19,%20,%21,%22,%23,%24,%25,%26,%27,%28,%29,%30,%31,"
        "%32,%33,%34,%35,%36,%37,%38,%39,%40,%41,%42,%43,%44,%45,%46,%47},"
        "{%48,%49,%50,%51}, %52, 1, 1, 1, 0;\n"
        : ACC8(d, 0), ACC8(d, 8), ACC8(d, 16), ACC8(d, 24), ACC8(d, 32), ACC8(d, 40)
        : "r"(a.x), "r"(a.y), "r"(a.z), "r"(a.w), "l"(db));
}

#define P1_WPF 30
#define P1_PACE 1
constexpr int P1_SLOT = LN_TILE / 6, P1_NST = 6;
constexpr int P1_W = 64 * C_DIM * 2;
constexpr int P1_X = 32 * C_DIM * 2;
constexpr int P1_OFF_W = LN_TILE;
constexpr int P1_OFF_X = P1_OFF_W + 2 * P1_W;
constexpr int P1_OFF_BAR = P1_OFF_X + P1_X;
constexpr int P1_OFF_TILE = P1_OFF_BAR + (2 * P1_NST + 2 + 4 + 4) * 8;
constexpr int P1_OFF_RAW = P1_OFF_TILE + 64;
constexpr int P1_OFF_EX = P1_OFF_RAW + 32;
constexpr int P1_SMEM = P1_OFF_EX + 256 * 4;

__device__ __forceinline__ float rsqrt_fast(float x) {
    float r;
    asm("rsqrt.approx.ftz.f32 %0, %1;\n" : "=f"(r) : "f"(x));
    return r;
}
__device__ __forceinline__ float row_sum(const uint32_t (&c)[4]) {
    const uint32_t u = bf2_add(bf2_add(c[0], c[1]), bf2_add(c[2], c[3]));
    float s = bf_lo(u) + bf_hi(u);
#pragma unroll
    for (int o = 1; o < 8; o <<= 1) s += __shfl_xor_sync(0xffffffffu, s, o);
    return s;
}
__device__ __forceinline__ uint32_t pace(uint32_t bar, uint32_t off, uint32_t val, uint32_t after, int zero) {
    asm volatile(
        "{\n.reg .pred p;\n.reg .b32 par;\n"
        "lop3.b32 par, %4, %2, %3, 0xea;\n"
        "mbarrier.test_wait.parity.shared::cta.b64 p, [%1], par;\n"
        "selp.u32 par, 1, 0, p;\n"
        "mbarrier.try_wait.parity.shared::cta.b64 p, [%1], par, 1000;\n"
        "@p or.b32 %0, %0, %2;\n"
        "}\n" : "+r"(val) : "r"(bar), "r"(zero), "r"(off), "r"(after));
    return val;
}
template <int PACE>
__device__ __forceinline__ void ln_row(uint32_t (&v)[6][4], const uint32_t (&d)[6][4], uint32_t bar, uint32_t off, int zero,
                                       uint32_t bar_read) {
    uint32_t c[4];
#pragma unroll
    for (int i = 0; i < 6; i++)
#pragma unroll
        for (int k = 0; k < 4; k++) c[k] = bf2_fma(v[i][k], d[i][k], i ? c[k] : 0);
    const float inv = 1.0f / C_DIM;
    const float m = row_sum(c) * inv;
    uint32_t nm = pack_bf16(-m, -m);
    const float e = m + bf_lo(nm);
    if (bar_read) mbar_arrive(bar_read + (nm & zero));
    if (PACE & 1) nm = pace(bar, off, nm, nm, zero);
#pragma unroll
    for (int i = 0; i < 6; i++) {
#pragma unroll
        for (int k = 0; k < 4; k++) {
            v[i][k] = bf2_fma(v[i][k], d[i][k], nm);
            c[k] = i ? bf2_fma(v[i][k], v[i][k], c[k]) : bf2_mul(v[i][k], v[i][k]);
        }
    }
    float r = KAPPA * rsqrt_fast(fmaxf(fmaf(-e, e, row_sum(c) * inv), 0.f) + 1e-5f);
    const float er = -e * r * 0x1p-116f;
    if (__any_sync(0xffffffffu, r < 0x1p-8f)) {
        const uint32_t p2 = __float_as_uint(r) & 0x7f800000u;
        r = __uint_as_float((__float_as_uint(r) & 0x007fffffu) | 0x3f800000u);
#pragma unroll
        for (int i = 0; i < 6; i++)
#pragma unroll
            for (int k = 0; k < 4; k++) v[i][k] = bf2_mul(v[i][k], p2 | p2 >> 16);
    }
    r *= 0x1p-116f;
    uint32_t rs = pack_bf16(r, r);
    const uint32_t sh = pack_bf16(er, er);
    if (PACE & 2) rs = pace(bar, off, rs, sh, zero);
#pragma unroll
    for (int i = 0; i < 6; i++)
#pragma unroll
        for (int k = 0; k < 4; k++) v[i][k] = bf2_to_h2(bf2_fma(v[i][k], rs, sh));
}

template <int R>
__device__ __forceinline__ uint32_t gelu2(uint32_t a, uint32_t sc2) {
    uint32_t y, t;
    if (R) asm("{\n.reg .b16 l, h;\n.reg .b32 f;\nmov.b32 {l, h}, %2;\nmov.b32 f, {h, h};\nmul.rn.f16x2 %0, %1, f;\n}\n" : "=r"(y) : "r"(a), "r"(sc2));
    else asm("{\n.reg .b16 l, h;\n.reg .b32 f;\nmov.b32 {l, h}, %2;\nmov.b32 f, {l, l};\nmul.rn.f16x2 %0, %1, f;\n}\n" : "=r"(y) : "r"(a), "r"(sc2));
    asm("tanh.approx.f16x2 %0, %1;\n" : "=r"(t) : "r"(h2_mul(y, h2_fma(y, y, GELU_C2))));
    return h2_fma(a, t, a);
}
constexpr uint32_t SPARE = 0x40074007u;

__device__ __forceinline__ uint32_t p1_parity(uint32_t sbase) {
    uint32_t v;
    asm volatile("ld.shared.u32 %0, [%1];\n" : "=r"(v) : "r"(sbase + P1_OFF_TILE - 4) : "memory");
    return v;
}
__device__ __forceinline__ uint32_t p1_exponent(float t, uint32_t saddr, int lane) {
    t += __shfl_xor_sync(0xffffffffu, t, 1);
    t += __shfl_xor_sync(0xffffffffu, t, 2);
    const uint32_t ex = min(max(__float_as_uint(13.9f * __fsqrt_rn(t)) >> 23, 72u), 198u);
    if ((lane & 3) == 0) asm volatile("st.shared.u32 [%0], %1;\n" ::"r"(saddr), "r"(ex << 23) : "memory");
    return ex;
}
__device__ __forceinline__ uint32_t p1_convert(uint32_t v, uint32_t ex) {
    return bf2_to_h2(bf2_mul(bf2_mul(v, (258u - ex) * 0x00800080u), 0x07800780u));
}
__device__ __forceinline__ uint32_t p1_scales(uint32_t ex0, uint32_t ex1) {
    return pack_f16(__uint_as_float(min(ex0, 142u) << 23), __uint_as_float(min(ex1, 142u) << 23));
}
__device__ __forceinline__ void p1_epilogue(const uint32_t (&acc)[2][32], const uint32_t (&sc2)[2], float (&ssq)[4], uint8_t* hp, int zero) {
    uint32_t sq[2], h[16][4];
#pragma unroll
    for (int i2 = 0; i2 < 9; i2++) {
#pragma unroll
        for (int c = 2 * i2 - 2; c < 2 * i2; c++) {
            if (c >= 0 && (c & 3)) {
                uint32_t o[4];
#pragma unroll
                for (int u = 0; u < 4; u++) {
                    const uint32_t v = h[c & 12][u];
                    o[u] = bitsel(h[c][u], (c & 3) == 2 ? prmt(v, v, 0xa381) : prmt(v >> 3, v, (c & 3) == 1 ? 0x6240 : 0xf3d1), SPARE);
                }
                stg128_cs(hp + (c >> 3) * 2 * H_STEP + ((c >> 2) & 1) * H_HALF + ((c & 3) - 1) * 512, o[0], o[1], o[2], o[3]);
            }
        }
        if (i2 < 8) {
#pragma unroll
            for (int u = 0; u < 4; u++) {
                h[2 * i2][u] = gelu2<0>(acc[i2 >> 2][8 * (i2 & 3) + 2 * u], sc2[i2 >> 2]);
                h[2 * i2 + 1][u] = gelu2<1>(acc[i2 >> 2][8 * (i2 & 3) + 2 * u + 1], sc2[i2 >> 2]);
#pragma unroll
                for (int r = 0; r < 2; r++) {
                    const uint32_t v = h[2 * i2 + r][u];
                    sq[r] = ((i2 & 3) | u) ? h2_fma(v, v, sq[r]) : h2_mul(v, v);
                }
            }
            if ((i2 & 3) == 3) {
#pragma unroll
                for (int r = 0; r < 2; r++) ssq[(i2 >> 2) * 2 + r] += h_lo(sq[r]) + h_hi(sq[r]);
            }
            sched_break(zero);
        }
    }
}
template <int WG>
__device__ __forceinline__ void p1_consumer(const uint32_t (&a)[24][4], const uint32_t (&sc2)[2], uint32_t sbase, int w, int lane, int zero) {
    const uint32_t bar_full = sbase + P1_OFF_BAR, bar_empty = bar_full + P1_NST * 8;
    const uint32_t empty_remote = mapa(bar_empty, lane & 1);
    const uint32_t bar_pace = bar_empty + P1_NST * 8 + 16 + w * 8;
    const int g = lane >> 2, q = lane & 3, cb = (blockIdx.x % GRP_CTAS) * 4 + WG * 2;
    uint32_t acc[2][32];
    float ssq[4] = {0.f, 0.f, 0.f, 0.f};
    TSTAMP(0, 1);

    uint8_t* hp = reinterpret_cast<uint8_t*>(g_h) + (size_t)(blockIdx.x / GRP_CTAS) * (2 * H_TILE) + ((cb * 2 + (w >> 1)) * H_STEP + (w & 1) * 1536) + g * 64 + (q ^ (g >> 1)) * 16;
    const uint64_t db = make_desc(sbase, 16, 1024) | (1ull << 62);
    const uint64_t da = db + (P1_OFF_W + WG * P1_W) / 16;
#pragma unroll 1
    for (int i = 0;; i++) {
        TRACE(WG, i, 0);
        if (WG == 0) mbar_wait(bar_full, i & 1);
        bar_sync(1 + WG, 256);
        TRACE(WG, i, 1);
        uint32_t step, more;
        wg_fence();
#pragma unroll
        for (int k = 0; k < 24; k++) {
            if (WG == 0 && k && k % 4 == 0) mbar_wait(bar_full + (k >> 2) * 8, i & 1);
            mma_rs_n128(acc[0], a[k], db + (uint64_t)((k >> 2) * 1024 + (k & 3) * 2), k != 0);
            mma_ss_n128(acc[1], da + (uint64_t)(k * 128), db + (uint64_t)((k >> 2) * 1024 + (k & 3) * 2), k != 0);
            if (k == 23) bar_arrive(2 - WG, 256);
            if (k == 23 || (WG == 1 && k % 4 == 3)) wg_commit();
            if (WG == 1 && k % 4 == 3 && k > 3) {
                wg_wait<1>();
                if (lane < 2) mbar_arrive_cluster(empty_remote + ((k >> 2) - 1) * 8);
            }
        }
        asm volatile("ld.shared.v2.u32 {%0, %1}, [%2];\n" : "=r"(step), "=r"(more) : "r"(sbase + P1_OFF_TILE + (i & 3) * 16) : "memory");
        TRACE(WG, i, 2);
        hp += step;
        TRACE(WG, i, 3);
        wg_wait<0>();
        TRACE(WG, i, 4);
        if (WG == 1 && lane < 2) mbar_arrive_cluster(empty_remote + 5 * 8);
        p1_epilogue(acc, sc2, ssq, hp, zero);
        if (lane == 0) mbar_arrive(bar_pace);
        if (!more) break;
    }
    TSTAMP(0, 21);
    if (WG == 0) bar_sync(1, 256);
#pragma unroll
    for (int r = 0; r < 4; r++) {
        const int ch = (r >> 1) * 64 + w * 16 + (r & 1) * 8 + g;
        ssq[r] += __shfl_xor_sync(0xffffffffu, ssq[r], 1);
        ssq[r] += __shfl_xor_sync(0xffffffffu, ssq[r], 2);
        float f;
        asm volatile("ld.shared.f32 %0, [%1];\n" : "=f"(f) : "r"(sbase + P1_OFF_EX + (WG * 128 + ch) * 4) : "memory");
        if (q == 0) atomicAdd(&g_sums[p1_parity(sbase)][cb * 64 + ch], ssq[r] * f * f);
    }
}

__global__ void __cluster_dims__(2, 1, 1) __launch_bounds__(512, 1)
pass1_kernel(const __grid_constant__ CUtensorMap wmap, const __nv_bfloat16* __restrict__ x, const __nv_bfloat16* __restrict__ dw,
             const __nv_bfloat16* __restrict__ w2, const __nv_bfloat16* __restrict__ grn_b, int zero) {
    extern __shared__ __align__(1024) uint8_t smem[];
    const uint32_t sbase = smem_u32(smem);
    const uint32_t bar_full = sbase + P1_OFF_BAR, bar_empty = bar_full + P1_NST * 8, bar_w = bar_empty + P1_NST * 8;
    const int tid = threadIdx.x;
    const int warp = __shfl_sync(0xffffffffu, tid >> 5, 0), lane = tid & 31;
    const uint32_t rank = cluster_rank();
    const int cig = blockIdx.x % GRP_CTAS;
    uint8_t* const ring = reinterpret_cast<uint8_t*>(g_ln);

    TSTAMP(0, 0);
    TRACEW(110 + warp, 0);
    const uint32_t bar_pace = bar_w + 16, bar_xfull = bar_pace + 32, bar_xempty = bar_xfull + 8, bar_done = bar_xfull + 16;
    const uint32_t bar_raw = sbase + P1_OFF_RAW;
    const int ln0 = blockIdx.x >> 2, first = blockIdx.x / GRP_CTAS;
    const uint8_t* xsrc = reinterpret_cast<const uint8_t*>(x) + (size_t)(NGRP * 4 + blockIdx.x) * P1_X;

    if (warp >= 12) {
        reg_dec<32>();
        asm volatile("barrier.cluster.arrive.relaxed.aligned;\n" ::: "memory");
        asm volatile("barrier.cluster.wait.aligned;\n" ::: "memory");
        if (warp == 12) {
            int prev = first - NGRP, t = first;
            const uint32_t rbase = mapa(sbase, lane & 1);
#pragma unroll 1
            for (int i = 1; t < NT_RING; i++) {
                const int round = t / LN_RING, slot = t - round * LN_RING;
                const uint8_t* src = ring + slot * LN_TILE + rank * (P1_SLOT / 2);
                int next = 0;
                if (rank == 0 && lane == 0) next = atomicAdd(&g_flag[LN_RING + (cig >> 1)][0][0], 1u);
                flag_wait<true>(&g_flag[slot][0][0], 4 * round + 4);
                TRACEW(i, 2);
                asm volatile("fence.proxy.async.global;\n" ::: "memory");
                next = NGRP + __shfl_sync(0xffffffffu, next, 0);
#pragma unroll 1
                for (int h = 0; h < P1_NST; h++) {
                    mbar_wait(bar_empty + h * 8, ~i & 1);
                    if (h == 0) TRACEW(i, 4);
                    if (h == 5) TRACEW(i, 5);
                    if (elect_one()) {
                        mbar_expect_tx(bar_full + h * 8, h ? P1_SLOT : P1_SLOT + 16);
                        bulk_g2s_mc(sbase + h * P1_SLOT + rank * (P1_SLOT / 2), src + h * P1_SLOT, P1_SLOT / 2, bar_full + h * 8, (uint16_t)3);
                    }
                    __syncwarp();
                    if (h == 0 && rank == 0 && lane < 2)
                        asm volatile("st.async.shared::cluster.mbarrier::complete_tx::bytes.v4.u32 [%0], {%1, %2, %3, %3}, [%4];\n"
                                     ::"r"(rbase + P1_OFF_TILE + (i & 3) * 16), "r"((t - prev) * (2 * H_TILE)), "r"((int)(next < NT_RING)), "r"(next),
                                       "r"(rbase + P1_OFF_BAR) : "memory");
                }
                prev = t;
                t = next;
                if (rank != 0) {
                    mbar_wait(bar_full, i & 1);
                    asm volatile("ld.shared.u32 %0, [%1];\n" : "=r"(t) : "r"(sbase + P1_OFF_TILE + (i & 3) * 16 + 8) : "memory");
                }
            }
        } else if (warp == 13) {
            int ph = 0;
            unsigned target = 0;
#pragma unroll 1
            for (int i = ln0 + LN_STEP; i < NT_RING; i += LN_STEP, ph ^= 1) {
                target += ph * (GRP_CTAS / 2);
                xsrc += (size_t)NUM_CTAS * P1_X;
                mbar_wait(bar_xempty, ph);
                if (elect_one()) {
                    mbar_expect_tx(bar_xfull, P1_X);
                    bulk_g2s(sbase + P1_OFF_X, xsrc, P1_X, bar_xfull);
                }
                __syncwarp();
                const uint32_t off = flag_wait<false>(&g_flag[ln0 + (ph ^ 1) * LN_STEP][1][0], target);
                mbar_wait(bar_done, ph);
                if (elect_one()) {
                    asm volatile("st.shared.u32 [%0], %1;\n" ::"r"(bar_done + 8), "r"(off) : "memory");
                    mbar_arrive(bar_xfull);
                }
                __syncwarp();
            }
        } else if (warp == 15) {
            const uint32_t par = g_epoch & 1;
            asm volatile("st.shared.u32 [%0], %1;\n" ::"r"(sbase + P1_OFF_TILE - 4), "r"(par) : "memory");
            if (blockIdx.x < 16) reinterpret_cast<float4*>(g_sums[par ^ 1])[blockIdx.x * 32 + lane] = make_float4(0.f, 0.f, 0.f, 0.f);
            {
                bar_sync(4, 288);
                TRACEW(110 + warp, 1);
                mbar_wait(bar_raw + 8, 0);
                TRACEW(110 + warp, 2);
                const uint32_t o = lane * 16384 + rank * 8192, peer = mapa(sbase, rank ^ 1);
                if (lane < 6)
                    asm volatile("cp.async.bulk.shared::cluster.shared::cta.mbarrier::complete_tx::bytes [%0], [%1], 8192, [%2];\n"
                                 ::"r"(peer + o), "r"(sbase + o), "r"(peer + P1_OFF_BAR + lane * 8) : "memory");
                __syncwarp();
            }
            int t = -1;
#pragma unroll 1
            for (int i = 0; rank == 1 && t < NT_RING; i++) {
#pragma unroll 1
                for (int h = 0; h < P1_NST; h++) mbar_wait(bar_full + h * 8, i & 1);
                if (lane == 0 && t >= 0) asm volatile("red.relaxed.gpu.global.add.u32 [%0], 1;\n" ::"l"(&g_flag[t % LN_RING][1][0]) : "memory");
                asm volatile("ld.shared.u32 %0, [%1];\n" : "=r"(t) : "r"(sbase + P1_OFF_TILE + (i & 3) * 16 + 8) : "memory");
                if (lane == 0) mbar_arrive(bar_empty);
                TRACEW(i, 3);
            }
            if (rank == 0) {
                mbar_wait(bar_full, 0);
                TRACEW(110 + warp, 3);
                mbar_wait(bar_full, 1);
                float* sums = g_sums[par] + HID;
                unsigned* flag = reinterpret_cast<unsigned*>(sums + C_DIM);
                float gs = 0.f;
#pragma unroll 1
                for (int pass = 0; pass < 2; pass++) {
                    float mx = 0.f;
#pragma unroll 1
                    for (int it = first; it < 96; it += NGRP) {
                        const int np = (it % 12) * 32 + lane, kb = cig * 4 + it / 12;
                        const __nv_bfloat16* wc = w2 + (size_t)kb * 64 * C_DIM + perm32(np);
                        const uint32_t sc = mapa(sbase + P1_OFF_EX + (kb & 3) * 256, it / 48);
                        float bsum = 0.f;
#pragma unroll 1
                        for (int c = 0; c < 8; c++) {
                            float f[8];
#pragma unroll
                            for (int e = 0; e < 8; e++) f[e] = __bfloat162float(wc[(c * 8 + e) * C_DIM]);
#pragma unroll
                            for (int e = 0; e < 8; e++) {
                                float t;
                                asm volatile("ld.shared::cluster.f32 %0, [%1];\n" : "=f"(t) : "r"(sc + (c * 8 + e) * 4) : "memory");
                                bsum = fmaf(__bfloat162float(grn_b[kb * 64 + c * 8 + e]), f[e], bsum);
                                f[e] *= t;
                                mx = fmaxf(mx, fabsf(f[e]));
                            }
                            if (pass)
                                g_w2img[0][(((kb * 4 + (c >> 1)) * 48 + (np >> 3)) * 2 + (c & 1)) * 8 + (np & 7)] = make_uint4(
                                    pack_f16(f[0] * gs, f[1] * gs), pack_f16(f[2] * gs, f[3] * gs), pack_f16(f[4] * gs, f[5] * gs), pack_f16(f[6] * gs, f[7] * gs));
                        }
                        if (pass) atomicAdd(&sums[np], bsum);
                    }
                    if (!pass) {
                        const uint32_t m = __reduce_max_sync(0xffffffffu, __float_as_uint(mx));
                        if (lane == 0) {
                            atomicMax(flag, m);
                            asm volatile("red.release.gpu.global.add.u32 [%0], 1;\n" ::"l"(flag + 32) : "memory");
                        }
                        flag_wait<true>(flag + 32, NUM_CTAS / 2);
                        gs = w2_scale(__ldcg(flag));
                    }
                }
                do {
                    __nanosleep(1000);
                    asm volatile("ld.volatile.shared.u32 %0, [%1];\n" : "=r"(t) : "r"(sbase + P1_OFF_TILE + (lane & 3) * 16 + 8) : "memory");
                    SAFE_BREAK;
                } while (__all_sync(0xffffffffu, t < NT_RING - P1_WPF));
                if (lane == 0 && blockIdx.x < 128)
                    asm volatile("cp.async.bulk.prefetch.L2.global [%0], %1;\n" ::"l"(g_w2img[0] + blockIdx.x * 576), "r"(18432) : "memory");
            }
        } else if (warp == 14) {
            int ph = 0;
#pragma unroll 1
            for (int i = ln0; i < NT_RING; i += LN_STEP, ph ^= 1) {
                mbar_wait(bar_done, ph);
                TRACEW(i / LN_STEP, 0);
                asm volatile("fence.proxy.async.global;\n" ::: "memory");
                if (elect_one()) asm volatile("red.release.gpu.global.add.u32 [%0], 1;\n" ::"l"(&g_flag[ln0 + ph * LN_STEP][0][0]) : "memory");
                __syncwarp();
                TRACEW(i / LN_STEP, 1);
            }
        }
        __syncwarp();
        cluster_sync();
    } else if (warp >= 8) {
        reg_dec<80>();
        asm volatile("barrier.cluster.arrive.relaxed.aligned;\n" ::: "memory");
        {
            const int l8 = lane & 7, row = (warp - 8) * 4 + (lane >> 3), px = (blockIdx.x & 3) * 32 + row;
            uint32_t d[6][4];
#pragma unroll
            for (int j = 0; j < 6; j++) {
                const uint4 t = reinterpret_cast<const uint4*>(dw)[j * 8 + l8];
                d[j][0] = t.x; d[j][1] = t.y; d[j][2] = t.z; d[j][3] = t.w;
            }
            const int n = (px & 64) + perm32(2 * row + ((px >> 5) & 1));
            uint8_t* const dst0 = ring + ln0 * LN_TILE + n * 128 + ((l8 ^ (n & 7)) << 4);
            const uint32_t src = sbase + P1_OFF_X + ((warp - 8) * 8 + (lane >> 3)) * (C_DIM * 2) + l8 * 16;
            int ph = 0;
            asm volatile("barrier.cluster.wait.aligned;\n" ::: "memory");
#pragma unroll 1
            for (int i = ln0; i < NT_RING; i += LN_STEP, ph ^= 1) {
                TRACE(2, i / LN_STEP, 0);
                mbar_wait(bar_xfull, ph);
                uint32_t off;
                asm volatile("ld.shared.u32 %0, [%1];\n" : "=r"(off) : "r"(bar_done + 8) : "memory");
                TRACE(2, i / LN_STEP, 1);
#pragma unroll 1
                for (int ps = 0; ps < 2; ps++) {
                    uint32_t v[6][4];
#pragma unroll
                    for (int j = 0; j < 6; j++)
                        asm volatile("ld.shared.v4.u32 {%0,%1,%2,%3}, [%4];\n"
                                     : "=r"(v[j][0]), "=r"(v[j][1]), "=r"(v[j][2]), "=r"(v[j][3]) : "r"(src + ps * (4 * C_DIM * 2) + j * 128) : "memory");
                    ln_row<P1_PACE>(v, d, bar_pace + (warp - 8) * 8, off, zero, ps == 1 && lane == 0 ? bar_xempty : 0);
                    uint8_t* dst = dst0 + ph * (LN_STEP * LN_TILE) + ps * 4096;
#pragma unroll
                    for (int j = 0; j < 6; j++) *reinterpret_cast<uint4*>(dst + j * 16384) = make_uint4(v[j][0], v[j][1], v[j][2], v[j][3]);
                    TRACE(2, i / LN_STEP, 3 + ps);
                }
                asm volatile("fence.proxy.async.global;\nfence.acq_rel.cta;\n" ::: "memory");
                __syncwarp();
                if (lane == 0) mbar_arrive(bar_done);
                TRACE(2, i / LN_STEP, 5);
                TRACE(2, i / LN_STEP, 2);
            }
        }
        __syncwarp();
        cluster_sync();
    } else {
        uint32_t d[6][4];
#pragma unroll
        for (int j = 0; j < 6; j++)
            asm volatile("ld.global.nc.v4.u32 {%0,%1,%2,%3}, [%4];\n" : "=r"(d[j][0]), "=r"(d[j][1]), "=r"(d[j][2]), "=r"(d[j][3])
                         : "l"(reinterpret_cast<const uint4*>(dw) + j * 8 + (lane & 7)) : "memory");
        if (tid == 0) {
            mbar_init(bar_raw, 1);
            mbar_init(bar_raw + 8, 8);
            asm volatile("fence.mbarrier_init.release.cluster;\n" ::: "memory");
            mbar_expect_tx(bar_raw, LN_TILE / 2);
            for (int i = 0; i < 6; i++)
                bulk_g2s(sbase + i * 16384 + (rank ^ 1) * 8192, x + (size_t)(first * 128 + rank * 64) * C_DIM + i * 4096, 8192, bar_raw);
        }
        if (tid == 32) {
            mbar_init(bar_xfull, 2);
            mbar_init(bar_xempty, 4);
            mbar_init(bar_done, 4);
            asm volatile("fence.mbarrier_init.release.cluster;\n" ::: "memory");
            mbar_expect_tx(bar_xfull, P1_X);
            bulk_g2s(sbase + P1_OFF_X, xsrc, P1_X, bar_xfull);
            asm volatile("st.shared.u32 [%0], 1;\n" ::"r"(bar_done + 8) : "memory");
            mbar_arrive(bar_xfull);
        }
        if (tid == 64) {
            asm volatile("st.shared.v4.u32 [%0], {0, 1, %1, %1};\n" ::"r"(sbase + P1_OFF_TILE), "r"(first) : "memory");
            for (int i = 0; i < P1_NST; i++) {
                mbar_init(bar_full + i * 8, 1);
                mbar_init(bar_empty + i * 8, i ? 8 : 8 + rank);
                if (i < 4) mbar_init(bar_pace + i * 8, 1);
                mbar_expect_tx(bar_full + i * 8, P1_SLOT / 2);
            }
            asm volatile("fence.mbarrier_init.release.cluster;\n" ::: "memory");
            if (blockIdx.x < 64) (&g_half[0][0])[blockIdx.x] = 0;
            else if (blockIdx.x < 66) g_prog[blockIdx.x - 64][0] = 0;
        }
        if (tid == 96) {
            for (int i = 0; i < 2; i++) mbar_init(bar_w + i * 8, 1);
            asm volatile("fence.mbarrier_init.release.cluster;\n" ::: "memory");
        }
        __syncwarp();
        asm volatile("barrier.cluster.arrive.relaxed.aligned;\n" ::: "memory");
        auto load_w = [&](int i, int ch) {
            mbar_expect_tx(bar_w + i * 8, P1_W);
            tma2(sbase + P1_OFF_W + i * P1_W, &wmap, cig * 256 + i * 128 + ch, 0, bar_w + i * 8);
            tma2(sbase + P1_OFF_W + i * P1_W + P1_W / 2, &wmap, cig * 256 + i * 128 + ch, 192, bar_w + i * 8);
        };
        if (tid == 96)
            for (int i = 0; i < 2; i++) load_w(i, 0);
        __syncwarp();
        reg_inc<200>();
        TRACEW(110 + warp, 1);
        const int wg = warp >> 2, w = warp & 3;
        uint32_t a[24][4];
        {
            const int n = warp * 8 + (lane >> 3), px = (n & 1) * 32 + (n >> 5) * 4 + ((n >> 1) & 1) * 8 + ((n >> 3) & 3);
            if (wg == 1) bar_arrive(1, 256);
            gdc_launch();
            asm volatile("barrier.cluster.wait.aligned;\n" ::: "memory");
#pragma unroll 1
            for (int ps = -1; ps < 2; ps++) {
                if (ps == 0) mbar_wait(bar_raw, 0);
                TRACEW(110 + warp, 2 + (ps == 0));
                uint32_t v[6][4];
#pragma unroll
                for (int j = 0; j < 6; j++) {
                    const uint32_t o = (px + (ps & 1) * 16) * (C_DIM * 2) + j * 128;
                    asm volatile("ld.shared.v4.u32 {%0,%1,%2,%3}, [%4];\n" : "=r"(v[j][0]), "=r"(v[j][1]), "=r"(v[j][2]), "=r"(v[j][3])
                                 : "r"(sbase + (rank ^ 1) * 8192 + (lane & 7) * 16 + o + (o & ~8191u)) : "memory");
                }
                ln_row<0>(v, d, 0, 0, zero, 0);
                const uint32_t p = sbase + (rank * 64 + n + (ps & 1) * 4) * 128 + (((lane ^ n ^ (ps & 1) * 4) & 7) << 4);
#pragma unroll
                for (int j = 0; j < 6; j++)
                    asm volatile("st.shared.v4.u32 [%4], {%0,%1,%2,%3};\n"
                                 ::"r"(v[j][0]), "r"(v[j][1]), "r"(v[j][2]), "r"(v[j][3]), "r"(p + j * 16384) : "memory");
            }
            asm volatile("fence.proxy.async.shared::cta;\n" ::: "memory");
            __syncwarp();
            if (lane == 0) mbar_arrive_cluster(mapa(bar_raw + 8, rank ^ 1));
            bar_arrive(4, 288);
            TRACEW(110 + warp, 4);
        }
        const uint32_t src = sbase + P1_OFF_W + wg * P1_W + ((lane >> 4) * 8 + (lane & 7)) * 128 + (((2 * w + ((lane >> 3) & 1)) ^ (lane & 7)) << 4);
        const uint32_t s_ex = sbase + P1_OFF_EX + (wg * 128 + w * 16 + (lane >> 2)) * 4;
        uint32_t sc2[2], ex[2];
        mbar_wait(bar_w + wg * 8, 0);
        TRACEW(110 + warp, 5);
#pragma unroll
        for (int k = 0; k < 24; k++) ldsm4t(a[k], src + k * 2048);
        bar_sync(6 + wg, 128);
        if ((tid & 127) == 0) load_w(wg, 64);
        TRACEW(110 + warp, 6);
#pragma unroll
        for (int r = 0; r < 2; r++) {
            float t = 0.f;
#pragma unroll
            for (int j = 0; j < 6; j++) {
                uint32_t c = bf2_mul(a[4 * j][r], a[4 * j][r]);
#pragma unroll
                for (int k = 1; k < 8; k++) c = bf2_fma(a[4 * j + k / 2][r + (k & 1) * 2], a[4 * j + k / 2][r + (k & 1) * 2], c);
                t += bf_lo(c) + bf_hi(c);
            }
            ex[r] = p1_exponent(t, s_ex + r * 32, lane);
#pragma unroll
            for (int k = 0; k < 48; k++) a[k >> 1][r + (k & 1) * 2] = p1_convert(a[k >> 1][r + (k & 1) * 2], ex[r]);
        }
        sc2[0] = p1_scales(ex[0], ex[1]);
        {
            float t[2] = {0.f, 0.f};
            mbar_wait(bar_w + wg * 8, 1);
#pragma unroll 1
            for (int j = 0; j < 6; j++) {
                uint32_t v[4][4];
#pragma unroll
                for (int k = 0; k < 4; k++) ldsm4t(v[k], src + (4 * j + k) * 2048);
#pragma unroll
                for (int r = 0; r < 2; r++) {
                    uint32_t c = bf2_mul(v[0][r], v[0][r]);
#pragma unroll
                    for (int k = 1; k < 8; k++) c = bf2_fma(v[k / 2][r + (k & 1) * 2], v[k / 2][r + (k & 1) * 2], c);
                    t[r] += bf_lo(c) + bf_hi(c);
                }
            }
#pragma unroll
            for (int r = 0; r < 2; r++) ex[r] = p1_exponent(t[r], s_ex + 256 + r * 32, lane);
#pragma unroll 1
            for (int j = 0; j < 6; j++) {
                uint32_t v[4][4];
#pragma unroll
                for (int k = 0; k < 4; k++) ldsm4t(v[k], src + (4 * j + k) * 2048);
#pragma unroll
                for (int k = 0; k < 4; k++)
                    asm volatile("stmatrix.sync.aligned.m8n8.x4.trans.shared.b16 [%0], {%1,%2,%3,%4};\n" ::"r"(src + (4 * j + k) * 2048),
                                 "r"(p1_convert(v[k][0], ex[0])), "r"(p1_convert(v[k][1], ex[1])), "r"(p1_convert(v[k][2], ex[0])), "r"(p1_convert(v[k][3], ex[1])) : "memory");
            }
            sc2[1] = p1_scales(ex[0], ex[1]);
            asm volatile("fence.proxy.async.shared::cta;\n" ::: "memory");
        }
        TRACEW(110 + warp, 7);
        bar_sync(5, 256);
        if (warp < 4) p1_consumer<0>(a, sc2, sbase, w, lane, zero);
        else p1_consumer<1>(a, sc2, sbase, w, lane, zero);
        cluster_sync();
        TSTAMP(0, 30);
    }
}

constexpr int P2_B = 24576, P2_NB = 4;
constexpr int P2_A = 3072, P2_NA = 8;
constexpr int P2_XROW = C_DIM * 2;
constexpr int P2_OFF_A = P2_B * P2_NB;
constexpr int P2_OFF_X = P2_OFF_A + 3 * P2_NA * P2_A;
constexpr int P2_XHALF = 32 * P2_XROW + 64;
constexpr int P2_OFF_GRN = P2_OFF_X + 64 * P2_XROW + 128;
constexpr int P2_OFF_BIAS = P2_OFF_GRN + HID * 2;
constexpr int P2_OFF_RED = P2_OFF_BIAS + C_DIM * 4;
constexpr int P2_OFF_BAR = P2_OFF_RED + 192;
constexpr int P2_SMEM = P2_OFF_BAR + (2 * P2_NB + 6 * P2_NA + 7) * 8;
#define P2_S1 16
constexpr int P2_S2 = 32;
constexpr int P2_NCL = NUM_CTAS / 2, P2_ITEMS = NT128 / P2_NCL, P2_SHARED = NT128 - P2_ITEMS * P2_NCL;
constexpr int P2_NPOS = 6 * 48 + P2_S1;
constexpr int P2_RAW = 24;
constexpr int P2_XC = 8 * P2_XROW;
#define P2_T0 4
#define P2_SLACK 0
#define P2_RAMP 2
#define P2_AH 2
__device__ __forceinline__ int p2_start(int n) { return n < 0 ? 0 : n / 3 * 48 + (n % 3 == 1 ? P2_S1 : n % 3 * (P2_S2 / 2)); }
__device__ __forceinline__ int p2_tile(int cl, int n) {
    return n == 0 ? NT128 - 1 - cl : n < 0 ? NT128 - 1 - P2_NCL - (cl >> 1) : cl + P2_NCL * (n - 1);
}

#define P2_EB 2
#define P2_EX 1
__device__ __forceinline__ void p2_epilogue(uint32_t (&acc0)[48], uint32_t (&acc1)[48], uint32_t up, uint32_t sx, uint32_t sb, int zero) {
    uint32_t v[12][3][4];
    auto load = [&](int t, int j) {
        if (t >= 12) return;
        uint32_t (&w)[4] = v[t][j];
        asm volatile("ld.shared.v4.u32 {%0,%1,%2,%3}, [%4];\n" : "=r"(w[0]), "=r"(w[1]), "=r"(w[2]), "=r"(w[3])
                     : "r"((j ? sx + (j - 1) * 4 * P2_XROW : sb) + t * 64) : "memory");
    };
    auto store = [&](int t, int r) {
        const uint32_t* w = (t < 6 ? acc0 : acc1) + 8 * (t % 6) + 4 * r;
        asm volatile("st.shared.v4.u32 [%4], {%0,%1,%2,%3};\n" ::"r"(w[0]), "r"(w[1]), "r"(w[2]), "r"(w[3]), "r"(sx + t * 64 + r * 4 * P2_XROW) : "memory");
    };
#pragma unroll
    for (int t = 0; t < P2_EB; t++) load(t, 0);
#pragma unroll
    for (int t = 0; t < 2 * P2_EX; t++) load(t >> 1, 1 + (t & 1));
#pragma unroll
    for (int t = 0; t < 12; t++) {
        load(t + P2_EX, 1);
        load(t + P2_EX, 2);
        load(t + P2_EB, 0);
        uint32_t* acc = (t < 6 ? acc0 : acc1) + 8 * (t % 6);
        uint32_t y[8];
#pragma unroll
        for (int e = 0; e < 8; e++) {
            y[e] = h2_add(acc[e], v[t][0][e >> 1]);
            y[e] = pack_bf16(h_lo(y[e]), h_hi(y[e]));
        }
#pragma unroll
        for (int e = 0; e < 8; e++) acc[(e & 1) * 4 + (e >> 1)] = bf2_fma(y[e], up, v[t][1 + (e & 1)][e >> 1]);
        store(t, 0);
        store(t, 1);
        sched_break(zero);
    }
    if (zero) {
#pragma unroll
        for (int t = 0; t < 24; t++) store(t >> 1, t & 1);
    }
}

__device__ __forceinline__ void p2_unpack(uint32_t (&u)[4], uint32_t o1, uint32_t o2, uint32_t o3) {
    u[2] = bitsel(o1, 0x00040004u, SPARE);
    u[1] = bitsel(o2, 0x00040004u, SPARE);
    u[3] = bitsel(o3, 0x00040004u, SPARE);
    const uint32_t t = bitsel(prmt(o1, o2, 0x6341), prmt(o1, o3, 0x6240) << 3, 0x38383838u);
    u[0] = bitsel(bitsel(t, prmt(o2, o3, 0x7351) << 1, 0x80808080u), 0x00040004u, SPARE);
}

__global__ void __cluster_dims__(2, 1, 1) __launch_bounds__(512, 1)
pass2_kernel(const __nv_bfloat16* __restrict__ x, const __nv_bfloat16* __restrict__ grn_g, __nv_bfloat16* __restrict__ out, int zero) {
    extern __shared__ __align__(1024) uint8_t smem[];
    const uint32_t sbase = smem_u32(smem);
    const uint32_t bar_bfull = sbase + P2_OFF_BAR, bar_bempty = bar_bfull + P2_NB * 8;
    const uint32_t bar_afull = bar_bempty + P2_NB * 8, bar_aempty = bar_afull + 3 * P2_NA * 8;
    const uint32_t bar_xfull = bar_aempty + 3 * P2_NA * 8, bar_oready = bar_xfull + 24, s_pos = bar_oready + 24;
    int tid;
    asm volatile("mov.u32 %0, %%tid.x;\n" : "=r"(tid));
    const int warp = __shfl_sync(0xffffffffu, tid >> 5, 0), lane = tid & 31;
    const uint32_t rank = cluster_rank();
    const int cl = blockIdx.x >> 1, pair = cl >> 1;
    const int half = pair < P2_SHARED, fin = half && (cl & 1);
    const int k0 = (pair + 3 * (cl & 1)) % 6 * 8;
    auto wait_pos = [&](int target) {
        int v;
        while (true) {
            asm volatile("ld.volatile.shared.u32 %0, [%1];\n" : "=r"(v) : "r"(s_pos) : "memory");
            if (v >= target) break;
            SAFE_BREAK;
            __nanosleep(100);
        }
    };

    TSTAMP(1, 0);
    if (tid == 384) {
        for (int i = 0; i < P2_NB; i++) {
            mbar_init(bar_bfull + i * 8, 1);
            mbar_init(bar_bempty + i * 8, 24);
        }
        for (int i = 0; i < 3 * P2_NA; i++) {
            mbar_init(bar_afull + i * 8, 1);
            mbar_init(bar_aempty + i * 8, 4);
        }
        for (int i = 0; i < 3; i++) {
            mbar_init(bar_xfull + i * 8, 2);
            mbar_init(bar_oready + i * 8, 4);
        }
        asm volatile("st.shared.u32 [%0], 0;\n" ::"r"(s_pos) : "memory");
        asm volatile("fence.mbarrier_init.release.cluster;\n" ::: "memory");
    }
    __syncthreads();
    cluster_sync_relaxed();

    if (warp >= 12) {
        reg_dec<32>();
        if (warp == 12) {
            const uint8_t* wsrc = reinterpret_cast<const uint8_t*>(g_w2img) + rank * (P2_B / 2);
            int kb = k0;
            gdc_wait();
#pragma unroll 1
            for (int p = 0; p < P2_NPOS; p++) {
                const int st = p & 3;
                if (p == P2_RAW) {
                    flag_wait<true>(&g_prog[1][0], NUM_CTAS);
                    asm volatile("fence.proxy.async.global;\n" ::: "memory");
                    wsrc += sizeof(g_w2img[0]);
                }
                const int idle = (p < P2_S1 || p >= 6 * 48) + (p < P2_S2 ? !half || p >= 24 : p >= 5 * 48 + P2_S2);
                mbar_wait(bar_bempty + st * 8, (~p >> 2) & 1);
                TR2(3, p, 0);
                if (elect_one()) {
                    const int len = P2_B / 2;
                    mbar_expect_tx(bar_bfull + st * 8, 2 * len);
                    bulk_g2s_mc(sbase + st * P2_B + rank * (P2_B / 2), wsrc + kb * P2_B, len, bar_bfull + st * 8, (uint16_t)3);
                    asm volatile("st.volatile.shared.u32 [%0], %1;\n" ::"r"(s_pos), "r"(p) : "memory");
                    if (rank == 0) asm volatile("red.relaxed.gpu.global.add.u32 [%0], 1;\n" ::"l"(&g_prog[0][0]) : "memory");
                    if (idle) asm volatile("mbarrier.arrive.shared::cta.b64 _, [%0], %1;\n" ::"r"(bar_bempty + st * 8), "r"(8 * idle) : "memory");
                }
                __syncwarp();
                if (++kb == 48) kb = 0;
            }
            mbar_wait(bar_bempty, 1);
            if (lane == 0) mbar_arrive(bar_bfull);
        } else if (warp == 13) {
            const int w = lane < 3 ? lane : 0;
            const uint32_t dst0 = sbase + P2_OFF_A + w * P2_NA * P2_A;
            const uint32_t bf = bar_afull + w * P2_NA * 8, be = bar_aempty + w * P2_NA * 8;
            int n = (w == 2 && half ? -1 : w) - 3, left = 0, u = 0, c = 0;
            const uint8_t* src = nullptr;
            bool act = lane < 3;
            gdc_wait();
            while (__any_sync(0xffffffffu, act)) {
                if (left == 0) {
                    n += 3;
                    left = n >= P2_ITEMS ? -1 : n < 0 ? 24 : 48;
                    u = (k0 + p2_start(n)) % 48;
                    src = reinterpret_cast<const uint8_t*>(g_h) + (size_t)p2_tile(cl, n) * (2 * H_TILE) + rank * H_HALF + u * H_STEP;
                }
                bool ok = act && mbar_test(be + ((c - 1) & 7) * 8, (~c >> 3) & 1);
                if (__any_sync(0xffffffffu, act && c < 16)) {
                    int v;
                    asm volatile("ld.volatile.shared.u32 %0, [%1];\n" : "=r"(v) : "r"(s_pos) : "memory");
                    ok = ok && c <= (n <= 0 ? 2 * v - P2_RAMP : c >= 16 ? c : v - p2_start(n) + 8);
                }
                if (ok) {
                    const int st = c & 7;
                    if (left > 0) {
                        mbar_expect_tx(bf + st * 8, P2_A);
                        bulk_g2s(dst0 + st * P2_A, src, P2_A, bf + st * 8);
                    } else {
                        mbar_arrive(bf + st * 8);
                        act = false;
                    }
                    src += H_STEP;
                    if (++u == 48) { u = 0; src -= 48 * H_STEP; }
                    c++;
                    left--;
                }
                SAFE_BREAK;
                if (!__any_sync(0xffffffffu, ok)) __nanosleep(100);
            }
        } else if (warp == 14) {
            const uint32_t sx = sbase + P2_OFF_X;
            size_t o = 0;
            int wp = 0;
            uint32_t par = 0;
            if (fin) {
#pragma unroll 1
                for (int c = lane * 16; c < 64 * P2_XROW + 128; c += 512) asm volatile("st.shared.v4.u32 [%0], {0, 0, 0, 0};\n" ::"r"(sx + c) : "memory");
                __syncwarp();
            }
#pragma unroll 1
            for (int n = -half; n <= P2_ITEMS; n++) {
                const int w = (n + 3) % 3, end = p2_start(n) + 48;
                const size_t on = (size_t)(2 * p2_tile(cl, n) + rank) * (64 * C_DIM * 2);
                const uint32_t xf = bar_xfull + w * 8;
                bool st = n + half > 0;
                const bool ld = n < P2_ITEMS && !(n < 0 && fin);
                if (n == P2_ITEMS - 1 && lane == 0)
                    asm volatile("cp.async.bulk.prefetch.L2.global [%0], %1;\n" ::"l"(reinterpret_cast<const uint8_t*>(x) + on), "r"(64 * P2_XROW) : "memory");
                if (st) {
                    mbar_wait(bar_oready + wp * 8, (par >> wp) & 1);
                    par ^= 1u << wp;
                }
                if (lane == 0) {
                    if (n < P2_ITEMS) mbar_expect_tx(xf, ld ? 64 * C_DIM * 2 : 0);
                    const int t0 = (n ? p2_start(n - 1) + 48 : P2_S2) + P2_T0, dt = end - t0;
                    int t = st && n < P2_ITEMS - 1 ? 16 * t0 : -4096;
                    if ((n == 0 && half) || n >= P2_ITEMS - 1) {
                        if (fin && n == 0) {
                            flag_wait<true>(&g_half[pair][rank], 1);
                            asm volatile("fence.proxy.async.global;\n" ::: "memory");
                        }
#pragma unroll 1
                        for (int c = 0; c < 2; c++) {
                            uint8_t* dst = reinterpret_cast<uint8_t*>(out) + o + c * 32 * P2_XROW;
                            if (!fin || n) bulk_s2g(dst, sx + c * P2_XHALF, 32 * P2_XROW);
                            else asm volatile("cp.reduce.async.bulk.global.shared::cta.bulk_group.add.noftz.bf16 [%0], [%1], %2;\n"
                                              ::"l"(dst), "r"(sx + c * P2_XHALF), "r"(32 * P2_XROW) : "memory");
                        }
                        asm volatile("cp.async.bulk.commit_group;\n" ::: "memory");
                        if (!fin && n == 0) {
                            asm volatile("cp.async.bulk.wait_group 0;\nfence.proxy.async.global;\n" ::: "memory");
                            asm volatile("st.release.gpu.global.u32 [%0], 1;\n" ::"l"(&g_half[pair][rank]) : "memory");
                        }
                        st = false;
                    }
#pragma unroll 1
                    for (int c = 0; c < 64 * P2_XROW; c += P2_XC, t += 2 * dt) {
                        const uint32_t sp = sx + c + (c >= 32 * P2_XROW ? 64 : 0);
                        wait_pos(t >> 4);
                        if (st) bulk_s2g(reinterpret_cast<uint8_t*>(out) + o + c, sp, P2_XC);
                        asm volatile("cp.async.bulk.commit_group;\n" ::: "memory");
                        if (ld) {
                            wait_pos((t + dt) >> 4);
                            asm volatile("cp.async.bulk.wait_group.read 0;\n" ::: "memory");
                            bulk_g2s(sp, reinterpret_cast<const uint8_t*>(x) + on + c, P2_XC, xf);
                        }
                    }
                    if (rank == 0 && n > 0 && n < P2_ITEMS - 1) flag_wait<false>(&g_prog[0][0], P2_NCL * (end + P2_SLACK));
                    if (n < P2_ITEMS) mbar_arrive(xf);
                }
                __syncwarp();
                o = on;
                wp = w;
            }
            asm volatile("cp.async.bulk.wait_group 0;\n" ::: "memory");
        }
        __syncwarp();
        cluster_sync();
    } else {
        reg_inc<160>();
        const int wg = warp >> 2, w = warp & 3, g = lane >> 2, q = lane & 3;
        const uint32_t sx = sbase + P2_OFF_X + (g & 1) * P2_XHALF + (w * 8 + (g >> 1)) * P2_XROW + q * 16;
        const uint32_t af = bar_afull + wg * P2_NA * 8;
        const uint32_t s_a = sbase + P2_OFF_A + wg * P2_NA * P2_A + (lane >> 3) * 512 + (lane & 7) * 64 + ((w ^ ((lane & 7) >> 1)) << 4);
        uint32_t acc0[48], acc1[48], up;
        uint4 a[2][2];

        {
            float* s_red = reinterpret_cast<float*>(smem + P2_OFF_RED);
            float gx[4], part = 0.f;
            __nv_bfloat16 gg[4];
#pragma unroll
            for (int i = 0; i < 4; i++) gg[i] = grn_g[tid + 384 * i];
            TSTAMP(1, 27);
            gdc_wait();
            TSTAMP(1, 1);
            if (blockIdx.x == 120 && tid < (LN_RING + 3) * 2) (&g_flag[0][0][0])[tid * 8] = 0;
            if (blockIdx.x == 121 && tid == 0) g_epoch++;
#pragma unroll
            for (int i = 0; i < 4; i++) gx[i] = __ldcg(&g_sums[0][tid + 384 * i]) + __ldcg(&g_sums[1][tid + 384 * i]);
            const float bias = __ldcg(&g_sums[0][HID + tid]) + __ldcg(&g_sums[1][HID + tid]);
            const float gs = w2_scale(__float_as_uint(__ldcg(&g_sums[0][HID + C_DIM])) | __float_as_uint(__ldcg(&g_sums[1][HID + C_DIM])));
            float mg = 0.f;
#pragma unroll
            for (int i = 0; i < 4; i++) {
                gx[i] = sqrtf(gx[i] * (HSCALE * HSCALE) + 1e-6f);
                part += gx[i];
                gx[i] *= __bfloat162float(gg[i]);
                mg = fmaxf(mg, fabsf(gx[i]));
            }
#pragma unroll
            for (int o = 16; o > 0; o >>= 1) part += __shfl_xor_sync(0xffffffffu, part, o);
            const uint32_t mgw = __reduce_max_sync(0xffffffffu, __float_as_uint(mg));
            const uint32_t mbw = __reduce_max_sync(0xffffffffu, __float_as_uint(fabsf(bias)));
            TSTAMP(1, 26);
            if (lane == 0) *reinterpret_cast<float4*>(s_red + warp * 4) = make_float4(part, __uint_as_float(mgw), __uint_as_float(mbw), 0.f);
            bar_sync(1, 384);
            float tot = 0.f, mb = 0.f;
#pragma unroll
            for (int i = 0; i < 12; i++) {
                const float4 t = *reinterpret_cast<const float4*>(s_red + i * 4);
                tot += t.x;
                mg = fmaxf(mg, t.y);
                mb = fmaxf(mb, t.z);
            }
            const float inv = 1.0f / (tot * (1.0f / HID) + 1e-6f);
            const uint32_t ej = min((__float_as_uint(fmaxf(fmaf(mg, inv, 1.0f) * HSCALE, mb * gs * 0x1p-13f)) >> 23) + 1, 250u);
            const float dn = __uint_as_float((254u - ej) << 23);
            up = min(ej + 127u - (__float_as_uint(gs) >> 23), 254u) * 0x00800080u;
            reinterpret_cast<uint16_t*>(smem + P2_OFF_BIAS + C_DIM * 2)[tid] = 0;
            *reinterpret_cast<__half*>(smem + P2_OFF_BIAS + (tid >> 5) * 64 + (tid & 6) * 8 + (tid & 24) / 2 + (tid & 1) * 2) = __float2half_rn(bias * gs * dn);
#pragma unroll
            for (int i = 0; i < 4; i++) {
                const int k = tid + 384 * i;
                *reinterpret_cast<__half*>(smem + P2_OFF_GRN + (k >> 4) * 32 + (k & 6) * 4 + (k & 8) / 2 + (k & 1) * 2) =
                    __float2half_rn(fmaf(gx[i], inv, 1.0f) * (HSCALE * dn));
            }
            TSTAMP(1, 25);
            bar_sync(1, 384);
        }
        TSTAMP(1, 28);
        if (wg == 1) {
            constexpr int N = sizeof(g_w2img[0]) / 16, PER = (N + NUM_CTAS - 1) / NUM_CTAS;
            uint4 v[5];
#pragma unroll
            for (int i = 0; i < 5; i++) v[i] = __ldcg(&g_w2img[0][min(blockIdx.x * PER + (tid & 127) + 128 * i, N - 1)]);
#pragma unroll
            for (int i = 0; i < 5; i++) {
                const int j = min(blockIdx.x * PER + (tid & 127) + 128 * i, N - 1);
                const uint32_t* t = reinterpret_cast<const uint32_t*>(smem + P2_OFF_GRN + (j / 768) * 32 + (j & 8) / 2);
                auto sc = [&](uint32_t u, int e) { return (h2_mul(u, t[2 * e]) + 0x00040004u) & 0xfff8fff8u; };
                g_w2img[1][j] = make_uint4(sc(v[i].x, 0), sc(v[i].y, 1), sc(v[i].z, 2), sc(v[i].w, 3));
            }
            asm volatile("fence.proxy.async.global;\n" ::: "memory");
            bar_sync(2, 128);
            if (tid == 128) asm volatile("fence.acq_rel.gpu;\nred.release.gpu.global.add.u32 [%0], 1;\n" ::"l"(&g_prog[1][0]) : "memory");
        }

        const int who = __shfl_sync(0xffffffffu, lane == 2 ? 0 : lane < 2 ? 1 : 2, lane);
        const uint32_t rel0 = who ? mapa(bar_bempty, lane & 1) : mapa(bar_aempty + wg * P2_NA * 8, rank), rel1 = rel0 + (who ? 0 : 32);
        auto publish = [&]() {
            asm volatile("fence.proxy.async.shared::cta;\n" ::: "memory");
            __syncwarp();
            if (who == 0) mbar_arrive(bar_oready + wg * 8);
        };
        bool ok_a, pend = false;
        uint32_t pa = 0, s_t;
        auto fetch = [&](int j, bool raw) {
            uint32_t o[6], u0[4], u1[4];
            uint2 t0 = make_uint2(0, 0), t1 = t0;
            if (raw) {
                asm volatile("ld.shared.v2.u32 {%0,%1}, [%2];\n" : "=r"(t0.x), "=r"(t0.y) : "r"(s_t + j * 64) : "memory");
                asm volatile("ld.shared.v2.u32 {%0,%1}, [%2];\n" : "=r"(t1.x), "=r"(t1.y) : "r"(s_t + j * 64 + 32) : "memory");
            }
            const bool ok_b = mbar_test(bar_bfull + (j & 3) * 8, j >> 2);
            if (j == 7) pa ^= 1;
            ok_a = mbar_test(af + ((j + 1) & 7) * 8, pa);
            asm volatile("ldmatrix.sync.aligned.m8n8.x4.trans.shared.b16 {%0,%1,%2,%3}, [%4];\n"
                         : "=r"(o[0]), "=r"(o[1]), "=r"(o[2]), "=r"(o[3]) : "r"(s_a + j * P2_A) : "memory");
            asm volatile("ldmatrix.sync.aligned.m8n8.x2.trans.shared.b16 {%0,%1}, [%2];\n"
                         : "=r"(o[4]), "=r"(o[5]) : "r"(s_a + j * P2_A + 2048) : "memory");
            p2_unpack(u0, o[0], o[1], o[2]);
            p2_unpack(u1, o[3], o[4], o[5]);
            if (raw) {
                u0[0] = h2_mul(u0[0], t0.x); u0[1] = h2_mul(u0[1], t0.x); u0[2] = h2_mul(u0[2], t0.y); u0[3] = h2_mul(u0[3], t0.y);
                u1[0] = h2_mul(u1[0], t1.x); u1[1] = h2_mul(u1[1], t1.x); u1[2] = h2_mul(u1[2], t1.y); u1[3] = h2_mul(u1[3], t1.y);
            }
            a[j & 1][0] = make_uint4(u0[0], u0[1], u0[2], u0[3]);
            a[j & 1][1] = make_uint4(u1[0], u1[1], u1[2], u1[3]);
            if (!ok_b) mbar_wait(bar_bfull + (j & 3) * 8, j >> 2);
        };
        auto table = [&](int pos) { s_t = sbase + P2_OFF_GRN + q * 8 + (k0 + pos) % 48 * 64; };
        const uint64_t db0 = make_desc(sbase, 128, 256);
        auto block8 = [&](bool raw, int pos, int thr0, int mode) {
#pragma unroll
            for (int j = 0; j < 8; j++) {
                const uint64_t db = db0 + (j & 3) * (P2_B / 16);
                if (j == 8 - P2_AH && mode == 1) bar_sync(4, 384);
                TR2(wg, pos + j, 0);
                wg_fence();
                mma_rs_n192(acc0, a[j & 1][0], db);
                mma_rs_n192(acc1, a[j & 1][0], db + 384);
                mma_rs_n192(acc0, a[j & 1][1], db + 768);
                mma_rs_n192(acc1, a[j & 1][1], db + 768 + 384);
                wg_commit();
                if (j == 7 && mode == 2) bar_arrive(4, 384);
                const uint32_t rel = ((j - 1) & 4 ? rel1 : rel0) + ((j - 1) & 3) * 8;
                TR2(wg, pos + j, 1);
                wg_wait<1>();
                TR2(wg, pos + j, 2);
                if (who < (j ? 2 : thr0)) mbar_arrive_cluster(rel);
                if (!ok_a) {
                    if (j == 0 && pend) { publish(); pend = false; }
                    mbar_wait(af + ((j + 1) & 7) * 8, pa);
                }
                TR2(wg, pos + j, 3);
                if (raw && j == 7) table(pos + 8);
                fetch((j + 1) & 7, raw && (j < 7 || pos + 8 < P2_RAW));
            }
        };
        int n = wg == 2 && half ? -1 : wg, pos = p2_start(n);
        uint32_t px = 0;
        wait_pos(pos);
        mbar_wait(af, 0);
        table(pos);
        fetch(0, pos < P2_RAW);
#pragma unroll 1
        for (;; n += 3) {
            TSTAMP(1, 2 + n);
            const int end = pos + (n < 0 ? 24 : 48);
#pragma unroll
            for (int i = 0; i < 48; i += 2) {
                asm volatile("mov.b64 {%0, %1}, 0;\n" : "=r"(acc0[i]), "=r"(acc0[i + 1]));
                asm volatile("mov.b64 {%0, %1}, 0;\n" : "=r"(acc1[i]), "=r"(acc1[i + 1]));
            }
            int thr = 1;
#pragma unroll 1
            for (; pos < P2_RAW; pos += 8, thr = 2) block8(true, pos, thr, 0);
#pragma unroll 1
            for (; pos < end; pos += 8, thr = 2) {
                const int e = pos + 8, r = e % 48;
                block8(false, pos, thr, e < 48 || e > 256 || (r != 0 && r != P2_S1 && r != P2_S2) ? 0 : e == end ? 2 : 1);
            }
            TR2(wg, pos - 1, 4);
            wg_wait<0>();
            TR2(wg, pos - 1, 5);
            if (who == 1) mbar_arrive_cluster(rel0 + 24);
            mbar_wait(bar_xfull + wg * 8, px);
            TR2(wg, pos - 1, 6);
            px ^= 1;
            __syncwarp();
            p2_epilogue(acc0, acc1, up, sx, sbase + P2_OFF_BIAS + q * 16 + (n < 0 && fin ? C_DIM * 2 : 0), zero);
            TR2(wg, pos - 1, 7);
            if (n + 3 >= P2_ITEMS) { publish(); break; }
            if (n < 0) {
                publish();
                pos = P2_S2;
                wait_pos(pos);
                mbar_wait(bar_bfull, 0);
            } else {
                pend = true;
                ok_a = false;
            }
        }
        TSTAMP(1, 29);
        cluster_sync();
        TSTAMP(1, 30);
    }
}

}

extern "C" void kernel_launch(void* const* d_in, const int* in_sizes, int n_in, void* d_out, int out_size) {
    const __nv_bfloat16* x = (const __nv_bfloat16*)d_in[0];
    const __nv_bfloat16* dw = (const __nv_bfloat16*)d_in[1];
    const __nv_bfloat16* w1 = (const __nv_bfloat16*)d_in[2];
    const __nv_bfloat16* w2 = (const __nv_bfloat16*)d_in[3];
    const __nv_bfloat16* grn_g = (const __nv_bfloat16*)d_in[4];
    const __nv_bfloat16* grn_b = (const __nv_bfloat16*)d_in[5];
    __nv_bfloat16* out = (__nv_bfloat16*)d_out;

    cudaFuncSetAttribute(pass1_kernel, cudaFuncAttributeMaxDynamicSharedMemorySize, P1_SMEM);
    cudaFuncSetAttribute(pass2_kernel, cudaFuncAttributeMaxDynamicSharedMemorySize, P2_SMEM);

    typedef CUresult (*EncodeFn)(CUtensorMap*, CUtensorMapDataType, cuuint32_t, void*, const cuuint64_t*, const cuuint64_t*,
                                 const cuuint32_t*, const cuuint32_t*, CUtensorMapInterleave, CUtensorMapSwizzle,
                                 CUtensorMapL2promotion, CUtensorMapFloatOOBfill);
    static EncodeFn encode = nullptr;
    if (!encode) {
        cudaDriverEntryPointQueryResult qres;
        cudaGetDriverEntryPoint("cuTensorMapEncodeTiled", (void**)&encode, cudaEnableDefault, &qres);
    }
    CUtensorMap wmap;
    const cuuint64_t gdim[2] = {HID, C_DIM};
    const cuuint64_t gstr[1] = {HID * 2};
    const cuuint32_t box[2] = {64, 192}, estr[2] = {1, 1};
    CUresult er = encode(&wmap, CU_TENSOR_MAP_DATA_TYPE_BFLOAT16, 2, (void*)w1, gdim, gstr, box, estr, CU_TENSOR_MAP_INTERLEAVE_NONE,
           CU_TENSOR_MAP_SWIZZLE_128B, CU_TENSOR_MAP_L2_PROMOTION_L2_128B, CU_TENSOR_MAP_FLOAT_OOB_FILL_NONE);
    if (er != CUDA_SUCCESS) printf("tensor map encode failed %d\n", (int)er);

    pass1_kernel<<<NUM_CTAS, 512, P1_SMEM>>>(wmap, x, dw, w2, grn_b, 0);

    cudaLaunchAttribute attr[1];
    attr[0].id = cudaLaunchAttributeProgrammaticStreamSerialization;
    attr[0].val.programmaticStreamSerializationAllowed = 1;
    cudaLaunchConfig_t cfg = {};
    cfg.gridDim = dim3(NUM_CTAS);
    cfg.stream = 0;
    cfg.attrs = attr;
    cfg.numAttrs = 1;
    cfg.blockDim = dim3(512);
    cfg.dynamicSmemBytes = P2_SMEM;
    cudaLaunchKernelEx(&cfg, pass2_kernel, x, grn_g, out, 0);
}
```

```cpp
#include <cuda.h>
#include <cuda_runtime.h>
#include <cuda_bf16.h>
#include <cuda_fp16.h>
#include <stdint.h>
#include <stdio.h>

namespace {

constexpr int M_TOTAL = 384 * 384;
constexpr int C_DIM   = 384;
constexpr int HID     = 1536;
constexpr int NT128   = M_TOTAL / 128;
constexpr int NUM_CTAS = 132;

constexpr int NGRP = 22, GRP_CTAS = 6;
constexpr int LN_STEP = NUM_CTAS / 4, LN_RING = 2 * LN_STEP;
constexpr int NT_RING = NT128 - NGRP;
constexpr int LN_TILE = 128 * C_DIM * 2;
constexpr int H_TILE = 64 * HID * 3 / 2;
constexpr int H_HALF = 3072, H_STEP = 6144;

__device__ __align__(1024) uint4 g_h[(size_t)M_TOTAL * HID * 3 / 32];
__device__ __align__(1024) uint4 g_ln[LN_RING * LN_TILE / 16];
__device__ __align__(1024) uint4 g_w2img[2][HID * C_DIM * 2 / 16];
__device__ __align__(16) float g_sums[2][HID + 512];
__device__ unsigned g_epoch;
__device__ __align__(128) unsigned g_prog[2][32];
__device__ __align__(128) unsigned g_half[32][2];
__device__ unsigned g_flag[LN_RING + 3][2][8];
#define TSTAMP(k, i)
#define TRACE(wg, pos, i)
#define TRACEW(pos, i)

#define TR2(wg, pos, i)
__host__ __device__ __forceinline__ int perm32(int n) {
    return (n & ~31) | (((n >> 1) & 3) << 3) | (((n >> 3) & 3) << 1) | (n & 1);
}

__device__ __forceinline__ uint32_t smem_u32(const void* p) { return (uint32_t)__cvta_generic_to_shared(p); }

__device__ __forceinline__ void mbar_init(uint32_t bar, uint32_t count) {
    asm volatile("mbarrier.init.shared::cta.b64 [%0], %1;\n" ::"r"(bar), "r"(count) : "memory");
}
__device__ __forceinline__ void mbar_expect_tx(uint32_t bar, uint32_t bytes) {
    asm volatile("mbarrier.arrive.expect_tx.shared::cta.b64 _, [%0], %1;\n" ::"r"(bar), "r"(bytes) : "memory");
}
__device__ __forceinline__ void mbar_arrive(uint32_t bar) {
    asm volatile("mbarrier.arrive.shared::cta.b64 _, [%0];\n" ::"r"(bar) : "memory");
}
__device__ __forceinline__ void mbar_arrive_cluster(uint32_t bar_cluster_addr) {
    asm volatile("mbarrier.arrive.shared::cluster.b64 _, [%0];\n" ::"r"(bar_cluster_addr) : "memory");
}
#define SAFE_BREAK
__device__ __forceinline__ void mbar_wait(uint32_t bar, uint32_t parity) {
    asm volatile(
        "{\n"
        ".reg .pred p;\n"
        "LAB_WAIT:\n"
        "mbarrier.try_wait.parity.shared::cta.b64 p, [%0], %1;\n"
        "@!p bra LAB_WAIT;\n"
        "}\n" ::"r"(bar), "r"(parity) : "memory");
}
__device__ __forceinline__ bool mbar_test(uint32_t bar, uint32_t parity) {
    uint32_t ok;
    asm volatile("{\n.reg .pred p;\n"
                 "mbarrier.test_wait.parity.shared::cta.b64 p, [%1], %2;\n"
                 "selp.u32 %0, 1, 0, p;\n}\n" : "=r"(ok) : "r"(bar), "r"(parity) : "memory");
    return ok != 0;
}
__device__ __forceinline__ uint32_t mapa(uint32_t addr, uint32_t rank) {
    uint32_t r;
    asm volatile("mapa.shared::cluster.u32 %0, %1, %2;\n" : "=r"(r) : "r"(addr), "r"(rank));
    return r;
}
__device__ __forceinline__ void bulk_g2s(uint32_t dst, const void* src, uint32_t bytes, uint32_t bar) {
    asm volatile("cp.async.bulk.shared::cluster.global.mbarrier::complete_tx::bytes [%0], [%1], %2, [%3];\n"
                 ::"r"(dst), "l"(src), "r"(bytes), "r"(bar) : "memory");
}
__device__ __forceinline__ void bulk_g2s_mc(uint32_t dst, const void* src, uint32_t bytes, uint32_t bar, uint16_t mask) {
    asm volatile("cp.async.bulk.shared::cluster.global.mbarrier::complete_tx::bytes.multicast::cluster [%0], [%1], %2, [%3], %4;\n"
                 ::"r"(dst), "l"(src), "r"(bytes), "r"(bar), "h"(mask) : "memory");
}
__device__ __forceinline__ void tma2(uint32_t dst, const CUtensorMap* map, int c0, int c1, uint32_t bar) {
    asm volatile("cp.async.bulk.tensor.2d.shared::cluster.global.tile.mbarrier::complete_tx::bytes [%0], [%1, {%2, %3}], [%4];\n"
                 ::"r"(dst), "l"(map), "r"(c0), "r"(c1), "r"(bar) : "memory");
}
template <bool ACQ>
__device__ __forceinline__ uint32_t flag_wait(const unsigned* p, unsigned target) {
    unsigned v, n = 0;
    do {
        if (ACQ) asm volatile("ld.acquire.gpu.global.u32 %0, [%1];\n" : "=r"(v) : "l"(p) : "memory");
        else asm volatile("ld.relaxed.gpu.global.u32 %0, [%1];\n" : "=r"(v) : "l"(p) : "memory");
        n++;
    } while (v < target);
    return n == 1;
}
__device__ __forceinline__ void ldsm4t(uint32_t (&r)[4], uint32_t addr) {
    asm volatile("ldmatrix.sync.aligned.m8n8.x4.trans.shared.b16 {%0,%1,%2,%3}, [%4];\n"
                 : "=r"(r[0]), "=r"(r[1]), "=r"(r[2]), "=r"(r[3]) : "r"(addr) : "memory");
}
__device__ __forceinline__ void bulk_s2g(void* dst, uint32_t src, uint32_t bytes) {
    asm volatile("cp.async.bulk.global.shared::cta.bulk_group [%0], [%1], %2;\n" ::"l"(dst), "r"(src), "r"(bytes) : "memory");
}
__device__ __forceinline__ void cluster_sync() {
    asm volatile("barrier.cluster.arrive.aligned;\nbarrier.cluster.wait.aligned;\n" ::: "memory");
}
__device__ __forceinline__ void cluster_sync_relaxed() {
    asm volatile("barrier.cluster.arrive.relaxed.aligned;\nbarrier.cluster.wait.aligned;\n" ::: "memory");
}
__device__ __forceinline__ void gdc_wait() { asm volatile("griddepcontrol.wait;\n" ::: "memory"); }
__device__ __forceinline__ void gdc_launch() { asm volatile("griddepcontrol.launch_dependents;\n" ::: "memory"); }
__device__ __forceinline__ uint32_t cluster_rank() {
    uint32_t r;
    asm volatile("mov.u32 %0, %%cluster_ctarank;\n" : "=r"(r));
    return r;
}
__device__ __forceinline__ bool elect_one() {
    uint32_t pred;
    asm volatile("{\n.reg .pred p;\nelect.sync _|p, 0xffffffff;\nselp.u32 %0, 1, 0, p;\n}\n" : "=r"(pred));
    return pred != 0;
}
__device__ __forceinline__ void wg_fence() { asm volatile("wgmma.fence.sync.aligned;\n" ::: "memory"); }
__device__ __forceinline__ void wg_commit() { asm volatile("wgmma.commit_group.sync.aligned;\n" ::: "memory"); }
template <int N> __device__ __forceinline__ void wg_wait() {
    asm volatile("wgmma.wait_group.sync.aligned %0;\n" ::"n"(N) : "memory");
}
template <int R> __device__ __forceinline__ void reg_inc() { asm volatile("setmaxnreg.inc.sync.aligned.u32 %0;\n" ::"n"(R)); }
template <int R> __device__ __forceinline__ void reg_dec() { asm volatile("setmaxnreg.dec.sync.aligned.u32 %0;\n" ::"n"(R)); }
__device__ __forceinline__ void bar_sync(int id, int n) { asm volatile("bar.sync %0, %1;\n" ::"r"(id), "r"(n) : "memory"); }
__device__ __forceinline__ void bar_arrive(int id, int n) { asm volatile("bar.arrive %0, %1;\n" ::"r"(id), "r"(n) : "memory"); }

__device__ __forceinline__ uint64_t make_desc(uint32_t saddr, uint32_t lbo, uint32_t sbo) {
    return (uint64_t)((saddr & 0x3FFFF) >> 4) | ((uint64_t)(lbo >> 4) << 16) | ((uint64_t)(sbo >> 4) << 32);
}

__device__ __forceinline__ void stg128_cs(void* p, uint32_t a, uint32_t b, uint32_t c, uint32_t d) {
    asm volatile("st.global.cs.v4.u32 [%0], {%1,%2,%3,%4};\n" ::"l"(p), "r"(a), "r"(b), "r"(c), "r"(d) : "memory");
}
__device__ __forceinline__ uint32_t pack_bf16(float lo, float hi) {
    uint32_t r;
    asm("cvt.rn.bf16x2.f32 %0, %1, %2;\n" : "=r"(r) : "f"(hi), "f"(lo));
    return r;
}
__device__ __forceinline__ float bf_lo(uint32_t v) { return __uint_as_float(v << 16); }
__device__ __forceinline__ float bf_hi(uint32_t v) { return __uint_as_float(v & 0xffff0000u); }
__device__ __forceinline__ uint32_t bf2_mul(uint32_t a, uint32_t b) {
    uint32_t r;
    asm("mul.rn.bf16x2 %0, %1, %2;\n" : "=r"(r) : "r"(a), "r"(b));
    return r;
}
__device__ __forceinline__ uint32_t bf2_fma(uint32_t a, uint32_t b, uint32_t c) {
    uint32_t r;
    asm("fma.rn.bf16x2 %0, %1, %2, %3;\n" : "=r"(r) : "r"(a), "r"(b), "r"(c));
    return r;
}
__device__ __forceinline__ uint32_t bf2_add(uint32_t a, uint32_t b) {
    uint32_t r;
    asm("add.rn.bf16x2 %0, %1, %2;\n" : "=r"(r) : "r"(a), "r"(b));
    return r;
}
__device__ __forceinline__ uint32_t h2_mul(uint32_t a, uint32_t b) {
    uint32_t r;
    asm("mul.rn.f16x2 %0, %1, %2;\n" : "=r"(r) : "r"(a), "r"(b));
    return r;
}
__device__ __forceinline__ uint32_t h2_fma(uint32_t a, uint32_t b, uint32_t c) {
    uint32_t r;
    asm("fma.rn.f16x2 %0, %1, %2, %3;\n" : "=r"(r) : "r"(a), "r"(b), "r"(c));
    return r;
}
__device__ __forceinline__ uint32_t h2_add(uint32_t a, uint32_t b) {
    uint32_t r;
    asm("add.rn.f16x2 %0, %1, %2;\n" : "=r"(r) : "r"(a), "r"(b));
    return r;
}
__device__ __forceinline__ uint32_t pack_f16(float lo, float hi) {
    uint32_t r;
    asm("cvt.rn.f16x2.f32 %0, %1, %2;\n" : "=r"(r) : "f"(hi), "f"(lo));
    return r;
}
__device__ __forceinline__ float h_lo(uint32_t v) { return __low2float(*reinterpret_cast<const __half2*>(&v)); }
__device__ __forceinline__ float h_hi(uint32_t v) { return __high2float(*reinterpret_cast<const __half2*>(&v)); }
__device__ __forceinline__ uint32_t bf2_to_h2(uint32_t v) { return (v & 0x7fff7fffu) * 7u + v; }
__device__ __forceinline__ uint32_t prmt(uint32_t a, uint32_t b, uint32_t sel) {
    uint32_t r;
    asm("prmt.b32 %0, %1, %2, %3;\n" : "=r"(r) : "r"(a), "r"(b), "r"(sel));
    return r;
}
__device__ __forceinline__ uint32_t bitsel(uint32_t a, uint32_t b, uint32_t m) {
    uint32_t r;
    asm("lop3.b32 %0, %1, %2, %3, 0xd8;\n" : "=r"(r) : "r"(a), "r"(b), "r"(m));
    return r;
}
constexpr float KAPPA = 0.3292034911525734f;
constexpr uint32_t GELU_C2 = 0x40d940d9u;
constexpr float HSCALE = 1.0f / (2.0f * KAPPA);
__device__ __forceinline__ float w2_scale(uint32_t m) { return __uint_as_float((257u - max(m >> 23, 16u)) << 23); }
__device__ __forceinline__ void sched_break(int zero) {
    asm volatile("{\n.reg .pred p;\nsetp.ne.s32 p, %0, 0;\nSB_LOOP:\n@p nanosleep.u32 1;\n@p bra SB_LOOP;\n}\n" ::"r"(zero));
}

#define ACC8(d, o) "+r"(d[o + 0]), "+r"(d[o + 1]), "+r"(d[o + 2]), "+r"(d[o + 3]), "+r"(d[o + 4]), "+r"(d[o + 5]), "+r"(d[o + 6]), "+r"(d[o + 7])

__device__ __forceinline__ void mma_rs_n128(uint32_t (&d)[32], const uint32_t (&a)[4], uint64_t desc, int scale_d) {
    asm volatile(
        "{\n.reg .pred p;\nsetp.ne.b32 p, %37, 0;\n"
        "wgmma.mma_async.sync.aligned.m64n128k16.f16.f16.f16 "
        "{%0,%1,%2,%3,%4,%5,%6,%7,%8,%9,%10,%11,%12,%13,%14,%15,"
        "%16,%17,%18,%19,%20,%21,%22,%23,%24,%25,%26,%27,%28,%29,%30,%31},"
        "{%32,%33,%34,%35}, %36, p, 1, 1, 0;\n}\n"
        : ACC8(d, 0), ACC8(d, 8), ACC8(d, 16), ACC8(d, 24)
        : "r"(a[0]), "r"(a[1]), "r"(a[2]), "r"(a[3]), "l"(desc), "r"(scale_d));
}

__device__ __forceinline__ void mma_ss_n128(uint32_t (&d)[32], uint64_t da, uint64_t db, int scale_d) {
    asm volatile(
        "{\n.reg .pred p;\nsetp.ne.b32 p, %34, 0;\n"
        "wgmma.mma_async.sync.aligned.m64n128k16.f16.f16.f16 "
        "{%0,%1,%2,%3,%4,%5,%6,%7,%8,%9,%10,%11,%12,%13,%14,%15,"
        "%16,%17,%18,%19,%20,%21,%22,%23,%24,%25,%26,%27,%28,%29,%30,%31},"
        "%32, %33, p, 1, 1, 1, 0;\n}\n"
        : ACC8(d, 0), ACC8(d, 8), ACC8(d, 16), ACC8(d, 24)
        : "l"(da), "l"(db), "r"(scale_d));
}

__device__ __forceinline__ void mma_rs_n192(uint32_t (&d)[48], const uint4& a, uint64_t db) {
    asm volatile(
        "wgmma.mma_async.sync.aligned.m64n192k16.f16.f16.f16 "
        "{%0,%1,%2,%3,%4,%5,%6,%7,%8,%9,%10,%11,%12,%13,%14,%15,"
        "%16,%17,%18,%19,%20,%21,%22,%23,%24,%25,%26,%27,%28,%29,%30,%31,"
        "%32,%33,%34,%35,%36,%37,%38,%39,%40,%41,%42,%43,%44,%45,%46,%47},"
        "{%48,%49,%50,%51}, %52, 1, 1, 1, 0;\n"
        : ACC8(d, 0), ACC8(d, 8), ACC8(d, 16), ACC8(d, 24), ACC8(d, 32), ACC8(d, 40)
        : "r"(a.x), "r"(a.y), "r"(a.z), "r"(a.w), "l"(db));
}

#define P1_WPF 30
#define P1_PACE 1
constexpr int P1_SLOT = LN_TILE / 6, P1_NST = 6;
constexpr int P1_W = 64 * C_DIM * 2;
constexpr int P1_X = 32 * C_DIM * 2;
constexpr int P1_OFF_W = LN_TILE;
constexpr int P1_OFF_X = P1_OFF_W + 2 * P1_W;
constexpr int P1_OFF_BAR = P1_OFF_X + P1_X;
constexpr int P1_OFF_TILE = P1_OFF_BAR + (2 * P1_NST + 2 + 4 + 4) * 8;
constexpr int P1_OFF_RAW = P1_OFF_TILE + 64;
constexpr int P1_OFF_EX = P1_OFF_RAW + 32;
constexpr int P1_SMEM = P1_OFF_EX + 256 * 4;

__device__ __forceinline__ float rsqrt_fast(float x) {
    float r;
    asm("rsqrt.approx.ftz.f32 %0, %1;\n" : "=f"(r) : "f"(x));
    return r;
}
__device__ __forceinline__ float row_sum(const uint32_t (&c)[4]) {
    const uint32_t u = bf2_add(bf2_add(c[0], c[1]), bf2_add(c[2], c[3]));
    float s = bf_lo(u) + bf_hi(u);
#pragma unroll
    for (int o = 1; o < 8; o <<= 1) s += __shfl_xor_sync(0xffffffffu, s, o);
    return s;
}
__device__ __forceinline__ uint32_t pace(uint32_t bar, uint32_t off, uint32_t val, uint32_t after, int zero) {
    asm volatile(
        "{\n.reg .pred p;\n.reg .b32 par;\n"
        "lop3.b32 par, %4, %2, %3, 0xea;\n"
        "mbarrier.test_wait.parity.shared::cta.b64 p, [%1], par;\n"
        "selp.u32 par, 1, 0, p;\n"
        "mbarrier.try_wait.parity.shared::cta.b64 p, [%1], par, 1000;\n"
        "@p or.b32 %0, %0, %2;\n"
        "}\n" : "+r"(val) : "r"(bar), "r"(zero), "r"(off), "r"(after));
    return val;
}
template <int PACE, int R>
__device__ __forceinline__ void ln_rows(uint32_t (&v)[R][6][4], const uint32_t (&d)[6][4], uint32_t bar, uint32_t off, int zero,
                                        uint32_t bar_read) {
    const float inv = 1.0f / C_DIM;
    uint32_t c[R][4], nm[R];
    float e[R], r[R], er[R];
    bool big = false;
#pragma unroll
    for (int p = 0; p < R; p++) {
#pragma unroll
        for (int i = 0; i < 6; i++)
#pragma unroll
            for (int k = 0; k < 4; k++) c[p][k] = bf2_fma(v[p][i][k], d[i][k], i ? c[p][k] : 0);
        const float m = row_sum(c[p]) * inv;
        nm[p] = pack_bf16(-m, -m);
        e[p] = m + bf_lo(nm[p]);
    }
    if (bar_read) mbar_arrive(bar_read + (nm[0] & zero));
    if (PACE & 1) nm[0] = pace(bar, off, nm[0], nm[0], zero);
#pragma unroll
    for (int p = 0; p < R; p++) {
#pragma unroll
        for (int i = 0; i < 6; i++) {
#pragma unroll
            for (int k = 0; k < 4; k++) {
                v[p][i][k] = bf2_fma(v[p][i][k], d[i][k], nm[p]);
                c[p][k] = i ? bf2_fma(v[p][i][k], v[p][i][k], c[p][k]) : bf2_mul(v[p][i][k], v[p][i][k]);
            }
        }
        r[p] = KAPPA * rsqrt_fast(fmaxf(fmaf(-e[p], e[p], row_sum(c[p]) * inv), 0.f) + 1e-5f);
        er[p] = -e[p] * r[p] * 0x1p-116f;
        big |= r[p] < 0x1p-8f;
    }
    if (__any_sync(0xffffffffu, big)) {
#pragma unroll
        for (int p = 0; p < R; p++) {
            const uint32_t p2 = __float_as_uint(r[p]) & 0x7f800000u;
            r[p] = __uint_as_float((__float_as_uint(r[p]) & 0x007fffffu) | 0x3f800000u);
#pragma unroll
            for (int i = 0; i < 6; i++)
#pragma unroll
                for (int k = 0; k < 4; k++) v[p][i][k] = bf2_mul(v[p][i][k], p2 | p2 >> 16);
        }
    }
#pragma unroll
    for (int p = 0; p < R; p++) {
        uint32_t rs = pack_bf16(r[p] * 0x1p-116f, r[p] * 0x1p-116f);
        const uint32_t sh = pack_bf16(er[p], er[p]);
        if (PACE & 2) rs = pace(bar, off, rs, sh, zero);
#pragma unroll
        for (int i = 0; i < 6; i++)
#pragma unroll
            for (int k = 0; k < 4; k++) v[p][i][k] = bf2_to_h2(bf2_fma(v[p][i][k], rs, sh));
    }
}

template <int R>
__device__ __forceinline__ uint32_t gelu2(uint32_t a, uint32_t sc2) {
    uint32_t y, t;
    if (R) asm("{\n.reg .b16 l, h;\n.reg .b32 f;\nmov.b32 {l, h}, %2;\nmov.b32 f, {h, h};\nmul.rn.f16x2 %0, %1, f;\n}\n" : "=r"(y) : "r"(a), "r"(sc2));
    else asm("{\n.reg .b16 l, h;\n.reg .b32 f;\nmov.b32 {l, h}, %2;\nmov.b32 f, {l, l};\nmul.rn.f16x2 %0, %1, f;\n}\n" : "=r"(y) : "r"(a), "r"(sc2));
    asm("tanh.approx.f16x2 %0, %1;\n" : "=r"(t) : "r"(h2_mul(y, h2_fma(y, y, GELU_C2))));
    return h2_fma(a, t, a);
}
constexpr uint32_t SPARE = 0x40074007u;

__device__ __forceinline__ uint32_t p1_parity(uint32_t sbase) {
    uint32_t v;
    asm volatile("ld.shared.u32 %0, [%1];\n" : "=r"(v) : "r"(sbase + P1_OFF_TILE - 4) : "memory");
    return v;
}
__device__ __forceinline__ uint32_t p1_exponents(float (&t)[2], uint32_t (&ex)[2], uint32_t saddr, int lane) {
#pragma unroll
    for (int r = 0; r < 2; r++) {
        t[r] += __shfl_xor_sync(0xffffffffu, t[r], 1);
        t[r] += __shfl_xor_sync(0xffffffffu, t[r], 2);
        ex[r] = min(max(((__float_as_uint(193.3f * t[r]) >> 23) + 127u) >> 1, 72u), 198u);
        asm volatile("st.shared.u32 [%0], %1;\n" ::"r"(saddr + r * 32), "r"(ex[r] << 23) : "memory");
    }
    return pack_f16(__uint_as_float(min(ex[0], 142u) << 23), __uint_as_float(min(ex[1], 142u) << 23));
}
template <int N>
__device__ __forceinline__ void p1_convert(uint32_t (*v)[4], const uint32_t (&ex)[2]) {
    if (__any_sync(0xffffffffu, max(ex[0], ex[1]) > 145u)) {
#pragma unroll
        for (int k = 0; k < 4 * N; k++) v[k >> 2][k & 3] = bf2_mul(v[k >> 2][k & 3], ex[k & 1] > 145u ? 0x1f801f80u : 0x3f803f80u);
    }
#pragma unroll
    for (int k = 0; k < 4 * N; k++) {
        const uint32_t u = bf2_mul(v[k >> 2][k & 3], ((ex[k & 1] > 145u ? 210u : 146u) - ex[k & 1]) * 0x00800080u);
        asm volatile("mad.lo.u32 %0, %1, 7, %2;\n" : "=r"(v[k >> 2][k & 3]) : "r"(u & 0x7fff7fffu), "r"(u));
    }
}
template <int N>
__device__ __forceinline__ void p1_squares(const uint32_t (&v)[N][4], float (&t)[2]) {
#pragma unroll
    for (int j = 0; j < N / 2; j++) {
        const int r = j & 1, b = (j >> 1) * 4;
        uint32_t c = bf2_mul(v[b][r], v[b][r]);
#pragma unroll
        for (int k = 1; k < 8; k++) c = bf2_fma(v[b + k / 2][r + (k & 1) * 2], v[b + k / 2][r + (k & 1) * 2], c);
        t[r] += bf_lo(c) + bf_hi(c);
    }
}
__device__ __forceinline__ void p1_epilogue(const uint32_t (&acc)[2][32], const uint32_t (&sc2)[2], float (&ssq)[4], uint8_t* hp, int zero) {
    uint32_t sq[2], h[16][4];
#pragma unroll
    for (int i2 = 0; i2 < 9; i2++) {
#pragma unroll
        for (int c = 2 * i2 - 2; c < 2 * i2; c++) {
            if (c >= 0 && (c & 3)) {
                uint32_t o[4];
#pragma unroll
                for (int u = 0; u < 4; u++) {
                    const uint32_t v = h[c & 12][u];
                    o[u] = bitsel(h[c][u], (c & 3) == 2 ? prmt(v, v, 0xa381) : prmt(v >> 3, v, (c & 3) == 1 ? 0x6240 : 0xf3d1), SPARE);
                }
                stg128_cs(hp + (c >> 3) * 2 * H_STEP + ((c >> 2) & 1) * H_HALF + ((c & 3) - 1) * 512, o[0], o[1], o[2], o[3]);
            }
        }
        if (i2 < 8) {
#pragma unroll
            for (int u = 0; u < 4; u++) {
                h[2 * i2][u] = gelu2<0>(acc[i2 >> 2][8 * (i2 & 3) + 2 * u], sc2[i2 >> 2]);
                h[2 * i2 + 1][u] = gelu2<1>(acc[i2 >> 2][8 * (i2 & 3) + 2 * u + 1], sc2[i2 >> 2]);
#pragma unroll
                for (int r = 0; r < 2; r++) {
                    const uint32_t v = h[2 * i2 + r][u];
                    sq[r] = ((i2 & 3) | u) ? h2_fma(v, v, sq[r]) : h2_mul(v, v);
                }
            }
            if ((i2 & 3) == 3) {
#pragma unroll
                for (int r = 0; r < 2; r++) ssq[(i2 >> 2) * 2 + r] += h_lo(sq[r]) + h_hi(sq[r]);
            }
            sched_break(zero);
        }
    }
}
template <int WG>
__device__ __forceinline__ void p1_mma(uint32_t (&acc)[2][32], const uint32_t (&a)[24][4], uint32_t sbase, uint32_t empty_remote, int i, int lane) {
    const uint32_t bar_full = sbase + P1_OFF_BAR;
    const uint64_t db = make_desc(sbase, 16, 1024) | (1ull << 62);
    const uint64_t da = db + (P1_OFF_W + WG * P1_W) / 16;
    if (WG == 0) mbar_wait(bar_full, i & 1);
    bar_sync(1 + WG, 256);
    TRACE(WG, i, 1);
    wg_fence();
#pragma unroll
    for (int k = 0; k < 24; k++) {
        if (WG == 0 && k && k % 4 == 0) mbar_wait(bar_full + (k >> 2) * 8, i & 1);
        mma_rs_n128(acc[0], a[k], db + (uint64_t)((k >> 2) * 1024 + (k & 3) * 2), k != 0);
        mma_ss_n128(acc[1], da + (uint64_t)(k * 128), db + (uint64_t)((k >> 2) * 1024 + (k & 3) * 2), k != 0);
        if (k == 23) bar_arrive(2 - WG, 256);
        if (k == 23 || (WG == 1 && k % 4 == 3)) wg_commit();
        if (WG == 1 && k % 4 == 3 && k > 3) {
            wg_wait<1>();
            if (lane < 2) mbar_arrive_cluster(empty_remote + ((k >> 2) - 1) * 8);
        }
    }
    TRACE(WG, i, 2);
    wg_wait<0>();
    if (WG == 1 && lane < 2) mbar_arrive_cluster(empty_remote + 5 * 8);
}
__device__ __forceinline__ void p1_consumer(const uint32_t (&a)[24][4], const uint32_t (&sc2)[2], uint32_t sbase, int WG, int w, int lane, int zero) {
    const uint32_t bar_full = sbase + P1_OFF_BAR, bar_empty = bar_full + P1_NST * 8;
    const uint32_t empty_remote = mapa(bar_empty, lane & 1);
    const uint32_t bar_pace = bar_empty + P1_NST * 8 + 16 + w * 8;
    const int g = lane >> 2, q = lane & 3, cb = (blockIdx.x % GRP_CTAS) * 4 + WG * 2;
    uint32_t acc[2][32];
    float ssq[4] = {0.f, 0.f, 0.f, 0.f};
    TSTAMP(0, 1);

    uint8_t* hp = reinterpret_cast<uint8_t*>(g_h) + (size_t)(blockIdx.x / GRP_CTAS) * (2 * H_TILE) + ((cb * 2 + (w >> 1)) * H_STEP + (w & 1) * 1536) + g * 64 + (q ^ (g >> 1)) * 16;
#pragma unroll 1
    for (int i = 0;; i++) {
        TRACE(WG, i, 0);
        if (WG == 0) p1_mma<0>(acc, a, sbase, empty_remote, i, lane);
        else p1_mma<1>(acc, a, sbase, empty_remote, i, lane);
        TRACE(WG, i, 4);
        uint32_t step, more;
        asm volatile("ld.shared.v2.u32 {%0, %1}, [%2];\n" : "=r"(step), "=r"(more) : "r"(sbase + P1_OFF_TILE + (i & 3) * 16) : "memory");
        hp += step;
        p1_epilogue(acc, sc2, ssq, hp, zero);
        if (lane == 0) mbar_arrive(bar_pace);
        if (!more) break;
    }
    TSTAMP(0, 21);
    if (WG == 0) bar_sync(1, 256);
#pragma unroll
    for (int r = 0; r < 4; r++) {
        const int ch = (r >> 1) * 64 + w * 16 + (r & 1) * 8 + g;
        ssq[r] += __shfl_xor_sync(0xffffffffu, ssq[r], 1);
        ssq[r] += __shfl_xor_sync(0xffffffffu, ssq[r], 2);
        float f;
        asm volatile("ld.shared.f32 %0, [%1];\n" : "=f"(f) : "r"(sbase + P1_OFF_EX + (WG * 128 + ch) * 4) : "memory");
        if (q == 0) atomicAdd(&g_sums[p1_parity(sbase)][cb * 64 + ch], ssq[r] * f * f);
    }
}

__global__ void __cluster_dims__(2, 1, 1) __launch_bounds__(512, 1)
pass1_kernel(const __grid_constant__ CUtensorMap wmap, const __nv_bfloat16* __restrict__ x, const __nv_bfloat16* __restrict__ dw,
             const __nv_bfloat16* __restrict__ w2, const __nv_bfloat16* __restrict__ grn_b, int zero) {
    extern __shared__ __align__(1024) uint8_t smem[];
    const uint32_t sbase = smem_u32(smem);
    const uint32_t bar_full = sbase + P1_OFF_BAR, bar_empty = bar_full + P1_NST * 8, bar_w = bar_empty + P1_NST * 8;
    const int tid = threadIdx.x;
    const int warp = __shfl_sync(0xffffffffu, tid >> 5, 0), lane = tid & 31;
    const uint32_t rank = cluster_rank();
    const int cig = blockIdx.x % GRP_CTAS;
    uint8_t* const ring = reinterpret_cast<uint8_t*>(g_ln);

    TSTAMP(0, 0);
    TRACEW(110 + warp, 0);
    const uint32_t bar_pace = bar_w + 16, bar_xfull = bar_pace + 32, bar_xempty = bar_xfull + 8, bar_done = bar_xfull + 16;
    const uint32_t bar_raw = sbase + P1_OFF_RAW;
    const int ln0 = blockIdx.x >> 2, first = blockIdx.x / GRP_CTAS;
    const uint8_t* xsrc = reinterpret_cast<const uint8_t*>(x) + (size_t)(NGRP * 4 + blockIdx.x) * P1_X;

    if (warp >= 12) {
        reg_dec<40>();
        asm volatile("barrier.cluster.arrive.relaxed.aligned;\n" ::: "memory");
        asm volatile("barrier.cluster.wait.aligned;\n" ::: "memory");
        if (warp == 12) {
            int prev = first - NGRP, t = first;
            const uint32_t rbase = mapa(sbase, lane & 1);
#pragma unroll 1
            for (int i = 1; t < NT_RING; i++) {
                const int round = t / LN_RING, slot = t - round * LN_RING;
                const uint8_t* src = ring + slot * LN_TILE + rank * (P1_SLOT / 2);
                int next = 0;
                if (rank == 0 && lane == 0) next = atomicAdd(&g_flag[LN_RING + (cig >> 1)][0][0], 1u);
                flag_wait<true>(&g_flag[slot][0][0], 4 * round + 4);
                TRACEW(i, 2);
                asm volatile("fence.proxy.async.global;\n" ::: "memory");
                next = NGRP + __shfl_sync(0xffffffffu, next, 0);
#pragma unroll 1
                for (int h = 0; h < P1_NST; h++) {
                    mbar_wait(bar_empty + h * 8, ~i & 1);
                    if (h == 0) TRACEW(i, 4);
                    if (h == 5) TRACEW(i, 5);
                    if (elect_one()) {
                        mbar_expect_tx(bar_full + h * 8, h ? P1_SLOT : P1_SLOT + 16);
                        bulk_g2s_mc(sbase + h * P1_SLOT + rank * (P1_SLOT / 2), src + h * P1_SLOT, P1_SLOT / 2, bar_full + h * 8, (uint16_t)3);
                    }
                    __syncwarp();
                    if (h == 0 && rank == 0 && lane < 2)
                        asm volatile("st.async.shared::cluster.mbarrier::complete_tx::bytes.v4.u32 [%0], {%1, %2, %3, %3}, [%4];\n"
                                     ::"r"(rbase + P1_OFF_TILE + (i & 3) * 16), "r"((t - prev) * (2 * H_TILE)), "r"((int)(next < NT_RING)), "r"(next),
                                       "r"(rbase + P1_OFF_BAR) : "memory");
                }
                prev = t;
                t = next;
                if (rank != 0) {
                    mbar_wait(bar_full, i & 1);
                    asm volatile("ld.shared.u32 %0, [%1];\n" : "=r"(t) : "r"(sbase + P1_OFF_TILE + (i & 3) * 16 + 8) : "memory");
                }
            }
        } else if (warp == 13) {
            int ph = 0;
            unsigned target = 0;
            mbar_wait(bar_raw, 0);
            if (elect_one()) {
                mbar_expect_tx(bar_xfull, P1_X);
                bulk_g2s(sbase + P1_OFF_X, xsrc, P1_X, bar_xfull);
                asm volatile("st.shared.u32 [%0], 1;\n" ::"r"(bar_done + 8) : "memory");
                mbar_arrive(bar_xfull);
            }
            __syncwarp();
#pragma unroll 1
            for (int i = ln0 + LN_STEP; i < NT_RING; i += LN_STEP, ph ^= 1) {
                target += ph * (GRP_CTAS / 2);
                xsrc += (size_t)NUM_CTAS * P1_X;
                mbar_wait(bar_xempty, ph);
                if (elect_one()) {
                    mbar_expect_tx(bar_xfull, P1_X);
                    bulk_g2s(sbase + P1_OFF_X, xsrc, P1_X, bar_xfull);
                }
                __syncwarp();
                const uint32_t off = flag_wait<false>(&g_flag[ln0 + (ph ^ 1) * LN_STEP][1][0], target);
                mbar_wait(bar_done, ph);
                if (elect_one()) {
                    asm volatile("st.shared.u32 [%0], %1;\n" ::"r"(bar_done + 8), "r"(off) : "memory");
                    mbar_arrive(bar_xfull);
                }
                __syncwarp();
            }
        } else if (warp == 15) {
            const uint32_t par = g_epoch & 1;
            asm volatile("st.shared.u32 [%0], %1;\n" ::"r"(sbase + P1_OFF_TILE - 4), "r"(par) : "memory");
            if (blockIdx.x < 16) reinterpret_cast<float4*>(g_sums[par ^ 1])[blockIdx.x * 32 + lane] = make_float4(0.f, 0.f, 0.f, 0.f);
            {
                bar_sync(4, 160);
                TRACEW(110 + warp, 1);
                mbar_wait(bar_raw + 8, 0);
                TRACEW(110 + warp, 2);
                const uint32_t o = lane * 16384 + rank * 8192, peer = mapa(sbase, rank ^ 1);
                if (lane < 6)
                    asm volatile("cp.async.bulk.shared::cluster.shared::cta.mbarrier::complete_tx::bytes [%0], [%1], 8192, [%2];\n"
                                 ::"r"(peer + o), "r"(sbase + o), "r"(peer + P1_OFF_BAR + lane * 8) : "memory");
                __syncwarp();
            }
            int t = -1;
#pragma unroll 1
            for (int i = 0; rank == 1 && t < NT_RING; i++) {
#pragma unroll 1
                for (int h = 0; h < P1_NST; h++) mbar_wait(bar_full + h * 8, i & 1);
                if (lane == 0 && t >= 0) asm volatile("red.relaxed.gpu.global.add.u32 [%0], 1;\n" ::"l"(&g_flag[t % LN_RING][1][0]) : "memory");
                asm volatile("ld.shared.u32 %0, [%1];\n" : "=r"(t) : "r"(sbase + P1_OFF_TILE + (i & 3) * 16 + 8) : "memory");
                if (lane == 0) mbar_arrive(bar_empty);
                TRACEW(i, 3);
            }
            if (rank == 0) {
                mbar_wait(bar_full, 0);
                TRACEW(110 + warp, 3);
                mbar_wait(bar_full, 1);
                float* sums = g_sums[par] + HID;
                unsigned* flag = reinterpret_cast<unsigned*>(sums + C_DIM);
                if (blockIdx.x == 0) reinterpret_cast<uint2*>(g_half)[lane] = make_uint2(0, 0);
                if (blockIdx.x == 2 && lane < 2) g_prog[lane][0] = 0;
                float gs = 0.f;
#pragma unroll 1
                for (int pass = 0; pass < 2; pass++) {
                    float mx = 0.f;
#pragma unroll 1
                    for (int it = first; it < 96; it += NGRP) {
                        const int nb = it % 12, k0 = (cig * 4 + it / 12) * 64 + (lane >> 2);
                        const uint32_t sc = mapa(sbase + P1_OFF_EX + (k0 & 255) * 4, it / 48);
                        uint32_t* dst = reinterpret_cast<uint32_t*>(g_w2img[0]) + (k0 >> 4) * 3072 + nb * 256 + lane;
                        float bs[8] = {};
#pragma unroll 2
                        for (int c = 0; c < 8; c++) {
                            const uint4 u = __ldg(reinterpret_cast<const uint4*>(w2 + (size_t)(k0 + c * 8) * C_DIM + nb * 32) + (lane & 3));
                            const float b = __bfloat162float(grn_b[k0 + c * 8]);
                            float t;
                            asm volatile("ld.shared::cluster.f32 %0, [%1];\n" : "=f"(t) : "r"(sc + c * 32) : "memory");
#pragma unroll
                            for (int j = 0; j < 4; j++) {
                                const uint32_t v = j == 0 ? u.x : j == 1 ? u.y : j == 2 ? u.z : u.w;
                                mx = fmaxf(mx, fmaxf(fabsf(bf_lo(v)), fabsf(bf_hi(v))) * t);
                                if (pass) {
                                    bs[2 * j] = fmaf(b, bf_lo(v), bs[2 * j]);
                                    bs[2 * j + 1] = fmaf(b, bf_hi(v), bs[2 * j + 1]);
                                    uint32_t h = pack_f16(bf_lo(v) * t * gs, bf_hi(v) * t * gs);
                                    asm volatile("movmatrix.sync.aligned.m8n8.trans.b16 %0, %0;\n" : "+r"(h));
                                    dst[(c >> 1) * 3072 + (c & 1) * 32 + j * 64] = h;
                                }
                            }
                        }
                        if (pass) {
#pragma unroll
                            for (int j = 0; j < 8; j++) {
#pragma unroll
                                for (int o = 4; o < 32; o <<= 1) bs[j] += __shfl_xor_sync(0xffffffffu, bs[j], o);
                                if (lane >> 2 == j) atomicAdd(&sums[nb * 32 + (j >> 1) * 8 + (lane & 3) * 2 + (j & 1)], bs[j]);
                            }
                        }
                    }
                    if (!pass) {
                        const uint32_t m = __reduce_max_sync(0xffffffffu, __float_as_uint(mx));
                        if (lane == 0) {
                            atomicMax(flag, m);
                            asm volatile("red.release.gpu.global.add.u32 [%0], 1;\n" ::"l"(flag + 32) : "memory");
                        }
                        flag_wait<true>(flag + 32, NUM_CTAS / 2);
                        gs = w2_scale(__ldcg(flag));
                    }
                }
                do {
                    __nanosleep(1000);
                    asm volatile("ld.volatile.shared.u32 %0, [%1];\n" : "=r"(t) : "r"(sbase + P1_OFF_TILE + (lane & 3) * 16 + 8) : "memory");
                    SAFE_BREAK;
                } while (__all_sync(0xffffffffu, t < NT_RING - P1_WPF));
                if (lane == 0 && blockIdx.x < 128)
                    asm volatile("cp.async.bulk.prefetch.L2.global [%0], %1;\n" ::"l"(g_w2img[0] + blockIdx.x * 576), "r"(18432) : "memory");
            }
        } else if (warp == 14) {
            int ph = 0;
#pragma unroll 1
            for (int i = ln0; i < NT_RING; i += LN_STEP, ph ^= 1) {
                mbar_wait(bar_done, ph);
                TRACEW(i / LN_STEP, 0);
                asm volatile("fence.proxy.async.global;\n" ::: "memory");
                if (elect_one()) asm volatile("red.release.gpu.global.add.u32 [%0], 1;\n" ::"l"(&g_flag[ln0 + ph * LN_STEP][0][0]) : "memory");
                __syncwarp();
                TRACEW(i / LN_STEP, 1);
            }
        }
        __syncwarp();
        cluster_sync();
    } else if (warp >= 8) {
        reg_dec<88>();
        asm volatile("barrier.cluster.arrive.relaxed.aligned;\n" ::: "memory");
        {
            const int l8 = lane & 7, row = (warp - 8) * 4 + (lane >> 3), px = (blockIdx.x & 3) * 32 + row;
            uint32_t d[6][4];
#pragma unroll
            for (int j = 0; j < 6; j++) {
                const uint4 t = reinterpret_cast<const uint4*>(dw)[j * 8 + l8];
                d[j][0] = t.x; d[j][1] = t.y; d[j][2] = t.z; d[j][3] = t.w;
            }
            const int n = (px & 64) + perm32(2 * row + ((px >> 5) & 1));
            uint8_t* const dst0 = ring + ln0 * LN_TILE + n * 128 + ((l8 ^ (n & 7)) << 4);
            const uint32_t src = sbase + P1_OFF_X + ((warp - 8) * 8 + (lane >> 3)) * (C_DIM * 2) + l8 * 16;
            int ph = 0;
            asm volatile("barrier.cluster.wait.aligned;\n" ::: "memory");
#pragma unroll 1
            for (int i = ln0; i < NT_RING; i += LN_STEP, ph ^= 1) {
                TRACE(2, i / LN_STEP, 0);
                mbar_wait(bar_xfull, ph);
                uint32_t off;
                asm volatile("ld.shared.u32 %0, [%1];\n" : "=r"(off) : "r"(bar_done + 8) : "memory");
                TRACE(2, i / LN_STEP, 1);
#pragma unroll 1
                for (int ps = 0; ps < 2; ps++) {
                    uint32_t v1[1][6][4];
                    uint32_t (&v)[6][4] = v1[0];
#pragma unroll
                    for (int j = 0; j < 6; j++)
                        asm volatile("ld.shared.v4.u32 {%0,%1,%2,%3}, [%4];\n"
                                     : "=r"(v[j][0]), "=r"(v[j][1]), "=r"(v[j][2]), "=r"(v[j][3]) : "r"(src + ps * (4 * C_DIM * 2) + j * 128) : "memory");
                    ln_rows<P1_PACE, 1>(v1, d, bar_pace + (warp - 8) * 8, off, zero, ps == 1 && lane == 0 ? bar_xempty : 0);
                    uint8_t* dst = dst0 + ph * (LN_STEP * LN_TILE) + ps * 4096;
#pragma unroll
                    for (int j = 0; j < 6; j++) *reinterpret_cast<uint4*>(dst + j * 16384) = make_uint4(v[j][0], v[j][1], v[j][2], v[j][3]);
                    TRACE(2, i / LN_STEP, 3 + ps);
                }
                asm volatile("fence.proxy.async.global;\nfence.acq_rel.cta;\n" ::: "memory");
                __syncwarp();
                if (lane == 0) mbar_arrive(bar_done);
                TRACE(2, i / LN_STEP, 5);
                TRACE(2, i / LN_STEP, 2);
            }
        }
        __syncwarp();
        cluster_sync();
    } else {
        const int wg = warp >> 2, w = warp & 3;
        auto load_w = [&](int i, int ch) {
            mbar_expect_tx(bar_w + i * 8, P1_W);
#pragma unroll 1
            for (int h = 0; h < 2; h++) tma2(sbase + P1_OFF_W + i * P1_W + h * (P1_W / 2), &wmap, cig * 256 + i * 128 + ch, h * 192, bar_w + i * 8);
        };
        uint32_t d[6][4];
        if (wg == 1) {
#pragma unroll
            for (int j = 0; j < 6; j++)
                asm volatile("ld.global.nc.v4.u32 {%0,%1,%2,%3}, [%4];\n" : "=r"(d[j][0]), "=r"(d[j][1]), "=r"(d[j][2]), "=r"(d[j][3])
                             : "l"(reinterpret_cast<const uint4*>(dw) + j * 8 + (lane & 7)) : "memory");
        }
        if (warp == 0 && elect_one()) {
            mbar_init(bar_raw, 1);
            mbar_init(bar_w, 1);
            mbar_init(bar_w + 8, 1);
            asm volatile("fence.mbarrier_init.release.cluster;\n" ::: "memory");
            mbar_expect_tx(bar_raw, LN_TILE / 2);
#pragma unroll 1
            for (int i = 0; i < 6; i++)
                bulk_g2s(sbase + i * 16384 + (rank ^ 1) * 8192, x + (size_t)(first * 128 + rank * 64) * C_DIM + i * 4096, 8192, bar_raw);
#pragma unroll 1
            for (int i = 0; i < 2; i++) load_w(i, 0);
            if (first < 4)
                asm volatile("cp.async.bulk.prefetch.tensor.2d.L2.global.tile [%0, {%1, %2}];\n"
                             ::"l"(&wmap), "r"(cig * 256 + (first >> 1) * 128 + 64), "r"((first & 1) * 192) : "memory");
        }
        if (warp == 1 && elect_one()) {
#pragma unroll 1
            for (int i = 0; i < P1_NST; i++) {
                mbar_init(bar_full + i * 8, 1);
                mbar_init(bar_empty + i * 8, i ? 8 : 8 + rank);
                mbar_init(bar_pace + i * 8, i < 4 ? 1 : 2 * i - 6);
                mbar_expect_tx(bar_full + i * 8, P1_SLOT / 2);
            }
            mbar_init(bar_done, 4);
            mbar_init(bar_raw + 8, 4);
            asm volatile("st.shared.v4.u32 [%0], {0, 1, %1, %1};\n" ::"r"(sbase + P1_OFF_TILE), "r"(first) : "memory");
            asm volatile("fence.mbarrier_init.release.cluster;\n" ::: "memory");
        }
        __syncwarp();
        asm volatile("barrier.cluster.arrive.relaxed.aligned;\n" ::: "memory");
        reg_inc<192>();
        TRACEW(110 + warp, 1);
        uint32_t a[24][4];
        gdc_launch();
        asm volatile("barrier.cluster.wait.aligned;\n" ::: "memory");
        if (wg == 1) {
#pragma unroll 1
            for (int it = -1; it < 4; it++) {
                const int n = (it & 1) * 32 + w * 8 + (it & 2) * 2 + (lane >> 3), px = (n & 1) * 32 + (n >> 5) * 4 + ((n >> 1) & 3) * 8 + ((n >> 3) & 3);
                if (it == 0) mbar_wait(bar_raw, 0);
                TRACEW(110 + warp, 2 + (it == 0));
                uint32_t v[1][6][4];
#pragma unroll
                for (int j = 0; j < 6; j++) {
                    const uint32_t o = px * (C_DIM * 2) + j * 128;
                    asm volatile("ld.shared.v4.u32 {%0,%1,%2,%3}, [%4];\n" : "=r"(v[0][j][0]), "=r"(v[0][j][1]), "=r"(v[0][j][2]), "=r"(v[0][j][3])
                                 : "r"(sbase + (rank ^ 1) * 8192 + (lane & 7) * 16 + o + (o & ~8191u)) : "memory");
                }
                ln_rows<0, 1>(v, d, 0, 0, zero, 0);
                const uint32_t p = sbase + (rank * 64 + n) * 128 + (((lane ^ n) & 7) << 4);
#pragma unroll
                for (int j = 0; j < 6; j++)
                    asm volatile("st.shared.v4.u32 [%4], {%0,%1,%2,%3};\n"
                                 ::"r"(v[0][j][0]), "r"(v[0][j][1]), "r"(v[0][j][2]), "r"(v[0][j][3]), "r"(p + j * 16384) : "memory");
            }
            asm volatile("fence.proxy.async.shared::cta;\n" ::: "memory");
            __syncwarp();
            if (lane == 0) mbar_arrive_cluster(mapa(bar_raw + 8, rank ^ 1));
            bar_arrive(4, 160);
            bar_arrive(1, 256);
            TRACEW(110 + warp, 4);
        }
        const uint32_t src = sbase + P1_OFF_W + wg * P1_W + ((lane >> 4) * 8 + (lane & 7)) * 128 + (((2 * w + ((lane >> 3) & 1)) ^ (lane & 7)) << 4);
        const uint32_t s_ex = sbase + P1_OFF_EX + (wg * 128 + w * 16 + (lane >> 2)) * 4;
        uint32_t sc2[2], ex[2];
#pragma unroll 1
        for (int it = wg; it < 2; it++) {
            float t[2] = {0.f, 0.f};
            if (it) mbar_wait(bar_w + wg * 8, 0);
            TRACEW(110 + warp, 5);
#pragma unroll
            for (int k = 0; k < 24; k++) ldsm4t(a[k], src + k * 2048);
            bar_sync(6 + wg, 128);
            if (it && w == 0 && elect_one()) load_w(wg, 64);
            __syncwarp();
            TRACEW(110 + warp, 6);
            p1_squares(a, t);
            sc2[0] = p1_exponents(t, ex, s_ex, lane);
            p1_convert<24>(a, ex);
        }
#pragma unroll 1
        for (int it = wg; it < 2; it++) {
            float t[2] = {0.f, 0.f};
            TRACEW(100 + warp, 0);
            if (it) mbar_wait(bar_w + wg * 8, 1);
            TRACEW(100 + warp, 1);
            uint32_t v[8][4];
#pragma unroll 1
            for (int j = 0; j <= 2 * it; j++) {
#pragma unroll
                for (int k = 0; k < 8; k++) ldsm4t(v[k], src + (8 * j + k) * 2048);
                p1_squares(v, t);
            }
            sc2[1] = p1_exponents(t, ex, s_ex + 256, lane);
#pragma unroll 1
            for (int j = 2 * it; j >= 0; j--) {
                p1_convert<8>(v, ex);
#pragma unroll
                for (int k = 0; k < 8; k++) {
                    if (it) asm volatile("stmatrix.sync.aligned.m8n8.x4.trans.shared.b16 [%0], {%1,%2,%3,%4};\n"
                                         ::"r"(src + (8 * j + k) * 2048), "r"(v[k][0]), "r"(v[k][1]), "r"(v[k][2]), "r"(v[k][3]) : "memory");
                    if (j) ldsm4t(v[k], src + (8 * j - 8 + k) * 2048);
                }
            }
        }
        asm volatile("fence.proxy.async.shared::cta;\n" ::: "memory");
        TRACEW(110 + warp, 7);
        bar_sync(6 + wg, 128);
        p1_consumer(a, sc2, sbase, wg, w, lane, zero);
        cluster_sync();
        TSTAMP(0, 30);
    }
}

constexpr int P2_B = 24576, P2_NB = 4;
constexpr int P2_A = 3072, P2_NA = 8;
constexpr int P2_XROW = C_DIM * 2;
constexpr int P2_OFF_A = P2_B * P2_NB;
constexpr int P2_OFF_X = P2_OFF_A + 3 * P2_NA * P2_A;
constexpr int P2_XHALF = 32 * P2_XROW + 64;
constexpr int P2_OFF_GRN = P2_OFF_X + 64 * P2_XROW + 128;
constexpr int P2_OFF_BIAS = P2_OFF_GRN + HID * 2;
constexpr int P2_OFF_RED = P2_OFF_BIAS + C_DIM * 4;
constexpr int P2_OFF_BAR = P2_OFF_RED + 192;
constexpr int P2_SMEM = P2_OFF_BAR + (2 * P2_NB + 6 * P2_NA + 7) * 8;
#define P2_S1 16
constexpr int P2_S2 = 32;
constexpr int P2_NCL = NUM_CTAS / 2, P2_ITEMS = NT128 / P2_NCL, P2_SHARED = NT128 - P2_ITEMS * P2_NCL;
constexpr int P2_NPOS = 6 * 48 + P2_S1;
constexpr int P2_RAW = 24;
constexpr int P2_XC = 8 * P2_XROW;
#define P2_T0 4
#define P2_SLACK 0
#define P2_RAMP 2
#define P2_AH 2
__device__ __forceinline__ int p2_start(int n) { return n < 0 ? 0 : n / 3 * 48 + (n % 3 == 1 ? P2_S1 : n % 3 * (P2_S2 / 2)); }
__device__ __forceinline__ int p2_tile(int cl, int n) {
    return n == 0 ? NT128 - 1 - cl : n < 0 ? NT128 - 1 - P2_NCL - (cl >> 1) : cl + P2_NCL * (n - 1);
}

#define P2_EB 2
#define P2_EX 1
__device__ __forceinline__ void p2_epilogue(uint32_t (&acc0)[48], uint32_t (&acc1)[48], uint32_t up, uint32_t sx, uint32_t sb, int zero) {
    uint32_t v[12][3][4];
    auto load = [&](int t, int j) {
        if (t >= 12) return;
        uint32_t (&w)[4] = v[t][j];
        asm volatile("ld.shared.v4.u32 {%0,%1,%2,%3}, [%4];\n" : "=r"(w[0]), "=r"(w[1]), "=r"(w[2]), "=r"(w[3])
                     : "r"((j ? sx + (j - 1) * 4 * P2_XROW : sb) + t * 64) : "memory");
    };
    auto store = [&](int t, int r) {
        const uint32_t* w = (t < 6 ? acc0 : acc1) + 8 * (t % 6) + 4 * r;
        asm volatile("st.shared.v4.u32 [%4], {%0,%1,%2,%3};\n" ::"r"(w[0]), "r"(w[1]), "r"(w[2]), "r"(w[3]), "r"(sx + t * 64 + r * 4 * P2_XROW) : "memory");
    };
#pragma unroll
    for (int t = 0; t < P2_EB; t++) load(t, 0);
#pragma unroll
    for (int t = 0; t < 2 * P2_EX; t++) load(t >> 1, 1 + (t & 1));
#pragma unroll
    for (int t = 0; t < 12; t++) {
        load(t + P2_EX, 1);
        load(t + P2_EX, 2);
        load(t + P2_EB, 0);
        uint32_t* acc = (t < 6 ? acc0 : acc1) + 8 * (t % 6);
        uint32_t y[8];
#pragma unroll
        for (int e = 0; e < 8; e++) {
            y[e] = h2_add(acc[e], v[t][0][e >> 1]);
            y[e] = pack_bf16(h_lo(y[e]), h_hi(y[e]));
        }
#pragma unroll
        for (int e = 0; e < 8; e++) acc[(e & 1) * 4 + (e >> 1)] = bf2_fma(y[e], up, v[t][1 + (e & 1)][e >> 1]);
        store(t, 0);
        store(t, 1);
        sched_break(zero);
    }
    if (zero) {
#pragma unroll
        for (int t = 0; t < 24; t++) store(t >> 1, t & 1);
    }
}

__device__ __forceinline__ void p2_unpack(uint32_t (&u)[4], uint32_t o1, uint32_t o2, uint32_t o3) {
    u[2] = bitsel(o1, 0x00040004u, SPARE);
    u[1] = bitsel(o2, 0x00040004u, SPARE);
    u[3] = bitsel(o3, 0x00040004u, SPARE);
    const uint32_t t = bitsel(prmt(o1, o2, 0x6341), prmt(o1, o3, 0x6240) << 3, 0x38383838u);
    u[0] = bitsel(bitsel(t, prmt(o2, o3, 0x7351) << 1, 0x80808080u), 0x00040004u, SPARE);
}

__global__ void __cluster_dims__(2, 1, 1) __launch_bounds__(512, 1)
pass2_kernel(const __nv_bfloat16* __restrict__ x, const __nv_bfloat16* __restrict__ grn_g, __nv_bfloat16* __restrict__ out, int zero) {
    extern __shared__ __align__(1024) uint8_t smem[];
    const uint32_t sbase = smem_u32(smem);
    const uint32_t bar_bfull = sbase + P2_OFF_BAR, bar_bempty = bar_bfull + P2_NB * 8;
    const uint32_t bar_afull = bar_bempty + P2_NB * 8, bar_aempty = bar_afull + 3 * P2_NA * 8;
    const uint32_t bar_xfull = bar_aempty + 3 * P2_NA * 8, bar_oready = bar_xfull + 24, s_pos = bar_oready + 24;
    int tid;
    asm volatile("mov.u32 %0, %%tid.x;\n" : "=r"(tid));
    const int warp = __shfl_sync(0xffffffffu, tid >> 5, 0), lane = tid & 31;
    const uint32_t rank = cluster_rank();
    const int cl = blockIdx.x >> 1, pair = cl >> 1;
    const int half = pair < P2_SHARED, fin = half && (cl & 1);
    const int k0 = (pair + 3 * (cl & 1)) % 6 * 8;
    auto wait_pos = [&](int target) {
        int v;
        while (true) {
            asm volatile("ld.volatile.shared.u32 %0, [%1];\n" : "=r"(v) : "r"(s_pos) : "memory");
            if (v >= target) break;
            SAFE_BREAK;
            __nanosleep(100);
        }
    };

    TSTAMP(1, 0);
    if (tid == 384) {
        for (int i = 0; i < P2_NB; i++) {
            mbar_init(bar_bfull + i * 8, 1);
            mbar_init(bar_bempty + i * 8, 24);
        }
        for (int i = 0; i < 3 * P2_NA; i++) {
            mbar_init(bar_afull + i * 8, 1);
            mbar_init(bar_aempty + i * 8, 4);
        }
        for (int i = 0; i < 3; i++) {
            mbar_init(bar_xfull + i * 8, 2);
            mbar_init(bar_oready + i * 8, 4);
        }
        asm volatile("st.shared.u32 [%0], 0;\n" ::"r"(s_pos) : "memory");
        asm volatile("fence.mbarrier_init.release.cluster;\n" ::: "memory");
    }
    __syncthreads();
    cluster_sync_relaxed();

    if (warp >= 12) {
        reg_dec<32>();
        if (warp == 12) {
            const uint8_t* wsrc = reinterpret_cast<const uint8_t*>(g_w2img) + rank * (P2_B / 2);
            int kb = k0;
            gdc_wait();
#pragma unroll 1
            for (int p = 0; p < P2_NPOS; p++) {
                const int st = p & 3;
                if (p == P2_RAW) {
                    flag_wait<true>(&g_prog[1][0], NUM_CTAS);
                    asm volatile("fence.proxy.async.global;\n" ::: "memory");
                    wsrc += sizeof(g_w2img[0]);
                }
                const int idle = (p < P2_S1 || p >= 6 * 48) + (p < P2_S2 ? !half || p >= 24 : p >= 5 * 48 + P2_S2);
                mbar_wait(bar_bempty + st * 8, (~p >> 2) & 1);
                TR2(3, p, 0);
                if (elect_one()) {
                    const int len = P2_B / 2;
                    mbar_expect_tx(bar_bfull + st * 8, 2 * len);
                    bulk_g2s_mc(sbase + st * P2_B + rank * (P2_B / 2), wsrc + kb * P2_B, len, bar_bfull + st * 8, (uint16_t)3);
                    asm volatile("st.volatile.shared.u32 [%0], %1;\n" ::"r"(s_pos), "r"(p) : "memory");
                    if (rank == 0) asm volatile("red.relaxed.gpu.global.add.u32 [%0], 1;\n" ::"l"(&g_prog[0][0]) : "memory");
                    if (idle) asm volatile("mbarrier.arrive.shared::cta.b64 _, [%0], %1;\n" ::"r"(bar_bempty + st * 8), "r"(8 * idle) : "memory");
                }
                __syncwarp();
                if (++kb == 48) kb = 0;
            }
            mbar_wait(bar_bempty, 1);
            if (lane == 0) mbar_arrive(bar_bfull);
        } else if (warp == 13) {
            const int w = lane < 3 ? lane : 0;
            const uint32_t dst0 = sbase + P2_OFF_A + w * P2_NA * P2_A;
            const uint32_t bf = bar_afull + w * P2_NA * 8, be = bar_aempty + w * P2_NA * 8;
            int n = (w == 2 && half ? -1 : w) - 3, left = 0, u = 0, c = 0;
            const uint8_t* src = nullptr;
            bool act = lane < 3;
            gdc_wait();
            while (__any_sync(0xffffffffu, act)) {
                if (left == 0) {
                    n += 3;
                    left = n >= P2_ITEMS ? -1 : n < 0 ? 24 : 48;
                    u = (k0 + p2_start(n)) % 48;
                    src = reinterpret_cast<const uint8_t*>(g_h) + (size_t)p2_tile(cl, n) * (2 * H_TILE) + rank * H_HALF + u * H_STEP;
                }
                bool ok = act && mbar_test(be + ((c - 1) & 7) * 8, (~c >> 3) & 1);
                if (__any_sync(0xffffffffu, act && c < 16)) {
                    int v;
                    asm volatile("ld.volatile.shared.u32 %0, [%1];\n" : "=r"(v) : "r"(s_pos) : "memory");
                    ok = ok && c <= (n <= 0 ? 2 * v - P2_RAMP : c >= 16 ? c : v - p2_start(n) + 8);
                }
                if (ok) {
                    const int st = c & 7;
                    if (left > 0) {
                        mbar_expect_tx(bf + st * 8, P2_A);
                        bulk_g2s(dst0 + st * P2_A, src, P2_A, bf + st * 8);
                    } else {
                        mbar_arrive(bf + st * 8);
                        act = false;
                    }
                    src += H_STEP;
                    if (++u == 48) { u = 0; src -= 48 * H_STEP; }
                    c++;
                    left--;
                }
                SAFE_BREAK;
                if (!__any_sync(0xffffffffu, ok)) __nanosleep(100);
            }
        } else if (warp == 14) {
            const uint32_t sx = sbase + P2_OFF_X;
            size_t o = 0;
            int wp = 0;
            uint32_t par = 0;
            if (fin) {
#pragma unroll 1
                for (int c = lane * 16; c < 64 * P2_XROW + 128; c += 512) asm volatile("st.shared.v4.u32 [%0], {0, 0, 0, 0};\n" ::"r"(sx + c) : "memory");
                __syncwarp();
            }
#pragma unroll 1
            for (int n = -half; n <= P2_ITEMS; n++) {
                const int w = (n + 3) % 3, end = p2_start(n) + 48;
                const size_t on = (size_t)(2 * p2_tile(cl, n) + rank) * (64 * C_DIM * 2);
                const uint32_t xf = bar_xfull + w * 8;
                bool st = n + half > 0;
                const bool ld = n < P2_ITEMS && !(n < 0 && fin);
                if (n == P2_ITEMS - 1 && lane == 0)
                    asm volatile("cp.async.bulk.prefetch.L2.global [%0], %1;\n" ::"l"(reinterpret_cast<const uint8_t*>(x) + on), "r"(64 * P2_XROW) : "memory");
                if (st) {
                    mbar_wait(bar_oready + wp * 8, (par >> wp) & 1);
                    par ^= 1u << wp;
                }
                if (lane == 0) {
                    if (n < P2_ITEMS) mbar_expect_tx(xf, ld ? 64 * C_DIM * 2 : 0);
                    const int t0 = (n ? p2_start(n - 1) + 48 : P2_S2) + P2_T0, dt = end - t0;
                    int t = st && n < P2_ITEMS - 1 ? 16 * t0 : -4096;
                    if ((n == 0 && half) || n >= P2_ITEMS - 1) {
                        if (fin && n == 0) {
                            flag_wait<true>(&g_half[pair][rank], 1);
                            asm volatile("fence.proxy.async.global;\n" ::: "memory");
                        }
#pragma unroll 1
                        for (int c = 0; c < 2; c++) {
                            uint8_t* dst = reinterpret_cast<uint8_t*>(out) + o + c * 32 * P2_XROW;
                            if (!fin || n) bulk_s2g(dst, sx + c * P2_XHALF, 32 * P2_XROW);
                            else asm volatile("cp.reduce.async.bulk.global.shared::cta.bulk_group.add.noftz.bf16 [%0], [%1], %2;\n"
                                              ::"l"(dst), "r"(sx + c * P2_XHALF), "r"(32 * P2_XROW) : "memory");
                        }
                        asm volatile("cp.async.bulk.commit_group;\n" ::: "memory");
                        if (!fin && n == 0) {
                            asm volatile("cp.async.bulk.wait_group 0;\nfence.proxy.async.global;\n" ::: "memory");
                            asm volatile("st.release.gpu.global.u32 [%0], 1;\n" ::"l"(&g_half[pair][rank]) : "memory");
                        }
                        st = false;
                    }
#pragma unroll 1
                    for (int c = 0; c < 64 * P2_XROW; c += P2_XC, t += 2 * dt) {
                        const uint32_t sp = sx + c + (c >= 32 * P2_XROW ? 64 : 0);
                        wait_pos(t >> 4);
                        if (st) bulk_s2g(reinterpret_cast<uint8_t*>(out) + o + c, sp, P2_XC);
                        asm volatile("cp.async.bulk.commit_group;\n" ::: "memory");
                        if (ld) {
                            wait_pos((t + dt) >> 4);
                            asm volatile("cp.async.bulk.wait_group.read 0;\n" ::: "memory");
                            bulk_g2s(sp, reinterpret_cast<const uint8_t*>(x) + on + c, P2_XC, xf);
                        }
                    }
                    if (rank == 0 && n > 0 && n < P2_ITEMS - 1) flag_wait<false>(&g_prog[0][0], P2_NCL * (end + P2_SLACK));
                    if (n < P2_ITEMS) mbar_arrive(xf);
                }
                __syncwarp();
                o = on;
                wp = w;
            }
            asm volatile("cp.async.bulk.wait_group 0;\n" ::: "memory");
        }
        __syncwarp();
        cluster_sync();
    } else {
        reg_inc<160>();
        const int wg = warp >> 2, w = warp & 3, g = lane >> 2, q = lane & 3;
        const uint32_t sx = sbase + P2_OFF_X + (g & 1) * P2_XHALF + (w * 8 + (g >> 1)) * P2_XROW + q * 16;
        const uint32_t af = bar_afull + wg * P2_NA * 8;
        const uint32_t s_a = sbase + P2_OFF_A + wg * P2_NA * P2_A + (lane >> 3) * 512 + (lane & 7) * 64 + ((w ^ ((lane & 7) >> 1)) << 4);
        uint32_t acc0[48], acc1[48], up;
        uint4 a[2][2];

        {
            float* s_red = reinterpret_cast<float*>(smem + P2_OFF_RED);
            float gx[4], part = 0.f;
            __nv_bfloat16 gg[4];
#pragma unroll
            for (int i = 0; i < 4; i++) gg[i] = grn_g[tid + 384 * i];
            TSTAMP(1, 27);
            gdc_wait();
            TSTAMP(1, 1);
            if (blockIdx.x == 120 && tid < (LN_RING + 3) * 2) (&g_flag[0][0][0])[tid * 8] = 0;
            if (blockIdx.x == 121 && tid == 0) g_epoch++;
#pragma unroll
            for (int i = 0; i < 4; i++) gx[i] = __ldcg(&g_sums[0][tid + 384 * i]) + __ldcg(&g_sums[1][tid + 384 * i]);
            const float bias = __ldcg(&g_sums[0][HID + tid]) + __ldcg(&g_sums[1][HID + tid]);
            const float gs = w2_scale(__float_as_uint(__ldcg(&g_sums[0][HID + C_DIM])) | __float_as_uint(__ldcg(&g_sums[1][HID + C_DIM])));
            float mg = 0.f;
#pragma unroll
            for (int i = 0; i < 4; i++) {
                gx[i] = sqrtf(gx[i] * (HSCALE * HSCALE) + 1e-6f);
                part += gx[i];
                gx[i] *= __bfloat162float(gg[i]);
                mg = fmaxf(mg, fabsf(gx[i]));
            }
#pragma unroll
            for (int o = 16; o > 0; o >>= 1) part += __shfl_xor_sync(0xffffffffu, part, o);
            const uint32_t mgw = __reduce_max_sync(0xffffffffu, __float_as_uint(mg));
            const uint32_t mbw = __reduce_max_sync(0xffffffffu, __float_as_uint(fabsf(bias)));
            TSTAMP(1, 26);
            if (lane == 0) *reinterpret_cast<float4*>(s_red + warp * 4) = make_float4(part, __uint_as_float(mgw), __uint_as_float(mbw), 0.f);
            bar_sync(1, 384);
            float tot = 0.f, mb = 0.f;
#pragma unroll
            for (int i = 0; i < 12; i++) {
                const float4 t = *reinterpret_cast<const float4*>(s_red + i * 4);
                tot += t.x;
                mg = fmaxf(mg, t.y);
                mb = fmaxf(mb, t.z);
            }
            const float inv = 1.0f / (tot * (1.0f / HID) + 1e-6f);
            const uint32_t ej = min((__float_as_uint(fmaxf(fmaf(mg, inv, 1.0f) * HSCALE, mb * gs * 0x1p-13f)) >> 23) + 1, 250u);
            const float dn = __uint_as_float((254u - ej) << 23);
            up = min(ej + 127u - (__float_as_uint(gs) >> 23), 254u) * 0x00800080u;
            reinterpret_cast<uint16_t*>(smem + P2_OFF_BIAS + C_DIM * 2)[tid] = 0;
            *reinterpret_cast<__half*>(smem + P2_OFF_BIAS + (tid >> 5) * 64 + (tid & 6) * 8 + (tid & 24) / 2 + (tid & 1) * 2) = __float2half_rn(bias * gs * dn);
#pragma unroll
            for (int i = 0; i < 4; i++) {
                const int k = tid + 384 * i;
                *reinterpret_cast<__half*>(smem + P2_OFF_GRN + (k >> 4) * 32 + (k & 6) * 4 + (k & 8) / 2 + (k & 1) * 2) =
                    __float2half_rn(fmaf(gx[i], inv, 1.0f) * (HSCALE * dn));
            }
            TSTAMP(1, 25);
            bar_sync(1, 384);
        }
        TSTAMP(1, 28);
        if (wg == 1) {
            constexpr int N = sizeof(g_w2img[0]) / 16, PER = (N + NUM_CTAS - 1) / NUM_CTAS;
            uint4 v[5];
#pragma unroll
            for (int i = 0; i < 5; i++) v[i] = __ldcg(&g_w2img[0][min(blockIdx.x * PER + (tid & 127) + 128 * i, N - 1)]);
#pragma unroll
            for (int i = 0; i < 5; i++) {
                const int j = min(blockIdx.x * PER + (tid & 127) + 128 * i, N - 1);
                const uint32_t* t = reinterpret_cast<const uint32_t*>(smem + P2_OFF_GRN + (j / 768) * 32 + (j & 8) / 2);
                auto sc = [&](uint32_t u, int e) { return (h2_mul(u, t[2 * e]) + 0x00040004u) & 0xfff8fff8u; };
                g_w2img[1][j] = make_uint4(sc(v[i].x, 0), sc(v[i].y, 1), sc(v[i].z, 2), sc(v[i].w, 3));
            }
            asm volatile("fence.proxy.async.global;\n" ::: "memory");
            bar_sync(2, 128);
            if (tid == 128) asm volatile("fence.acq_rel.gpu;\nred.release.gpu.global.add.u32 [%0], 1;\n" ::"l"(&g_prog[1][0]) : "memory");
        }

        const int who = __shfl_sync(0xffffffffu, lane == 2 ? 0 : lane < 2 ? 1 : 2, lane);
        const uint32_t rel0 = who ? mapa(bar_bempty, lane & 1) : mapa(bar_aempty + wg * P2_NA * 8, rank), rel1 = rel0 + (who ? 0 : 32);
        auto publish = [&]() {
            asm volatile("fence.proxy.async.shared::cta;\n" ::: "memory");
            __syncwarp();
            if (who == 0) mbar_arrive(bar_oready + wg * 8);
        };
        bool ok_a, pend = false;
        uint32_t pa = 0, s_t;
        auto fetch = [&](int j, bool raw) {
            uint32_t o[6], u0[4], u1[4];
            uint2 t0 = make_uint2(0, 0), t1 = t0;
            if (raw) {
                asm volatile("ld.shared.v2.u32 {%0,%1}, [%2];\n" : "=r"(t0.x), "=r"(t0.y) : "r"(s_t + j * 64) : "memory");
                asm volatile("ld.shared.v2.u32 {%0,%1}, [%2];\n" : "=r"(t1.x), "=r"(t1.y) : "r"(s_t + j * 64 + 32) : "memory");
            }
            const bool ok_b = mbar_test(bar_bfull + (j & 3) * 8, j >> 2);
            if (j == 7) pa ^= 1;
            ok_a = mbar_test(af + ((j + 1) & 7) * 8, pa);
            asm volatile("ldmatrix.sync.aligned.m8n8.x4.trans.shared.b16 {%0,%1,%2,%3}, [%4];\n"
                         : "=r"(o[0]), "=r"(o[1]), "=r"(o[2]), "=r"(o[3]) : "r"(s_a + j * P2_A) : "memory");
            asm volatile("ldmatrix.sync.aligned.m8n8.x2.trans.shared.b16 {%0,%1}, [%2];\n"
                         : "=r"(o[4]), "=r"(o[5]) : "r"(s_a + j * P2_A + 2048) : "memory");
            p2_unpack(u0, o[0], o[1], o[2]);
            p2_unpack(u1, o[3], o[4], o[5]);
            if (raw) {
                u0[0] = h2_mul(u0[0], t0.x); u0[1] = h2_mul(u0[1], t0.x); u0[2] = h2_mul(u0[2], t0.y); u0[3] = h2_mul(u0[3], t0.y);
                u1[0] = h2_mul(u1[0], t1.x); u1[1] = h2_mul(u1[1], t1.x); u1[2] = h2_mul(u1[2], t1.y); u1[3] = h2_mul(u1[3], t1.y);
            }
            a[j & 1][0] = make_uint4(u0[0], u0[1], u0[2], u0[3]);
            a[j & 1][1] = make_uint4(u1[0], u1[1], u1[2], u1[3]);
            if (!ok_b) mbar_wait(bar_bfull + (j & 3) * 8, j >> 2);
        };
        auto table = [&](int pos) { s_t = sbase + P2_OFF_GRN + q * 8 + (k0 + pos) % 48 * 64; };
        const uint64_t db0 = make_desc(sbase, 128, 256);
        auto block8 = [&](bool raw, int pos, int thr0, int mode) {
#pragma unroll
            for (int j = 0; j < 8; j++) {
                const uint64_t db = db0 + (j & 3) * (P2_B / 16);
                if (j == 8 - P2_AH && mode == 1) bar_sync(4, 384);
                TR2(wg, pos + j, 0);
                wg_fence();
                mma_rs_n192(acc0, a[j & 1][0], db);
                mma_rs_n192(acc1, a[j & 1][0], db + 384);
                mma_rs_n192(acc0, a[j & 1][1], db + 768);
                mma_rs_n192(acc1, a[j & 1][1], db + 768 + 384);
                wg_commit();
                if (j == 7 && mode == 2) bar_arrive(4, 384);
                const uint32_t rel = ((j - 1) & 4 ? rel1 : rel0) + ((j - 1) & 3) * 8;
                TR2(wg, pos + j, 1);
                wg_wait<1>();
                TR2(wg, pos + j, 2);
                if (who < (j ? 2 : thr0)) mbar_arrive_cluster(rel);
                if (!ok_a) {
                    if (j == 0 && pend) { publish(); pend = false; }
                    mbar_wait(af + ((j + 1) & 7) * 8, pa);
                }
                TR2(wg, pos + j, 3);
                if (raw && j == 7) table(pos + 8);
                fetch((j + 1) & 7, raw && (j < 7 || pos + 8 < P2_RAW));
            }
        };
        int n = wg == 2 && half ? -1 : wg, pos = p2_start(n);
        uint32_t px = 0;
        wait_pos(pos);
        mbar_wait(af, 0);
        table(pos);
        fetch(0, pos < P2_RAW);
#pragma unroll 1
        for (;; n += 3) {
            TSTAMP(1, 2 + n);
            const int end = pos + (n < 0 ? 24 : 48);
#pragma unroll
            for (int i = 0; i < 48; i += 2) {
                asm volatile("mov.b64 {%0, %1}, 0;\n" : "=r"(acc0[i]), "=r"(acc0[i + 1]));
                asm volatile("mov.b64 {%0, %1}, 0;\n" : "=r"(acc1[i]), "=r"(acc1[i + 1]));
            }
            int thr = 1;
#pragma unroll 1
            for (; pos < P2_RAW; pos += 8, thr = 2) block8(true, pos, thr, 0);
#pragma unroll 1
            for (; pos < end; pos += 8, thr = 2) {
                const int e = pos + 8, r = e % 48;
                block8(false, pos, thr, e < 48 || e > 256 || (r != 0 && r != P2_S1 && r != P2_S2) ? 0 : e == end ? 2 : 1);
            }
            TR2(wg, pos - 1, 4);
            wg_wait<0>();
            TR2(wg, pos - 1, 5);
            if (who == 1) mbar_arrive_cluster(rel0 + 24);
            mbar_wait(bar_xfull + wg * 8, px);
            TR2(wg, pos - 1, 6);
            px ^= 1;
            __syncwarp();
            p2_epilogue(acc0, acc1, up, sx, sbase + P2_OFF_BIAS + q * 16 + (n < 0 && fin ? C_DIM * 2 : 0), zero);
            TR2(wg, pos - 1, 7);
            if (n + 3 >= P2_ITEMS) { publish(); break; }
            if (n < 0) {
                publish();
                pos = P2_S2;
                wait_pos(pos);
                mbar_wait(bar_bfull, 0);
            } else {
                pend = true;
                ok_a = false;
            }
        }
        TSTAMP(1, 29);
        cluster_sync();
        TSTAMP(1, 30);
    }
}

}

extern "C" void kernel_launch(void* const* d_in, const int* in_sizes, int n_in, void* d_out, int out_size) {
    const __nv_bfloat16* x = (const __nv_bfloat16*)d_in[0];
    const __nv_bfloat16* dw = (const __nv_bfloat16*)d_in[1];
    const __nv_bfloat16* w1 = (const __nv_bfloat16*)d_in[2];
    const __nv_bfloat16* w2 = (const __nv_bfloat16*)d_in[3];
    const __nv_bfloat16* grn_g = (const __nv_bfloat16*)d_in[4];
    const __nv_bfloat16* grn_b = (const __nv_bfloat16*)d_in[5];
    __nv_bfloat16* out = (__nv_bfloat16*)d_out;

    cudaFuncSetAttribute(pass1_kernel, cudaFuncAttributeMaxDynamicSharedMemorySize, P1_SMEM);
    cudaFuncSetAttribute(pass2_kernel, cudaFuncAttributeMaxDynamicSharedMemorySize, P2_SMEM);

    typedef CUresult (*EncodeFn)(CUtensorMap*, CUtensorMapDataType, cuuint32_t, void*, const cuuint64_t*, const cuuint64_t*,
                                 const cuuint32_t*, const cuuint32_t*, CUtensorMapInterleave, CUtensorMapSwizzle,
                                 CUtensorMapL2promotion, CUtensorMapFloatOOBfill);
    static EncodeFn encode = nullptr;
    if (!encode) {
        cudaDriverEntryPointQueryResult qres;
        cudaGetDriverEntryPoint("cuTensorMapEncodeTiled", (void**)&encode, cudaEnableDefault, &qres);
    }
    CUtensorMap wmap;
    const cuuint64_t gdim[2] = {HID, C_DIM};
    const cuuint64_t gstr[1] = {HID * 2};
    const cuuint32_t box[2] = {64, 192}, estr[2] = {1, 1};
    CUresult er = encode(&wmap, CU_TENSOR_MAP_DATA_TYPE_BFLOAT16, 2, (void*)w1, gdim, gstr, box, estr, CU_TENSOR_MAP_INTERLEAVE_NONE,
           CU_TENSOR_MAP_SWIZZLE_128B, CU_TENSOR_MAP_L2_PROMOTION_L2_128B, CU_TENSOR_MAP_FLOAT_OOB_FILL_NONE);
    if (er != CUDA_SUCCESS) printf("tensor map encode failed %d\n", (int)er);

    pass1_kernel<<<NUM_CTAS, 512, P1_SMEM>>>(wmap, x, dw, w2, grn_b, 0);

    cudaLaunchAttribute attr[1];
    attr[0].id = cudaLaunchAttributeProgrammaticStreamSerialization;
    attr[0].val.programmaticStreamSerializationAllowed = 1;
    cudaLaunchConfig_t cfg = {};
    cfg.gridDim = dim3(NUM_CTAS);
    cfg.stream = 0;
    cfg.attrs = attr;
    cfg.numAttrs = 1;
    cfg.blockDim = dim3(512);
    cfg.dynamicSmemBytes = P2_SMEM;
    cudaLaunchKernelEx(&cfg, pass2_kernel, x, grn_g, out, 0);
}
```

```cpp
#include <cuda.h>
#include <cuda_runtime.h>
#include <cuda_bf16.h>
#include <cuda_fp16.h>
#include <stdint.h>
#include <stdio.h>

namespace {

constexpr int M_TOTAL = 384 * 384;
constexpr int C_DIM   = 384;
constexpr int HID     = 1536;
constexpr int NT128   = M_TOTAL / 128;
constexpr int NUM_CTAS = 132;

constexpr int NGRP = 22, GRP_CTAS = 6;
constexpr int LN_STEP = NUM_CTAS / 4, LN_RING = 2 * LN_STEP;
constexpr int LN_TILE = 128 * C_DIM * 2;
constexpr int H_TILE = 64 * HID * 3 / 2;
constexpr int H_HALF = 3072, H_STEP = 6144;

__device__ __align__(1024) uint4 g_h[(size_t)M_TOTAL * HID * 3 / 32];
__device__ __align__(1024) uint4 g_ln[LN_RING * LN_TILE / 16];
__device__ __align__(1024) uint4 g_w2img[2][HID * C_DIM * 2 / 16];
__device__ __align__(16) float g_sums[2][HID + 512];
__device__ unsigned g_epoch;
__device__ __align__(128) unsigned g_prog[2][32];
__device__ __align__(128) unsigned g_half[32][2];
__device__ unsigned g_flag[LN_RING + 3][2][8];
#define TSTAMP(k, i)
#define TRACE(wg, pos, i)
#define TRACEW(pos, i)

#define TR2(wg, pos, i)
__host__ __device__ __forceinline__ int perm32(int n) {
    return (n & ~31) | (((n >> 1) & 3) << 3) | (((n >> 3) & 3) << 1) | (n & 1);
}

__device__ __forceinline__ uint32_t smem_u32(const void* p) { return (uint32_t)__cvta_generic_to_shared(p); }

__device__ __forceinline__ void mbar_init(uint32_t bar, uint32_t count) {
    asm volatile("mbarrier.init.shared::cta.b64 [%0], %1;\n" ::"r"(bar), "r"(count) : "memory");
}
__device__ __forceinline__ void mbar_expect_tx(uint32_t bar, uint32_t bytes) {
    asm volatile("mbarrier.arrive.expect_tx.shared::cta.b64 _, [%0], %1;\n" ::"r"(bar), "r"(bytes) : "memory");
}
__device__ __forceinline__ void mbar_arrive(uint32_t bar) {
    asm volatile("mbarrier.arrive.shared::cta.b64 _, [%0];\n" ::"r"(bar) : "memory");
}
__device__ __forceinline__ void mbar_arrive_cluster(uint32_t bar_cluster_addr) {
    asm volatile("mbarrier.arrive.shared::cluster.b64 _, [%0];\n" ::"r"(bar_cluster_addr) : "memory");
}
#define SAFE_BREAK
__device__ __forceinline__ void mbar_wait(uint32_t bar, uint32_t parity) {
    asm volatile(
        "{\n"
        ".reg .pred p;\n"
        "LAB_WAIT:\n"
        "mbarrier.try_wait.parity.shared::cta.b64 p, [%0], %1;\n"
        "@!p bra LAB_WAIT;\n"
        "}\n" ::"r"(bar), "r"(parity) : "memory");
}
__device__ __forceinline__ bool mbar_test(uint32_t bar, uint32_t parity) {
    uint32_t ok;
    asm volatile("{\n.reg .pred p;\n"
                 "mbarrier.test_wait.parity.shared::cta.b64 p, [%1], %2;\n"
                 "selp.u32 %0, 1, 0, p;\n}\n" : "=r"(ok) : "r"(bar), "r"(parity) : "memory");
    return ok != 0;
}
__device__ __forceinline__ uint32_t mapa(uint32_t addr, uint32_t rank) {
    uint32_t r;
    asm volatile("mapa.shared::cluster.u32 %0, %1, %2;\n" : "=r"(r) : "r"(addr), "r"(rank));
    return r;
}
__device__ __forceinline__ void bulk_g2s(uint32_t dst, const void* src, uint32_t bytes, uint32_t bar) {
    asm volatile("cp.async.bulk.shared::cluster.global.mbarrier::complete_tx::bytes [%0], [%1], %2, [%3];\n"
                 ::"r"(dst), "l"(src), "r"(bytes), "r"(bar) : "memory");
}
__device__ __forceinline__ void bulk_g2s_mc(uint32_t dst, const void* src, uint32_t bytes, uint32_t bar, uint16_t mask) {
    asm volatile("cp.async.bulk.shared::cluster.global.mbarrier::complete_tx::bytes.multicast::cluster [%0], [%1], %2, [%3], %4;\n"
                 ::"r"(dst), "l"(src), "r"(bytes), "r"(bar), "h"(mask) : "memory");
}
__device__ __forceinline__ void tma2(uint32_t dst, const CUtensorMap* map, int c0, int c1, uint32_t bar) {
    asm volatile("cp.async.bulk.tensor.2d.shared::cluster.global.tile.mbarrier::complete_tx::bytes [%0], [%1, {%2, %3}], [%4];\n"
                 ::"r"(dst), "l"(map), "r"(c0), "r"(c1), "r"(bar) : "memory");
}
template <bool ACQ>
__device__ __forceinline__ uint32_t flag_wait(const unsigned* p, unsigned target) {
    unsigned v, n = 0;
    do {
        if (ACQ) asm volatile("ld.acquire.gpu.global.u32 %0, [%1];\n" : "=r"(v) : "l"(p) : "memory");
        else asm volatile("ld.relaxed.gpu.global.u32 %0, [%1];\n" : "=r"(v) : "l"(p) : "memory");
        n++;
    } while (v < target);
    return n == 1;
}
__device__ __forceinline__ void ldsm4t(uint32_t (&r)[4], uint32_t addr) {
    asm volatile("ldmatrix.sync.aligned.m8n8.x4.trans.shared.b16 {%0,%1,%2,%3}, [%4];\n"
                 : "=r"(r[0]), "=r"(r[1]), "=r"(r[2]), "=r"(r[3]) : "r"(addr) : "memory");
}
__device__ __forceinline__ void bulk_s2g(void* dst, uint32_t src, uint32_t bytes) {
    asm volatile("cp.async.bulk.global.shared::cta.bulk_group [%0], [%1], %2;\n" ::"l"(dst), "r"(src), "r"(bytes) : "memory");
}
__device__ __forceinline__ void cluster_sync() {
    asm volatile("barrier.cluster.arrive.aligned;\nbarrier.cluster.wait.aligned;\n" ::: "memory");
}
__device__ __forceinline__ void cluster_sync_relaxed() {
    asm volatile("barrier.cluster.arrive.relaxed.aligned;\nbarrier.cluster.wait.aligned;\n" ::: "memory");
}
__device__ __forceinline__ void gdc_wait() { asm volatile("griddepcontrol.wait;\n" ::: "memory"); }
__device__ __forceinline__ void gdc_launch() { asm volatile("griddepcontrol.launch_dependents;\n" ::: "memory"); }
__device__ __forceinline__ uint32_t cluster_rank() {
    uint32_t r;
    asm volatile("mov.u32 %0, %%cluster_ctarank;\n" : "=r"(r));
    return r;
}
__device__ __forceinline__ bool elect_one() {
    uint32_t pred;
    asm volatile("{\n.reg .pred p;\nelect.sync _|p, 0xffffffff;\nselp.u32 %0, 1, 0, p;\n}\n" : "=r"(pred));
    return pred != 0;
}
__device__ __forceinline__ void wg_fence() { asm volatile("wgmma.fence.sync.aligned;\n" ::: "memory"); }
__device__ __forceinline__ void wg_commit() { asm volatile("wgmma.commit_group.sync.aligned;\n" ::: "memory"); }
template <int N> __device__ __forceinline__ void wg_wait() {
    asm volatile("wgmma.wait_group.sync.aligned %0;\n" ::"n"(N) : "memory");
}
template <int R> __device__ __forceinline__ void reg_inc() { asm volatile("setmaxnreg.inc.sync.aligned.u32 %0;\n" ::"n"(R)); }
template <int R> __device__ __forceinline__ void reg_dec() { asm volatile("setmaxnreg.dec.sync.aligned.u32 %0;\n" ::"n"(R)); }
__device__ __forceinline__ void bar_sync(int id, int n) { asm volatile("bar.sync %0, %1;\n" ::"r"(id), "r"(n) : "memory"); }
__device__ __forceinline__ void bar_arrive(int id, int n) { asm volatile("bar.arrive %0, %1;\n" ::"r"(id), "r"(n) : "memory"); }

__device__ __forceinline__ uint64_t make_desc(uint32_t saddr, uint32_t lbo, uint32_t sbo) {
    return (uint64_t)((saddr & 0x3FFFF) >> 4) | ((uint64_t)(lbo >> 4) << 16) | ((uint64_t)(sbo >> 4) << 32);
}

__device__ __forceinline__ void stg128_cs(void* p, uint32_t a, uint32_t b, uint32_t c, uint32_t d) {
    asm volatile("st.global.cs.v4.u32 [%0], {%1,%2,%3,%4};\n" ::"l"(p), "r"(a), "r"(b), "r"(c), "r"(d) : "memory");
}
__device__ __forceinline__ uint32_t pack_bf16(float lo, float hi) {
    uint32_t r;
    asm("cvt.rn.bf16x2.f32 %0, %1, %2;\n" : "=r"(r) : "f"(hi), "f"(lo));
    return r;
}
__device__ __forceinline__ float bf_lo(uint32_t v) { return __uint_as_float(v << 16); }
__device__ __forceinline__ float bf_hi(uint32_t v) { return __uint_as_float(v & 0xffff0000u); }
__device__ __forceinline__ uint32_t bf2_mul(uint32_t a, uint32_t b) {
    uint32_t r;
    asm("mul.rn.bf16x2 %0, %1, %2;\n" : "=r"(r) : "r"(a), "r"(b));
    return r;
}
__device__ __forceinline__ uint32_t bf2_fma(uint32_t a, uint32_t b, uint32_t c) {
    uint32_t r;
    asm("fma.rn.bf16x2 %0, %1, %2, %3;\n" : "=r"(r) : "r"(a), "r"(b), "r"(c));
    return r;
}
__device__ __forceinline__ uint32_t bf2_add(uint32_t a, uint32_t b) {
    uint32_t r;
    asm("add.rn.bf16x2 %0, %1, %2;\n" : "=r"(r) : "r"(a), "r"(b));
    return r;
}
__device__ __forceinline__ uint32_t h2_mul(uint32_t a, uint32_t b) {
    uint32_t r;
    asm("mul.rn.f16x2 %0, %1, %2;\n" : "=r"(r) : "r"(a), "r"(b));
    return r;
}
__device__ __forceinline__ uint32_t h2_fma(uint32_t a, uint32_t b, uint32_t c) {
    uint32_t r;
    asm("fma.rn.f16x2 %0, %1, %2, %3;\n" : "=r"(r) : "r"(a), "r"(b), "r"(c));
    return r;
}
__device__ __forceinline__ uint32_t h2_add(uint32_t a, uint32_t b) {
    uint32_t r;
    asm("add.rn.f16x2 %0, %1, %2;\n" : "=r"(r) : "r"(a), "r"(b));
    return r;
}
__device__ __forceinline__ uint32_t pack_f16(float lo, float hi) {
    uint32_t r;
    asm("cvt.rn.f16x2.f32 %0, %1, %2;\n" : "=r"(r) : "f"(hi), "f"(lo));
    return r;
}
__device__ __forceinline__ float h_lo(uint32_t v) { return __low2float(*reinterpret_cast<const __half2*>(&v)); }
__device__ __forceinline__ float h_hi(uint32_t v) { return __high2float(*reinterpret_cast<const __half2*>(&v)); }
__device__ __forceinline__ uint32_t bf2_to_h2(uint32_t v) { return (v & 0x7fff7fffu) * 7u + v; }
__device__ __forceinline__ uint32_t prmt(uint32_t a, uint32_t b, uint32_t sel) {
    uint32_t r;
    asm("prmt.b32 %0, %1, %2, %3;\n" : "=r"(r) : "r"(a), "r"(b), "r"(sel));
    return r;
}
__device__ __forceinline__ uint32_t bitsel(uint32_t a, uint32_t b, uint32_t m) {
    uint32_t r;
    asm("lop3.b32 %0, %1, %2, %3, 0xd8;\n" : "=r"(r) : "r"(a), "r"(b), "r"(m));
    return r;
}
constexpr float KAPPA = 0.3292034911525734f;
constexpr uint32_t GELU_C2 = 0x40d940d9u;
constexpr float HSCALE = 1.0f / (2.0f * KAPPA);
__device__ __forceinline__ float w2_scale(uint32_t m) { return __uint_as_float((257u - max(m >> 23, 16u)) << 23); }
__device__ __forceinline__ void sched_break(int zero) {
    asm volatile("{\n.reg .pred p;\nsetp.ne.s32 p, %0, 0;\nSB_LOOP:\n@p nanosleep.u32 1;\n@p bra SB_LOOP;\n}\n" ::"r"(zero));
}

#define ACC8(d, o) "+r"(d[o + 0]), "+r"(d[o + 1]), "+r"(d[o + 2]), "+r"(d[o + 3]), "+r"(d[o + 4]), "+r"(d[o + 5]), "+r"(d[o + 6]), "+r"(d[o + 7])

__device__ __forceinline__ void mma_rs_n128(uint32_t (&d)[32], const uint32_t (&a)[4], uint64_t desc, int scale_d) {
    asm volatile(
        "{\n.reg .pred p;\nsetp.ne.b32 p, %37, 0;\n"
        "wgmma.mma_async.sync.aligned.m64n128k16.f16.f16.f16 "
        "{%0,%1,%2,%3,%4,%5,%6,%7,%8,%9,%10,%11,%12,%13,%14,%15,"
        "%16,%17,%18,%19,%20,%21,%22,%23,%24,%25,%26,%27,%28,%29,%30,%31},"
        "{%32,%33,%34,%35}, %36, p, 1, 1, 0;\n}\n"
        : ACC8(d, 0), ACC8(d, 8), ACC8(d, 16), ACC8(d, 24)
        : "r"(a[0]), "r"(a[1]), "r"(a[2]), "r"(a[3]), "l"(desc), "r"(scale_d));
}

__device__ __forceinline__ void mma_ss_n128(uint32_t (&d)[32], uint64_t da, uint64_t db, int scale_d) {
    asm volatile(
        "{\n.reg .pred p;\nsetp.ne.b32 p, %34, 0;\n"
        "wgmma.mma_async.sync.aligned.m64n128k16.f16.f16.f16 "
        "{%0,%1,%2,%3,%4,%5,%6,%7,%8,%9,%10,%11,%12,%13,%14,%15,"
        "%16,%17,%18,%19,%20,%21,%22,%23,%24,%25,%26,%27,%28,%29,%30,%31},"
        "%32, %33, p, 1, 1, 1, 0;\n}\n"
        : ACC8(d, 0), ACC8(d, 8), ACC8(d, 16), ACC8(d, 24)
        : "l"(da), "l"(db), "r"(scale_d));
}

__device__ __forceinline__ void mma_rs_n192(uint32_t (&d)[48], const uint4& a, uint64_t db) {
    asm volatile(
        "wgmma.mma_async.sync.aligned.m64n192k16.f16.f16.f16 "
        "{%0,%1,%2,%3,%4,%5,%6,%7,%8,%9,%10,%11,%12,%13,%14,%15,"
        "%16,%17,%18,%19,%20,%21,%22,%23,%24,%25,%26,%27,%28,%29,%30,%31,"
        "%32,%33,%34,%35,%36,%37,%38,%39,%40,%41,%42,%43,%44,%45,%46,%47},"
        "{%48,%49,%50,%51}, %52, 1, 1, 1, 0;\n"
        : ACC8(d, 0), ACC8(d, 8), ACC8(d, 16), ACC8(d, 24), ACC8(d, 32), ACC8(d, 40)
        : "r"(a.x), "r"(a.y), "r"(a.z), "r"(a.w), "l"(db));
}

#define P1_WPF 30
#define P1_PACE 1
constexpr int P1_SLOT = LN_TILE / 6, P1_NST = 6;
constexpr int P1_W = 64 * C_DIM * 2;
constexpr int P1_X = 32 * C_DIM * 2;
constexpr int P1_OFF_W = LN_TILE;
constexpr int P1_OFF_X = P1_OFF_W + 2 * P1_W;
constexpr int P1_OFF_BAR = P1_OFF_X + P1_X;
constexpr int P1_OFF_TILE = P1_OFF_BAR + (2 * P1_NST + 4 + 4 + 4) * 8;
constexpr int P1_OFF_EX = P1_OFF_TILE + 64;
constexpr int P1_OFF_DW = P1_OFF_EX + 256 * 4;
constexpr int P1_SMEM = P1_OFF_DW + C_DIM * 2;

__device__ __forceinline__ float rsqrt_fast(float x) {
    float r;
    asm("rsqrt.approx.ftz.f32 %0, %1;\n" : "=f"(r) : "f"(x));
    return r;
}
__device__ __forceinline__ float row_sum(const uint32_t (&c)[4]) {
    const uint32_t u = bf2_add(bf2_add(c[0], c[1]), bf2_add(c[2], c[3]));
    float s = bf_lo(u) + bf_hi(u);
#pragma unroll
    for (int o = 1; o < 8; o <<= 1) s += __shfl_xor_sync(0xffffffffu, s, o);
    return s;
}
__device__ __forceinline__ uint32_t pace(uint32_t bar, uint32_t off, uint32_t val, uint32_t after, int zero) {
    asm volatile(
        "{\n.reg .pred p, q;\n.reg .b32 par;\n"
        "lop3.b32 par, %4, %2, %3, 0xea;\n"
        "setp.eq.u32 q, par, 0;\n"
        "mov.pred p, 0;\n"
        "@q mbarrier.test_wait.parity.shared::cta.b64 p, [%1], par;\n"
        "selp.u32 par, 1, 0, p;\n"
        "@q mbarrier.try_wait.parity.shared::cta.b64 p, [%1], par, 1000;\n"
        "@p or.b32 %0, %0, %2;\n"
        "}\n" : "+r"(val) : "r"(bar), "r"(zero), "r"(off), "r"(after));
    return val;
}
template <int PACE, int R>
__device__ __forceinline__ void ln_rows(uint32_t (&v)[R][6][4], const uint32_t (&d)[6][4], uint32_t bar, uint32_t off, int zero,
                                        uint32_t bar_read) {
    const float inv = 1.0f / C_DIM;
    uint32_t c[R][4], nm[R];
    float e[R], r[R], er[R];
    bool big = false;
#pragma unroll
    for (int p = 0; p < R; p++) {
#pragma unroll
        for (int i = 0; i < 6; i++)
#pragma unroll
            for (int k = 0; k < 4; k++) c[p][k] = bf2_fma(v[p][i][k], d[i][k], i ? c[p][k] : 0);
        const float m = row_sum(c[p]) * inv;
        nm[p] = pack_bf16(-m, -m);
        e[p] = m + bf_lo(nm[p]);
    }
    if (bar_read) mbar_arrive(bar_read + (nm[0] & zero));
    if (PACE & 1) nm[0] = pace(bar, off, nm[0], nm[0], zero);
#pragma unroll
    for (int p = 0; p < R; p++) {
#pragma unroll
        for (int i = 0; i < 6; i++) {
#pragma unroll
            for (int k = 0; k < 4; k++) {
                v[p][i][k] = bf2_fma(v[p][i][k], d[i][k], nm[p]);
                c[p][k] = i ? bf2_fma(v[p][i][k], v[p][i][k], c[p][k]) : bf2_mul(v[p][i][k], v[p][i][k]);
            }
        }
        r[p] = KAPPA * rsqrt_fast(fmaxf(fmaf(-e[p], e[p], row_sum(c[p]) * inv), 0.f) + 1e-5f);
        er[p] = -e[p] * r[p] * 0x1p-116f;
        big |= r[p] < 0x1p-8f;
    }
    if (__any_sync(0xffffffffu, big)) {
#pragma unroll
        for (int p = 0; p < R; p++) {
            const uint32_t p2 = __float_as_uint(r[p]) & 0x7f800000u;
            r[p] = __uint_as_float((__float_as_uint(r[p]) & 0x007fffffu) | 0x3f800000u);
#pragma unroll
            for (int i = 0; i < 6; i++)
#pragma unroll
                for (int k = 0; k < 4; k++) v[p][i][k] = bf2_mul(v[p][i][k], p2 | p2 >> 16);
        }
    }
#pragma unroll
    for (int p = 0; p < R; p++) {
        uint32_t rs = pack_bf16(r[p] * 0x1p-116f, r[p] * 0x1p-116f);
        const uint32_t sh = pack_bf16(er[p], er[p]);
        if (PACE & 2) rs = pace(bar, off, rs, sh, zero);
#pragma unroll
        for (int i = 0; i < 6; i++)
#pragma unroll
            for (int k = 0; k < 4; k++) v[p][i][k] = bf2_to_h2(bf2_fma(v[p][i][k], rs, sh));
    }
}

template <int R>
__device__ __forceinline__ uint32_t gelu2(uint32_t a, uint32_t sc2) {
    uint32_t y, t;
    if (R) asm("{\n.reg .b16 l, h;\n.reg .b32 f;\nmov.b32 {l, h}, %2;\nmov.b32 f, {h, h};\nmul.rn.f16x2 %0, %1, f;\n}\n" : "=r"(y) : "r"(a), "r"(sc2));
    else asm("{\n.reg .b16 l, h;\n.reg .b32 f;\nmov.b32 {l, h}, %2;\nmov.b32 f, {l, l};\nmul.rn.f16x2 %0, %1, f;\n}\n" : "=r"(y) : "r"(a), "r"(sc2));
    asm("tanh.approx.f16x2 %0, %1;\n" : "=r"(t) : "r"(h2_mul(y, h2_fma(y, y, GELU_C2))));
    return h2_fma(a, t, a);
}
constexpr uint32_t SPARE = 0x40074007u;

__device__ __forceinline__ uint32_t p1_parity(uint32_t sbase) {
    uint32_t v;
    asm volatile("ld.shared.u32 %0, [%1];\n" : "=r"(v) : "r"(sbase + P1_OFF_TILE - 4) : "memory");
    return v;
}
__device__ __forceinline__ uint32_t p1_exponents(float (&t)[2], uint32_t (&ex)[2], uint32_t saddr, int lane) {
#pragma unroll
    for (int r = 0; r < 2; r++) {
        t[r] += __shfl_xor_sync(0xffffffffu, t[r], 1);
        t[r] += __shfl_xor_sync(0xffffffffu, t[r], 2);
        ex[r] = min(max(((__float_as_uint(193.3f * t[r]) >> 23) + 127u) >> 1, 72u), 198u);
        asm volatile("st.shared.u32 [%0], %1;\n" ::"r"(saddr + r * 32), "r"(ex[r] << 23) : "memory");
    }
    return pack_f16(__uint_as_float(min(ex[0], 142u) << 23), __uint_as_float(min(ex[1], 142u) << 23));
}
template <int N>
__device__ __forceinline__ void p1_convert(uint32_t (&o)[N][4], uint32_t (&v)[N][4], const uint32_t (&ex)[2]) {
    if (__any_sync(0xffffffffu, max(ex[0], ex[1]) > 145u)) {
#pragma unroll
        for (int k = 0; k < 4 * N; k++) v[k >> 2][k & 3] = bf2_mul(v[k >> 2][k & 3], ex[k & 1] > 145u ? 0x1f801f80u : 0x3f803f80u);
    }
#pragma unroll
    for (int k = 0; k < 4 * N; k++) {
        const uint32_t u = bf2_mul(v[k >> 2][k & 3], ((ex[k & 1] > 145u ? 210u : 146u) - ex[k & 1]) * 0x00800080u);
        asm volatile("mad.lo.u32 %0, %1, 7, %2;\n" : "=r"(o[k >> 2][k & 3]) : "r"(u & 0x7fff7fffu), "r"(u));
    }
}
template <int N>
__device__ __forceinline__ void p1_squares(const uint32_t (&v)[N][4], float (&t)[2]) {
#pragma unroll
    for (int j = 0; j < N / 2; j++) {
        const int r = j & 1, b = (j >> 1) * 4;
        uint32_t c = bf2_mul(v[b][r], v[b][r]);
#pragma unroll
        for (int k = 1; k < 8; k++) c = bf2_fma(v[b + k / 2][r + (k & 1) * 2], v[b + k / 2][r + (k & 1) * 2], c);
        t[r] += bf_lo(c) + bf_hi(c);
    }
}
__device__ __forceinline__ void p1_epilogue(const uint32_t (&acc)[2][32], const uint32_t (&sc2)[2], float (&ssq)[4], uint8_t* hp, int zero) {
    uint32_t sq[2], h[16][4];
#pragma unroll
    for (int i2 = 0; i2 < 9; i2++) {
#pragma unroll
        for (int c = 2 * i2 - 2; c < 2 * i2; c++) {
            if (c >= 0 && (c & 3)) {
                uint32_t o[4];
#pragma unroll
                for (int u = 0; u < 4; u++) {
                    const uint32_t v = h[c & 12][u];
                    o[u] = bitsel(h[c][u], (c & 3) == 2 ? prmt(v, v, 0xa381) : prmt(v >> 3, v, (c & 3) == 1 ? 0x6240 : 0xf3d1), SPARE);
                }
                stg128_cs(hp + (c >> 3) * 2 * H_STEP + ((c >> 2) & 1) * H_HALF + ((c & 3) - 1) * 512, o[0], o[1], o[2], o[3]);
            }
        }
        if (i2 < 8) {
#pragma unroll
            for (int u = 0; u < 4; u++) {
                h[2 * i2][u] = gelu2<0>(acc[i2 >> 2][8 * (i2 & 3) + 2 * u], sc2[i2 >> 2]);
                h[2 * i2 + 1][u] = gelu2<1>(acc[i2 >> 2][8 * (i2 & 3) + 2 * u + 1], sc2[i2 >> 2]);
#pragma unroll
                for (int r = 0; r < 2; r++) {
                    const uint32_t v = h[2 * i2 + r][u];
                    sq[r] = ((i2 & 3) | u) ? h2_fma(v, v, sq[r]) : h2_mul(v, v);
                }
            }
            if ((i2 & 3) == 3) {
#pragma unroll
                for (int r = 0; r < 2; r++) ssq[(i2 >> 2) * 2 + r] += h_lo(sq[r]) + h_hi(sq[r]);
            }
            sched_break(zero);
        }
    }
}
template <int WG>
__device__ __forceinline__ void p1_mma(uint32_t (&acc)[2][32], const uint32_t (&a)[24][4], uint32_t sbase, uint32_t empty_remote, int i, int lane) {
    const uint32_t bar_full = sbase + P1_OFF_BAR;
    const uint64_t db = make_desc(sbase, 16, 1024) | (1ull << 62);
    const uint64_t da = db + (P1_OFF_W + WG * P1_W) / 16;
    if (WG == 0) mbar_wait(bar_full, i & 1);
    bar_sync(1 + WG, 256);
    TRACE(WG, i, 1);
    wg_fence();
#pragma unroll
    for (int k = 0; k < 24; k++) {
        if (WG == 0 && k && k % 4 == 0) mbar_wait(bar_full + (k >> 2) * 8, i & 1);
        mma_rs_n128(acc[0], a[k], db + (uint64_t)((k >> 2) * 1024 + (k & 3) * 2), k != 0);
        mma_ss_n128(acc[1], da + (uint64_t)(k * 128), db + (uint64_t)((k >> 2) * 1024 + (k & 3) * 2), k != 0);
        if (k == 23) bar_arrive(2 - WG, 256);
        if (k == 23 || (WG == 1 && k % 4 == 3)) wg_commit();
        if (WG == 1 && k % 4 == 3 && k > 3) {
            wg_wait<1>();
            if (lane < 2) mbar_arrive_cluster(empty_remote + ((k >> 2) - 1) * 8);
        }
    }
    TRACE(WG, i, 2);
    wg_wait<0>();
    if (WG == 1 && lane < 2) mbar_arrive_cluster(empty_remote + 5 * 8);
}
__device__ __forceinline__ void p1_consumer(const uint32_t (&a)[24][4], const uint32_t (&sc2)[2], uint32_t sbase, int WG, int w, int lane, int zero) {
    const uint32_t bar_full = sbase + P1_OFF_BAR, bar_empty = bar_full + P1_NST * 8;
    const uint32_t empty_remote = mapa(bar_empty, lane & 1);
    const uint32_t bar_pace = bar_empty + P1_NST * 8 + 32 + w * 8;
    const int g = lane >> 2, q = lane & 3, cb = (blockIdx.x % GRP_CTAS) * 4 + WG * 2;
    uint32_t acc[2][32];
    float ssq[4] = {0.f, 0.f, 0.f, 0.f};
    TSTAMP(0, 1);

    uint8_t* hp = reinterpret_cast<uint8_t*>(g_h) + ((cb * 2 + (w >> 1)) * H_STEP + (w & 1) * 1536) + g * 64 + (q ^ (g >> 1)) * 16;
#pragma unroll 1
    for (int i = 0;; i++) {
        TRACE(WG, i, 0);
        if (WG == 0) p1_mma<0>(acc, a, sbase, empty_remote, i, lane);
        else p1_mma<1>(acc, a, sbase, empty_remote, i, lane);
        TRACE(WG, i, 4);
        uint32_t step, more;
        asm volatile("ld.shared.v2.u32 {%0, %1}, [%2];\n" : "=r"(step), "=r"(more) : "r"(sbase + P1_OFF_TILE + (i & 3) * 16) : "memory");
        hp += step;
        p1_epilogue(acc, sc2, ssq, hp, zero);
        if (lane == 0) mbar_arrive(bar_pace);
        if (!more) break;
    }
    TSTAMP(0, 21);
    if (WG == 0) bar_sync(1, 256);
#pragma unroll
    for (int r = 0; r < 4; r++) {
        const int ch = (r >> 1) * 64 + w * 16 + (r & 1) * 8 + g;
        ssq[r] += __shfl_xor_sync(0xffffffffu, ssq[r], 1);
        ssq[r] += __shfl_xor_sync(0xffffffffu, ssq[r], 2);
        float f;
        asm volatile("ld.shared.f32 %0, [%1];\n" : "=f"(f) : "r"(sbase + P1_OFF_EX + (WG * 128 + ch) * 4) : "memory");
        if (q == 0) atomicAdd(&g_sums[p1_parity(sbase)][cb * 64 + ch], ssq[r] * f * f);
    }
}

__global__ void __cluster_dims__(2, 1, 1) __launch_bounds__(512, 1)
pass1_kernel(const __grid_constant__ CUtensorMap wmap, const __nv_bfloat16* __restrict__ x, const __nv_bfloat16* __restrict__ dw,
             const __nv_bfloat16* __restrict__ w2, const __nv_bfloat16* __restrict__ grn_b, int zero) {
    extern __shared__ __align__(1024) uint8_t smem[];
    const uint32_t sbase = smem_u32(smem);
    const uint32_t bar_full = sbase + P1_OFF_BAR, bar_empty = bar_full + P1_NST * 8, bar_w = bar_empty + P1_NST * 8;
    const int tid = threadIdx.x;
    const int warp = __shfl_sync(0xffffffffu, tid >> 5, 0), lane = tid & 31;
    const uint32_t rank = cluster_rank();
    const int cig = blockIdx.x % GRP_CTAS;
    uint8_t* const ring = reinterpret_cast<uint8_t*>(g_ln);

    TSTAMP(0, 0);
    TRACEW(110 + warp, 0);
    const uint32_t bar_pace = bar_w + 32, bar_xfull = bar_pace + 32, bar_xempty = bar_xfull + 8, bar_done = bar_xfull + 16;
    const int ln0 = blockIdx.x >> 2, first = blockIdx.x / GRP_CTAS;
    const uint8_t* xsrc = reinterpret_cast<const uint8_t*>(x) + (size_t)blockIdx.x * P1_X;

    if (warp >= 12) {
        reg_dec<40>();
        asm volatile("barrier.cluster.arrive.relaxed.aligned;\n" ::: "memory");
        asm volatile("barrier.cluster.wait.aligned;\n" ::: "memory");
        if (warp == 12) {
            int prev = 0, t = first;
            const uint32_t rbase = mapa(sbase, lane & 1);
#pragma unroll 1
            for (int i = 0; t < NT128; i++) {
                const int round = t / LN_RING, slot = t - round * LN_RING;
                const uint8_t* src = ring + slot * LN_TILE + rank * (P1_SLOT / 2);
                int next = 0;
                if (rank == 0 && lane == 0) next = atomicAdd(&g_flag[LN_RING + (cig >> 1)][0][0], 1u);
                flag_wait<true>(&g_flag[slot][0][0], 4 * round + 4);
                TRACEW(i, 2);
                asm volatile("fence.proxy.async.global;\n" ::: "memory");
                next = NGRP + __shfl_sync(0xffffffffu, next, 0);
#pragma unroll 1
                for (int h = 0; h < P1_NST; h++) {
                    mbar_wait(bar_empty + h * 8, i & 1);
                    if (h == 0) TRACEW(i, 4);
                    if (h == 5) TRACEW(i, 5);
                    if (elect_one()) {
                        mbar_expect_tx(bar_full + h * 8, h ? P1_SLOT : P1_SLOT + 16);
                        bulk_g2s_mc(sbase + h * P1_SLOT + rank * (P1_SLOT / 2), src + h * P1_SLOT, P1_SLOT / 2, bar_full + h * 8, (uint16_t)3);
                    }
                    __syncwarp();
                    if (h == 0 && rank == 0 && lane < 2)
                        asm volatile("st.async.shared::cluster.mbarrier::complete_tx::bytes.v4.u32 [%0], {%1, %2, %3, %3}, [%4];\n"
                                     ::"r"(rbase + P1_OFF_TILE + (i & 3) * 16), "r"((t - prev) * (2 * H_TILE)), "r"((int)(next < NT128)), "r"(next),
                                       "r"(rbase + P1_OFF_BAR) : "memory");
                }
                prev = t;
                t = next;
                if (rank != 0) {
                    mbar_wait(bar_full, i & 1);
                    asm volatile("ld.shared.u32 %0, [%1];\n" : "=r"(t) : "r"(sbase + P1_OFF_TILE + (i & 3) * 16 + 8) : "memory");
                }
            }
        } else if (warp == 13) {
            int ph = 0;
            unsigned target = 0;
#pragma unroll 1
            for (int i = ln0 + LN_STEP; i < NT128; i += LN_STEP, ph ^= 1) {
                target += ph * (GRP_CTAS / 2);
                xsrc += (size_t)NUM_CTAS * P1_X;
                mbar_wait(bar_xempty, ph);
                if (elect_one()) {
                    mbar_expect_tx(bar_xfull, P1_X);
                    bulk_g2s(sbase + P1_OFF_X, xsrc, P1_X, bar_xfull);
                }
                __syncwarp();
                const uint32_t off = flag_wait<false>(&g_flag[ln0 + (ph ^ 1) * LN_STEP][1][0], target);
                mbar_wait(bar_done, ph);
                if (elect_one()) {
                    asm volatile("st.shared.u32 [%0], %1;\n" ::"r"(bar_done + 8), "r"(off) : "memory");
                    mbar_arrive(bar_xfull);
                }
                __syncwarp();
            }
        } else if (warp == 15) {
            const uint32_t par = g_epoch & 1;
            asm volatile("st.shared.u32 [%0], %1;\n" ::"r"(sbase + P1_OFF_TILE - 4), "r"(par) : "memory");
            if (blockIdx.x < 16) reinterpret_cast<float4*>(g_sums[par ^ 1])[blockIdx.x * 32 + lane] = make_float4(0.f, 0.f, 0.f, 0.f);
            int t = first;
            if (rank == 1 && lane == 0) mbar_arrive(bar_empty);
#pragma unroll 1
            for (int i = 0; rank == 1 && t < NT128; i++) {
#pragma unroll 1
                for (int h = 0; h < P1_NST; h++) mbar_wait(bar_full + h * 8, i & 1);
                if (lane == 0) asm volatile("red.relaxed.gpu.global.add.u32 [%0], 1;\n" ::"l"(&g_flag[t % LN_RING][1][0]) : "memory");
                asm volatile("ld.shared.u32 %0, [%1];\n" : "=r"(t) : "r"(sbase + P1_OFF_TILE + (i & 3) * 16 + 8) : "memory");
                if (lane == 0) mbar_arrive(bar_empty);
                TRACEW(i, 3);
            }
            if (rank == 0) {
                mbar_wait(bar_full, 0);
                TRACEW(110 + warp, 3);
                mbar_wait(bar_full, 1);
                float* sums = g_sums[par] + HID;
                unsigned* flag = reinterpret_cast<unsigned*>(sums + C_DIM);
                if (blockIdx.x == 0) reinterpret_cast<uint2*>(g_half)[lane] = make_uint2(0, 0);
                if (blockIdx.x == 2 && lane < 2) g_prog[lane][0] = 0;
                float gs = 0.f;
#pragma unroll 1
                for (int pass = 0; pass < 2; pass++) {
                    float mx = 0.f;
#pragma unroll 1
                    for (int it = first; it < 96; it += NGRP) {
                        const int nb = it % 12, k0 = (cig * 4 + it / 12) * 64 + (lane >> 2);
                        const uint32_t sc = mapa(sbase + P1_OFF_EX + (k0 & 255) * 4, it / 48);
                        uint32_t* dst = reinterpret_cast<uint32_t*>(g_w2img[0]) + (k0 >> 4) * 3072 + nb * 256 + lane;
                        float bs[8] = {};
#pragma unroll 1
                        for (int c = 0; c < 8; c++) {
                            const uint4 u = __ldg(reinterpret_cast<const uint4*>(w2 + (size_t)(k0 + c * 8) * C_DIM + nb * 32) + (lane & 3));
                            const float b = __bfloat162float(grn_b[k0 + c * 8]);
                            float t;
                            asm volatile("ld.shared::cluster.f32 %0, [%1];\n" : "=f"(t) : "r"(sc + c * 32) : "memory");
#pragma unroll
                            for (int j = 0; j < 4; j++) {
                                const uint32_t v = j == 0 ? u.x : j == 1 ? u.y : j == 2 ? u.z : u.w;
                                mx = fmaxf(mx, fmaxf(fabsf(bf_lo(v)), fabsf(bf_hi(v))) * t);
                                if (pass) {
                                    bs[2 * j] = fmaf(b, bf_lo(v), bs[2 * j]);
                                    bs[2 * j + 1] = fmaf(b, bf_hi(v), bs[2 * j + 1]);
                                    uint32_t h = pack_f16(bf_lo(v) * t * gs, bf_hi(v) * t * gs);
                                    asm volatile("movmatrix.sync.aligned.m8n8.trans.b16 %0, %0;\n" : "+r"(h));
                                    dst[(c >> 1) * 3072 + (c & 1) * 32 + j * 64] = h;
                                }
                            }
                        }
                        if (pass) {
#pragma unroll
                            for (int j = 0; j < 8; j++) {
#pragma unroll
                                for (int o = 4; o < 32; o <<= 1) bs[j] += __shfl_xor_sync(0xffffffffu, bs[j], o);
                                if (lane >> 2 == j) atomicAdd(&sums[nb * 32 + (j >> 1) * 8 + (lane & 3) * 2 + (j & 1)], bs[j]);
                            }
                        }
                    }
                    if (!pass) {
                        const uint32_t m = __reduce_max_sync(0xffffffffu, __float_as_uint(mx));
                        if (lane == 0) {
                            atomicMax(flag, m);
                            asm volatile("red.release.gpu.global.add.u32 [%0], 1;\n" ::"l"(flag + 32) : "memory");
                        }
                        flag_wait<true>(flag + 32, NUM_CTAS / 2);
                        gs = w2_scale(__ldcg(flag));
                    }
                }
                do {
                    __nanosleep(1000);
                    asm volatile("ld.volatile.shared.u32 %0, [%1];\n" : "=r"(t) : "r"(sbase + P1_OFF_TILE + (lane & 3) * 16 + 8) : "memory");
                    SAFE_BREAK;
                } while (__all_sync(0xffffffffu, t < NT128 - P1_WPF));
                if (lane == 0 && blockIdx.x < 128)
                    asm volatile("cp.async.bulk.prefetch.L2.global [%0], %1;\n" ::"l"(g_w2img[0] + blockIdx.x * 576), "r"(18432) : "memory");
            }
        } else if (warp == 14) {
            int ph = 0;
#pragma unroll 1
            for (int i = ln0; i < NT128; i += LN_STEP, ph ^= 1) {
                mbar_wait(bar_done, ph);
                TRACEW(i / LN_STEP, 0);
                asm volatile("fence.proxy.async.global;\n" ::: "memory");
                if (elect_one()) asm volatile("red.release.gpu.global.add.u32 [%0], 1;\n" ::"l"(&g_flag[ln0 + ph * LN_STEP][0][0]) : "memory");
                __syncwarp();
                TRACEW(i / LN_STEP, 1);
            }
        }
        __syncwarp();
        cluster_sync();
    } else if (warp >= 8) {
        reg_dec<88>();
        asm volatile("barrier.cluster.arrive.relaxed.aligned;\n" ::: "memory");
        {
            const int l8 = lane & 7, row = (warp - 8) * 4 + (lane >> 3), px = (blockIdx.x & 3) * 32 + row;
            uint32_t d[6][4];
            const int n = (px & 64) + perm32(2 * row + ((px >> 5) & 1));
            uint8_t* const dst0 = ring + ln0 * LN_TILE + n * 128 + ((l8 ^ (n & 7)) << 4);
            const uint32_t src = sbase + P1_OFF_X + ((warp - 8) * 8 + (lane >> 3)) * (C_DIM * 2) + l8 * 16;
            int ph = 0;
#pragma unroll 1
            for (int i = ln0; i < NT128; i += LN_STEP, ph ^= 1) {
                TRACE(2, i / LN_STEP, 0);
                uint32_t off = 1;
#pragma unroll 1
                for (int ps = i == ln0 ? -2 : 0; ps < 2; ps += ps < 0 ? 2 : 1) {
                    if (ps == 0) {
                        if (i == ln0) asm volatile("barrier.cluster.wait.aligned;\n" ::: "memory");
                        mbar_wait(bar_xfull, ph);
                        asm volatile("ld.shared.u32 %0, [%1];\n" : "=r"(off) : "r"(bar_done + 8) : "memory");
                    }
                    if (ps == 0) TRACE(2, i / LN_STEP, 1);
                    if (i == ln0) {
#pragma unroll
                        for (int j = 0; j < 6; j++)
                            asm volatile("ld.shared.v4.u32 {%0,%1,%2,%3}, [%4];\n"
                                         : "=r"(d[j][0]), "=r"(d[j][1]), "=r"(d[j][2]), "=r"(d[j][3]) : "r"(sbase + P1_OFF_DW + j * 128 + l8 * 16) : "memory");
                    }
                    uint32_t v1[1][6][4];
                    uint32_t (&v)[6][4] = v1[0];
#pragma unroll
                    for (int j = 0; j < 6; j++)
                        asm volatile("ld.shared.v4.u32 {%0,%1,%2,%3}, [%4];\n"
                                     : "=r"(v[j][0]), "=r"(v[j][1]), "=r"(v[j][2]), "=r"(v[j][3]) : "r"(src + (ps & 1) * (4 * C_DIM * 2) + j * 128) : "memory");
                    ln_rows<P1_PACE, 1>(v1, d, bar_pace + (warp - 8) * 8, off, zero, ps == 1 && lane == 0 ? bar_xempty : 0);
                    uint8_t* dst = dst0 + ph * (LN_STEP * LN_TILE) + (ps & 1) * 4096;
#pragma unroll
                    for (int j = 0; j < 6; j++) *reinterpret_cast<uint4*>(dst + j * 16384) = make_uint4(v[j][0], v[j][1], v[j][2], v[j][3]);
                    TRACE(2, i / LN_STEP, 3 + (ps & 1));
                }
                asm volatile("fence.proxy.async.global;\nfence.acq_rel.cta;\n" ::: "memory");
                __syncwarp();
                if (lane == 0) mbar_arrive(bar_done);
                TRACE(2, i / LN_STEP, 5);
                TRACE(2, i / LN_STEP, 2);
            }
        }
        __syncwarp();
        cluster_sync();
    } else {
        const int wg = warp >> 2, w = warp & 3;
        auto load_w = [&](int i0, int i1) {
#pragma unroll 1
            for (int i = i0; i < i1; i++) {
                if (!(i & 1)) mbar_expect_tx(bar_w + (i >> 1) * 8, P1_W);
                tma2(sbase + (i & 2) * P1_W + (i >> 2) * P1_W + (i & 1) * (P1_W / 2), &wmap, cig * 256 + (i >> 1) * 64, (i & 1) * 192, bar_w + (i >> 1) * 8);
            }
        };
        if (warp == 4 && elect_one()) {
            mbar_init(bar_xfull, 2);
#pragma unroll
            for (int i = 0; i < 4; i++) mbar_init(bar_w + i * 8, 1);
            asm volatile("fence.mbarrier_init.release.cluster;\n" ::: "memory");
            mbar_expect_tx(bar_xfull, P1_X + C_DIM * 2);
            bulk_g2s(sbase + P1_OFF_X, xsrc, P1_X, bar_xfull);
            bulk_g2s(sbase + P1_OFF_DW, dw, C_DIM * 2, bar_xfull);
            load_w(0, 4);
            asm volatile("st.shared.u32 [%0], 1;\n" ::"r"(bar_done + 8) : "memory");
            mbar_arrive(bar_xfull);
        }
        if (warp == 5 && elect_one()) {
#pragma unroll
            for (int i = 0; i < P1_NST; i++) {
                mbar_init(bar_full + i * 8, 1);
                mbar_init(bar_empty + i * 8, i ? 8 : 8 + rank);
                if (i < 4) mbar_init(bar_pace + i * 8, 1);
            }
            mbar_init(bar_xempty, 4);
            mbar_init(bar_done, 4);
            asm volatile("fence.mbarrier_init.release.cluster;\n" ::: "memory");
        }
        __syncwarp();
        asm volatile("barrier.cluster.arrive.relaxed.aligned;\n" ::: "memory");
        reg_inc<192>();
        TRACEW(110 + warp, 1);
        uint32_t a[24][4];
        gdc_launch();
        const uint32_t src = sbase + wg * P1_W + ((lane >> 4) * 8 + (lane & 7)) * 128 + (((2 * w + ((lane >> 3) & 1)) ^ (lane & 7)) << 4);
        const uint32_t s_ex = sbase + P1_OFF_EX + (wg * 128 + w * 16 + (lane >> 2)) * 4;
        uint32_t sc2[2], ex[2];
        if (wg == 1) bar_arrive(1, 256);
#pragma unroll 1
        for (int it = 0; it < 2; it++) {
          if (it != wg) asm volatile("barrier.cluster.wait.aligned;\n" ::: "memory");
          if (it < wg) {
              mbar_wait(bar_xfull, 0);
              if (w == 0 && elect_one()) load_w(4, 8);
              __syncwarp();
          }
          if (it || wg == 0) {
            float t[2] = {0.f, 0.f};
            if (it) {
                TRACEW(110 + warp, 2);
                mbar_wait(bar_w + wg * 16, 0);
            }
            TRACEW(110 + warp, 5);
#pragma unroll
            for (int k = 0; k < 24; k++) ldsm4t(a[k], src + k * 2048);
            TRACEW(110 + warp, 6);
            p1_squares(a, t);
            sc2[0] = p1_exponents(t, ex, s_ex, lane);
            if (it && lane < 6) mbar_arrive_cluster(mapa(bar_empty, lane & 1) + (wg * 3 + (lane >> 1)) * 8 + (sc2[0] & zero));
            p1_convert<24>(a, a, ex);
          }
          if (it || wg == 1) {
            float t[2] = {0.f, 0.f};
            TRACEW(100 + warp, 0);
            if (it) mbar_wait(bar_w + wg * 16 + 8, 0);
            TRACEW(100 + warp, 1);
            uint32_t v[8][4], o[8][4];
#pragma unroll 1
            for (int j = 0; j <= 2 * it; j++) {
#pragma unroll
                for (int k = 0; k < 8; k++) ldsm4t(v[k], src + P1_OFF_W + (8 * j + k) * 2048);
                p1_squares(v, t);
            }
            sc2[1] = p1_exponents(t, ex, s_ex + 256, lane);
#pragma unroll 1
            for (int j = 2 * it; j >= 0; j--) {
                p1_convert<8>(o, v, ex);
#pragma unroll
                for (int k = 0; k < 8; k++) {
                    if (j) ldsm4t(v[k], src + P1_OFF_W + (8 * j - 8 + k) * 2048);
                    if (it) asm volatile("stmatrix.sync.aligned.m8n8.x4.trans.shared.b16 [%0], {%1,%2,%3,%4};\n"
                                         ::"r"(src + P1_OFF_W + (8 * j + k) * 2048), "r"(o[k][0]), "r"(o[k][1]), "r"(o[k][2]), "r"(o[k][3]) : "memory");
                }
            }
          }
        }
        asm volatile("fence.proxy.async.shared::cta;\n" ::: "memory");
        TRACEW(110 + warp, 7);
        bar_sync(6 + wg, 128);
        p1_consumer(a, sc2, sbase, wg, w, lane, zero);
        cluster_sync();
        TSTAMP(0, 30);
    }
}

constexpr int P2_B = 24576, P2_NB = 4;
constexpr int P2_A = 3072, P2_NA = 8;
constexpr int P2_XROW = C_DIM * 2;
constexpr int P2_OFF_A = P2_B * P2_NB;
constexpr int P2_OFF_X = P2_OFF_A + 3 * P2_NA * P2_A;
constexpr int P2_XHALF = 32 * P2_XROW + 64;
constexpr int P2_OFF_GRN = P2_OFF_X + 64 * P2_XROW + 128;
constexpr int P2_OFF_BIAS = P2_OFF_GRN + HID * 2;
constexpr int P2_OFF_RED = P2_OFF_BIAS + C_DIM * 4;
constexpr int P2_OFF_BAR = P2_OFF_RED + 192;
constexpr int P2_SMEM = P2_OFF_BAR + (2 * P2_NB + 6 * P2_NA + 7) * 8;
#define P2_S1 16
constexpr int P2_S2 = 32;
constexpr int P2_NCL = NUM_CTAS / 2, P2_ITEMS = NT128 / P2_NCL, P2_SHARED = NT128 - P2_ITEMS * P2_NCL;
constexpr int P2_NPOS = 6 * 48 + P2_S1;
constexpr int P2_RAW = 24;
constexpr int P2_XC = 8 * P2_XROW;
#define P2_T0 4
#define P2_SLACK 0
#define P2_RAMP 2
#define P2_LATE 88
#define P2_GATE 1
#define P2_AH 2
__device__ __forceinline__ int p2_start(int n) { return n < 0 ? 0 : n / 3 * 48 + (n % 3 == 1 ? P2_S1 : n % 3 * (P2_S2 / 2)); }
__device__ __forceinline__ int p2_tile(int cl, int n) {
    return n == 0 ? NT128 - 1 - cl : n < 0 ? NT128 - 1 - P2_NCL - (cl >> 1) : cl + P2_NCL * (n - 1);
}

#define P2_EB 2
#define P2_EX 1
__device__ __forceinline__ void p2_epilogue(uint32_t (&acc0)[48], uint32_t (&acc1)[48], uint32_t up, uint32_t sx, uint32_t sb, int zero) {
    uint32_t v[12][3][4];
    auto load = [&](int t, int j) {
        if (t >= 12) return;
        uint32_t (&w)[4] = v[t][j];
        asm volatile("ld.shared.v4.u32 {%0,%1,%2,%3}, [%4];\n" : "=r"(w[0]), "=r"(w[1]), "=r"(w[2]), "=r"(w[3])
                     : "r"((j ? sx + (j - 1) * 4 * P2_XROW : sb) + t * 64) : "memory");
    };
    auto store = [&](int t, int r) {
        const uint32_t* w = (t < 6 ? acc0 : acc1) + 8 * (t % 6) + 4 * r;
        asm volatile("st.shared.v4.u32 [%4], {%0,%1,%2,%3};\n" ::"r"(w[0]), "r"(w[1]), "r"(w[2]), "r"(w[3]), "r"(sx + t * 64 + r * 4 * P2_XROW) : "memory");
    };
#pragma unroll
    for (int t = 0; t < P2_EB; t++) load(t, 0);
#pragma unroll
    for (int t = 0; t < 2 * P2_EX; t++) load(t >> 1, 1 + (t & 1));
#pragma unroll
    for (int t = 0; t < 12; t++) {
        load(t + P2_EX, 1);
        load(t + P2_EX, 2);
        load(t + P2_EB, 0);
        uint32_t* acc = (t < 6 ? acc0 : acc1) + 8 * (t % 6);
        uint32_t y[8];
#pragma unroll
        for (int e = 0; e < 8; e++) {
            y[e] = h2_add(acc[e], v[t][0][e >> 1]);
            y[e] = pack_bf16(h_lo(y[e]), h_hi(y[e]));
        }
#pragma unroll
        for (int e = 0; e < 8; e++) acc[(e & 1) * 4 + (e >> 1)] = bf2_fma(y[e], up, v[t][1 + (e & 1)][e >> 1]);
        store(t, 0);
        store(t, 1);
        sched_break(zero);
    }
    if (zero) {
#pragma unroll
        for (int t = 0; t < 24; t++) store(t >> 1, t & 1);
    }
}

__device__ __forceinline__ void p2_unpack(uint32_t (&u)[4], uint32_t o1, uint32_t o2, uint32_t o3) {
    u[2] = bitsel(o1, 0x00040004u, SPARE);
    u[1] = bitsel(o2, 0x00040004u, SPARE);
    u[3] = bitsel(o3, 0x00040004u, SPARE);
    const uint32_t t = bitsel(prmt(o1, o2, 0x6341), prmt(o1, o3, 0x6240) << 3, 0x38383838u);
    u[0] = bitsel(bitsel(t, prmt(o2, o3, 0x7351) << 1, 0x80808080u), 0x00040004u, SPARE);
}

__global__ void __cluster_dims__(2, 1, 1) __launch_bounds__(512, 1)
pass2_kernel(const __nv_bfloat16* __restrict__ x, const __nv_bfloat16* __restrict__ grn_g, __nv_bfloat16* __restrict__ out, int zero) {
    extern __shared__ __align__(1024) uint8_t smem[];
    const uint32_t sbase = smem_u32(smem);
    const uint32_t bar_bfull = sbase + P2_OFF_BAR, bar_bempty = bar_bfull + P2_NB * 8;
    const uint32_t bar_afull = bar_bempty + P2_NB * 8, bar_aempty = bar_afull + 3 * P2_NA * 8;
    const uint32_t bar_xfull = bar_aempty + 3 * P2_NA * 8, bar_oready = bar_xfull + 24, s_pos = bar_oready + 24;
    int tid;
    asm volatile("mov.u32 %0, %%tid.x;\n" : "=r"(tid));
    const int warp = __shfl_sync(0xffffffffu, tid >> 5, 0), lane = tid & 31;
    const uint32_t rank = cluster_rank();
    const int cl = blockIdx.x >> 1, pair = cl >> 1;
    const int half = pair < P2_SHARED, fin = half && (cl & 1);
    const int k0 = (pair + 3 * (cl & 1)) % 6 * 8;
    const bool late = blockIdx.x >= P2_LATE;
    auto wait_pos = [&](int target) {
        int v;
        while (true) {
            asm volatile("ld.volatile.shared.u32 %0, [%1];\n" : "=r"(v) : "r"(s_pos) : "memory");
            if (v >= target) break;
            SAFE_BREAK;
            __nanosleep(100);
        }
    };

    TSTAMP(1, 0);
    if (tid == 384) {
        for (int i = 0; i < P2_NB; i++) {
            mbar_init(bar_bfull + i * 8, 1);
            mbar_init(bar_bempty + i * 8, 24);
        }
        for (int i = 0; i < 3 * P2_NA; i++) {
            mbar_init(bar_afull + i * 8, 1);
            mbar_init(bar_aempty + i * 8, 4);
        }
        for (int i = 0; i < 3; i++) {
            mbar_init(bar_xfull + i * 8, 2);
            mbar_init(bar_oready + i * 8, 4);
        }
        asm volatile("st.shared.u32 [%0], 0;\n" ::"r"(s_pos) : "memory");
        asm volatile("fence.mbarrier_init.release.cluster;\n" ::: "memory");
    }
    __syncthreads();
    cluster_sync_relaxed();

    if (warp >= 12) {
        reg_dec<32>();
        if (warp == 12) {
            const uint8_t* wsrc = reinterpret_cast<const uint8_t*>(g_w2img) + rank * (P2_B / 2);
            int kb = k0;
            gdc_wait();
            if (P2_GATE) bar_sync(5, 448);
#pragma unroll 1
            for (int p = 0; p < P2_NPOS; p++) {
                const int st = p & 3;
                if (p == P2_RAW) {
                    flag_wait<true>(&g_prog[1][0], NUM_CTAS);
                    asm volatile("fence.proxy.async.global;\n" ::: "memory");
                    wsrc += sizeof(g_w2img[0]);
                }
                const int idle = (p < P2_S1 || p >= 6 * 48) + (p < P2_S2 ? !half || p >= 24 : p >= 5 * 48 + P2_S2);
                mbar_wait(bar_bempty + st * 8, (~p >> 2) & 1);
                TR2(3, p, 0);
                if (elect_one()) {
                    const int len = P2_B / 2;
                    mbar_expect_tx(bar_bfull + st * 8, 2 * len);
                    bulk_g2s_mc(sbase + st * P2_B + rank * (P2_B / 2), wsrc + kb * P2_B, len, bar_bfull + st * 8, (uint16_t)3);
                    asm volatile("st.volatile.shared.u32 [%0], %1;\n" ::"r"(s_pos), "r"(p) : "memory");
                    if (rank == 0) asm volatile("red.relaxed.gpu.global.add.u32 [%0], 1;\n" ::"l"(&g_prog[0][0]) : "memory");
                    if (idle) asm volatile("mbarrier.arrive.shared::cta.b64 _, [%0], %1;\n" ::"r"(bar_bempty + st * 8), "r"(8 * idle) : "memory");
                }
                __syncwarp();
                if (++kb == 48) kb = 0;
            }
            mbar_wait(bar_bempty, 1);
            if (lane == 0) mbar_arrive(bar_bfull);
        } else if (warp == 13) {
            const int w = lane < 3 ? lane : 0;
            const uint32_t dst0 = sbase + P2_OFF_A + w * P2_NA * P2_A;
            const uint32_t bf = bar_afull + w * P2_NA * 8, be = bar_aempty + w * P2_NA * 8;
            int n = (w == 2 && half ? -1 : w) - 3, left = 0, u = 0, c = 0;
            const uint8_t* src = nullptr;
            bool act = lane < 3;
            gdc_wait();
            if (P2_GATE) bar_sync(5, 448);
            while (__any_sync(0xffffffffu, act)) {
                if (left == 0) {
                    n += 3;
                    left = n >= P2_ITEMS ? -1 : n < 0 ? 24 : 48;
                    u = (k0 + p2_start(n)) % 48;
                    src = reinterpret_cast<const uint8_t*>(g_h) + (size_t)p2_tile(cl, n) * (2 * H_TILE) + rank * H_HALF + u * H_STEP;
                }
                bool ok = act && mbar_test(be + ((c - 1) & 7) * 8, (~c >> 3) & 1);
                if (__any_sync(0xffffffffu, act && c < 16)) {
                    int v;
                    asm volatile("ld.volatile.shared.u32 %0, [%1];\n" : "=r"(v) : "r"(s_pos) : "memory");
                    ok = ok && c <= (n <= 0 ? 2 * v - P2_RAMP : c >= 16 ? c : v - p2_start(n) + 8);
                }
                if (ok) {
                    const int st = c & 7;
                    if (left > 0) {
                        mbar_expect_tx(bf + st * 8, P2_A);
                        bulk_g2s(dst0 + st * P2_A, src, P2_A, bf + st * 8);
                    } else {
                        mbar_arrive(bf + st * 8);
                        act = false;
                    }
                    src += H_STEP;
                    if (++u == 48) { u = 0; src -= 48 * H_STEP; }
                    c++;
                    left--;
                }
                SAFE_BREAK;
                if (!__any_sync(0xffffffffu, ok)) __nanosleep(100);
            }
        } else if (warp == 14) {
            const uint32_t sx = sbase + P2_OFF_X;
            size_t o = 0;
            int wp = 0;
            uint32_t par = 0;
            if (fin) {
#pragma unroll 1
                for (int c = lane * 16; c < 64 * P2_XROW + 128; c += 512) asm volatile("st.shared.v4.u32 [%0], {0, 0, 0, 0};\n" ::"r"(sx + c) : "memory");
                __syncwarp();
            }
            if (late) wait_pos(6);
#pragma unroll 1
            for (int n = -half; n <= P2_ITEMS; n++) {
                const int w = (n + 3) % 3, end = p2_start(n) + 48;
                const size_t on = (size_t)(2 * p2_tile(cl, n) + rank) * (64 * C_DIM * 2);
                const uint32_t xf = bar_xfull + w * 8;
                bool st = n + half > 0;
                const bool ld = n < P2_ITEMS && !(n < 0 && fin);
                if (n == P2_ITEMS - 1 && lane == 0)
                    asm volatile("cp.async.bulk.prefetch.L2.global [%0], %1;\n" ::"l"(reinterpret_cast<const uint8_t*>(x) + on), "r"(64 * P2_XROW) : "memory");
                if (st) {
                    mbar_wait(bar_oready + wp * 8, (par >> wp) & 1);
                    par ^= 1u << wp;
                }
                if (lane == 0) {
                    if (n < P2_ITEMS) mbar_expect_tx(xf, ld ? 64 * C_DIM * 2 : 0);
                    const int t0 = (n ? p2_start(n - 1) + 48 : P2_S2) + P2_T0, dt = end - t0;
                    int t = st && n < P2_ITEMS - 1 ? 16 * t0 : -4096;
                    if ((n == 0 && half) || n >= P2_ITEMS - 1) {
                        if (fin && n == 0) {
                            flag_wait<true>(&g_half[pair][rank], 1);
                            asm volatile("fence.proxy.async.global;\n" ::: "memory");
                        }
#pragma unroll 1
                        for (int c = 0; c < 2; c++) {
                            uint8_t* dst = reinterpret_cast<uint8_t*>(out) + o + c * 32 * P2_XROW;
                            if (!fin || n) bulk_s2g(dst, sx + c * P2_XHALF, 32 * P2_XROW);
                            else asm volatile("cp.reduce.async.bulk.global.shared::cta.bulk_group.add.noftz.bf16 [%0], [%1], %2;\n"
                                              ::"l"(dst), "r"(sx + c * P2_XHALF), "r"(32 * P2_XROW) : "memory");
                        }
                        asm volatile("cp.async.bulk.commit_group;\n" ::: "memory");
                        if (!fin && n == 0) {
                            asm volatile("cp.async.bulk.wait_group 0;\nfence.proxy.async.global;\n" ::: "memory");
                            asm volatile("st.release.gpu.global.u32 [%0], 1;\n" ::"l"(&g_half[pair][rank]) : "memory");
                        }
                        st = false;
                    }
#pragma unroll 1
                    for (int c = 0; c < 64 * P2_XROW; c += P2_XC, t += 2 * dt) {
                        const uint32_t sp = sx + c + (c >= 32 * P2_XROW ? 64 : 0);
                        wait_pos(t >> 4);
                        if (st) bulk_s2g(reinterpret_cast<uint8_t*>(out) + o + c, sp, P2_XC);
                        asm volatile("cp.async.bulk.commit_group;\n" ::: "memory");
                        if (ld) {
                            wait_pos((t + dt) >> 4);
                            asm volatile("cp.async.bulk.wait_group.read 0;\n" ::: "memory");
                            bulk_g2s(sp, reinterpret_cast<const uint8_t*>(x) + on + c, P2_XC, xf);
                        }
                    }
                    if (rank == 0 && n > 0 && n < P2_ITEMS - 1) flag_wait<false>(&g_prog[0][0], P2_NCL * (end + P2_SLACK));
                    if (n < P2_ITEMS) mbar_arrive(xf);
                }
                __syncwarp();
                o = on;
                wp = w;
            }
            asm volatile("cp.async.bulk.wait_group 0;\n" ::: "memory");
        } else if (blockIdx.x == 120) {
            gdc_wait();
            for (int i = lane; i < (LN_RING + 3) * 2; i += 32) (&g_flag[0][0][0])[i * 8] = 0;
            if (lane == 0) g_epoch++;
        }
        __syncwarp();
        cluster_sync();
    } else {
        reg_inc<160>();
        const int wg = warp >> 2, w = warp & 3, g = lane >> 2, q = lane & 3;
        const uint32_t sx = sbase + P2_OFF_X + (g & 1) * P2_XHALF + (w * 8 + (g >> 1)) * P2_XROW + q * 16;
        const uint32_t af = bar_afull + wg * P2_NA * 8;
        const uint32_t s_a = sbase + P2_OFF_A + wg * P2_NA * P2_A + (lane >> 3) * 512 + (lane & 7) * 64 + ((w ^ ((lane & 7) >> 1)) << 4);
        uint32_t acc0[48], acc1[48], up;
        uint4 a[2][2];

        __nv_bfloat16 gg[4];
#pragma unroll
        for (int i = 0; i < 4; i++) gg[i] = grn_g[tid + 384 * i];
#pragma unroll 1
        for (int it = late; it < 2; it++) {
            float* s_red = reinterpret_cast<float*>(smem + P2_OFF_RED);
            float gx[6], part = 0.f;
            if (it) {
                TSTAMP(1, 27);
                gdc_wait();
                TSTAMP(1, 1);
            }
            float gy[6];
#pragma unroll
            for (int i = 0; i < 6; i++) {
                const float* p = &g_sums[0][i < 5 ? tid + 384 * i : HID + C_DIM];
                asm volatile("ld.global.cg.f32 %0, [%1];\n" : "=f"(gx[i]) : "l"(p) : "memory");
                asm volatile("ld.global.cg.f32 %0, [%1];\n" : "=f"(gy[i]) : "l"(p + HID + 512) : "memory");
            }
            if (P2_GATE && it) bar_arrive(5, 448);
            const float bias = gx[4] + gy[4];
            const float gs = w2_scale(__float_as_uint(gx[5]) | __float_as_uint(gy[5]));
            float mg = 0.f;
#pragma unroll
            for (int i = 0; i < 4; i++) {
                gx[i] = gx[i] + gy[i];
                gx[i] = __fsqrt_rn(gx[i] * (HSCALE * HSCALE) + 1e-6f);
                part += gx[i];
                gx[i] *= __bfloat162float(gg[i]);
                mg = fmaxf(mg, fabsf(gx[i]));
            }
#pragma unroll
            for (int o = 16; o > 0; o >>= 1) part += __shfl_xor_sync(0xffffffffu, part, o);
            const uint32_t mgw = __reduce_max_sync(0xffffffffu, __float_as_uint(mg));
            const uint32_t mbw = __reduce_max_sync(0xffffffffu, __float_as_uint(fabsf(bias)));
            TSTAMP(1, 26);
            if (lane == 0) *reinterpret_cast<float4*>(s_red + warp * 4) = make_float4(part, __uint_as_float(mgw), __uint_as_float(mbw), 0.f);
            bar_sync(1, 384);
            float tot = 0.f, mb = 0.f;
#pragma unroll
            for (int i = 0; i < 12; i++) {
                const float4 t = *reinterpret_cast<const float4*>(s_red + i * 4);
                tot += t.x;
                mg = fmaxf(mg, t.y);
                mb = fmaxf(mb, t.z);
            }
            const float inv = 1.0f / (tot * (1.0f / HID) + 1e-6f);
            const uint32_t ej = min((__float_as_uint(fmaxf(fmaf(mg, inv, 1.0f) * HSCALE, mb * gs * 0x1p-13f)) >> 23) + 1, 250u);
            const float dn = __uint_as_float((254u - ej) << 23);
            up = min(ej + 127u - (__float_as_uint(gs) >> 23), 254u) * 0x00800080u;
            reinterpret_cast<uint16_t*>(smem + P2_OFF_BIAS + C_DIM * 2)[tid] = 0;
            *reinterpret_cast<__half*>(smem + P2_OFF_BIAS + (tid >> 5) * 64 + (tid & 6) * 8 + (tid & 24) / 2 + (tid & 1) * 2) = __float2half_rn(bias * gs * dn);
#pragma unroll
            for (int i = 0; i < 4; i++) {
                const int k = tid + 384 * i;
                *reinterpret_cast<__half*>(smem + P2_OFF_GRN + (k >> 4) * 32 + (k & 6) * 4 + (k & 8) / 2 + (k & 1) * 2) =
                    __float2half_rn(fmaf(gx[i], inv, 1.0f) * (HSCALE * dn));
            }
            TSTAMP(1, 25);
            bar_sync(1, 384);
        }
        TSTAMP(1, 28);
        if (wg == 1) {
            constexpr int N = sizeof(g_w2img[0]) / 16, PER = (N + NUM_CTAS - 1) / NUM_CTAS;
            uint4 v[5];
#pragma unroll
            for (int i = 0; i < 5; i++) v[i] = __ldcg(&g_w2img[0][min(blockIdx.x * PER + (tid & 127) + 128 * i, N - 1)]);
#pragma unroll
            for (int i = 0; i < 5; i++) {
                const int j = min(blockIdx.x * PER + (tid & 127) + 128 * i, N - 1);
                const uint32_t* t = reinterpret_cast<const uint32_t*>(smem + P2_OFF_GRN + (j / 768) * 32 + (j & 8) / 2);
                auto sc = [&](uint32_t u, int e) { return (h2_mul(u, t[2 * e]) + 0x00040004u) & 0xfff8fff8u; };
                g_w2img[1][j] = make_uint4(sc(v[i].x, 0), sc(v[i].y, 1), sc(v[i].z, 2), sc(v[i].w, 3));
            }
            asm volatile("fence.proxy.async.global;\n" ::: "memory");
            bar_sync(2, 128);
            if (tid == 128) asm volatile("fence.acq_rel.gpu;\nred.release.gpu.global.add.u32 [%0], 1;\n" ::"l"(&g_prog[1][0]) : "memory");
        }

        const int who = __shfl_sync(0xffffffffu, lane == 2 ? 0 : lane < 2 ? 1 : 2, lane);
        const uint32_t rel0 = who ? mapa(bar_bempty, lane & 1) : mapa(bar_aempty + wg * P2_NA * 8, rank), rel1 = rel0 + (who ? 0 : 32);
        auto publish = [&]() {
            asm volatile("fence.proxy.async.shared::cta;\n" ::: "memory");
            __syncwarp();
            if (who == 0) mbar_arrive(bar_oready + wg * 8);
        };
        bool ok_a, pend = false;
        uint32_t pa = 0, s_t;
        auto fetch = [&](int j, bool raw) {
            uint32_t o[6], u0[4], u1[4];
            uint2 t0 = make_uint2(0, 0), t1 = t0;
            if (raw) {
                asm volatile("ld.shared.v2.u32 {%0,%1}, [%2];\n" : "=r"(t0.x), "=r"(t0.y) : "r"(s_t + j * 64) : "memory");
                asm volatile("ld.shared.v2.u32 {%0,%1}, [%2];\n" : "=r"(t1.x), "=r"(t1.y) : "r"(s_t + j * 64 + 32) : "memory");
            }
            const bool ok_b = mbar_test(bar_bfull + (j & 3) * 8, j >> 2);
            if (j == 7) pa ^= 1;
            ok_a = mbar_test(af + ((j + 1) & 7) * 8, pa);
            asm volatile("ldmatrix.sync.aligned.m8n8.x4.trans.shared.b16 {%0,%1,%2,%3}, [%4];\n"
                         : "=r"(o[0]), "=r"(o[1]), "=r"(o[2]), "=r"(o[3]) : "r"(s_a + j * P2_A) : "memory");
            asm volatile("ldmatrix.sync.aligned.m8n8.x2.trans.shared.b16 {%0,%1}, [%2];\n"
                         : "=r"(o[4]), "=r"(o[5]) : "r"(s_a + j * P2_A + 2048) : "memory");
            p2_unpack(u0, o[0], o[1], o[2]);
            p2_unpack(u1, o[3], o[4], o[5]);
            if (raw) {
                u0[0] = h2_mul(u0[0], t0.x); u0[1] = h2_mul(u0[1], t0.x); u0[2] = h2_mul(u0[2], t0.y); u0[3] = h2_mul(u0[3], t0.y);
                u1[0] = h2_mul(u1[0], t1.x); u1[1] = h2_mul(u1[1], t1.x); u1[2] = h2_mul(u1[2], t1.y); u1[3] = h2_mul(u1[3], t1.y);
            }
            a[j & 1][0] = make_uint4(u0[0], u0[1], u0[2], u0[3]);
            a[j & 1][1] = make_uint4(u1[0], u1[1], u1[2], u1[3]);
            if (!ok_b) mbar_wait(bar_bfull + (j & 3) * 8, j >> 2);
        };
        auto table = [&](int pos) { s_t = sbase + P2_OFF_GRN + q * 8 + (k0 + pos) % 48 * 64; };
        const uint64_t db0 = make_desc(sbase, 128, 256);
        auto block8 = [&](bool raw, int pos, int thr0, int mode) {
#pragma unroll
            for (int j = 0; j < 8; j++) {
                const uint64_t db = db0 + (j & 3) * (P2_B / 16);
                if (j == 8 - P2_AH && mode == 1) bar_sync(4, 384);
                TR2(wg, pos + j, 0);
                wg_fence();
                mma_rs_n192(acc0, a[j & 1][0], db);
                mma_rs_n192(acc1, a[j & 1][0], db + 384);
                mma_rs_n192(acc0, a[j & 1][1], db + 768);
                mma_rs_n192(acc1, a[j & 1][1], db + 768 + 384);
                wg_commit();
                if (j == 7 && mode == 2) bar_arrive(4, 384);
                const uint32_t rel = ((j - 1) & 4 ? rel1 : rel0) + ((j - 1) & 3) * 8;
                TR2(wg, pos + j, 1);
                wg_wait<1>();
                TR2(wg, pos + j, 2);
                if (who < (j ? 2 : thr0)) mbar_arrive_cluster(rel);
                if (!ok_a) {
                    if (j == 0 && pend) { publish(); pend = false; }
                    mbar_wait(af + ((j + 1) & 7) * 8, pa);
                }
                TR2(wg, pos + j, 3);
                if (raw && j == 7) table(pos + 8);
                fetch((j + 1) & 7, raw && (j < 7 || pos + 8 < P2_RAW));
            }
        };
        int n = wg == 2 && half ? -1 : wg, pos = p2_start(n);
        uint32_t px = 0;
        wait_pos(pos);
        mbar_wait(af, 0);
        table(pos);
        fetch(0, pos < P2_RAW);
#pragma unroll 1
        for (;; n += 3) {
            TSTAMP(1, 2 + n);
            const int end = pos + (n < 0 ? 24 : 48);
#pragma unroll
            for (int i = 0; i < 48; i += 2) {
                asm volatile("mov.b64 {%0, %1}, 0;\n" : "=r"(acc0[i]), "=r"(acc0[i + 1]));
                asm volatile("mov.b64 {%0, %1}, 0;\n" : "=r"(acc1[i]), "=r"(acc1[i + 1]));
            }
            int thr = 1;
#pragma unroll 1
            for (; pos < P2_RAW; pos += 8, thr = 2) block8(true, pos, thr, 0);
#pragma unroll 1
            for (; pos < end; pos += 8, thr = 2) {
                const int e = pos + 8, r = e % 48;
                block8(false, pos, thr, e < 48 || e > 256 || (r != 0 && r != P2_S1 && r != P2_S2) ? 0 : e == end ? 2 : 1);
            }
            TR2(wg, pos - 1, 4);
            wg_wait<0>();
            TR2(wg, pos - 1, 5);
            if (who == 1) mbar_arrive_cluster(rel0 + 24);
            mbar_wait(bar_xfull + wg * 8, px);
            TR2(wg, pos - 1, 6);
            px ^= 1;
            __syncwarp();
            p2_epilogue(acc0, acc1, up, sx, sbase + P2_OFF_BIAS + q * 16 + (n < 0 && fin ? C_DIM * 2 : 0), zero);
            TR2(wg, pos - 1, 7);
            if (n + 3 >= P2_ITEMS) { publish(); break; }
            if (n < 0) {
                publish();
                pos = P2_S2;
                wait_pos(pos);
                mbar_wait(bar_bfull, 0);
            } else {
                pend = true;
                ok_a = false;
            }
        }
        TSTAMP(1, 29);
        cluster_sync();
        TSTAMP(1, 30);
    }
}

}

extern "C" void kernel_launch(void* const* d_in, const int* in_sizes, int n_in, void* d_out, int out_size) {
    const __nv_bfloat16* x = (const __nv_bfloat16*)d_in[0];
    const __nv_bfloat16* dw = (const __nv_bfloat16*)d_in[1];
    const __nv_bfloat16* w1 = (const __nv_bfloat16*)d_in[2];
    const __nv_bfloat16* w2 = (const __nv_bfloat16*)d_in[3];
    const __nv_bfloat16* grn_g = (const __nv_bfloat16*)d_in[4];
    const __nv_bfloat16* grn_b = (const __nv_bfloat16*)d_in[5];
    __nv_bfloat16* out = (__nv_bfloat16*)d_out;

    cudaFuncSetAttribute(pass1_kernel, cudaFuncAttributeMaxDynamicSharedMemorySize, P1_SMEM);
    cudaFuncSetAttribute(pass2_kernel, cudaFuncAttributeMaxDynamicSharedMemorySize, P2_SMEM);

    typedef CUresult (*EncodeFn)(CUtensorMap*, CUtensorMapDataType, cuuint32_t, void*, const cuuint64_t*, const cuuint64_t*,
                                 const cuuint32_t*, const cuuint32_t*, CUtensorMapInterleave, CUtensorMapSwizzle,
                                 CUtensorMapL2promotion, CUtensorMapFloatOOBfill);
    static EncodeFn encode = nullptr;
    if (!encode) {
        cudaDriverEntryPointQueryResult qres;
        cudaGetDriverEntryPoint("cuTensorMapEncodeTiled", (void**)&encode, cudaEnableDefault, &qres);
    }
    CUtensorMap wmap;
    const cuuint64_t gdim[2] = {HID, C_DIM};
    const cuuint64_t gstr[1] = {HID * 2};
    const cuuint32_t box[2] = {64, 192}, estr[2] = {1, 1};
    CUresult er = encode(&wmap, CU_TENSOR_MAP_DATA_TYPE_BFLOAT16, 2, (void*)w1, gdim, gstr, box, estr, CU_TENSOR_MAP_INTERLEAVE_NONE,
           CU_TENSOR_MAP_SWIZZLE_128B, CU_TENSOR_MAP_L2_PROMOTION_L2_128B, CU_TENSOR_MAP_FLOAT_OOB_FILL_NONE);
    if (er != CUDA_SUCCESS) printf("tensor map encode failed %d\n", (int)er);

    pass1_kernel<<<NUM_CTAS, 512, P1_SMEM>>>(wmap, x, dw, w2, grn_b, 0);

    cudaLaunchAttribute attr[1];
    attr[0].id = cudaLaunchAttributeProgrammaticStreamSerialization;
    attr[0].val.programmaticStreamSerializationAllowed = 1;
    cudaLaunchConfig_t cfg = {};
    cfg.gridDim = dim3(NUM_CTAS);
    cfg.stream = 0;
    cfg.attrs = attr;
    cfg.numAttrs = 1;
    cfg.blockDim = dim3(512);
    cfg.dynamicSmemBytes = P2_SMEM;
    cudaLaunchKernelEx(&cfg, pass2_kernel, x, grn_g, out, 0);
}
```

```cpp
#include <cuda.h>
#include <cuda_runtime.h>
#include <cuda_bf16.h>
#include <cuda_fp16.h>
#include <stdint.h>
#include <stdio.h>

namespace {

constexpr int M_TOTAL = 384 * 384;
constexpr int C_DIM   = 384;
constexpr int HID     = 1536;
constexpr int NT128   = M_TOTAL / 128;
constexpr int NUM_CTAS = 132;

constexpr int NGRP = 22, GRP_CTAS = 6;
constexpr int LN_STEP = NUM_CTAS / 4, LN_RING = 2 * LN_STEP;
constexpr int LN_TILE = 128 * C_DIM * 2;
constexpr int H_TILE = 64 * HID * 3 / 2;
constexpr int H_HALF = 3072, H_STEP = 6144;

__device__ __align__(1024) uint4 g_h[(size_t)M_TOTAL * HID * 3 / 32];
__device__ __align__(1024) uint4 g_ln[LN_RING * LN_TILE / 16];
__device__ __align__(1024) uint4 g_w2img[2][HID * C_DIM * 2 / 16];
__device__ __align__(16) float g_sums[2][HID + 512];
__device__ float g_scale[HID];
__device__ float g_redo[HID];
__device__ unsigned g_epoch;
__device__ __align__(128) unsigned g_prog[3][32];
__device__ __align__(128) unsigned g_half[32][2];
__device__ unsigned g_flag[LN_RING + 3][2][8];
#define TSTAMP(k, i)
#define TRACE(wg, pos, i)
#define TRACEW(pos, i)

#define TR2(wg, pos, i)
__host__ __device__ __forceinline__ int perm32(int n) {
    return (n & ~31) | (((n >> 1) & 3) << 3) | (((n >> 3) & 3) << 1) | (n & 1);
}

__device__ __forceinline__ uint32_t smem_u32(const void* p) { return (uint32_t)__cvta_generic_to_shared(p); }

__device__ __forceinline__ void mbar_init(uint32_t bar, uint32_t count) {
    asm volatile("mbarrier.init.shared::cta.b64 [%0], %1;\n" ::"r"(bar), "r"(count) : "memory");
}
__device__ __forceinline__ void mbar_expect_tx(uint32_t bar, uint32_t bytes) {
    asm volatile("mbarrier.arrive.expect_tx.shared::cta.b64 _, [%0], %1;\n" ::"r"(bar), "r"(bytes) : "memory");
}
__device__ __forceinline__ void mbar_arrive(uint32_t bar) {
    asm volatile("mbarrier.arrive.shared::cta.b64 _, [%0];\n" ::"r"(bar) : "memory");
}
__device__ __forceinline__ void mbar_arrive_cluster(uint32_t bar_cluster_addr) {
    asm volatile("mbarrier.arrive.shared::cluster.b64 _, [%0];\n" ::"r"(bar_cluster_addr) : "memory");
}
#define SAFE_BREAK
__device__ __forceinline__ void mbar_wait(uint32_t bar, uint32_t parity) {
    asm volatile(
        "{\n"
        ".reg .pred p;\n"
        "LAB_WAIT:\n"
        "mbarrier.try_wait.parity.shared::cta.b64 p, [%0], %1;\n"
        "@!p bra LAB_WAIT;\n"
        "}\n" ::"r"(bar), "r"(parity) : "memory");
}
__device__ __forceinline__ bool mbar_test(uint32_t bar, uint32_t parity) {
    uint32_t ok;
    asm volatile("{\n.reg .pred p;\n"
                 "mbarrier.test_wait.parity.shared::cta.b64 p, [%1], %2;\n"
                 "selp.u32 %0, 1, 0, p;\n}\n" : "=r"(ok) : "r"(bar), "r"(parity) : "memory");
    return ok != 0;
}
__device__ __forceinline__ uint32_t mapa(uint32_t addr, uint32_t rank) {
    uint32_t r;
    asm volatile("mapa.shared::cluster.u32 %0, %1, %2;\n" : "=r"(r) : "r"(addr), "r"(rank));
    return r;
}
__device__ __forceinline__ void bulk_g2s(uint32_t dst, const void* src, uint32_t bytes, uint32_t bar) {
    asm volatile("cp.async.bulk.shared::cluster.global.mbarrier::complete_tx::bytes [%0], [%1], %2, [%3];\n"
                 ::"r"(dst), "l"(src), "r"(bytes), "r"(bar) : "memory");
}
__device__ __forceinline__ void bulk_g2s_mc(uint32_t dst, const void* src, uint32_t bytes, uint32_t bar, uint16_t mask) {
    asm volatile("cp.async.bulk.shared::cluster.global.mbarrier::complete_tx::bytes.multicast::cluster [%0], [%1], %2, [%3], %4;\n"
                 ::"r"(dst), "l"(src), "r"(bytes), "r"(bar), "h"(mask) : "memory");
}
__device__ __forceinline__ void tma2(uint32_t dst, const CUtensorMap* map, int c0, int c1, uint32_t bar) {
    asm volatile("cp.async.bulk.tensor.2d.shared::cluster.global.tile.mbarrier::complete_tx::bytes [%0], [%1, {%2, %3}], [%4];\n"
                 ::"r"(dst), "l"(map), "r"(c0), "r"(c1), "r"(bar) : "memory");
}
template <bool ACQ>
__device__ __forceinline__ uint32_t flag_wait(const unsigned* p, unsigned target) {
    unsigned v, n = 0;
    do {
        if (ACQ) asm volatile("ld.acquire.gpu.global.u32 %0, [%1];\n" : "=r"(v) : "l"(p) : "memory");
        else asm volatile("ld.relaxed.gpu.global.u32 %0, [%1];\n" : "=r"(v) : "l"(p) : "memory");
        n++;
    } while (v < target);
    return n == 1;
}
__device__ __forceinline__ void ldsm4t(uint32_t (&r)[4], uint32_t addr) {
    asm volatile("ldmatrix.sync.aligned.m8n8.x4.trans.shared.b16 {%0,%1,%2,%3}, [%4];\n"
                 : "=r"(r[0]), "=r"(r[1]), "=r"(r[2]), "=r"(r[3]) : "r"(addr) : "memory");
}
__device__ __forceinline__ void bulk_s2g(void* dst, uint32_t src, uint32_t bytes) {
    asm volatile("cp.async.bulk.global.shared::cta.bulk_group [%0], [%1], %2;\n" ::"l"(dst), "r"(src), "r"(bytes) : "memory");
}
__device__ __forceinline__ void cluster_sync() {
    asm volatile("barrier.cluster.arrive.aligned;\nbarrier.cluster.wait.aligned;\n" ::: "memory");
}
__device__ __forceinline__ void cluster_sync_relaxed() {
    asm volatile("barrier.cluster.arrive.relaxed.aligned;\nbarrier.cluster.wait.aligned;\n" ::: "memory");
}
__device__ __forceinline__ void gdc_wait() { asm volatile("griddepcontrol.wait;\n" ::: "memory"); }
__device__ __forceinline__ void gdc_launch() { asm volatile("griddepcontrol.launch_dependents;\n" ::: "memory"); }
__device__ __forceinline__ uint32_t cluster_rank() {
    uint32_t r;
    asm volatile("mov.u32 %0, %%cluster_ctarank;\n" : "=r"(r));
    return r;
}
__device__ __forceinline__ bool elect_one() {
    uint32_t pred;
    asm volatile("{\n.reg .pred p;\nelect.sync _|p, 0xffffffff;\nselp.u32 %0, 1, 0, p;\n}\n" : "=r"(pred));
    return pred != 0;
}
__device__ __forceinline__ void wg_fence() { asm volatile("wgmma.fence.sync.aligned;\n" ::: "memory"); }
__device__ __forceinline__ void wg_commit() { asm volatile("wgmma.commit_group.sync.aligned;\n" ::: "memory"); }
template <int N> __device__ __forceinline__ void wg_wait() {
    asm volatile("wgmma.wait_group.sync.aligned %0;\n" ::"n"(N) : "memory");
}
template <int R> __device__ __forceinline__ void reg_inc() { asm volatile("setmaxnreg.inc.sync.aligned.u32 %0;\n" ::"n"(R)); }
template <int R> __device__ __forceinline__ void reg_dec() { asm volatile("setmaxnreg.dec.sync.aligned.u32 %0;\n" ::"n"(R)); }
__device__ __forceinline__ void bar_sync(int id, int n) { asm volatile("bar.sync %0, %1;\n" ::"r"(id), "r"(n) : "memory"); }
__device__ __forceinline__ void bar_arrive(int id, int n) { asm volatile("bar.arrive %0, %1;\n" ::"r"(id), "r"(n) : "memory"); }

__device__ __forceinline__ uint64_t make_desc(uint32_t saddr, uint32_t lbo, uint32_t sbo) {
    return (uint64_t)((saddr & 0x3FFFF) >> 4) | ((uint64_t)(lbo >> 4) << 16) | ((uint64_t)(sbo >> 4) << 32);
}

__device__ __forceinline__ void stg128_cs(void* p, uint32_t a, uint32_t b, uint32_t c, uint32_t d) {
    asm volatile("st.global.cs.v4.u32 [%0], {%1,%2,%3,%4};\n" ::"l"(p), "r"(a), "r"(b), "r"(c), "r"(d) : "memory");
}
__device__ __forceinline__ uint32_t pack_bf16(float lo, float hi) {
    uint32_t r;
    asm("cvt.rn.bf16x2.f32 %0, %1, %2;\n" : "=r"(r) : "f"(hi), "f"(lo));
    return r;
}
__device__ __forceinline__ float bf_lo(uint32_t v) { return __uint_as_float(v << 16); }
__device__ __forceinline__ float bf_hi(uint32_t v) { return __uint_as_float(v & 0xffff0000u); }
__device__ __forceinline__ uint32_t bf2_mul(uint32_t a, uint32_t b) {
    uint32_t r;
    asm("mul.rn.bf16x2 %0, %1, %2;\n" : "=r"(r) : "r"(a), "r"(b));
    return r;
}
__device__ __forceinline__ uint32_t bf2_fma(uint32_t a, uint32_t b, uint32_t c) {
    uint32_t r;
    asm("fma.rn.bf16x2 %0, %1, %2, %3;\n" : "=r"(r) : "r"(a), "r"(b), "r"(c));
    return r;
}
__device__ __forceinline__ uint32_t bf2_add(uint32_t a, uint32_t b) {
    uint32_t r;
    asm("add.rn.bf16x2 %0, %1, %2;\n" : "=r"(r) : "r"(a), "r"(b));
    return r;
}
__device__ __forceinline__ uint32_t h2_mul(uint32_t a, uint32_t b) {
    uint32_t r;
    asm("mul.rn.f16x2 %0, %1, %2;\n" : "=r"(r) : "r"(a), "r"(b));
    return r;
}
__device__ __forceinline__ uint32_t h2_fma(uint32_t a, uint32_t b, uint32_t c) {
    uint32_t r;
    asm("fma.rn.f16x2 %0, %1, %2, %3;\n" : "=r"(r) : "r"(a), "r"(b), "r"(c));
    return r;
}
__device__ __forceinline__ uint32_t h2_add(uint32_t a, uint32_t b) {
    uint32_t r;
    asm("add.rn.f16x2 %0, %1, %2;\n" : "=r"(r) : "r"(a), "r"(b));
    return r;
}
__device__ __forceinline__ uint32_t pack_f16(float lo, float hi) {
    uint32_t r;
    asm("cvt.rn.f16x2.f32 %0, %1, %2;\n" : "=r"(r) : "f"(hi), "f"(lo));
    return r;
}
__device__ __forceinline__ float h_lo(uint32_t v) { return __low2float(*reinterpret_cast<const __half2*>(&v)); }
__device__ __forceinline__ float h_hi(uint32_t v) { return __high2float(*reinterpret_cast<const __half2*>(&v)); }
__device__ __forceinline__ uint32_t bf2_to_h2(uint32_t v) { return (v & 0x7fff7fffu) * 7u + v; }
__device__ __forceinline__ uint32_t prmt(uint32_t a, uint32_t b, uint32_t sel) {
    uint32_t r;
    asm("prmt.b32 %0, %1, %2, %3;\n" : "=r"(r) : "r"(a), "r"(b), "r"(sel));
    return r;
}
__device__ __forceinline__ uint32_t bitsel(uint32_t a, uint32_t b, uint32_t m) {
    uint32_t r;
    asm("lop3.b32 %0, %1, %2, %3, 0xd8;\n" : "=r"(r) : "r"(a), "r"(b), "r"(m));
    return r;
}
constexpr float KAPPA = 0.3292034911525734f;
constexpr uint32_t GELU_C2 = 0x40d940d9u;
constexpr float HSCALE = 1.0f / (2.0f * KAPPA);
__device__ __forceinline__ float w2_scale(uint32_t m) { return __uint_as_float((257u - max(m >> 23, 16u)) << 23); }
__device__ __forceinline__ void sched_break(int zero) {
    asm volatile("{\n.reg .pred p;\nsetp.ne.s32 p, %0, 0;\nSB_LOOP:\n@p nanosleep.u32 1;\n@p bra SB_LOOP;\n}\n" ::"r"(zero));
}

#define ACC8(d, o) "+r"(d[o + 0]), "+r"(d[o + 1]), "+r"(d[o + 2]), "+r"(d[o + 3]), "+r"(d[o + 4]), "+r"(d[o + 5]), "+r"(d[o + 6]), "+r"(d[o + 7])

__device__ __forceinline__ void mma_rs_n128(uint32_t (&d)[32], const uint32_t (&a)[4], uint64_t desc, int scale_d) {
    asm volatile(
        "{\n.reg .pred p;\nsetp.ne.b32 p, %37, 0;\n"
        "wgmma.mma_async.sync.aligned.m64n128k16.f16.f16.f16 "
        "{%0,%1,%2,%3,%4,%5,%6,%7,%8,%9,%10,%11,%12,%13,%14,%15,"
        "%16,%17,%18,%19,%20,%21,%22,%23,%24,%25,%26,%27,%28,%29,%30,%31},"
        "{%32,%33,%34,%35}, %36, p, 1, 1, 0;\n}\n"
        : ACC8(d, 0), ACC8(d, 8), ACC8(d, 16), ACC8(d, 24)
        : "r"(a[0]), "r"(a[1]), "r"(a[2]), "r"(a[3]), "l"(desc), "r"(scale_d));
}

__device__ __forceinline__ void mma_ss_n128(uint32_t (&d)[32], uint64_t da, uint64_t db, int scale_d) {
    asm volatile(
        "{\n.reg .pred p;\nsetp.ne.b32 p, %34, 0;\n"
        "wgmma.mma_async.sync.aligned.m64n128k16.f16.f16.f16 "
        "{%0,%1,%2,%3,%4,%5,%6,%7,%8,%9,%10,%11,%12,%13,%14,%15,"
        "%16,%17,%18,%19,%20,%21,%22,%23,%24,%25,%26,%27,%28,%29,%30,%31},"
        "%32, %33, p, 1, 1, 1, 0;\n}\n"
        : ACC8(d, 0), ACC8(d, 8), ACC8(d, 16), ACC8(d, 24)
        : "l"(da), "l"(db), "r"(scale_d));
}

__device__ __forceinline__ void mma_rs_n192(uint32_t (&d)[48], const uint4& a, uint64_t db) {
    asm volatile(
        "wgmma.mma_async.sync.aligned.m64n192k16.f16.f16.f16 "
        "{%0,%1,%2,%3,%4,%5,%6,%7,%8,%9,%10,%11,%12,%13,%14,%15,"
        "%16,%17,%18,%19,%20,%21,%22,%23,%24,%25,%26,%27,%28,%29,%30,%31,"
        "%32,%33,%34,%35,%36,%37,%38,%39,%40,%41,%42,%43,%44,%45,%46,%47},"
        "{%48,%49,%50,%51}, %52, 1, 1, 1, 0;\n"
        : ACC8(d, 0), ACC8(d, 8), ACC8(d, 16), ACC8(d, 24), ACC8(d, 32), ACC8(d, 40)
        : "r"(a.x), "r"(a.y), "r"(a.z), "r"(a.w), "l"(db));
}

#define P1_WPF 30
#define P1_PACE 1
constexpr int P1_SLOT = LN_TILE / 6, P1_NST = 6;
constexpr int P1_W = 64 * C_DIM * 2;
constexpr int P1_X = 32 * C_DIM * 2;
constexpr int P1_OFF_W = LN_TILE;
constexpr int P1_OFF_X = P1_OFF_W + 2 * P1_W;
constexpr int P1_OFF_BAR = P1_OFF_X + P1_X;
constexpr int P1_OFF_TILE = P1_OFF_BAR + (2 * P1_NST + 4 + 4 + 4) * 8;
constexpr int P1_OFF_EX = P1_OFF_TILE + 64;
constexpr int P1_OFF_DW = P1_OFF_EX + 256 * 4;
constexpr int P1_SMEM = P1_OFF_DW + C_DIM * 2;

__device__ __forceinline__ float rsqrt_fast(float x) {
    float r;
    asm("rsqrt.approx.ftz.f32 %0, %1;\n" : "=f"(r) : "f"(x));
    return r;
}
__device__ __forceinline__ float row_sum(const uint32_t (&c)[4]) {
    const uint32_t u = bf2_add(bf2_add(c[0], c[1]), bf2_add(c[2], c[3]));
    float s = bf_lo(u) + bf_hi(u);
#pragma unroll
    for (int o = 1; o < 8; o <<= 1) s += __shfl_xor_sync(0xffffffffu, s, o);
    return s;
}
__device__ __forceinline__ uint32_t pace(uint32_t bar, uint32_t off, uint32_t val, uint32_t after, int zero) {
    asm volatile(
        "{\n.reg .pred p, q;\n.reg .b32 par;\n"
        "lop3.b32 par, %4, %2, %3, 0xea;\n"
        "setp.eq.u32 q, par, 0;\n"
        "mov.pred p, 0;\n"
        "@q mbarrier.test_wait.parity.shared::cta.b64 p, [%1], par;\n"
        "selp.u32 par, 1, 0, p;\n"
        "@q mbarrier.try_wait.parity.shared::cta.b64 p, [%1], par, 1000;\n"
        "@p or.b32 %0, %0, %2;\n"
        "}\n" : "+r"(val) : "r"(bar), "r"(zero), "r"(off), "r"(after));
    return val;
}
template <int PACE, int R>
__device__ __forceinline__ void ln_rows(uint32_t (&v)[R][6][4], const uint32_t (&d)[6][4], uint32_t bar, uint32_t off, int zero,
                                        uint32_t bar_read) {
    const float inv = 1.0f / C_DIM;
    uint32_t c[R][4], nm[R];
    float e[R], r[R], er[R];
    bool big = false;
#pragma unroll
    for (int p = 0; p < R; p++) {
#pragma unroll
        for (int i = 0; i < 6; i++)
#pragma unroll
            for (int k = 0; k < 4; k++) c[p][k] = bf2_fma(v[p][i][k], d[i][k], i ? c[p][k] : 0);
        const float m = row_sum(c[p]) * inv;
        nm[p] = pack_bf16(-m, -m);
        e[p] = m + bf_lo(nm[p]);
    }
    if (bar_read) mbar_arrive(bar_read + (nm[0] & zero));
    if (PACE & 1) nm[0] = pace(bar, off, nm[0], nm[0], zero);
#pragma unroll
    for (int p = 0; p < R; p++) {
#pragma unroll
        for (int i = 0; i < 6; i++) {
#pragma unroll
            for (int k = 0; k < 4; k++) {
                v[p][i][k] = bf2_fma(v[p][i][k], d[i][k], nm[p]);
                c[p][k] = i ? bf2_fma(v[p][i][k], v[p][i][k], c[p][k]) : bf2_mul(v[p][i][k], v[p][i][k]);
            }
        }
        r[p] = KAPPA * rsqrt_fast(fmaxf(fmaf(-e[p], e[p], row_sum(c[p]) * inv), 0.f) + 1e-5f);
        er[p] = -e[p] * r[p] * 0x1p-112f;
        big |= r[p] < 0x1p-8f;
    }
    if (__any_sync(0xffffffffu, big)) {
#pragma unroll
        for (int p = 0; p < R; p++) {
            const uint32_t p2 = __float_as_uint(r[p]) & 0x7f800000u;
            r[p] = __uint_as_float((__float_as_uint(r[p]) & 0x007fffffu) | 0x3f800000u);
#pragma unroll
            for (int i = 0; i < 6; i++)
#pragma unroll
                for (int k = 0; k < 4; k++) v[p][i][k] = bf2_mul(v[p][i][k], p2 | p2 >> 16);
        }
    }
#pragma unroll
    for (int p = 0; p < R; p++) {
        uint32_t rs = pack_bf16(r[p] * 0x1p-112f, r[p] * 0x1p-112f);
        const uint32_t sh = pack_bf16(er[p], er[p]);
        if (PACE & 2) rs = pace(bar, off, rs, sh, zero);
#pragma unroll
        for (int i = 0; i < 6; i++)
#pragma unroll
            for (int k = 0; k < 4; k++) v[p][i][k] = bf2_to_h2(bf2_fma(v[p][i][k], rs, sh));
    }
}

template <int R>
__device__ __forceinline__ uint32_t gelu2(uint32_t a, uint32_t sc2) {
    uint32_t y, t;
    if (R) asm("{\n.reg .b16 l, h;\n.reg .b32 f;\nmov.b32 {l, h}, %2;\nmov.b32 f, {h, h};\nmul.rn.f16x2 %0, %1, f;\n}\n" : "=r"(y) : "r"(a), "r"(sc2));
    else asm("{\n.reg .b16 l, h;\n.reg .b32 f;\nmov.b32 {l, h}, %2;\nmov.b32 f, {l, l};\nmul.rn.f16x2 %0, %1, f;\n}\n" : "=r"(y) : "r"(a), "r"(sc2));
    asm("tanh.approx.f16x2 %0, %1;\n" : "=r"(t) : "r"(h2_mul(y, h2_fma(y, y, GELU_C2))));
    return h2_fma(a, t, a);
}
constexpr uint32_t SPARE = 0x40074007u;

__device__ __forceinline__ uint32_t p1_parity(uint32_t sbase) {
    uint32_t v;
    asm volatile("ld.shared.u32 %0, [%1];\n" : "=r"(v) : "r"(sbase + P1_OFF_TILE - 4) : "memory");
    return v;
}
__device__ __forceinline__ uint32_t p1_exponents(float (&t)[2], uint32_t (&ex)[2], uint32_t saddr, int lane) {
#pragma unroll
    for (int r = 0; r < 2; r++) {
        t[r] += __shfl_xor_sync(0xffffffffu, t[r], 1);
        t[r] += __shfl_xor_sync(0xffffffffu, t[r], 2);
        ex[r] = min(max(((__float_as_uint(193.3f * t[r]) >> 23) + 127u) >> 1, 72u), 198u);
        asm volatile("st.shared.u32 [%0], %1;\n" ::"r"(saddr + r * 32), "r"(ex[r] << 23) : "memory");
    }
    return pack_f16(__uint_as_float(min(ex[0], 142u) << 23), __uint_as_float(min(ex[1], 142u) << 23));
}
template <int N>
__device__ __forceinline__ void p1_convert(uint32_t (&o)[N][4], uint32_t (&v)[N][4], const uint32_t (&ex)[2]) {
    if (__any_sync(0xffffffffu, max(ex[0], ex[1]) > 141u)) {
#pragma unroll
        for (int k = 0; k < 4 * N; k++) v[k >> 2][k & 3] = bf2_mul(v[k >> 2][k & 3], ex[k & 1] > 141u ? 0x1f801f80u : 0x3f803f80u);
    }
#pragma unroll
    for (int k = 0; k < 4 * N; k++) {
        const uint32_t u = bf2_mul(v[k >> 2][k & 3], ((ex[k & 1] > 141u ? 206u : 142u) - ex[k & 1]) * 0x00800080u);
        asm volatile("mad.lo.u32 %0, %1, 7, %2;\n" : "=r"(o[k >> 2][k & 3]) : "r"(u & 0x7fff7fffu), "r"(u));
    }
}
template <int N>
__device__ __forceinline__ void p1_squares(const uint32_t (&v)[N][4], float (&t)[2]) {
#pragma unroll
    for (int j = 0; j < N / 2; j++) {
        const int r = j & 1, b = (j >> 1) * 4;
        uint32_t c = bf2_mul(v[b][r], v[b][r]);
#pragma unroll
        for (int k = 1; k < 8; k++) c = bf2_fma(v[b + k / 2][r + (k & 1) * 2], v[b + k / 2][r + (k & 1) * 2], c);
        t[r] += bf_lo(c) + bf_hi(c);
    }
}
__device__ __forceinline__ void p1_epilogue(const uint32_t (&acc)[2][32], const uint32_t (&sc2)[2], float (&ssq)[4], uint8_t* hp, int zero) {
    uint32_t sq[2], h[16][4];
#pragma unroll
    for (int i2 = 0; i2 < 9; i2++) {
#pragma unroll
        for (int c = 2 * i2 - 2; c < 2 * i2; c++) {
            if (c >= 0 && (c & 3)) {
                uint32_t o[4];
#pragma unroll
                for (int u = 0; u < 4; u++) {
                    const uint32_t v = h[c & 12][u];
                    o[u] = bitsel(h[c][u], (c & 3) == 2 ? prmt(v, v, 0xa381) : prmt(v >> 3, v, (c & 3) == 1 ? 0x6240 : 0xf3d1), SPARE);
                }
                stg128_cs(hp + (c >> 3) * 2 * H_STEP + ((c >> 2) & 1) * H_HALF + ((c & 3) - 1) * 512, o[0], o[1], o[2], o[3]);
            }
        }
        if (i2 < 8) {
#pragma unroll
            for (int u = 0; u < 4; u++) {
                h[2 * i2][u] = gelu2<0>(acc[i2 >> 2][8 * (i2 & 3) + 2 * u], sc2[i2 >> 2]);
                h[2 * i2 + 1][u] = gelu2<1>(acc[i2 >> 2][8 * (i2 & 3) + 2 * u + 1], sc2[i2 >> 2]);
#pragma unroll
                for (int r = 0; r < 2; r++) {
                    const uint32_t v = h[2 * i2 + r][u];
                    sq[r] = ((i2 & 3) | u) ? h2_fma(v, v, sq[r]) : h2_mul(v, v);
                }
            }
            if ((i2 & 3) == 3) {
#pragma unroll
                for (int r = 0; r < 2; r++) ssq[(i2 >> 2) * 2 + r] += h_lo(sq[r]) + h_hi(sq[r]);
            }
            sched_break(zero);
        }
    }
}
template <int WG>
__device__ __forceinline__ void p1_mma(uint32_t (&acc)[2][32], const uint32_t (&a)[24][4], uint32_t sbase, uint32_t empty_remote, int i, int lane) {
    const uint32_t bar_full = sbase + P1_OFF_BAR;
    const uint64_t db = make_desc(sbase, 16, 1024) | (1ull << 62);
    const uint64_t da = db + (P1_OFF_W + WG * P1_W) / 16;
    if (WG == 0) mbar_wait(bar_full, i & 1);
    bar_sync(1 + WG, 256);
    TRACE(WG, i, 1);
    wg_fence();
#pragma unroll
    for (int k = 0; k < 24; k++) {
        if (WG == 0 && k && k % 4 == 0) mbar_wait(bar_full + (k >> 2) * 8, i & 1);
        mma_rs_n128(acc[0], a[k], db + (uint64_t)((k >> 2) * 1024 + (k & 3) * 2), k != 0);
        mma_ss_n128(acc[1], da + (uint64_t)(k * 128), db + (uint64_t)((k >> 2) * 1024 + (k & 3) * 2), k != 0);
        if (k == 23) bar_arrive(2 - WG, 256);
        if (k == 23 || (WG == 1 && k % 4 == 3)) wg_commit();
        if (WG == 1 && k % 4 == 3 && k > 3) {
            wg_wait<1>();
            if (lane < 2) mbar_arrive_cluster(empty_remote + ((k >> 2) - 1) * 8);
        }
    }
    TRACE(WG, i, 2);
    wg_wait<0>();
    if (WG == 1 && lane < 2) mbar_arrive_cluster(empty_remote + 5 * 8);
}
__device__ __forceinline__ void p1_consumer(const uint32_t (&a)[24][4], const uint32_t (&sc2)[2], uint32_t sbase, int WG, int w, int lane, int zero) {
    const uint32_t bar_full = sbase + P1_OFF_BAR, bar_empty = bar_full + P1_NST * 8;
    const uint32_t empty_remote = mapa(bar_empty, lane & 1);
    const uint32_t bar_pace = bar_empty + P1_NST * 8 + 32 + w * 8;
    const int g = lane >> 2, q = lane & 3, cb = (blockIdx.x % GRP_CTAS) * 4 + WG * 2;
    uint32_t acc[2][32];
    float ssq[4] = {0.f, 0.f, 0.f, 0.f};
    TSTAMP(0, 1);

    uint8_t* hp = reinterpret_cast<uint8_t*>(g_h) + ((cb * 2 + (w >> 1)) * H_STEP + (w & 1) * 1536) + g * 64 + (q ^ (g >> 1)) * 16;
    int i = 0;
#pragma unroll 1
    for (;; i++) {
        TRACE(WG, i, 0);
        if (WG == 0) p1_mma<0>(acc, a, sbase, empty_remote, i, lane);
        else p1_mma<1>(acc, a, sbase, empty_remote, i, lane);
        TRACE(WG, i, 4);
        uint32_t step, more;
        asm volatile("ld.shared.v2.u32 {%0, %1}, [%2];\n" : "=r"(step), "=r"(more) : "r"(sbase + P1_OFF_TILE + (i & 3) * 16) : "memory");
        hp += step;
        p1_epilogue(acc, sc2, ssq, hp, zero);
        if (lane == 0) mbar_arrive(bar_pace);
        if (!more) break;
    }
    TSTAMP(0, 21);
    if (WG == 0) bar_sync(1, 256);
#pragma unroll
    for (int r = 0; r < 4; r++) {
        const int ch = (r >> 1) * 64 + w * 16 + (r & 1) * 8 + g;
        ssq[r] += __shfl_xor_sync(0xffffffffu, ssq[r], 1);
        ssq[r] += __shfl_xor_sync(0xffffffffu, ssq[r], 2);
        float f;
        asm volatile("ld.shared.f32 %0, [%1];\n" : "=f"(f) : "r"(sbase + P1_OFF_EX + (WG * 128 + ch) * 4) : "memory");
        if (q == 0) {
            float* sums = g_sums[p1_parity(sbase)];
            atomicAdd(&sums[cb * 64 + ch], ssq[r] * f * f);
            g_scale[cb * 64 + ch] = f;
            if (ssq[r] < (i + 1) * 0x1p-12f) sums[HID + C_DIM + 1] = 1.f;
        }
    }
}

__global__ void __cluster_dims__(2, 1, 1) __launch_bounds__(512, 1)
pass1_kernel(const __grid_constant__ CUtensorMap wmap, const __nv_bfloat16* __restrict__ x, const __nv_bfloat16* __restrict__ dw,
             const __nv_bfloat16* __restrict__ w2, const __nv_bfloat16* __restrict__ grn_b, int zero) {
    extern __shared__ __align__(1024) uint8_t smem[];
    const uint32_t sbase = smem_u32(smem);
    const uint32_t bar_full = sbase + P1_OFF_BAR, bar_empty = bar_full + P1_NST * 8, bar_w = bar_empty + P1_NST * 8;
    const int tid = threadIdx.x;
    const int warp = __shfl_sync(0xffffffffu, tid >> 5, 0), lane = tid & 31;
    const uint32_t rank = cluster_rank();
    const int cig = blockIdx.x % GRP_CTAS;
    uint8_t* const ring = reinterpret_cast<uint8_t*>(g_ln);

    TSTAMP(0, 0);
    TRACEW(110 + warp, 0);
    const uint32_t bar_pace = bar_w + 32, bar_xfull = bar_pace + 32, bar_xempty = bar_xfull + 8, bar_done = bar_xfull + 16;
    const int ln0 = blockIdx.x >> 2, first = blockIdx.x / GRP_CTAS;
    const uint8_t* xsrc = reinterpret_cast<const uint8_t*>(x) + (size_t)blockIdx.x * P1_X;

    if (warp >= 12) {
        reg_dec<40>();
        asm volatile("barrier.cluster.arrive.relaxed.aligned;\n" ::: "memory");
        asm volatile("barrier.cluster.wait.aligned;\n" ::: "memory");
        if (warp == 12) {
            int prev = 0, t = first;
            const uint32_t rbase = mapa(sbase, lane & 1);
#pragma unroll 1
            for (int i = 0; t < NT128; i++) {
                const int round = t / LN_RING, slot = t - round * LN_RING;
                const uint8_t* src = ring + slot * LN_TILE + rank * (P1_SLOT / 2);
                int next = 0;
                if (rank == 0 && lane == 0) next = atomicAdd(&g_flag[LN_RING + (cig >> 1)][0][0], 1u);
                flag_wait<true>(&g_flag[slot][0][0], 4 * round + 4);
                TRACEW(i, 2);
                asm volatile("fence.proxy.async.global;\n" ::: "memory");
                next = NGRP + __shfl_sync(0xffffffffu, next, 0);
#pragma unroll 1
                for (int h = 0; h < P1_NST; h++) {
                    mbar_wait(bar_empty + h * 8, i & 1);
                    if (h == 0) TRACEW(i, 4);
                    if (h == 5) TRACEW(i, 5);
                    if (elect_one()) {
                        mbar_expect_tx(bar_full + h * 8, h ? P1_SLOT : P1_SLOT + 16);
                        bulk_g2s_mc(sbase + h * P1_SLOT + rank * (P1_SLOT / 2), src + h * P1_SLOT, P1_SLOT / 2, bar_full + h * 8, (uint16_t)3);
                    }
                    __syncwarp();
                    if (h == 0 && rank == 0 && lane < 2)
                        asm volatile("st.async.shared::cluster.mbarrier::complete_tx::bytes.v4.u32 [%0], {%1, %2, %3, %3}, [%4];\n"
                                     ::"r"(rbase + P1_OFF_TILE + (i & 3) * 16), "r"((t - prev) * (2 * H_TILE)), "r"((int)(next < NT128)), "r"(next),
                                       "r"(rbase + P1_OFF_BAR) : "memory");
                }
                prev = t;
                t = next;
                if (rank != 0) {
                    mbar_wait(bar_full, i & 1);
                    asm volatile("ld.shared.u32 %0, [%1];\n" : "=r"(t) : "r"(sbase + P1_OFF_TILE + (i & 3) * 16 + 8) : "memory");
                }
            }
        } else if (warp == 13) {
            int ph = 0;
            unsigned target = 0;
#pragma unroll 1
            for (int i = ln0 + LN_STEP; i < NT128; i += LN_STEP, ph ^= 1) {
                target += ph * (GRP_CTAS / 2);
                xsrc += (size_t)NUM_CTAS * P1_X;
                mbar_wait(bar_xempty, ph);
                if (elect_one()) {
                    mbar_expect_tx(bar_xfull, P1_X);
                    bulk_g2s(sbase + P1_OFF_X, xsrc, P1_X, bar_xfull);
                }
                __syncwarp();
                const uint32_t off = flag_wait<false>(&g_flag[ln0 + (ph ^ 1) * LN_STEP][1][0], target);
                mbar_wait(bar_done, ph);
                if (elect_one()) {
                    asm volatile("st.shared.u32 [%0], %1;\n" ::"r"(bar_done + 8), "r"(off) : "memory");
                    mbar_arrive(bar_xfull);
                }
                __syncwarp();
            }
        } else if (warp == 15) {
            const uint32_t par = g_epoch & 1;
            asm volatile("st.shared.u32 [%0], %1;\n" ::"r"(sbase + P1_OFF_TILE - 4), "r"(par) : "memory");
            if (blockIdx.x < 16) reinterpret_cast<float4*>(g_sums[par ^ 1])[blockIdx.x * 32 + lane] = make_float4(0.f, 0.f, 0.f, 0.f);
            int t = first;
            if (rank == 1 && lane == 0) mbar_arrive(bar_empty);
#pragma unroll 1
            for (int i = 0; rank == 1 && t < NT128; i++) {
#pragma unroll 1
                for (int h = 0; h < P1_NST; h++) mbar_wait(bar_full + h * 8, i & 1);
                if (lane == 0) asm volatile("red.relaxed.gpu.global.add.u32 [%0], 1;\n" ::"l"(&g_flag[t % LN_RING][1][0]) : "memory");
                asm volatile("ld.shared.u32 %0, [%1];\n" : "=r"(t) : "r"(sbase + P1_OFF_TILE + (i & 3) * 16 + 8) : "memory");
                if (lane == 0) mbar_arrive(bar_empty);
                TRACEW(i, 3);
            }
            if (rank == 0) {
                mbar_wait(bar_full, 0);
                TRACEW(110 + warp, 3);
                mbar_wait(bar_full, 1);
                float* sums = g_sums[par] + HID;
                unsigned* flag = reinterpret_cast<unsigned*>(sums + C_DIM);
                if (blockIdx.x == 0) reinterpret_cast<uint2*>(g_half)[lane] = make_uint2(0, 0);
                if (blockIdx.x == 2 && lane < 3) g_prog[lane][0] = 0;
                if (blockIdx.x < 96) g_redo[blockIdx.x * 16 + lane] = 0.f;
                float gs = 0.f;
#pragma unroll 1
                for (int pass = 0; pass < 2; pass++) {
                    float mx = 0.f;
#pragma unroll 1
                    for (int it = first; it < 96; it += NGRP) {
                        const int nb = it % 12, k0 = (cig * 4 + it / 12) * 64 + (lane >> 2);
                        const uint32_t sc = mapa(sbase + P1_OFF_EX + (k0 & 255) * 4, it / 48);
                        uint32_t* dst = reinterpret_cast<uint32_t*>(g_w2img[0]) + (k0 >> 4) * 3072 + nb * 256 + lane;
                        float bs[8] = {};
#pragma unroll 1
                        for (int c = 0; c < 8; c++) {
                            const uint4 u = __ldg(reinterpret_cast<const uint4*>(w2 + (size_t)(k0 + c * 8) * C_DIM + nb * 32) + (lane & 3));
                            const float b = __bfloat162float(grn_b[k0 + c * 8]);
                            float t;
                            asm volatile("ld.shared::cluster.f32 %0, [%1];\n" : "=f"(t) : "r"(sc + c * 32) : "memory");
#pragma unroll
                            for (int j = 0; j < 4; j++) {
                                const uint32_t v = j == 0 ? u.x : j == 1 ? u.y : j == 2 ? u.z : u.w;
                                mx = fmaxf(mx, fmaxf(fabsf(bf_lo(v)), fabsf(bf_hi(v))) * t);
                                if (pass) {
                                    bs[2 * j] = fmaf(b, bf_lo(v), bs[2 * j]);
                                    bs[2 * j + 1] = fmaf(b, bf_hi(v), bs[2 * j + 1]);
                                    uint32_t h = pack_f16(bf_lo(v) * t * gs, bf_hi(v) * t * gs);
                                    asm volatile("movmatrix.sync.aligned.m8n8.trans.b16 %0, %0;\n" : "+r"(h));
                                    dst[(c >> 1) * 3072 + (c & 1) * 32 + j * 64] = h;
                                }
                            }
                        }
                        if (pass) {
#pragma unroll
                            for (int j = 0; j < 8; j++) {
#pragma unroll
                                for (int o = 4; o < 32; o <<= 1) bs[j] += __shfl_xor_sync(0xffffffffu, bs[j], o);
                                if (lane >> 2 == j) atomicAdd(&sums[nb * 32 + (j >> 1) * 8 + (lane & 3) * 2 + (j & 1)], bs[j]);
                            }
                        }
                    }
                    if (!pass) {
                        const uint32_t m = __reduce_max_sync(0xffffffffu, __float_as_uint(mx));
                        if (lane == 0) {
                            atomicMax(flag, m);
                            asm volatile("red.release.gpu.global.add.u32 [%0], 1;\n" ::"l"(flag + 32) : "memory");
                        }
                        flag_wait<true>(flag + 32, NUM_CTAS / 2);
                        gs = w2_scale(__ldcg(flag));
                    }
                }
                do {
                    __nanosleep(1000);
                    asm volatile("ld.volatile.shared.u32 %0, [%1];\n" : "=r"(t) : "r"(sbase + P1_OFF_TILE + (lane & 3) * 16 + 8) : "memory");
                    SAFE_BREAK;
                } while (__all_sync(0xffffffffu, t < NT128 - P1_WPF));
                if (lane == 0 && blockIdx.x < 128)
                    asm volatile("cp.async.bulk.prefetch.L2.global [%0], %1;\n" ::"l"(g_w2img[0] + blockIdx.x * 576), "r"(18432) : "memory");
            }
        } else if (warp == 14) {
            int ph = 0;
#pragma unroll 1
            for (int i = ln0; i < NT128; i += LN_STEP, ph ^= 1) {
                mbar_wait(bar_done, ph);
                TRACEW(i / LN_STEP, 0);
                asm volatile("fence.proxy.async.global;\n" ::: "memory");
                if (elect_one()) asm volatile("red.release.gpu.global.add.u32 [%0], 1;\n" ::"l"(&g_flag[ln0 + ph * LN_STEP][0][0]) : "memory");
                __syncwarp();
                TRACEW(i / LN_STEP, 1);
            }
        }
        __syncwarp();
        cluster_sync();
    } else if (warp >= 8) {
        reg_dec<88>();
        asm volatile("barrier.cluster.arrive.relaxed.aligned;\n" ::: "memory");
        {
            const int l8 = lane & 7, row = (warp - 8) * 4 + (lane >> 3), px = (blockIdx.x & 3) * 32 + row;
            uint32_t d[6][4];
            const int n = (px & 64) + perm32(2 * row + ((px >> 5) & 1));
            uint8_t* const dst0 = ring + ln0 * LN_TILE + n * 128 + ((l8 ^ (n & 7)) << 4);
            const uint32_t src = sbase + P1_OFF_X + ((warp - 8) * 8 + (lane >> 3)) * (C_DIM * 2) + l8 * 16;
            int ph = 0;
#pragma unroll 1
            for (int i = ln0; i < NT128; i += LN_STEP, ph ^= 1) {
                TRACE(2, i / LN_STEP, 0);
                uint32_t off = 1;
#pragma unroll 1
                for (int ps = i == ln0 ? -2 : 0; ps < 2; ps += ps < 0 ? 2 : 1) {
                    if (ps == 0) {
                        if (i == ln0) asm volatile("barrier.cluster.wait.aligned;\n" ::: "memory");
                        mbar_wait(bar_xfull, ph);
                        asm volatile("ld.shared.u32 %0, [%1];\n" : "=r"(off) : "r"(bar_done + 8) : "memory");
                    }
                    if (ps == 0) TRACE(2, i / LN_STEP, 1);
                    if (i == ln0) {
#pragma unroll
                        for (int j = 0; j < 6; j++)
                            asm volatile("ld.shared.v4.u32 {%0,%1,%2,%3}, [%4];\n"
                                         : "=r"(d[j][0]), "=r"(d[j][1]), "=r"(d[j][2]), "=r"(d[j][3]) : "r"(sbase + P1_OFF_DW + j * 128 + l8 * 16) : "memory");
                    }
                    uint32_t v1[1][6][4];
                    uint32_t (&v)[6][4] = v1[0];
#pragma unroll
                    for (int j = 0; j < 6; j++)
                        asm volatile("ld.shared.v4.u32 {%0,%1,%2,%3}, [%4];\n"
                                     : "=r"(v[j][0]), "=r"(v[j][1]), "=r"(v[j][2]), "=r"(v[j][3]) : "r"(src + (ps & 1) * (4 * C_DIM * 2) + j * 128) : "memory");
                    ln_rows<P1_PACE, 1>(v1, d, bar_pace + (warp - 8) * 8, off, zero, ps == 1 && lane == 0 ? bar_xempty : 0);
                    uint8_t* dst = dst0 + ph * (LN_STEP * LN_TILE) + (ps & 1) * 4096;
#pragma unroll
                    for (int j = 0; j < 6; j++) *reinterpret_cast<uint4*>(dst + j * 16384) = make_uint4(v[j][0], v[j][1], v[j][2], v[j][3]);
                    TRACE(2, i / LN_STEP, 3 + (ps & 1));
                }
                asm volatile("fence.proxy.async.global;\nfence.acq_rel.cta;\n" ::: "memory");
                __syncwarp();
                if (lane == 0) mbar_arrive(bar_done);
                TRACE(2, i / LN_STEP, 5);
                TRACE(2, i / LN_STEP, 2);
            }
        }
        __syncwarp();
        cluster_sync();
    } else {
        const int wg = warp >> 2, w = warp & 3;
        auto load_w = [&](int i0, int i1) {
#pragma unroll 1
            for (int i = i0; i < i1; i++) {
                if (!(i & 1)) mbar_expect_tx(bar_w + (i >> 1) * 8, P1_W);
                tma2(sbase + (i & 2) * P1_W + (i >> 2) * P1_W + (i & 1) * (P1_W / 2), &wmap, cig * 256 + (i >> 1) * 64, (i & 1) * 192, bar_w + (i >> 1) * 8);
            }
        };
        if (warp == 4 && elect_one()) {
            mbar_init(bar_xfull, 2);
#pragma unroll
            for (int i = 0; i < 4; i++) mbar_init(bar_w + i * 8, 1);
            asm volatile("fence.mbarrier_init.release.cluster;\n" ::: "memory");
            mbar_expect_tx(bar_xfull, P1_X + C_DIM * 2);
            bulk_g2s(sbase + P1_OFF_X, xsrc, P1_X, bar_xfull);
            bulk_g2s(sbase + P1_OFF_DW, dw, C_DIM * 2, bar_xfull);
            load_w(0, 4);
            asm volatile("st.shared.u32 [%0], 1;\n" ::"r"(bar_done + 8) : "memory");
            mbar_arrive(bar_xfull);
        }
        if (warp == 5 && elect_one()) {
#pragma unroll
            for (int i = 0; i < P1_NST; i++) {
                mbar_init(bar_full + i * 8, 1);
                mbar_init(bar_empty + i * 8, i ? 8 : 8 + rank);
                if (i < 4) mbar_init(bar_pace + i * 8, 1);
            }
            mbar_init(bar_xempty, 4);
            mbar_init(bar_done, 4);
            asm volatile("fence.mbarrier_init.release.cluster;\n" ::: "memory");
        }
        __syncwarp();
        asm volatile("barrier.cluster.arrive.relaxed.aligned;\n" ::: "memory");
        reg_inc<192>();
        TRACEW(110 + warp, 1);
        uint32_t a[24][4];
        gdc_launch();
        const uint32_t src = sbase + wg * P1_W + ((lane >> 4) * 8 + (lane & 7)) * 128 + (((2 * w + ((lane >> 3) & 1)) ^ (lane & 7)) << 4);
        const uint32_t s_ex = sbase + P1_OFF_EX + (wg * 128 + w * 16 + (lane >> 2)) * 4;
        uint32_t sc2[2], ex[2];
        if (wg == 1) bar_arrive(1, 256);
#pragma unroll 1
        for (int it = 0; it < 2; it++) {
          if (it != wg) asm volatile("barrier.cluster.wait.aligned;\n" ::: "memory");
          if (it < wg) {
              mbar_wait(bar_xfull, 0);
              if (w == 0 && elect_one()) load_w(4, 8);
              __syncwarp();
          }
          if (it || wg == 0) {
            float t[2] = {0.f, 0.f};
            if (it) {
                TRACEW(110 + warp, 2);
                mbar_wait(bar_w + wg * 16, 0);
            }
            TRACEW(110 + warp, 5);
#pragma unroll
            for (int k = 0; k < 24; k++) ldsm4t(a[k], src + k * 2048);
            TRACEW(110 + warp, 6);
            p1_squares(a, t);
            sc2[0] = p1_exponents(t, ex, s_ex, lane);
            if (it && lane < 6) mbar_arrive_cluster(mapa(bar_empty, lane & 1) + (wg * 3 + (lane >> 1)) * 8 + (sc2[0] & zero));
            p1_convert<24>(a, a, ex);
          }
          if (it || wg == 1) {
            float t[2] = {0.f, 0.f};
            TRACEW(100 + warp, 0);
            if (it) mbar_wait(bar_w + wg * 16 + 8, 0);
            TRACEW(100 + warp, 1);
            uint32_t v[8][4], o[8][4];
#pragma unroll 1
            for (int j = 0; j <= 2 * it; j++) {
#pragma unroll
                for (int k = 0; k < 8; k++) ldsm4t(v[k], src + P1_OFF_W + (8 * j + k) * 2048);
                p1_squares(v, t);
            }
            sc2[1] = p1_exponents(t, ex, s_ex + 256, lane);
#pragma unroll 1
            for (int j = 2 * it; j >= 0; j--) {
                p1_convert<8>(o, v, ex);
#pragma unroll
                for (int k = 0; k < 8; k++) {
                    if (j) ldsm4t(v[k], src + P1_OFF_W + (8 * j - 8 + k) * 2048);
                    if (it) asm volatile("stmatrix.sync.aligned.m8n8.x4.trans.shared.b16 [%0], {%1,%2,%3,%4};\n"
                                         ::"r"(src + P1_OFF_W + (8 * j + k) * 2048), "r"(o[k][0]), "r"(o[k][1]), "r"(o[k][2]), "r"(o[k][3]) : "memory");
                }
            }
          }
        }
        asm volatile("fence.proxy.async.shared::cta;\n" ::: "memory");
        TRACEW(110 + warp, 7);
        bar_sync(6 + wg, 128);
        p1_consumer(a, sc2, sbase, wg, w, lane, zero);
        cluster_sync();
        TSTAMP(0, 30);
    }
}

constexpr int P2_B = 24576, P2_NB = 4;
constexpr int P2_A = 3072, P2_NA = 8;
constexpr int P2_XROW = C_DIM * 2;
constexpr int P2_OFF_A = P2_B * P2_NB;
constexpr int P2_OFF_X = P2_OFF_A + 3 * P2_NA * P2_A;
constexpr int P2_XHALF = 32 * P2_XROW + 64;
constexpr int P2_OFF_GRN = P2_OFF_X + 64 * P2_XROW + 128;
constexpr int P2_OFF_BIAS = P2_OFF_GRN + HID * 2;
constexpr int P2_OFF_RED = P2_OFF_BIAS + C_DIM * 4;
constexpr int P2_OFF_BAR = P2_OFF_RED + 192;
constexpr int P2_SMEM = P2_OFF_BAR + (2 * P2_NB + 6 * P2_NA + 7) * 8;
#define P2_S1 16
constexpr int P2_S2 = 32;
constexpr int P2_NCL = NUM_CTAS / 2, P2_ITEMS = NT128 / P2_NCL, P2_SHARED = NT128 - P2_ITEMS * P2_NCL;
constexpr int P2_NPOS = 6 * 48 + P2_S1;
constexpr int P2_RAW = 24;
constexpr int P2_XC = 8 * P2_XROW;
#define P2_T0 4
#define P2_SLACK 0
#define P2_RAMP 2
#define P2_LATE 88
#define P2_GATE 1
#define P2_AH 2
__device__ __forceinline__ int p2_start(int n) { return n < 0 ? 0 : n / 3 * 48 + (n % 3 == 1 ? P2_S1 : n % 3 * (P2_S2 / 2)); }
__device__ __forceinline__ int p2_tile(int cl, int n) {
    return n == 0 ? NT128 - 1 - cl : n < 0 ? NT128 - 1 - P2_NCL - (cl >> 1) : cl + P2_NCL * (n - 1);
}

#define P2_EB 2
#define P2_EX 1
__device__ __forceinline__ void p2_epilogue(uint32_t (&acc0)[48], uint32_t (&acc1)[48], uint32_t up, uint32_t sx, uint32_t sb, int zero) {
    uint32_t v[12][3][4];
    auto load = [&](int t, int j) {
        if (t >= 12) return;
        uint32_t (&w)[4] = v[t][j];
        asm volatile("ld.shared.v4.u32 {%0,%1,%2,%3}, [%4];\n" : "=r"(w[0]), "=r"(w[1]), "=r"(w[2]), "=r"(w[3])
                     : "r"((j ? sx + (j - 1) * 4 * P2_XROW : sb) + t * 64) : "memory");
    };
    auto store = [&](int t, int r) {
        const uint32_t* w = (t < 6 ? acc0 : acc1) + 8 * (t % 6) + 4 * r;
        asm volatile("st.shared.v4.u32 [%4], {%0,%1,%2,%3};\n" ::"r"(w[0]), "r"(w[1]), "r"(w[2]), "r"(w[3]), "r"(sx + t * 64 + r * 4 * P2_XROW) : "memory");
    };
#pragma unroll
    for (int t = 0; t < P2_EB; t++) load(t, 0);
#pragma unroll
    for (int t = 0; t < 2 * P2_EX; t++) load(t >> 1, 1 + (t & 1));
#pragma unroll
    for (int t = 0; t < 12; t++) {
        load(t + P2_EX, 1);
        load(t + P2_EX, 2);
        load(t + P2_EB, 0);
        uint32_t* acc = (t < 6 ? acc0 : acc1) + 8 * (t % 6);
        uint32_t y[8];
#pragma unroll
        for (int e = 0; e < 8; e++) {
            y[e] = h2_add(acc[e], v[t][0][e >> 1]);
            y[e] = pack_bf16(h_lo(y[e]), h_hi(y[e]));
        }
#pragma unroll
        for (int e = 0; e < 8; e++) acc[(e & 1) * 4 + (e >> 1)] = bf2_fma(y[e], up, v[t][1 + (e & 1)][e >> 1]);
        store(t, 0);
        store(t, 1);
        sched_break(zero);
    }
    if (zero) {
#pragma unroll
        for (int t = 0; t < 24; t++) store(t >> 1, t & 1);
    }
}

__device__ __forceinline__ void p2_unpack(uint32_t (&u)[4], uint32_t o1, uint32_t o2, uint32_t o3) {
    u[2] = bitsel(o1, 0x00040004u, SPARE);
    u[1] = bitsel(o2, 0x00040004u, SPARE);
    u[3] = bitsel(o3, 0x00040004u, SPARE);
    const uint32_t t = bitsel(prmt(o1, o2, 0x6341), prmt(o1, o3, 0x6240) << 3, 0x38383838u);
    u[0] = bitsel(bitsel(t, prmt(o2, o3, 0x7351) << 1, 0x80808080u), 0x00040004u, SPARE);
}

__device__ __forceinline__ void p2_redo_sums(int warp, int lane) {
#pragma unroll 1
    for (int s = warp; s < 96; s += 12) {
        float t[2] = {0.f, 0.f};
#pragma unroll 1
        for (int tile = blockIdx.x; tile < 2 * NT128; tile += NUM_CTAS) {
            const uint32_t* p = reinterpret_cast<const uint32_t*>(reinterpret_cast<const uint8_t*>(g_h) + (size_t)(tile >> 1) * (2 * H_TILE) +
                                                                  (s >> 1) * H_STEP + (tile & 1) * H_HALF + (s & 1) * 1536) + lane * 4;
#pragma unroll
            for (int j = 0; j < 4; j++) {
                uint32_t u[4];
                p2_unpack(u, __ldcg(p + j), __ldcg(p + j + 128), __ldcg(p + j + 256));
#pragma unroll
                for (int c = 0; c < 4; c++) t[c >> 1] += h_lo(u[c]) * h_lo(u[c]) + h_hi(u[c]) * h_hi(u[c]);
            }
        }
#pragma unroll
        for (int r = 0; r < 2; r++) {
            const int ch = s * 16 + r * 8 + (lane >> 2);
            const float f = __ldcg(&g_scale[ch]);
            atomicAdd(&g_redo[ch], t[r] * f * f);
        }
    }
    __threadfence();
    __syncwarp();
    if (lane == 0) asm volatile("red.release.gpu.global.add.u32 [%0], 1;\n" ::"l"(&g_prog[2][0]) : "memory");
    flag_wait<true>(&g_prog[2][0], 12 * NUM_CTAS);
}

__global__ void __cluster_dims__(2, 1, 1) __launch_bounds__(512, 1)
pass2_kernel(const __nv_bfloat16* __restrict__ x, const __nv_bfloat16* __restrict__ grn_g, __nv_bfloat16* __restrict__ out, int zero) {
    extern __shared__ __align__(1024) uint8_t smem[];
    const uint32_t sbase = smem_u32(smem);
    const uint32_t bar_bfull = sbase + P2_OFF_BAR, bar_bempty = bar_bfull + P2_NB * 8;
    const uint32_t bar_afull = bar_bempty + P2_NB * 8, bar_aempty = bar_afull + 3 * P2_NA * 8;
    const uint32_t bar_xfull = bar_aempty + 3 * P2_NA * 8, bar_oready = bar_xfull + 24, s_pos = bar_oready + 24;
    int tid;
    asm volatile("mov.u32 %0, %%tid.x;\n" : "=r"(tid));
    const int warp = __shfl_sync(0xffffffffu, tid >> 5, 0), lane = tid & 31;
    const uint32_t rank = cluster_rank();
    const int cl = blockIdx.x >> 1, pair = cl >> 1;
    const int half = pair < P2_SHARED, fin = half && (cl & 1);
    const int k0 = (pair + 3 * (cl & 1)) % 6 * 8;
    const bool late = blockIdx.x >= P2_LATE;
    auto wait_pos = [&](int target) {
        int v;
        while (true) {
            asm volatile("ld.volatile.shared.u32 %0, [%1];\n" : "=r"(v) : "r"(s_pos) : "memory");
            if (v >= target) break;
            SAFE_BREAK;
            __nanosleep(100);
        }
    };

    TSTAMP(1, 0);
    if (tid == 384) {
        for (int i = 0; i < P2_NB; i++) {
            mbar_init(bar_bfull + i * 8, 1);
            mbar_init(bar_bempty + i * 8, 24);
        }
        for (int i = 0; i < 3 * P2_NA; i++) {
            mbar_init(bar_afull + i * 8, 1);
            mbar_init(bar_aempty + i * 8, 4);
        }
        for (int i = 0; i < 3; i++) {
            mbar_init(bar_xfull + i * 8, 2);
            mbar_init(bar_oready + i * 8, 4);
        }
        asm volatile("st.shared.u32 [%0], 0;\n" ::"r"(s_pos) : "memory");
        asm volatile("fence.mbarrier_init.release.cluster;\n" ::: "memory");
    }
    __syncthreads();
    cluster_sync_relaxed();

    if (warp >= 12) {
        reg_dec<32>();
        if (warp == 12) {
            const uint8_t* wsrc = reinterpret_cast<const uint8_t*>(g_w2img) + rank * (P2_B / 2);
            int kb = k0;
            gdc_wait();
            if (P2_GATE) bar_sync(5, 448);
#pragma unroll 1
            for (int p = 0; p < P2_NPOS; p++) {
                const int st = p & 3;
                if (p == P2_RAW) {
                    flag_wait<true>(&g_prog[1][0], NUM_CTAS);
                    asm volatile("fence.proxy.async.global;\n" ::: "memory");
                    wsrc += sizeof(g_w2img[0]);
                }
                const int idle = (p < P2_S1 || p >= 6 * 48) + (p < P2_S2 ? !half || p >= 24 : p >= 5 * 48 + P2_S2);
                mbar_wait(bar_bempty + st * 8, (~p >> 2) & 1);
                TR2(3, p, 0);
                if (elect_one()) {
                    const int len = P2_B / 2;
                    mbar_expect_tx(bar_bfull + st * 8, 2 * len);
                    bulk_g2s_mc(sbase + st * P2_B + rank * (P2_B / 2), wsrc + kb * P2_B, len, bar_bfull + st * 8, (uint16_t)3);
                    asm volatile("st.volatile.shared.u32 [%0], %1;\n" ::"r"(s_pos), "r"(p) : "memory");
                    if (rank == 0) asm volatile("red.relaxed.gpu.global.add.u32 [%0], 1;\n" ::"l"(&g_prog[0][0]) : "memory");
                    if (idle) asm volatile("mbarrier.arrive.shared::cta.b64 _, [%0], %1;\n" ::"r"(bar_bempty + st * 8), "r"(8 * idle) : "memory");
                }
                __syncwarp();
                if (++kb == 48) kb = 0;
            }
            mbar_wait(bar_bempty, 1);
            if (lane == 0) mbar_arrive(bar_bfull);
        } else if (warp == 13) {
            const int w = lane < 3 ? lane : 0;
            const uint32_t dst0 = sbase + P2_OFF_A + w * P2_NA * P2_A;
            const uint32_t bf = bar_afull + w * P2_NA * 8, be = bar_aempty + w * P2_NA * 8;
            int n = (w == 2 && half ? -1 : w) - 3, left = 0, u = 0, c = 0;
            const uint8_t* src = nullptr;
            bool act = lane < 3;
            gdc_wait();
            if (P2_GATE) bar_sync(5, 448);
            while (__any_sync(0xffffffffu, act)) {
                if (left == 0) {
                    n += 3;
                    left = n >= P2_ITEMS ? -1 : n < 0 ? 24 : 48;
                    u = (k0 + p2_start(n)) % 48;
                    src = reinterpret_cast<const uint8_t*>(g_h) + (size_t)p2_tile(cl, n) * (2 * H_TILE) + rank * H_HALF + u * H_STEP;
                }
                bool ok = act && mbar_test(be + ((c - 1) & 7) * 8, (~c >> 3) & 1);
                if (__any_sync(0xffffffffu, act && c < 16)) {
                    int v;
                    asm volatile("ld.volatile.shared.u32 %0, [%1];\n" : "=r"(v) : "r"(s_pos) : "memory");
                    ok = ok && c <= (n <= 0 ? 2 * v - P2_RAMP : c >= 16 ? c : v - p2_start(n) + 8);
                }
                if (ok) {
                    const int st = c & 7;
                    if (left > 0) {
                        mbar_expect_tx(bf + st * 8, P2_A);
                        bulk_g2s(dst0 + st * P2_A, src, P2_A, bf + st * 8);
                    } else {
                        mbar_arrive(bf + st * 8);
                        act = false;
                    }
                    src += H_STEP;
                    if (++u == 48) { u = 0; src -= 48 * H_STEP; }
                    c++;
                    left--;
                }
                SAFE_BREAK;
                if (!__any_sync(0xffffffffu, ok)) __nanosleep(100);
            }
        } else if (warp == 14) {
            const uint32_t sx = sbase + P2_OFF_X;
            size_t o = 0;
            int wp = 0;
            uint32_t par = 0;
            if (fin) {
#pragma unroll 1
                for (int c = lane * 16; c < 64 * P2_XROW + 128; c += 512) asm volatile("st.shared.v4.u32 [%0], {0, 0, 0, 0};\n" ::"r"(sx + c) : "memory");
                __syncwarp();
            }
            if (late) wait_pos(6);
#pragma unroll 1
            for (int n = -half; n <= P2_ITEMS; n++) {
                const int w = (n + 3) % 3, end = p2_start(n) + 48;
                const size_t on = (size_t)(2 * p2_tile(cl, n) + rank) * (64 * C_DIM * 2);
                const uint32_t xf = bar_xfull + w * 8;
                bool st = n + half > 0;
                const bool ld = n < P2_ITEMS && !(n < 0 && fin);
                if (n == P2_ITEMS - 1 && lane == 0)
                    asm volatile("cp.async.bulk.prefetch.L2.global [%0], %1;\n" ::"l"(reinterpret_cast<const uint8_t*>(x) + on), "r"(64 * P2_XROW) : "memory");
                if (st) {
                    mbar_wait(bar_oready + wp * 8, (par >> wp) & 1);
                    par ^= 1u << wp;
                }
                if (lane == 0) {
                    if (n < P2_ITEMS) mbar_expect_tx(xf, ld ? 64 * C_DIM * 2 : 0);
                    const int t0 = (n ? p2_start(n - 1) + 48 : P2_S2) + P2_T0, dt = end - t0;
                    int t = st && n < P2_ITEMS - 1 ? 16 * t0 : -4096;
                    if ((n == 0 && half) || n >= P2_ITEMS - 1) {
                        if (fin && n == 0) {
                            flag_wait<true>(&g_half[pair][rank], 1);
                            asm volatile("fence.proxy.async.global;\n" ::: "memory");
                        }
#pragma unroll 1
                        for (int c = 0; c < 2; c++) {
                            uint8_t* dst = reinterpret_cast<uint8_t*>(out) + o + c * 32 * P2_XROW;
                            if (!fin || n) bulk_s2g(dst, sx + c * P2_XHALF, 32 * P2_XROW);
                            else asm volatile("cp.reduce.async.bulk.global.shared::cta.bulk_group.add.noftz.bf16 [%0], [%1], %2;\n"
                                              ::"l"(dst), "r"(sx + c * P2_XHALF), "r"(32 * P2_XROW) : "memory");
                        }
                        asm volatile("cp.async.bulk.commit_group;\n" ::: "memory");
                        if (!fin && n == 0) {
                            asm volatile("cp.async.bulk.wait_group 0;\nfence.proxy.async.global;\n" ::: "memory");
                            asm volatile("st.release.gpu.global.u32 [%0], 1;\n" ::"l"(&g_half[pair][rank]) : "memory");
                        }
                        st = false;
                    }
#pragma unroll 1
                    for (int c = 0; c < 64 * P2_XROW; c += P2_XC, t += 2 * dt) {
                        const uint32_t sp = sx + c + (c >= 32 * P2_XROW ? 64 : 0);
                        wait_pos(t >> 4);
                        if (st) bulk_s2g(reinterpret_cast<uint8_t*>(out) + o + c, sp, P2_XC);
                        asm volatile("cp.async.bulk.commit_group;\n" ::: "memory");
                        if (ld) {
                            wait_pos((t + dt) >> 4);
                            asm volatile("cp.async.bulk.wait_group.read 0;\n" ::: "memory");
                            bulk_g2s(sp, reinterpret_cast<const uint8_t*>(x) + on + c, P2_XC, xf);
                        }
                    }
                    if (rank == 0 && n > 0 && n < P2_ITEMS - 1) flag_wait<false>(&g_prog[0][0], P2_NCL * (end + P2_SLACK));
                    if (n < P2_ITEMS) mbar_arrive(xf);
                }
                __syncwarp();
                o = on;
                wp = w;
            }
            asm volatile("cp.async.bulk.wait_group 0;\n" ::: "memory");
        } else if (blockIdx.x == 120) {
            gdc_wait();
            for (int i = lane; i < (LN_RING + 3) * 2; i += 32) (&g_flag[0][0][0])[i * 8] = 0;
            if (lane == 0) g_epoch++;
        }
        __syncwarp();
        cluster_sync();
    } else {
        reg_inc<160>();
        const int wg = warp >> 2, w = warp & 3, g = lane >> 2, q = lane & 3;
        const uint32_t sx = sbase + P2_OFF_X + (g & 1) * P2_XHALF + (w * 8 + (g >> 1)) * P2_XROW + q * 16;
        const uint32_t af = bar_afull + wg * P2_NA * 8;
        const uint32_t s_a = sbase + P2_OFF_A + wg * P2_NA * P2_A + (lane >> 3) * 512 + (lane & 7) * 64 + ((w ^ ((lane & 7) >> 1)) << 4);
        uint32_t acc0[48], acc1[48], up;
        uint4 a[2][2];

        __nv_bfloat16 gg[4];
#pragma unroll
        for (int i = 0; i < 4; i++) gg[i] = grn_g[tid + 384 * i];
#pragma unroll 1
        for (int it = late; it < 2; it++) {
            float* s_red = reinterpret_cast<float*>(smem + P2_OFF_RED);
            float gx[7], part = 0.f;
            if (it) {
                TSTAMP(1, 27);
                gdc_wait();
                TSTAMP(1, 1);
            }
            float gy[7];
#pragma unroll
            for (int i = 0; i < 7; i++) {
                const float* p = &g_sums[0][i < 5 ? tid + 384 * i : HID + C_DIM + i - 5];
                asm volatile("ld.global.cg.f32 %0, [%1];\n" : "=f"(gx[i]) : "l"(p) : "memory");
                asm volatile("ld.global.cg.f32 %0, [%1];\n" : "=f"(gy[i]) : "l"(p + HID + 512) : "memory");
            }
            if (P2_GATE && it) bar_arrive(5, 448);
            const float bias = gx[4] + gy[4];
            const float gs = w2_scale(__float_as_uint(gx[5]) | __float_as_uint(gy[5]));
            if (it && gx[6] + gy[6] != 0.f) {
                p2_redo_sums(warp, lane);
#pragma unroll
                for (int i = 0; i < 4; i++) {
                    gx[i] = __ldcg(&g_redo[tid + 384 * i]);
                    gy[i] = 0.f;
                }
            }
            float mg = 0.f;
#pragma unroll
            for (int i = 0; i < 4; i++) {
                gx[i] = gx[i] + gy[i];
                gx[i] = __fsqrt_rn(gx[i] * (HSCALE * HSCALE) + 1e-6f);
                part += gx[i];
                gx[i] *= __bfloat162float(gg[i]);
                mg = fmaxf(mg, fabsf(gx[i]));
            }
#pragma unroll
            for (int o = 16; o > 0; o >>= 1) part += __shfl_xor_sync(0xffffffffu, part, o);
            const uint32_t mgw = __reduce_max_sync(0xffffffffu, __float_as_uint(mg));
            const uint32_t mbw = __reduce_max_sync(0xffffffffu, __float_as_uint(fabsf(bias)));
            TSTAMP(1, 26);
            if (lane == 0) *reinterpret_cast<float4*>(s_red + warp * 4) = make_float4(part, __uint_as_float(mgw), __uint_as_float(mbw), 0.f);
            bar_sync(1, 384);
            float tot = 0.f, mb = 0.f;
#pragma unroll
            for (int i = 0; i < 12; i++) {
                const float4 t = *reinterpret_cast<const float4*>(s_red + i * 4);
                tot += t.x;
                mg = fmaxf(mg, t.y);
                mb = fmaxf(mb, t.z);
            }
            const float inv = 1.0f / (tot * (1.0f / HID) + 1e-6f);
            const uint32_t ej = min((__float_as_uint(fmaxf(fmaf(mg, inv, 1.0f) * HSCALE, mb * gs * 0x1p-13f)) >> 23) + 1, 250u);
            const float dn = __uint_as_float((254u - ej) << 23);
            up = min(ej + 127u - (__float_as_uint(gs) >> 23), 254u) * 0x00800080u;
            reinterpret_cast<uint16_t*>(smem + P2_OFF_BIAS + C_DIM * 2)[tid] = 0;
            *reinterpret_cast<__half*>(smem + P2_OFF_BIAS + (tid >> 5) * 64 + (tid & 6) * 8 + (tid & 24) / 2 + (tid & 1) * 2) = __float2half_rn(bias * gs * dn);
#pragma unroll
            for (int i = 0; i < 4; i++) {
                const int k = tid + 384 * i;
                *reinterpret_cast<__half*>(smem + P2_OFF_GRN + (k >> 4) * 32 + (k & 6) * 4 + (k & 8) / 2 + (k & 1) * 2) =
                    __float2half_rn(fmaf(gx[i], inv, 1.0f) * (HSCALE * dn));
            }
            TSTAMP(1, 25);
            bar_sync(1, 384);
        }
        TSTAMP(1, 28);
        if (wg == 1) {
            constexpr int N = sizeof(g_w2img[0]) / 16, PER = (N + NUM_CTAS - 1) / NUM_CTAS;
            uint4 v[5];
#pragma unroll
            for (int i = 0; i < 5; i++) v[i] = __ldcg(&g_w2img[0][min(blockIdx.x * PER + (tid & 127) + 128 * i, N - 1)]);
#pragma unroll
            for (int i = 0; i < 5; i++) {
                const int j = min(blockIdx.x * PER + (tid & 127) + 128 * i, N - 1);
                const uint32_t* t = reinterpret_cast<const uint32_t*>(smem + P2_OFF_GRN + (j / 768) * 32 + (j & 8) / 2);
                auto sc = [&](uint32_t u, int e) { return (h2_mul(u, t[2 * e]) + 0x00040004u) & 0xfff8fff8u; };
                g_w2img[1][j] = make_uint4(sc(v[i].x, 0), sc(v[i].y, 1), sc(v[i].z, 2), sc(v[i].w, 3));
            }
            asm volatile("fence.proxy.async.global;\n" ::: "memory");
            bar_sync(2, 128);
            if (tid == 128) asm volatile("fence.acq_rel.gpu;\nred.release.gpu.global.add.u32 [%0], 1;\n" ::"l"(&g_prog[1][0]) : "memory");
        }

        const int who = __shfl_sync(0xffffffffu, lane == 2 ? 0 : lane < 2 ? 1 : 2, lane);
        const uint32_t rel0 = who ? mapa(bar_bempty, lane & 1) : mapa(bar_aempty + wg * P2_NA * 8, rank), rel1 = rel0 + (who ? 0 : 32);
        auto publish = [&]() {
            asm volatile("fence.proxy.async.shared::cta;\n" ::: "memory");
            __syncwarp();
            if (who == 0) mbar_arrive(bar_oready + wg * 8);
        };
        bool ok_a, pend = false;
        uint32_t pa = 0, s_t;
        auto fetch = [&](int j, bool raw) {
            uint32_t o[6], u0[4], u1[4];
            uint2 t0 = make_uint2(0, 0), t1 = t0;
            if (raw) {
                asm volatile("ld.shared.v2.u32 {%0,%1}, [%2];\n" : "=r"(t0.x), "=r"(t0.y) : "r"(s_t + j * 64) : "memory");
                asm volatile("ld.shared.v2.u32 {%0,%1}, [%2];\n" : "=r"(t1.x), "=r"(t1.y) : "r"(s_t + j * 64 + 32) : "memory");
            }
            const bool ok_b = mbar_test(bar_bfull + (j & 3) * 8, j >> 2);
            if (j == 7) pa ^= 1;
            ok_a = mbar_test(af + ((j + 1) & 7) * 8, pa);
            asm volatile("ldmatrix.sync.aligned.m8n8.x4.trans.shared.b16 {%0,%1,%2,%3}, [%4];\n"
                         : "=r"(o[0]), "=r"(o[1]), "=r"(o[2]), "=r"(o[3]) : "r"(s_a + j * P2_A) : "memory");
            asm volatile("ldmatrix.sync.aligned.m8n8.x2.trans.shared.b16 {%0,%1}, [%2];\n"
                         : "=r"(o[4]), "=r"(o[5]) : "r"(s_a + j * P2_A + 2048) : "memory");
            p2_unpack(u0, o[0], o[1], o[2]);
            p2_unpack(u1, o[3], o[4], o[5]);
            if (raw) {
                u0[0] = h2_mul(u0[0], t0.x); u0[1] = h2_mul(u0[1], t0.x); u0[2] = h2_mul(u0[2], t0.y); u0[3] = h2_mul(u0[3], t0.y);
                u1[0] = h2_mul(u1[0], t1.x); u1[1] = h2_mul(u1[1], t1.x); u1[2] = h2_mul(u1[2], t1.y); u1[3] = h2_mul(u1[3], t1.y);
            }
            a[j & 1][0] = make_uint4(u0[0], u0[1], u0[2], u0[3]);
            a[j & 1][1] = make_uint4(u1[0], u1[1], u1[2], u1[3]);
            if (!ok_b) mbar_wait(bar_bfull + (j & 3) * 8, j >> 2);
        };
        auto table = [&](int pos) { s_t = sbase + P2_OFF_GRN + q * 8 + (k0 + pos) % 48 * 64; };
        const uint64_t db0 = make_desc(sbase, 128, 256);
        auto block8 = [&](bool raw, int pos, int thr0, int mode) {
#pragma unroll
            for (int j = 0; j < 8; j++) {
                const uint64_t db = db0 + (j & 3) * (P2_B / 16);
                if (j == 8 - P2_AH && mode == 1) bar_sync(4, 384);
                TR2(wg, pos + j, 0);
                wg_fence();
                mma_rs_n192(acc0, a[j & 1][0], db);
                mma_rs_n192(acc1, a[j & 1][0], db + 384);
                mma_rs_n192(acc0, a[j & 1][1], db + 768);
                mma_rs_n192(acc1, a[j & 1][1], db + 768 + 384);
                wg_commit();
                if (j == 7 && mode == 2) bar_arrive(4, 384);
                const uint32_t rel = ((j - 1) & 4 ? rel1 : rel0) + ((j - 1) & 3) * 8;
                TR2(wg, pos + j, 1);
                wg_wait<1>();
                TR2(wg, pos + j, 2);
                if (who < (j ? 2 : thr0)) mbar_arrive_cluster(rel);
                if (!ok_a) {
                    if (j == 0 && pend) { publish(); pend = false; }
                    mbar_wait(af + ((j + 1) & 7) * 8, pa);
                }
                TR2(wg, pos + j, 3);
                if (raw && j == 7) table(pos + 8);
                fetch((j + 1) & 7, raw && (j < 7 || pos + 8 < P2_RAW));
            }
        };
        int n = wg == 2 && half ? -1 : wg, pos = p2_start(n);
        uint32_t px = 0;
        wait_pos(pos);
        mbar_wait(af, 0);
        table(pos);
        fetch(0, pos < P2_RAW);
#pragma unroll 1
        for (;; n += 3) {
            TSTAMP(1, 2 + n);
            const int end = pos + (n < 0 ? 24 : 48);
#pragma unroll
            for (int i = 0; i < 48; i += 2) {
                asm volatile("mov.b64 {%0, %1}, 0;\n" : "=r"(acc0[i]), "=r"(acc0[i + 1]));
                asm volatile("mov.b64 {%0, %1}, 0;\n" : "=r"(acc1[i]), "=r"(acc1[i + 1]));
            }
            int thr = 1;
#pragma unroll 1
            for (; pos < P2_RAW; pos += 8, thr = 2) block8(true, pos, thr, 0);
#pragma unroll 1
            for (; pos < end; pos += 8, thr = 2) {
                const int e = pos + 8, r = e % 48;
                block8(false, pos, thr, e < 48 || e > 256 || (r != 0 && r != P2_S1 && r != P2_S2) ? 0 : e == end ? 2 : 1);
            }
            TR2(wg, pos - 1, 4);
            wg_wait<0>();
            TR2(wg, pos - 1, 5);
            if (who == 1) mbar_arrive_cluster(rel0 + 24);
            mbar_wait(bar_xfull + wg * 8, px);
            TR2(wg, pos - 1, 6);
            px ^= 1;
            __syncwarp();
            p2_epilogue(acc0, acc1, up, sx, sbase + P2_OFF_BIAS + q * 16 + (n < 0 && fin ? C_DIM * 2 : 0), zero);
            TR2(wg, pos - 1, 7);
            if (n + 3 >= P2_ITEMS) { publish(); break; }
            if (n < 0) {
                publish();
                pos = P2_S2;
                wait_pos(pos);
                mbar_wait(bar_bfull, 0);
            } else {
                pend = true;
                ok_a = false;
            }
        }
        TSTAMP(1, 29);
        cluster_sync();
        TSTAMP(1, 30);
    }
}

}

extern "C" void kernel_launch(void* const* d_in, const int* in_sizes, int n_in, void* d_out, int out_size) {
    const __nv_bfloat16* x = (const __nv_bfloat16*)d_in[0];
    const __nv_bfloat16* dw = (const __nv_bfloat16*)d_in[1];
    const __nv_bfloat16* w1 = (const __nv_bfloat16*)d_in[2];
    const __nv_bfloat16* w2 = (const __nv_bfloat16*)d_in[3];
    const __nv_bfloat16* grn_g = (const __nv_bfloat16*)d_in[4];
    const __nv_bfloat16* grn_b = (const __nv_bfloat16*)d_in[5];
    __nv_bfloat16* out = (__nv_bfloat16*)d_out;

    cudaFuncSetAttribute(pass1_kernel, cudaFuncAttributeMaxDynamicSharedMemorySize, P1_SMEM);
    cudaFuncSetAttribute(pass2_kernel, cudaFuncAttributeMaxDynamicSharedMemorySize, P2_SMEM);

    typedef CUresult (*EncodeFn)(CUtensorMap*, CUtensorMapDataType, cuuint32_t, void*, const cuuint64_t*, const cuuint64_t*,
                                 const cuuint32_t*, const cuuint32_t*, CUtensorMapInterleave, CUtensorMapSwizzle,
                                 CUtensorMapL2promotion, CUtensorMapFloatOOBfill);
    static EncodeFn encode = nullptr;
    if (!encode) {
        cudaDriverEntryPointQueryResult qres;
        cudaGetDriverEntryPoint("cuTensorMapEncodeTiled", (void**)&encode, cudaEnableDefault, &qres);
    }
    CUtensorMap wmap;
    const cuuint64_t gdim[2] = {HID, C_DIM};
    const cuuint64_t gstr[1] = {HID * 2};
    const cuuint32_t box[2] = {64, 192}, estr[2] = {1, 1};
    CUresult er = encode(&wmap, CU_TENSOR_MAP_DATA_TYPE_BFLOAT16, 2, (void*)w1, gdim, gstr, box, estr, CU_TENSOR_MAP_INTERLEAVE_NONE,
           CU_TENSOR_MAP_SWIZZLE_128B, CU_TENSOR_MAP_L2_PROMOTION_L2_128B, CU_TENSOR_MAP_FLOAT_OOB_FILL_NONE);
    if (er != CUDA_SUCCESS) printf("tensor map encode failed %d\n", (int)er);

    pass1_kernel<<<NUM_CTAS, 512, P1_SMEM>>>(wmap, x, dw, w2, grn_b, 0);

    cudaLaunchAttribute attr[1];
    attr[0].id = cudaLaunchAttributeProgrammaticStreamSerialization;
    attr[0].val.programmaticStreamSerializationAllowed = 1;
    cudaLaunchConfig_t cfg = {};
    cfg.gridDim = dim3(NUM_CTAS);
    cfg.stream = 0;
    cfg.attrs = attr;
    cfg.numAttrs = 1;
    cfg.blockDim = dim3(512);
    cfg.dynamicSmemBytes = P2_SMEM;
    cudaLaunchKernelEx(&cfg, pass2_kernel, x, grn_g, out, 0);
}
```

```cpp
#include <cuda.h>
#include <cuda_runtime.h>
#include <cuda_bf16.h>
#include <cuda_fp16.h>
#include <stdint.h>
#include <stdio.h>

namespace {

constexpr int M_TOTAL = 384 * 384;
constexpr int C_DIM   = 384;
constexpr int HID     = 1536;
constexpr int NT128   = M_TOTAL / 128;
constexpr int NUM_CTAS = 132;

constexpr int NGRP = 22, GRP_CTAS = 6;
constexpr int LN_STEP = NUM_CTAS / 4, LN_RING = 2 * LN_STEP;
constexpr int LN_TILE = 128 * C_DIM * 2;
constexpr int H_TILE = 64 * HID * 3 / 2;
constexpr int H_HALF = 3072, H_STEP = 6144;

__device__ __align__(1024) uint4 g_h[(size_t)M_TOTAL * HID * 3 / 32];
__device__ __align__(1024) uint4 g_ln[LN_RING * LN_TILE / 16];
__device__ __align__(1024) uint4 g_w2img[2][HID * C_DIM * 2 / 16];
__device__ __align__(16) float g_sums[2][HID + 512];
__device__ float g_scale[HID];
__device__ float g_redo[HID];
__device__ unsigned g_epoch;
__device__ __align__(128) unsigned g_prog[3][32];
__device__ __align__(128) unsigned g_half[32][2];
__device__ unsigned g_flag[LN_RING + 3][2][8];
#define TSTAMP(k, i)
#define TRACE(wg, pos, i)
#define TRACEW(pos, i)

#define TR2(wg, pos, i)
__host__ __device__ __forceinline__ int perm32(int n) {
    return (n & ~31) | (((n >> 1) & 3) << 3) | (((n >> 3) & 3) << 1) | (n & 1);
}

__device__ __forceinline__ uint32_t smem_u32(const void* p) { return (uint32_t)__cvta_generic_to_shared(p); }

__device__ __forceinline__ void mbar_init(uint32_t bar, uint32_t count) {
    asm volatile("mbarrier.init.shared::cta.b64 [%0], %1;\n" ::"r"(bar), "r"(count) : "memory");
}
__device__ __forceinline__ void mbar_expect_tx(uint32_t bar, uint32_t bytes) {
    asm volatile("mbarrier.arrive.expect_tx.shared::cta.b64 _, [%0], %1;\n" ::"r"(bar), "r"(bytes) : "memory");
}
__device__ __forceinline__ void mbar_arrive(uint32_t bar) {
    asm volatile("mbarrier.arrive.shared::cta.b64 _, [%0];\n" ::"r"(bar) : "memory");
}
__device__ __forceinline__ void mbar_arrive_cluster(uint32_t bar_cluster_addr) {
    asm volatile("mbarrier.arrive.shared::cluster.b64 _, [%0];\n" ::"r"(bar_cluster_addr) : "memory");
}
#define SAFE_BREAK
__device__ __forceinline__ void mbar_wait(uint32_t bar, uint32_t parity) {
    asm volatile(
        "{\n"
        ".reg .pred p;\n"
        "LAB_WAIT:\n"
        "mbarrier.try_wait.parity.shared::cta.b64 p, [%0], %1;\n"
        "@!p bra LAB_WAIT;\n"
        "}\n" ::"r"(bar), "r"(parity) : "memory");
}
__device__ __forceinline__ bool mbar_test(uint32_t bar, uint32_t parity) {
    uint32_t ok;
    asm volatile("{\n.reg .pred p;\n"
                 "mbarrier.test_wait.parity.shared::cta.b64 p, [%1], %2;\n"
                 "selp.u32 %0, 1, 0, p;\n}\n" : "=r"(ok) : "r"(bar), "r"(parity) : "memory");
    return ok != 0;
}
__device__ __forceinline__ uint32_t mapa(uint32_t addr, uint32_t rank) {
    uint32_t r;
    asm volatile("mapa.shared::cluster.u32 %0, %1, %2;\n" : "=r"(r) : "r"(addr), "r"(rank));
    return r;
}
__device__ __forceinline__ void bulk_g2s(uint32_t dst, const void* src, uint32_t bytes, uint32_t bar) {
    asm volatile("cp.async.bulk.shared::cluster.global.mbarrier::complete_tx::bytes [%0], [%1], %2, [%3];\n"
                 ::"r"(dst), "l"(src), "r"(bytes), "r"(bar) : "memory");
}
__device__ __forceinline__ void bulk_g2s_mc(uint32_t dst, const void* src, uint32_t bytes, uint32_t bar, uint16_t mask) {
    asm volatile("cp.async.bulk.shared::cluster.global.mbarrier::complete_tx::bytes.multicast::cluster [%0], [%1], %2, [%3], %4;\n"
                 ::"r"(dst), "l"(src), "r"(bytes), "r"(bar), "h"(mask) : "memory");
}
__device__ __forceinline__ void tma2(uint32_t dst, const CUtensorMap* map, int c0, int c1, uint32_t bar) {
    asm volatile("cp.async.bulk.tensor.2d.shared::cluster.global.tile.mbarrier::complete_tx::bytes [%0], [%1, {%2, %3}], [%4];\n"
                 ::"r"(dst), "l"(map), "r"(c0), "r"(c1), "r"(bar) : "memory");
}
template <bool ACQ>
__device__ __forceinline__ uint32_t flag_wait(const unsigned* p, unsigned target) {
    unsigned v, n = 0;
    do {
        if (ACQ) asm volatile("ld.acquire.gpu.global.u32 %0, [%1];\n" : "=r"(v) : "l"(p) : "memory");
        else asm volatile("ld.relaxed.gpu.global.u32 %0, [%1];\n" : "=r"(v) : "l"(p) : "memory");
        n++;
    } while (v < target);
    return n == 1;
}
__device__ __forceinline__ void ldsm4t(uint32_t (&r)[4], uint32_t addr) {
    asm volatile("ldmatrix.sync.aligned.m8n8.x4.trans.shared.b16 {%0,%1,%2,%3}, [%4];\n"
                 : "=r"(r[0]), "=r"(r[1]), "=r"(r[2]), "=r"(r[3]) : "r"(addr) : "memory");
}
__device__ __forceinline__ void bulk_s2g(void* dst, uint32_t src, uint32_t bytes) {
    asm volatile("cp.async.bulk.global.shared::cta.bulk_group [%0], [%1], %2;\n" ::"l"(dst), "r"(src), "r"(bytes) : "memory");
}
__device__ __forceinline__ void cluster_sync() {
    asm volatile("barrier.cluster.arrive.aligned;\nbarrier.cluster.wait.aligned;\n" ::: "memory");
}
__device__ __forceinline__ void cluster_sync_relaxed() {
    asm volatile("barrier.cluster.arrive.relaxed.aligned;\nbarrier.cluster.wait.aligned;\n" ::: "memory");
}
__device__ __forceinline__ void gdc_wait() { asm volatile("griddepcontrol.wait;\n" ::: "memory"); }
__device__ __forceinline__ void gdc_launch() { asm volatile("griddepcontrol.launch_dependents;\n" ::: "memory"); }
__device__ __forceinline__ uint32_t cluster_rank() {
    uint32_t r;
    asm volatile("mov.u32 %0, %%cluster_ctarank;\n" : "=r"(r));
    return r;
}
__device__ __forceinline__ bool elect_one() {
    uint32_t pred;
    asm volatile("{\n.reg .pred p;\nelect.sync _|p, 0xffffffff;\nselp.u32 %0, 1, 0, p;\n}\n" : "=r"(pred));
    return pred != 0;
}
__device__ __forceinline__ void wg_fence() { asm volatile("wgmma.fence.sync.aligned;\n" ::: "memory"); }
__device__ __forceinline__ void wg_commit() { asm volatile("wgmma.commit_group.sync.aligned;\n" ::: "memory"); }
template <int N> __device__ __forceinline__ void wg_wait() {
    asm volatile("wgmma.wait_group.sync.aligned %0;\n" ::"n"(N) : "memory");
}
template <int R> __device__ __forceinline__ void reg_inc() { asm volatile("setmaxnreg.inc.sync.aligned.u32 %0;\n" ::"n"(R)); }
template <int R> __device__ __forceinline__ void reg_dec() { asm volatile("setmaxnreg.dec.sync.aligned.u32 %0;\n" ::"n"(R)); }
__device__ __forceinline__ void bar_sync(int id, int n) { asm volatile("bar.sync %0, %1;\n" ::"r"(id), "r"(n) : "memory"); }
__device__ __forceinline__ void bar_arrive(int id, int n) { asm volatile("bar.arrive %0, %1;\n" ::"r"(id), "r"(n) : "memory"); }

__device__ __forceinline__ uint64_t make_desc(uint32_t saddr, uint32_t lbo, uint32_t sbo) {
    return (uint64_t)((saddr & 0x3FFFF) >> 4) | ((uint64_t)(lbo >> 4) << 16) | ((uint64_t)(sbo >> 4) << 32);
}

__device__ __forceinline__ void stg128_cs(void* p, uint32_t a, uint32_t b, uint32_t c, uint32_t d) {
    asm volatile("st.global.cs.v4.u32 [%0], {%1,%2,%3,%4};\n" ::"l"(p), "r"(a), "r"(b), "r"(c), "r"(d) : "memory");
}
__device__ __forceinline__ uint32_t pack_bf16(float lo, float hi) {
    uint32_t r;
    asm("cvt.rn.bf16x2.f32 %0, %1, %2;\n" : "=r"(r) : "f"(hi), "f"(lo));
    return r;
}
__device__ __forceinline__ float bf_lo(uint32_t v) { return __uint_as_float(v << 16); }
__device__ __forceinline__ float bf_hi(uint32_t v) { return __uint_as_float(v & 0xffff0000u); }
__device__ __forceinline__ uint32_t bf2_mul(uint32_t a, uint32_t b) {
    uint32_t r;
    asm("mul.rn.bf16x2 %0, %1, %2;\n" : "=r"(r) : "r"(a), "r"(b));
    return r;
}
__device__ __forceinline__ uint32_t bf2_fma(uint32_t a, uint32_t b, uint32_t c) {
    uint32_t r;
    asm("fma.rn.bf16x2 %0, %1, %2, %3;\n" : "=r"(r) : "r"(a), "r"(b), "r"(c));
    return r;
}
__device__ __forceinline__ uint32_t bf2_add(uint32_t a, uint32_t b) {
    uint32_t r;
    asm("add.rn.bf16x2 %0, %1, %2;\n" : "=r"(r) : "r"(a), "r"(b));
    return r;
}
__device__ __forceinline__ uint32_t h2_mul(uint32_t a, uint32_t b) {
    uint32_t r;
    asm("mul.rn.f16x2 %0, %1, %2;\n" : "=r"(r) : "r"(a), "r"(b));
    return r;
}
__device__ __forceinline__ uint32_t h2_fma(uint32_t a, uint32_t b, uint32_t c) {
    uint32_t r;
    asm("fma.rn.f16x2 %0, %1, %2, %3;\n" : "=r"(r) : "r"(a), "r"(b), "r"(c));
    return r;
}
__device__ __forceinline__ uint32_t h2_add(uint32_t a, uint32_t b) {
    uint32_t r;
    asm("add.rn.f16x2 %0, %1, %2;\n" : "=r"(r) : "r"(a), "r"(b));
    return r;
}
__device__ __forceinline__ uint32_t pack_f16(float lo, float hi) {
    uint32_t r;
    asm("cvt.rn.f16x2.f32 %0, %1, %2;\n" : "=r"(r) : "f"(hi), "f"(lo));
    return r;
}
__device__ __forceinline__ float h_lo(uint32_t v) { return __low2float(*reinterpret_cast<const __half2*>(&v)); }
__device__ __forceinline__ float h_hi(uint32_t v) { return __high2float(*reinterpret_cast<const __half2*>(&v)); }
__device__ __forceinline__ uint32_t bf2_to_h2(uint32_t v) { return (v & 0x7fff7fffu) * 7u + v; }
__device__ __forceinline__ uint32_t prmt(uint32_t a, uint32_t b, uint32_t sel) {
    uint32_t r;
    asm("prmt.b32 %0, %1, %2, %3;\n" : "=r"(r) : "r"(a), "r"(b), "r"(sel));
    return r;
}
__device__ __forceinline__ uint32_t bitsel(uint32_t a, uint32_t b, uint32_t m) {
    uint32_t r;
    asm("lop3.b32 %0, %1, %2, %3, 0xd8;\n" : "=r"(r) : "r"(a), "r"(b), "r"(m));
    return r;
}
constexpr float KAPPA = 0.3292034911525734f;
constexpr uint32_t GELU_C2 = 0x40d940d9u;
constexpr float HSCALE = 1.0f / (2.0f * KAPPA);
__device__ __forceinline__ float w2_scale(uint32_t m) { return __uint_as_float((257u - max(m >> 23, 16u)) << 23); }
__device__ __forceinline__ void sched_break(int zero) {
    asm volatile("{\n.reg .pred p;\nsetp.ne.s32 p, %0, 0;\nSB_LOOP:\n@p nanosleep.u32 1;\n@p bra SB_LOOP;\n}\n" ::"r"(zero));
}

#define ACC8(d, o) "+r"(d[o + 0]), "+r"(d[o + 1]), "+r"(d[o + 2]), "+r"(d[o + 3]), "+r"(d[o + 4]), "+r"(d[o + 5]), "+r"(d[o + 6]), "+r"(d[o + 7])

__device__ __forceinline__ void mma_rs_n128(uint32_t (&d)[32], const uint32_t (&a)[4], uint32_t desc, int scale_d) {
    asm volatile(
        "{\n.reg .pred p;\n.reg .b64 db;\nsetp.ne.b32 p, %37, 0;\nmov.b64 db, {%36, 0x40000040};\n"
        "wgmma.mma_async.sync.aligned.m64n128k16.f16.f16.f16 "
        "{%0,%1,%2,%3,%4,%5,%6,%7,%8,%9,%10,%11,%12,%13,%14,%15,"
        "%16,%17,%18,%19,%20,%21,%22,%23,%24,%25,%26,%27,%28,%29,%30,%31},"
        "{%32,%33,%34,%35}, db, p, 1, 1, 0;\n}\n"
        : ACC8(d, 0), ACC8(d, 8), ACC8(d, 16), ACC8(d, 24)
        : "r"(a[0]), "r"(a[1]), "r"(a[2]), "r"(a[3]), "r"(desc), "r"(scale_d));
}

__device__ __forceinline__ void mma_ss_n128(uint32_t (&d)[32], uint32_t da, uint32_t db, int scale_d) {
    asm volatile(
        "{\n.reg .pred p;\n.reg .b64 da, db;\nsetp.ne.b32 p, %34, 0;\nmov.b64 da, {%32, 0x40000040};\nmov.b64 db, {%33, 0x40000040};\n"
        "wgmma.mma_async.sync.aligned.m64n128k16.f16.f16.f16 "
        "{%0,%1,%2,%3,%4,%5,%6,%7,%8,%9,%10,%11,%12,%13,%14,%15,"
        "%16,%17,%18,%19,%20,%21,%22,%23,%24,%25,%26,%27,%28,%29,%30,%31},"
        "da, db, p, 1, 1, 1, 0;\n}\n"
        : ACC8(d, 0), ACC8(d, 8), ACC8(d, 16), ACC8(d, 24)
        : "r"(da), "r"(db), "r"(scale_d));
}

__device__ __forceinline__ void mma_rs_n192(uint32_t (&d)[48], const uint4& a, uint32_t db) {
    asm volatile(
        "{\n.reg .b64 db;\nmov.b64 db, {%52, 16};\n"
        "wgmma.mma_async.sync.aligned.m64n192k16.f16.f16.f16 "
        "{%0,%1,%2,%3,%4,%5,%6,%7,%8,%9,%10,%11,%12,%13,%14,%15,"
        "%16,%17,%18,%19,%20,%21,%22,%23,%24,%25,%26,%27,%28,%29,%30,%31,"
        "%32,%33,%34,%35,%36,%37,%38,%39,%40,%41,%42,%43,%44,%45,%46,%47},"
        "{%48,%49,%50,%51}, db, 1, 1, 1, 0;\n}\n"
        : ACC8(d, 0), ACC8(d, 8), ACC8(d, 16), ACC8(d, 24), ACC8(d, 32), ACC8(d, 40)
        : "r"(a.x), "r"(a.y), "r"(a.z), "r"(a.w), "r"(db));
}

#define P1_WPF 30
#define P1_PACE 1
constexpr int P1_SLOT = LN_TILE / 6, P1_NST = 6;
constexpr int P1_W = 64 * C_DIM * 2;
constexpr int P1_X = 32 * C_DIM * 2;
constexpr int P1_OFF_W = LN_TILE;
constexpr int P1_OFF_X = P1_OFF_W + 2 * P1_W;
constexpr int P1_OFF_BAR = P1_OFF_X + P1_X;
constexpr int P1_OFF_TILE = P1_OFF_BAR + (2 * P1_NST + 4 + 4 + 4) * 8;
constexpr int P1_OFF_EX = P1_OFF_TILE + 64;
constexpr int P1_OFF_DW = P1_OFF_EX + 256 * 4;
constexpr int P1_SMEM = P1_OFF_DW + C_DIM * 2;

__device__ __forceinline__ float rsqrt_fast(float x) {
    float r;
    asm("rsqrt.approx.ftz.f32 %0, %1;\n" : "=f"(r) : "f"(x));
    return r;
}
__device__ __forceinline__ float row_sum(const uint32_t (&c)[4]) {
    const uint32_t u = bf2_add(bf2_add(c[0], c[1]), bf2_add(c[2], c[3]));
    float s = bf_lo(u) + bf_hi(u);
#pragma unroll
    for (int o = 1; o < 8; o <<= 1) s += __shfl_xor_sync(0xffffffffu, s, o);
    return s;
}
__device__ __forceinline__ uint32_t pace(uint32_t bar, uint32_t off, uint32_t val, uint32_t after, int zero) {
    asm volatile(
        "{\n.reg .pred p, q;\n.reg .b32 par;\n"
        "lop3.b32 par, %4, %2, %3, 0xea;\n"
        "setp.eq.u32 q, par, 0;\n"
        "mov.pred p, 0;\n"
        "@q mbarrier.test_wait.parity.shared::cta.b64 p, [%1], par;\n"
        "selp.u32 par, 1, 0, p;\n"
        "@q mbarrier.try_wait.parity.shared::cta.b64 p, [%1], par, 1000;\n"
        "@p or.b32 %0, %0, %2;\n"
        "}\n" : "+r"(val) : "r"(bar), "r"(zero), "r"(off), "r"(after));
    return val;
}
template <int PACE, int R>
__device__ __forceinline__ void ln_rows(uint32_t (&v)[R][6][4], const uint32_t (&d)[6][4], uint32_t bar, uint32_t off, int zero,
                                        uint32_t bar_read) {
    const float inv = 1.0f / C_DIM;
    uint32_t c[R][4], nm[R];
    float e[R], r[R], er[R];
    bool big = false;
#pragma unroll
    for (int p = 0; p < R; p++) {
#pragma unroll
        for (int i = 0; i < 6; i++)
#pragma unroll
            for (int k = 0; k < 4; k++) c[p][k] = bf2_fma(v[p][i][k], d[i][k], i ? c[p][k] : 0);
        const float m = row_sum(c[p]) * inv;
        nm[p] = pack_bf16(-m, -m);
        e[p] = m + bf_lo(nm[p]);
    }
    if (bar_read) mbar_arrive(bar_read + (nm[0] & zero));
    if (PACE & 1) nm[0] = pace(bar, off, nm[0], nm[0], zero);
#pragma unroll
    for (int p = 0; p < R; p++) {
#pragma unroll
        for (int i = 0; i < 6; i++) {
#pragma unroll
            for (int k = 0; k < 4; k++) {
                v[p][i][k] = bf2_fma(v[p][i][k], d[i][k], nm[p]);
                c[p][k] = i ? bf2_fma(v[p][i][k], v[p][i][k], c[p][k]) : bf2_mul(v[p][i][k], v[p][i][k]);
            }
        }
        r[p] = KAPPA * rsqrt_fast(fmaxf(fmaf(-e[p], e[p], row_sum(c[p]) * inv), 0.f) + 1e-5f);
        er[p] = -e[p] * r[p] * 0x1p-112f;
        big |= r[p] < 0x1p-8f;
    }
    if (__any_sync(0xffffffffu, big)) {
#pragma unroll
        for (int p = 0; p < R; p++) {
            const uint32_t p2 = __float_as_uint(r[p]) & 0x7f800000u;
            r[p] = __uint_as_float((__float_as_uint(r[p]) & 0x007fffffu) | 0x3f800000u);
#pragma unroll
            for (int i = 0; i < 6; i++)
#pragma unroll
                for (int k = 0; k < 4; k++) v[p][i][k] = bf2_mul(v[p][i][k], p2 | p2 >> 16);
        }
    }
#pragma unroll
    for (int p = 0; p < R; p++) {
        uint32_t rs = pack_bf16(r[p] * 0x1p-112f, r[p] * 0x1p-112f);
        const uint32_t sh = pack_bf16(er[p], er[p]);
        if (PACE & 2) rs = pace(bar, off, rs, sh, zero);
#pragma unroll
        for (int i = 0; i < 6; i++)
#pragma unroll
            for (int k = 0; k < 4; k++) v[p][i][k] = bf2_to_h2(bf2_fma(v[p][i][k], rs, sh));
    }
}

template <int R>
__device__ __forceinline__ uint32_t gelu2(uint32_t a, uint32_t sc2) {
    uint32_t y, t;
    if (R) asm("{\n.reg .b16 l, h;\n.reg .b32 f;\nmov.b32 {l, h}, %2;\nmov.b32 f, {h, h};\nmul.rn.f16x2 %0, %1, f;\n}\n" : "=r"(y) : "r"(a), "r"(sc2));
    else asm("{\n.reg .b16 l, h;\n.reg .b32 f;\nmov.b32 {l, h}, %2;\nmov.b32 f, {l, l};\nmul.rn.f16x2 %0, %1, f;\n}\n" : "=r"(y) : "r"(a), "r"(sc2));
    asm("tanh.approx.f16x2 %0, %1;\n" : "=r"(t) : "r"(h2_mul(y, h2_fma(y, y, GELU_C2))));
    return h2_fma(a, t, a);
}
constexpr uint32_t SPARE = 0x40074007u;

__device__ __forceinline__ uint32_t p1_parity(uint32_t sbase) {
    uint32_t v;
    asm volatile("ld.shared.u32 %0, [%1];\n" : "=r"(v) : "r"(sbase + P1_OFF_TILE - 4) : "memory");
    return v;
}
__device__ __forceinline__ uint32_t p1_exponents(float (&t)[2], uint32_t (&ex)[2], uint32_t saddr, int lane) {
#pragma unroll
    for (int r = 0; r < 2; r++) {
        t[r] += __shfl_xor_sync(0xffffffffu, t[r], 1);
        t[r] += __shfl_xor_sync(0xffffffffu, t[r], 2);
        ex[r] = min(max(((__float_as_uint(193.3f * t[r]) >> 23) + 127u) >> 1, 72u), 198u);
        asm volatile("st.shared.u32 [%0], %1;\n" ::"r"(saddr + r * 32), "r"(ex[r] << 23) : "memory");
    }
    return pack_f16(__uint_as_float(min(ex[0], 142u) << 23), __uint_as_float(min(ex[1], 142u) << 23));
}
template <int N>
__device__ __forceinline__ void p1_convert(uint32_t (&o)[N][4], uint32_t (&v)[N][4], const uint32_t (&ex)[2]) {
    if (__any_sync(0xffffffffu, max(ex[0], ex[1]) > 141u)) {
#pragma unroll
        for (int k = 0; k < 4 * N; k++) v[k >> 2][k & 3] = bf2_mul(v[k >> 2][k & 3], ex[k & 1] > 141u ? 0x1f801f80u : 0x3f803f80u);
    }
#pragma unroll
    for (int k = 0; k < 4 * N; k++) {
        const uint32_t u = bf2_mul(v[k >> 2][k & 3], ((ex[k & 1] > 141u ? 206u : 142u) - ex[k & 1]) * 0x00800080u);
        asm volatile("mad.lo.u32 %0, %1, 7, %2;\n" : "=r"(o[k >> 2][k & 3]) : "r"(u & 0x7fff7fffu), "r"(u));
    }
}
template <int N>
__device__ __forceinline__ void p1_squares(const uint32_t (&v)[N][4], float (&t)[2]) {
#pragma unroll
    for (int j = 0; j < N / 2; j++) {
        const int r = j & 1, b = (j >> 1) * 4;
        uint32_t c = bf2_mul(v[b][r], v[b][r]);
#pragma unroll
        for (int k = 1; k < 8; k++) c = bf2_fma(v[b + k / 2][r + (k & 1) * 2], v[b + k / 2][r + (k & 1) * 2], c);
        t[r] += bf_lo(c) + bf_hi(c);
    }
}
__device__ __forceinline__ void p1_epilogue(const uint32_t (&acc)[2][32], const uint32_t (&sc2)[2], float (&ssq)[4], uint8_t* hp, int zero) {
    uint32_t sq[2], h[16][4];
#pragma unroll
    for (int i2 = 0; i2 < 9; i2++) {
#pragma unroll
        for (int c = 2 * i2 - 2; c < 2 * i2; c++) {
            if (c >= 0 && (c & 3)) {
                uint32_t o[4];
#pragma unroll
                for (int u = 0; u < 4; u++) {
                    const uint32_t v = h[c & 12][u];
                    o[u] = bitsel(h[c][u], (c & 3) == 2 ? prmt(v, v, 0xa381) : prmt(v >> 3, v, (c & 3) == 1 ? 0x6240 : 0xf3d1), SPARE);
                }
                stg128_cs(hp + (c >> 3) * 2 * H_STEP + ((c >> 2) & 1) * H_HALF + ((c & 3) - 1) * 512, o[0], o[1], o[2], o[3]);
            }
        }
        if (i2 < 8) {
#pragma unroll
            for (int u = 0; u < 4; u++) {
                h[2 * i2][u] = gelu2<0>(acc[i2 >> 2][8 * (i2 & 3) + 2 * u], sc2[i2 >> 2]);
                h[2 * i2 + 1][u] = gelu2<1>(acc[i2 >> 2][8 * (i2 & 3) + 2 * u + 1], sc2[i2 >> 2]);
#pragma unroll
                for (int r = 0; r < 2; r++) {
                    const uint32_t v = h[2 * i2 + r][u];
                    sq[r] = ((i2 & 3) | u) ? h2_fma(v, v, sq[r]) : h2_mul(v, v);
                }
            }
            if ((i2 & 3) == 3) {
#pragma unroll
                for (int r = 0; r < 2; r++) ssq[(i2 >> 2) * 2 + r] += h_lo(sq[r]) + h_hi(sq[r]);
            }
            sched_break(zero);
        }
    }
}
template <int WG>
__device__ __forceinline__ void p1_mma(uint32_t (&acc)[2][32], const uint32_t (&a)[24][4], uint32_t sbase, uint32_t empty_remote, int i, int lane) {
    const uint32_t bar_full = sbase + P1_OFF_BAR;
    const uint32_t db = (uint32_t)make_desc(sbase, 16, 1024), da = db + (P1_OFF_W + WG * P1_W) / 16;
    if (WG == 0) mbar_wait(bar_full, i & 1);
    bar_sync(1 + WG, 256);
    TRACE(WG, i, 1);
    wg_fence();
#pragma unroll
    for (int k = 0; k < 24; k++) {
        if (WG == 0 && k && k % 4 == 0) mbar_wait(bar_full + (k >> 2) * 8, i & 1);
        mma_rs_n128(acc[0], a[k], db + (k >> 2) * 1024 + (k & 3) * 2, k != 0);
        mma_ss_n128(acc[1], da + k * 128, db + (k >> 2) * 1024 + (k & 3) * 2, k != 0);
        if (k == 23) bar_arrive(2 - WG, 256);
        if (k == 23 || (WG == 1 && k % 4 == 3)) wg_commit();
        if (WG == 1 && k % 4 == 3 && k > 3) {
            wg_wait<1>();
            if (lane < 2) mbar_arrive_cluster(empty_remote + ((k >> 2) - 1) * 8);
        }
    }
    TRACE(WG, i, 2);
    wg_wait<0>();
    if (WG == 1 && lane < 2) mbar_arrive_cluster(empty_remote + 5 * 8);
}
__device__ __forceinline__ void p1_consumer(const uint32_t (&a)[24][4], const uint32_t (&sc2)[2], uint32_t sbase, int WG, int w, int lane, int zero) {
    const uint32_t bar_full = sbase + P1_OFF_BAR, bar_empty = bar_full + P1_NST * 8;
    const uint32_t empty_remote = mapa(bar_empty, lane & 1);
    const uint32_t bar_pace = bar_empty + P1_NST * 8 + 32 + w * 8;
    const int g = lane >> 2, q = lane & 3, cb = (blockIdx.x % GRP_CTAS) * 4 + WG * 2;
    uint32_t acc[2][32];
    float ssq[4] = {0.f, 0.f, 0.f, 0.f};
    TSTAMP(0, 1);

    uint8_t* hp = reinterpret_cast<uint8_t*>(g_h) + ((cb * 2 + (w >> 1)) * H_STEP + (w & 1) * 1536) + g * 64 + (q ^ (g >> 1)) * 16;
    int i = 0;
#pragma unroll 1
    for (;; i++) {
        TRACE(WG, i, 0);
        if (WG == 0) p1_mma<0>(acc, a, sbase, empty_remote, i, lane);
        else p1_mma<1>(acc, a, sbase, empty_remote, i, lane);
        TRACE(WG, i, 4);
        uint32_t step, more;
        asm volatile("ld.shared.v2.u32 {%0, %1}, [%2];\n" : "=r"(step), "=r"(more) : "r"(sbase + P1_OFF_TILE + (i & 3) * 16) : "memory");
        hp += step;
        p1_epilogue(acc, sc2, ssq, hp, zero);
        if (lane == 0) mbar_arrive(bar_pace);
        if (!more) break;
    }
    TSTAMP(0, 21);
    if (WG == 0) bar_sync(1, 256);
#pragma unroll
    for (int r = 0; r < 4; r++) {
        const int ch = (r >> 1) * 64 + w * 16 + (r & 1) * 8 + g;
        ssq[r] += __shfl_xor_sync(0xffffffffu, ssq[r], 1);
        ssq[r] += __shfl_xor_sync(0xffffffffu, ssq[r], 2);
        float f;
        asm volatile("ld.shared.f32 %0, [%1];\n" : "=f"(f) : "r"(sbase + P1_OFF_EX + (WG * 128 + ch) * 4) : "memory");
        if (q == 0) {
            float* sums = g_sums[p1_parity(sbase)];
            atomicAdd(&sums[cb * 64 + ch], ssq[r] * f * f);
            g_scale[cb * 64 + ch] = f;
            if (ssq[r] < (i + 1) * 0x1p-12f) sums[HID + C_DIM + 1] = 1.f;
        }
    }
}

__global__ void __cluster_dims__(2, 1, 1) __launch_bounds__(512, 1)
pass1_kernel(const __grid_constant__ CUtensorMap wmap, const __nv_bfloat16* __restrict__ x, const __nv_bfloat16* __restrict__ dw,
             const __nv_bfloat16* __restrict__ w2, const __nv_bfloat16* __restrict__ grn_b, int zero) {
    extern __shared__ __align__(1024) uint8_t smem[];
    const uint32_t sbase = smem_u32(smem);
    const uint32_t bar_full = sbase + P1_OFF_BAR, bar_empty = bar_full + P1_NST * 8, bar_w = bar_empty + P1_NST * 8;
    const int tid = threadIdx.x;
    const int warp = __shfl_sync(0xffffffffu, tid >> 5, 0), lane = tid & 31;
    const uint32_t rank = cluster_rank();
    const int cig = blockIdx.x % GRP_CTAS;
    uint8_t* const ring = reinterpret_cast<uint8_t*>(g_ln);

    TSTAMP(0, 0);
    TRACEW(110 + warp, 0);
    const uint32_t bar_pace = bar_w + 32, bar_xfull = bar_pace + 32, bar_xempty = bar_xfull + 8, bar_done = bar_xfull + 16;
    const int ln0 = blockIdx.x >> 2, first = blockIdx.x / GRP_CTAS;
    const uint8_t* xsrc = reinterpret_cast<const uint8_t*>(x) + (size_t)blockIdx.x * P1_X;

    if (warp >= 12) {
        reg_dec<40>();
        asm volatile("barrier.cluster.arrive.relaxed.aligned;\n" ::: "memory");
        asm volatile("barrier.cluster.wait.aligned;\n" ::: "memory");
        if (warp == 12) {
            int prev = 0, t = first;
            const uint32_t rbase = mapa(sbase, lane & 1);
#pragma unroll 1
            for (int i = 0; t < NT128; i++) {
                const int round = t / LN_RING, slot = t - round * LN_RING;
                const uint8_t* src = ring + slot * LN_TILE + rank * (P1_SLOT / 2);
                int next = 0;
                if (rank == 0 && lane == 0) next = atomicAdd(&g_flag[LN_RING + (cig >> 1)][0][0], 1u);
                flag_wait<true>(&g_flag[slot][0][0], 4 * round + 4);
                TRACEW(i, 2);
                asm volatile("fence.proxy.async.global;\n" ::: "memory");
                next = NGRP + __shfl_sync(0xffffffffu, next, 0);
#pragma unroll 1
                for (int h = 0; h < P1_NST; h++) {
                    mbar_wait(bar_empty + h * 8, i & 1);
                    if (h == 0) TRACEW(i, 4);
                    if (h == 5) TRACEW(i, 5);
                    if (elect_one()) {
                        mbar_expect_tx(bar_full + h * 8, h ? P1_SLOT : P1_SLOT + 16);
                        bulk_g2s_mc(sbase + h * P1_SLOT + rank * (P1_SLOT / 2), src + h * P1_SLOT, P1_SLOT / 2, bar_full + h * 8, (uint16_t)3);
                    }
                    __syncwarp();
                    if (h == 0 && rank == 0 && lane < 2)
                        asm volatile("st.async.shared::cluster.mbarrier::complete_tx::bytes.v4.u32 [%0], {%1, %2, %3, %3}, [%4];\n"
                                     ::"r"(rbase + P1_OFF_TILE + (i & 3) * 16), "r"((t - prev) * (2 * H_TILE)), "r"((int)(next < NT128)), "r"(next),
                                       "r"(rbase + P1_OFF_BAR) : "memory");
                }
                prev = t;
                t = next;
                if (rank != 0) {
                    mbar_wait(bar_full, i & 1);
                    asm volatile("ld.shared.u32 %0, [%1];\n" : "=r"(t) : "r"(sbase + P1_OFF_TILE + (i & 3) * 16 + 8) : "memory");
                }
            }
        } else if (warp == 13) {
            int ph = 0;
            unsigned target = 0;
#pragma unroll 1
            for (int i = ln0 + LN_STEP; i < NT128; i += LN_STEP, ph ^= 1) {
                target += ph * (GRP_CTAS / 2);
                xsrc += (size_t)NUM_CTAS * P1_X;
                mbar_wait(bar_xempty, ph);
                if (elect_one()) {
                    mbar_expect_tx(bar_xfull, P1_X);
                    bulk_g2s(sbase + P1_OFF_X, xsrc, P1_X, bar_xfull);
                }
                __syncwarp();
                const uint32_t off = flag_wait<false>(&g_flag[ln0 + (ph ^ 1) * LN_STEP][1][0], target);
                mbar_wait(bar_done, ph);
                if (elect_one()) {
                    asm volatile("st.shared.u32 [%0], %1;\n" ::"r"(bar_done + 8), "r"(off) : "memory");
                    mbar_arrive(bar_xfull);
                }
                __syncwarp();
            }
        } else if (warp == 15) {
            const uint32_t par = g_epoch & 1;
            asm volatile("st.shared.u32 [%0], %1;\n" ::"r"(sbase + P1_OFF_TILE - 4), "r"(par) : "memory");
            if (blockIdx.x < 16) reinterpret_cast<float4*>(g_sums[par ^ 1])[blockIdx.x * 32 + lane] = make_float4(0.f, 0.f, 0.f, 0.f);
            int t = first;
            if (rank == 1 && lane == 0) mbar_arrive(bar_empty);
#pragma unroll 1
            for (int i = 0; rank == 1 && t < NT128; i++) {
#pragma unroll 1
                for (int h = 0; h < P1_NST; h++) mbar_wait(bar_full + h * 8, i & 1);
                if (lane == 0) asm volatile("red.relaxed.gpu.global.add.u32 [%0], 1;\n" ::"l"(&g_flag[t % LN_RING][1][0]) : "memory");
                asm volatile("ld.shared.u32 %0, [%1];\n" : "=r"(t) : "r"(sbase + P1_OFF_TILE + (i & 3) * 16 + 8) : "memory");
                if (lane == 0) mbar_arrive(bar_empty);
                TRACEW(i, 3);
            }
            if (rank == 0) {
                mbar_wait(bar_full, 0);
                TRACEW(110 + warp, 3);
                mbar_wait(bar_full, 1);
                float* sums = g_sums[par] + HID;
                unsigned* flag = reinterpret_cast<unsigned*>(sums + C_DIM);
                if (blockIdx.x == 0) reinterpret_cast<uint2*>(g_half)[lane] = make_uint2(0, 0);
                if (blockIdx.x == 2 && lane < 3) g_prog[lane][0] = 0;
                if (blockIdx.x < 96) g_redo[blockIdx.x * 16 + lane] = 0.f;
                float gs = 0.f;
#pragma unroll 1
                for (int pass = 0; pass < 2; pass++) {
                    float mx = 0.f;
#pragma unroll 1
                    for (int it = first; it < 96; it += NGRP) {
                        const int nb = it % 12, k0 = (cig * 4 + it / 12) * 64 + (lane >> 2);
                        const uint32_t sc = mapa(sbase + P1_OFF_EX + (k0 & 255) * 4, it / 48);
                        uint32_t* dst = reinterpret_cast<uint32_t*>(g_w2img[0]) + (k0 >> 4) * 3072 + nb * 256 + lane;
                        float bs[8] = {};
#pragma unroll 1
                        for (int c = 0; c < 8; c++) {
                            const uint4 u = __ldg(reinterpret_cast<const uint4*>(w2 + (size_t)(k0 + c * 8) * C_DIM + nb * 32) + (lane & 3));
                            const float b = __bfloat162float(grn_b[k0 + c * 8]);
                            float t;
                            asm volatile("ld.shared::cluster.f32 %0, [%1];\n" : "=f"(t) : "r"(sc + c * 32) : "memory");
#pragma unroll
                            for (int j = 0; j < 4; j++) {
                                const uint32_t v = j == 0 ? u.x : j == 1 ? u.y : j == 2 ? u.z : u.w;
                                mx = fmaxf(mx, fmaxf(fabsf(bf_lo(v)), fabsf(bf_hi(v))) * t);
                                if (pass) {
                                    bs[2 * j] = fmaf(b, bf_lo(v), bs[2 * j]);
                                    bs[2 * j + 1] = fmaf(b, bf_hi(v), bs[2 * j + 1]);
                                    uint32_t h = pack_f16(bf_lo(v) * t * gs, bf_hi(v) * t * gs);
                                    asm volatile("movmatrix.sync.aligned.m8n8.trans.b16 %0, %0;\n" : "+r"(h));
                                    dst[(c >> 1) * 3072 + (c & 1) * 32 + j * 64] = h;
                                }
                            }
                        }
                        if (pass) {
#pragma unroll
                            for (int j = 0; j < 8; j++) {
#pragma unroll
                                for (int o = 4; o < 32; o <<= 1) bs[j] += __shfl_xor_sync(0xffffffffu, bs[j], o);
                                if (lane >> 2 == j) atomicAdd(&sums[nb * 32 + (j >> 1) * 8 + (lane & 3) * 2 + (j & 1)], bs[j]);
                            }
                        }
                    }
                    if (!pass) {
                        const uint32_t m = __reduce_max_sync(0xffffffffu, __float_as_uint(mx));
                        if (lane == 0) {
                            atomicMax(flag, m);
                            asm volatile("red.release.gpu.global.add.u32 [%0], 1;\n" ::"l"(flag + 32) : "memory");
                        }
                        flag_wait<true>(flag + 32, NUM_CTAS / 2);
                        gs = w2_scale(__ldcg(flag));
                    }
                }
                do {
                    __nanosleep(1000);
                    asm volatile("ld.volatile.shared.u32 %0, [%1];\n" : "=r"(t) : "r"(sbase + P1_OFF_TILE + (lane & 3) * 16 + 8) : "memory");
                    SAFE_BREAK;
                } while (__all_sync(0xffffffffu, t < NT128 - P1_WPF));
                if (lane == 0 && blockIdx.x < 128)
                    asm volatile("cp.async.bulk.prefetch.L2.global [%0], %1;\n" ::"l"(g_w2img[0] + blockIdx.x * 576), "r"(18432) : "memory");
            }
        } else if (warp == 14) {
            int ph = 0;
#pragma unroll 1
            for (int i = ln0; i < NT128; i += LN_STEP, ph ^= 1) {
                mbar_wait(bar_done, ph);
                TRACEW(i / LN_STEP, 0);
                asm volatile("fence.proxy.async.global;\n" ::: "memory");
                if (elect_one()) asm volatile("red.release.gpu.global.add.u32 [%0], 1;\n" ::"l"(&g_flag[ln0 + ph * LN_STEP][0][0]) : "memory");
                __syncwarp();
                TRACEW(i / LN_STEP, 1);
            }
        }
        __syncwarp();
        cluster_sync();
    } else if (warp >= 8) {
        reg_dec<88>();
        asm volatile("barrier.cluster.arrive.relaxed.aligned;\n" ::: "memory");
        {
            const int l8 = lane & 7, row = (warp - 8) * 4 + (lane >> 3), px = (blockIdx.x & 3) * 32 + row;
            uint32_t d[6][4];
            const int n = (px & 64) + perm32(2 * row + ((px >> 5) & 1));
            uint8_t* const dst0 = ring + ln0 * LN_TILE + n * 128 + ((l8 ^ (n & 7)) << 4);
            const uint32_t src = sbase + P1_OFF_X + ((warp - 8) * 8 + (lane >> 3)) * (C_DIM * 2) + l8 * 16;
            int ph = 0;
#pragma unroll 1
            for (int i = ln0; i < NT128; i += LN_STEP, ph ^= 1) {
                TRACE(2, i / LN_STEP, 0);
                uint32_t off = 1;
#pragma unroll 1
                for (int ps = i == ln0 ? -2 : 0; ps < 2; ps += ps < 0 ? 2 : 1) {
                    if (ps == 0) {
                        if (i == ln0) asm volatile("barrier.cluster.wait.aligned;\n" ::: "memory");
                        mbar_wait(bar_xfull, ph);
                        asm volatile("ld.shared.u32 %0, [%1];\n" : "=r"(off) : "r"(bar_done + 8) : "memory");
                    }
                    if (ps == 0) TRACE(2, i / LN_STEP, 1);
                    if (i == ln0) {
#pragma unroll
                        for (int j = 0; j < 6; j++)
                            asm volatile("ld.shared.v4.u32 {%0,%1,%2,%3}, [%4];\n"
                                         : "=r"(d[j][0]), "=r"(d[j][1]), "=r"(d[j][2]), "=r"(d[j][3]) : "r"(sbase + P1_OFF_DW + j * 128 + l8 * 16) : "memory");
                    }
                    uint32_t v1[1][6][4];
                    uint32_t (&v)[6][4] = v1[0];
#pragma unroll
                    for (int j = 0; j < 6; j++)
                        asm volatile("ld.shared.v4.u32 {%0,%1,%2,%3}, [%4];\n"
                                     : "=r"(v[j][0]), "=r"(v[j][1]), "=r"(v[j][2]), "=r"(v[j][3]) : "r"(src + (ps & 1) * (4 * C_DIM * 2) + j * 128) : "memory");
                    ln_rows<P1_PACE, 1>(v1, d, bar_pace + (warp - 8) * 8, off, zero, ps == 1 && lane == 0 ? bar_xempty : 0);
                    uint8_t* dst = dst0 + ph * (LN_STEP * LN_TILE) + (ps & 1) * 4096;
#pragma unroll
                    for (int j = 0; j < 6; j++) *reinterpret_cast<uint4*>(dst + j * 16384) = make_uint4(v[j][0], v[j][1], v[j][2], v[j][3]);
                    TRACE(2, i / LN_STEP, 3 + (ps & 1));
                }
                asm volatile("fence.proxy.async.global;\nfence.acq_rel.cta;\n" ::: "memory");
                __syncwarp();
                if (lane == 0) mbar_arrive(bar_done);
                TRACE(2, i / LN_STEP, 5);
                TRACE(2, i / LN_STEP, 2);
            }
        }
        __syncwarp();
        cluster_sync();
    } else {
        const int wg = warp >> 2, w = warp & 3;
        auto load_w = [&](int i0, int i1) {
#pragma unroll 1
            for (int i = i0; i < i1; i++) {
                if (!(i & 1)) mbar_expect_tx(bar_w + (i >> 1) * 8, P1_W);
                tma2(sbase + (i & 2) * P1_W + (i >> 2) * P1_W + (i & 1) * (P1_W / 2), &wmap, cig * 256 + (i >> 1) * 64, (i & 1) * 192, bar_w + (i >> 1) * 8);
            }
        };
        if (warp == 4 && elect_one()) {
            mbar_init(bar_xfull, 2);
#pragma unroll
            for (int i = 0; i < 4; i++) mbar_init(bar_w + i * 8, 1);
            asm volatile("fence.mbarrier_init.release.cluster;\n" ::: "memory");
            mbar_expect_tx(bar_xfull, P1_X + C_DIM * 2);
            bulk_g2s(sbase + P1_OFF_X, xsrc, P1_X, bar_xfull);
            bulk_g2s(sbase + P1_OFF_DW, dw, C_DIM * 2, bar_xfull);
            load_w(0, 4);
            asm volatile("st.shared.u32 [%0], 1;\n" ::"r"(bar_done + 8) : "memory");
            mbar_arrive(bar_xfull);
        }
        if (warp == 5 && elect_one()) {
#pragma unroll
            for (int i = 0; i < P1_NST; i++) {
                mbar_init(bar_full + i * 8, 1);
                mbar_init(bar_empty + i * 8, i ? 8 : 8 + rank);
                if (i < 4) mbar_init(bar_pace + i * 8, 1);
            }
            mbar_init(bar_xempty, 4);
            mbar_init(bar_done, 4);
            asm volatile("fence.mbarrier_init.release.cluster;\n" ::: "memory");
        }
        __syncwarp();
        asm volatile("barrier.cluster.arrive.relaxed.aligned;\n" ::: "memory");
        reg_inc<192>();
        TRACEW(110 + warp, 1);
        uint32_t a[24][4];
        gdc_launch();
        const uint32_t src = sbase + wg * P1_W + ((lane >> 4) * 8 + (lane & 7)) * 128 + (((2 * w + ((lane >> 3) & 1)) ^ (lane & 7)) << 4);
        const uint32_t s_ex = sbase + P1_OFF_EX + (wg * 128 + w * 16 + (lane >> 2)) * 4;
        uint32_t sc2[2], ex[2];
        if (wg == 1) bar_arrive(1, 256);
#pragma unroll 1
        for (int it = 0; it < 2; it++) {
          if (it != wg) asm volatile("barrier.cluster.wait.aligned;\n" ::: "memory");
          if (it < wg) {
              mbar_wait(bar_xfull, 0);
              if (w == 0 && elect_one()) load_w(4, 8);
              __syncwarp();
          }
          if (it || wg == 0) {
            float t[2] = {0.f, 0.f};
            if (it) {
                TRACEW(110 + warp, 2);
                mbar_wait(bar_w + wg * 16, 0);
            }
            TRACEW(110 + warp, 5);
#pragma unroll
            for (int k = 0; k < 24; k++) ldsm4t(a[k], src + k * 2048);
            TRACEW(110 + warp, 6);
            p1_squares(a, t);
            sc2[0] = p1_exponents(t, ex, s_ex, lane);
            if (it && lane < 6) mbar_arrive_cluster(mapa(bar_empty, lane & 1) + (wg * 3 + (lane >> 1)) * 8 + (sc2[0] & zero));
            p1_convert<24>(a, a, ex);
          }
          if (it || wg == 1) {
            float t[2] = {0.f, 0.f};
            TRACEW(100 + warp, 0);
            if (it) mbar_wait(bar_w + wg * 16 + 8, 0);
            TRACEW(100 + warp, 1);
            uint32_t v[8][4], o[8][4];
#pragma unroll 1
            for (int j = 0; j <= 2 * it; j++) {
#pragma unroll
                for (int k = 0; k < 8; k++) ldsm4t(v[k], src + P1_OFF_W + (8 * j + k) * 2048);
                p1_squares(v, t);
            }
            sc2[1] = p1_exponents(t, ex, s_ex + 256, lane);
#pragma unroll 1
            for (int j = 2 * it; j >= 0; j--) {
                p1_convert<8>(o, v, ex);
#pragma unroll
                for (int k = 0; k < 8; k++) {
                    if (j) ldsm4t(v[k], src + P1_OFF_W + (8 * j - 8 + k) * 2048);
                    if (it) asm volatile("stmatrix.sync.aligned.m8n8.x4.trans.shared.b16 [%0], {%1,%2,%3,%4};\n"
                                         ::"r"(src + P1_OFF_W + (8 * j + k) * 2048), "r"(o[k][0]), "r"(o[k][1]), "r"(o[k][2]), "r"(o[k][3]) : "memory");
                }
            }
          }
        }
        asm volatile("fence.proxy.async.shared::cta;\n" ::: "memory");
        TRACEW(110 + warp, 7);
        bar_sync(6 + wg, 128);
        p1_consumer(a, sc2, sbase, wg, w, lane, zero);
        cluster_sync();
        TSTAMP(0, 30);
    }
}

constexpr int P2_B = 24576, P2_NB = 4;
constexpr int P2_A = 3072, P2_NA = 8;
constexpr int P2_XROW = C_DIM * 2;
constexpr int P2_OFF_A = P2_B * P2_NB;
constexpr int P2_OFF_X = P2_OFF_A + 3 * P2_NA * P2_A;
constexpr int P2_XHALF = 32 * P2_XROW + 64;
constexpr int P2_OFF_GRN = P2_OFF_X + 64 * P2_XROW + 128;
constexpr int P2_OFF_BIAS = P2_OFF_GRN + HID * 2;
constexpr int P2_OFF_RED = P2_OFF_BIAS + C_DIM * 4;
constexpr int P2_OFF_BAR = P2_OFF_RED + 192;
constexpr int P2_SMEM = P2_OFF_BAR + (2 * P2_NB + 6 * P2_NA + 7) * 8;
#define P2_S1 16
constexpr int P2_S2 = 32;
constexpr int P2_NCL = NUM_CTAS / 2, P2_ITEMS = NT128 / P2_NCL, P2_SHARED = NT128 - P2_ITEMS * P2_NCL;
constexpr int P2_NPOS = 6 * 48 + P2_S1;
constexpr int P2_RAW = 24;
constexpr int P2_XC = 8 * P2_XROW;
#define P2_T0 4
#define P2_SLACK 0
#define P2_RAMP 2
#define P2_LATE 88
#define P2_GATE 1
#define P2_AH 2
__device__ __forceinline__ int p2_start(int n) { return n < 0 ? 0 : n / 3 * 48 + (n % 3 == 1 ? P2_S1 : n % 3 * (P2_S2 / 2)); }
__device__ __forceinline__ int p2_tile(int cl, int n) {
    return n == 0 ? NT128 - 1 - cl : n < 0 ? NT128 - 1 - P2_NCL - (cl >> 1) : cl + P2_NCL * (n - 1);
}

#define P2_EB 2
#define P2_EX 1
__device__ __forceinline__ void p2_epilogue(uint32_t (&acc0)[48], uint32_t (&acc1)[48], uint32_t up, uint32_t sx, uint32_t sb, int zero) {
    uint32_t v[12][3][4];
    auto load = [&](int t, int j) {
        if (t >= 12) return;
        uint32_t (&w)[4] = v[t][j];
        asm volatile("ld.shared.v4.u32 {%0,%1,%2,%3}, [%4];\n" : "=r"(w[0]), "=r"(w[1]), "=r"(w[2]), "=r"(w[3])
                     : "r"((j ? sx + (j - 1) * 4 * P2_XROW : sb) + t * 64) : "memory");
    };
    auto store = [&](int t, int r) {
        const uint32_t* w = (t < 6 ? acc0 : acc1) + 8 * (t % 6) + 4 * r;
        asm volatile("st.shared.v4.u32 [%4], {%0,%1,%2,%3};\n" ::"r"(w[0]), "r"(w[1]), "r"(w[2]), "r"(w[3]), "r"(sx + t * 64 + r * 4 * P2_XROW) : "memory");
    };
#pragma unroll
    for (int t = 0; t < P2_EB; t++) load(t, 0);
#pragma unroll
    for (int t = 0; t < 2 * P2_EX; t++) load(t >> 1, 1 + (t & 1));
#pragma unroll
    for (int t = 0; t < 12; t++) {
        load(t + P2_EX, 1);
        load(t + P2_EX, 2);
        load(t + P2_EB, 0);
        uint32_t* acc = (t < 6 ? acc0 : acc1) + 8 * (t % 6);
        uint32_t y[8];
#pragma unroll
        for (int e = 0; e < 8; e++) {
            y[e] = h2_add(acc[e], v[t][0][e >> 1]);
            y[e] = pack_bf16(h_lo(y[e]), h_hi(y[e]));
        }
#pragma unroll
        for (int e = 0; e < 8; e++) acc[(e & 1) * 4 + (e >> 1)] = bf2_fma(y[e], up, v[t][1 + (e & 1)][e >> 1]);
        store(t, 0);
        store(t, 1);
        sched_break(zero);
    }
    if (zero) {
#pragma unroll
        for (int t = 0; t < 24; t++) store(t >> 1, t & 1);
    }
}

__device__ __forceinline__ void p2_unpack(uint32_t (&u)[4], uint32_t o1, uint32_t o2, uint32_t o3) {
    u[2] = bitsel(o1, 0x00040004u, SPARE);
    u[1] = bitsel(o2, 0x00040004u, SPARE);
    u[3] = bitsel(o3, 0x00040004u, SPARE);
    const uint32_t t = bitsel(prmt(o1, o2, 0x6341), prmt(o1, o3, 0x6240) << 3, 0x38383838u);
    u[0] = bitsel(bitsel(t, prmt(o2, o3, 0x7351) << 1, 0x80808080u), 0x00040004u, SPARE);
}

__device__ __forceinline__ void p2_redo_sums(int warp, int lane) {
#pragma unroll 1
    for (int s = warp; s < 96; s += 12) {
        float t[2] = {0.f, 0.f};
#pragma unroll 1
        for (int tile = blockIdx.x; tile < 2 * NT128; tile += NUM_CTAS) {
            const uint32_t* p = reinterpret_cast<const uint32_t*>(reinterpret_cast<const uint8_t*>(g_h) + (size_t)(tile >> 1) * (2 * H_TILE) +
                                                                  (s >> 1) * H_STEP + (tile & 1) * H_HALF + (s & 1) * 1536) + lane * 4;
#pragma unroll
            for (int j = 0; j < 4; j++) {
                uint32_t u[4];
                p2_unpack(u, __ldcg(p + j), __ldcg(p + j + 128), __ldcg(p + j + 256));
#pragma unroll
                for (int c = 0; c < 4; c++) t[c >> 1] += h_lo(u[c]) * h_lo(u[c]) + h_hi(u[c]) * h_hi(u[c]);
            }
        }
#pragma unroll
        for (int r = 0; r < 2; r++) {
            const int ch = s * 16 + r * 8 + (lane >> 2);
            const float f = __ldcg(&g_scale[ch]);
            atomicAdd(&g_redo[ch], t[r] * f * f);
        }
    }
    __threadfence();
    __syncwarp();
    if (lane == 0) asm volatile("red.release.gpu.global.add.u32 [%0], 1;\n" ::"l"(&g_prog[2][0]) : "memory");
    flag_wait<true>(&g_prog[2][0], 12 * NUM_CTAS);
}

__global__ void __cluster_dims__(2, 1, 1) __launch_bounds__(512, 1)
pass2_kernel(const __nv_bfloat16* __restrict__ x, const __nv_bfloat16* __restrict__ grn_g, __nv_bfloat16* __restrict__ out, int zero) {
    extern __shared__ __align__(1024) uint8_t smem[];
    const uint32_t sbase = smem_u32(smem);
    const uint32_t bar_bfull = sbase + P2_OFF_BAR, bar_bempty = bar_bfull + P2_NB * 8;
    const uint32_t bar_afull = bar_bempty + P2_NB * 8, bar_aempty = bar_afull + 3 * P2_NA * 8;
    const uint32_t bar_xfull = bar_aempty + 3 * P2_NA * 8, bar_oready = bar_xfull + 24, s_pos = bar_oready + 24;
    int tid;
    asm volatile("mov.u32 %0, %%tid.x;\n" : "=r"(tid));
    const int warp = __shfl_sync(0xffffffffu, tid >> 5, 0), lane = tid & 31;
    const uint32_t rank = cluster_rank();
    const int cl = blockIdx.x >> 1, pair = cl >> 1;
    const int half = pair < P2_SHARED, fin = half && (cl & 1);
    const int k0 = (pair + 3 * (cl & 1)) % 6 * 8;
    const bool late = blockIdx.x >= P2_LATE;
    auto wait_pos = [&](int target) {
        int v;
        while (true) {
            asm volatile("ld.volatile.shared.u32 %0, [%1];\n" : "=r"(v) : "r"(s_pos) : "memory");
            if (v >= target) break;
            SAFE_BREAK;
            __nanosleep(100);
        }
    };

    TSTAMP(1, 0);
    if (tid == 384) {
        for (int i = 0; i < P2_NB; i++) {
            mbar_init(bar_bfull + i * 8, 1);
            mbar_init(bar_bempty + i * 8, 24);
        }
        for (int i = 0; i < 3 * P2_NA; i++) {
            mbar_init(bar_afull + i * 8, 1);
            mbar_init(bar_aempty + i * 8, 4);
        }
        for (int i = 0; i < 3; i++) {
            mbar_init(bar_xfull + i * 8, 2);
            mbar_init(bar_oready + i * 8, 4);
        }
        asm volatile("st.shared.u32 [%0], 0;\n" ::"r"(s_pos) : "memory");
        asm volatile("fence.mbarrier_init.release.cluster;\n" ::: "memory");
    }
    __syncthreads();
    cluster_sync_relaxed();

    if (warp >= 12) {
        reg_dec<32>();
        if (warp == 12) {
            const uint8_t* wsrc = reinterpret_cast<const uint8_t*>(g_w2img) + rank * (P2_B / 2);
            int kb = k0;
            gdc_wait();
            if (P2_GATE) bar_sync(5, 448);
#pragma unroll 1
            for (int p = 0; p < P2_NPOS; p++) {
                const int st = p & 3;
                if (p == P2_RAW) {
                    flag_wait<true>(&g_prog[1][0], NUM_CTAS);
                    asm volatile("fence.proxy.async.global;\n" ::: "memory");
                    wsrc += sizeof(g_w2img[0]);
                }
                const int idle = (p < P2_S1 || p >= 6 * 48) + (p < P2_S2 ? !half || p >= 24 : p >= 5 * 48 + P2_S2);
                mbar_wait(bar_bempty + st * 8, (~p >> 2) & 1);
                TR2(3, p, 0);
                if (elect_one()) {
                    const int len = P2_B / 2;
                    mbar_expect_tx(bar_bfull + st * 8, 2 * len);
                    bulk_g2s_mc(sbase + st * P2_B + rank * (P2_B / 2), wsrc + kb * P2_B, len, bar_bfull + st * 8, (uint16_t)3);
                    asm volatile("st.volatile.shared.u32 [%0], %1;\n" ::"r"(s_pos), "r"(p) : "memory");
                    if (rank == 0) asm volatile("red.relaxed.gpu.global.add.u32 [%0], 1;\n" ::"l"(&g_prog[0][0]) : "memory");
                    if (idle) asm volatile("mbarrier.arrive.shared::cta.b64 _, [%0], %1;\n" ::"r"(bar_bempty + st * 8), "r"(8 * idle) : "memory");
                }
                __syncwarp();
                if (++kb == 48) kb = 0;
            }
            mbar_wait(bar_bempty, 1);
            if (lane == 0) mbar_arrive(bar_bfull);
        } else if (warp == 13) {
            const int w = lane < 3 ? lane : 0;
            const uint32_t dst0 = sbase + P2_OFF_A + w * P2_NA * P2_A;
            const uint32_t bf = bar_afull + w * P2_NA * 8, be = bar_aempty + w * P2_NA * 8;
            int n = (w == 2 && half ? -1 : w) - 3, left = 0, u = 0, c = 0;
            const uint8_t* src = nullptr;
            bool act = lane < 3;
            gdc_wait();
            if (P2_GATE) bar_sync(5, 448);
            while (__any_sync(0xffffffffu, act)) {
                if (left == 0) {
                    n += 3;
                    left = n >= P2_ITEMS ? -1 : n < 0 ? 24 : 48;
                    u = (k0 + p2_start(n)) % 48;
                    src = reinterpret_cast<const uint8_t*>(g_h) + (size_t)p2_tile(cl, n) * (2 * H_TILE) + rank * H_HALF + u * H_STEP;
                }
                bool ok = act && mbar_test(be + ((c - 1) & 7) * 8, (~c >> 3) & 1);
                if (__any_sync(0xffffffffu, act && c < 16)) {
                    int v;
                    asm volatile("ld.volatile.shared.u32 %0, [%1];\n" : "=r"(v) : "r"(s_pos) : "memory");
                    ok = ok && c <= (n <= 0 ? 2 * v - P2_RAMP : c >= 16 ? c : v - p2_start(n) + 8);
                }
                if (ok) {
                    const int st = c & 7;
                    if (left > 0) {
                        mbar_expect_tx(bf + st * 8, P2_A);
                        bulk_g2s(dst0 + st * P2_A, src, P2_A, bf + st * 8);
                    } else {
                        mbar_arrive(bf + st * 8);
                        act = false;
                    }
                    src += H_STEP;
                    if (++u == 48) { u = 0; src -= 48 * H_STEP; }
                    c++;
                    left--;
                }
                SAFE_BREAK;
                if (!__any_sync(0xffffffffu, ok)) __nanosleep(100);
            }
        } else if (warp == 14) {
            const uint32_t sx = sbase + P2_OFF_X;
            size_t o = 0;
            int wp = 0;
            uint32_t par = 0;
            if (fin) {
#pragma unroll 1
                for (int c = lane * 16; c < 64 * P2_XROW + 128; c += 512) asm volatile("st.shared.v4.u32 [%0], {0, 0, 0, 0};\n" ::"r"(sx + c) : "memory");
                __syncwarp();
            }
            if (late) wait_pos(6);
#pragma unroll 1
            for (int n = -half; n <= P2_ITEMS; n++) {
                const int w = (n + 3) % 3, end = p2_start(n) + 48;
                const size_t on = (size_t)(2 * p2_tile(cl, n) + rank) * (64 * C_DIM * 2);
                const uint32_t xf = bar_xfull + w * 8;
                bool st = n + half > 0;
                const bool ld = n < P2_ITEMS && !(n < 0 && fin);
                if (n == P2_ITEMS - 1 && lane == 0)
                    asm volatile("cp.async.bulk.prefetch.L2.global [%0], %1;\n" ::"l"(reinterpret_cast<const uint8_t*>(x) + on), "r"(64 * P2_XROW) : "memory");
                if (st) {
                    mbar_wait(bar_oready + wp * 8, (par >> wp) & 1);
                    par ^= 1u << wp;
                }
                if (lane == 0) {
                    if (n < P2_ITEMS) mbar_expect_tx(xf, ld ? 64 * C_DIM * 2 : 0);
                    const int t0 = (n ? p2_start(n - 1) + 48 : P2_S2) + P2_T0, dt = end - t0;
                    int t = st && n < P2_ITEMS - 1 ? 16 * t0 : -4096;
                    if ((n == 0 && half) || n >= P2_ITEMS - 1) {
                        if (fin && n == 0) {
                            flag_wait<true>(&g_half[pair][rank], 1);
                            asm volatile("fence.proxy.async.global;\n" ::: "memory");
                        }
#pragma unroll 1
                        for (int c = 0; c < 2; c++) {
                            uint8_t* dst = reinterpret_cast<uint8_t*>(out) + o + c * 32 * P2_XROW;
                            if (!fin || n) bulk_s2g(dst, sx + c * P2_XHALF, 32 * P2_XROW);
                            else asm volatile("cp.reduce.async.bulk.global.shared::cta.bulk_group.add.noftz.bf16 [%0], [%1], %2;\n"
                                              ::"l"(dst), "r"(sx + c * P2_XHALF), "r"(32 * P2_XROW) : "memory");
                        }
                        asm volatile("cp.async.bulk.commit_group;\n" ::: "memory");
                        if (!fin && n == 0) {
                            asm volatile("cp.async.bulk.wait_group 0;\nfence.proxy.async.global;\n" ::: "memory");
                            asm volatile("st.release.gpu.global.u32 [%0], 1;\n" ::"l"(&g_half[pair][rank]) : "memory");
                        }
                        st = false;
                    }
#pragma unroll 1
                    for (int c = 0; c < 64 * P2_XROW; c += P2_XC, t += 2 * dt) {
                        const uint32_t sp = sx + c + (c >= 32 * P2_XROW ? 64 : 0);
                        wait_pos(t >> 4);
                        if (st) bulk_s2g(reinterpret_cast<uint8_t*>(out) + o + c, sp, P2_XC);
                        asm volatile("cp.async.bulk.commit_group;\n" ::: "memory");
                        if (ld) {
                            wait_pos((t + dt) >> 4);
                            asm volatile("cp.async.bulk.wait_group.read 0;\n" ::: "memory");
                            bulk_g2s(sp, reinterpret_cast<const uint8_t*>(x) + on + c, P2_XC, xf);
                        }
                    }
                    if (rank == 0 && n > 0 && n < P2_ITEMS - 1) flag_wait<false>(&g_prog[0][0], P2_NCL * (end + P2_SLACK));
                    if (n < P2_ITEMS) mbar_arrive(xf);
                }
                __syncwarp();
                o = on;
                wp = w;
            }
            asm volatile("cp.async.bulk.wait_group 0;\n" ::: "memory");
        } else if (blockIdx.x == 120) {
            gdc_wait();
            for (int i = lane; i < (LN_RING + 3) * 2; i += 32) (&g_flag[0][0][0])[i * 8] = 0;
            if (lane == 0) g_epoch++;
        }
        __syncwarp();
        cluster_sync();
    } else {
        reg_inc<160>();
        const int wg = warp >> 2, w = warp & 3, g = lane >> 2, q = lane & 3;
        const uint32_t sx = sbase + P2_OFF_X + (g & 1) * P2_XHALF + (w * 8 + (g >> 1)) * P2_XROW + q * 16;
        const uint32_t af = bar_afull + wg * P2_NA * 8;
        const uint32_t s_a = sbase + P2_OFF_A + wg * P2_NA * P2_A + (lane >> 3) * 512 + (lane & 7) * 64 + ((w ^ ((lane & 7) >> 1)) << 4);
        uint32_t acc0[48], acc1[48], up;
        uint4 a[2][2];

        __nv_bfloat16 gg[4];
#pragma unroll
        for (int i = 0; i < 4; i++) gg[i] = grn_g[tid + 384 * i];
#pragma unroll 1
        for (int it = late; it < 2; it++) {
            float* s_red = reinterpret_cast<float*>(smem + P2_OFF_RED);
            float gx[7], part = 0.f;
            if (it) {
                TSTAMP(1, 27);
                gdc_wait();
                TSTAMP(1, 1);
            }
            float gy[7];
#pragma unroll
            for (int i = 0; i < 7; i++) {
                const float* p = &g_sums[0][i < 5 ? tid + 384 * i : HID + C_DIM + i - 5];
                asm volatile("ld.global.cg.f32 %0, [%1];\n" : "=f"(gx[i]) : "l"(p) : "memory");
                asm volatile("ld.global.cg.f32 %0, [%1];\n" : "=f"(gy[i]) : "l"(p + HID + 512) : "memory");
            }
            if (P2_GATE && it) bar_arrive(5, 448);
            const float bias = gx[4] + gy[4];
            const float gs = w2_scale(__float_as_uint(gx[5]) | __float_as_uint(gy[5]));
            if (it && gx[6] + gy[6] != 0.f) {
                p2_redo_sums(warp, lane);
#pragma unroll
                for (int i = 0; i < 4; i++) {
                    gx[i] = __ldcg(&g_redo[tid + 384 * i]);
                    gy[i] = 0.f;
                }
            }
            float mg = 0.f;
#pragma unroll
            for (int i = 0; i < 4; i++) {
                gx[i] = gx[i] + gy[i];
                gx[i] = __fsqrt_rn(gx[i] * (HSCALE * HSCALE) + 1e-6f);
                part += gx[i];
                gx[i] *= __bfloat162float(gg[i]);
                mg = fmaxf(mg, fabsf(gx[i]));
            }
#pragma unroll
            for (int o = 16; o > 0; o >>= 1) part += __shfl_xor_sync(0xffffffffu, part, o);
            const uint32_t mgw = __reduce_max_sync(0xffffffffu, __float_as_uint(mg));
            const uint32_t mbw = __reduce_max_sync(0xffffffffu, __float_as_uint(fabsf(bias)));
            TSTAMP(1, 26);
            if (lane == 0) *reinterpret_cast<float4*>(s_red + warp * 4) = make_float4(part, __uint_as_float(mgw), __uint_as_float(mbw), 0.f);
            bar_sync(1, 384);
            float tot = 0.f, mb = 0.f;
#pragma unroll
            for (int i = 0; i < 12; i++) {
                const float4 t = *reinterpret_cast<const float4*>(s_red + i * 4);
                tot += t.x;
                mg = fmaxf(mg, t.y);
                mb = fmaxf(mb, t.z);
            }
            const float inv = 1.0f / (tot * (1.0f / HID) + 1e-6f);
            const uint32_t ej = min((__float_as_uint(fmaxf(fmaf(mg, inv, 1.0f) * HSCALE, mb * gs * 0x1p-13f)) >> 23) + 1, 250u);
            const float dn = __uint_as_float((254u - ej) << 23);
            up = min(ej + 127u - (__float_as_uint(gs) >> 23), 254u) * 0x00800080u;
            reinterpret_cast<uint16_t*>(smem + P2_OFF_BIAS + C_DIM * 2)[tid] = 0;
            *reinterpret_cast<__half*>(smem + P2_OFF_BIAS + (tid >> 5) * 64 + (tid & 6) * 8 + (tid & 24) / 2 + (tid & 1) * 2) = __float2half_rn(bias * gs * dn);
#pragma unroll
            for (int i = 0; i < 4; i++) {
                const int k = tid + 384 * i;
                *reinterpret_cast<__half*>(smem + P2_OFF_GRN + (k >> 4) * 32 + (k & 6) * 4 + (k & 8) / 2 + (k & 1) * 2) =
                    __float2half_rn(fmaf(gx[i], inv, 1.0f) * (HSCALE * dn));
            }
            TSTAMP(1, 25);
            bar_sync(1, 384);
        }
        TSTAMP(1, 28);
        if (wg == 1) {
            constexpr int N = sizeof(g_w2img[0]) / 16, PER = (N + NUM_CTAS - 1) / NUM_CTAS;
            uint4 v[5];
#pragma unroll
            for (int i = 0; i < 5; i++) v[i] = __ldcg(&g_w2img[0][min(blockIdx.x * PER + (tid & 127) + 128 * i, N - 1)]);
#pragma unroll
            for (int i = 0; i < 5; i++) {
                const int j = min(blockIdx.x * PER + (tid & 127) + 128 * i, N - 1);
                const uint32_t* t = reinterpret_cast<const uint32_t*>(smem + P2_OFF_GRN + (j / 768) * 32 + (j & 8) / 2);
                auto sc = [&](uint32_t u, int e) { return (h2_mul(u, t[2 * e]) + 0x00040004u) & 0xfff8fff8u; };
                g_w2img[1][j] = make_uint4(sc(v[i].x, 0), sc(v[i].y, 1), sc(v[i].z, 2), sc(v[i].w, 3));
            }
            asm volatile("fence.proxy.async.global;\n" ::: "memory");
            bar_sync(2, 128);
            if (tid == 128) asm volatile("fence.acq_rel.gpu;\nred.release.gpu.global.add.u32 [%0], 1;\n" ::"l"(&g_prog[1][0]) : "memory");
        }

        const int who = __shfl_sync(0xffffffffu, lane == 2 ? 0 : lane < 2 ? 1 : 2, lane);
        const uint32_t rel0 = who ? mapa(bar_bempty, lane & 1) : mapa(bar_aempty + wg * P2_NA * 8, rank), rel1 = rel0 + (who ? 0 : 32);
        auto publish = [&]() {
            asm volatile("fence.proxy.async.shared::cta;\n" ::: "memory");
            __syncwarp();
            if (who == 0) mbar_arrive(bar_oready + wg * 8);
        };
        bool ok_a, pend = false;
        uint32_t pa = 0, s_t;
        auto fetch = [&](int j, bool raw) {
            uint32_t o[6], u0[4], u1[4];
            uint2 t0 = make_uint2(0, 0), t1 = t0;
            if (raw) {
                asm volatile("ld.shared.v2.u32 {%0,%1}, [%2];\n" : "=r"(t0.x), "=r"(t0.y) : "r"(s_t + j * 64) : "memory");
                asm volatile("ld.shared.v2.u32 {%0,%1}, [%2];\n" : "=r"(t1.x), "=r"(t1.y) : "r"(s_t + j * 64 + 32) : "memory");
            }
            const bool ok_b = mbar_test(bar_bfull + (j & 3) * 8, j >> 2);
            if (j == 7) pa ^= 1;
            ok_a = mbar_test(af + ((j + 1) & 7) * 8, pa);
            asm volatile("ldmatrix.sync.aligned.m8n8.x4.trans.shared.b16 {%0,%1,%2,%3}, [%4];\n"
                         : "=r"(o[0]), "=r"(o[1]), "=r"(o[2]), "=r"(o[3]) : "r"(s_a + j * P2_A) : "memory");
            asm volatile("ldmatrix.sync.aligned.m8n8.x2.trans.shared.b16 {%0,%1}, [%2];\n"
                         : "=r"(o[4]), "=r"(o[5]) : "r"(s_a + j * P2_A + 2048) : "memory");
            p2_unpack(u0, o[0], o[1], o[2]);
            p2_unpack(u1, o[3], o[4], o[5]);
            if (raw) {
                u0[0] = h2_mul(u0[0], t0.x); u0[1] = h2_mul(u0[1], t0.x); u0[2] = h2_mul(u0[2], t0.y); u0[3] = h2_mul(u0[3], t0.y);
                u1[0] = h2_mul(u1[0], t1.x); u1[1] = h2_mul(u1[1], t1.x); u1[2] = h2_mul(u1[2], t1.y); u1[3] = h2_mul(u1[3], t1.y);
            }
            a[j & 1][0] = make_uint4(u0[0], u0[1], u0[2], u0[3]);
            a[j & 1][1] = make_uint4(u1[0], u1[1], u1[2], u1[3]);
            if (!ok_b) mbar_wait(bar_bfull + (j & 3) * 8, j >> 2);
        };
        auto table = [&](int pos) { s_t = sbase + P2_OFF_GRN + q * 8 + (k0 + pos) % 48 * 64; };
        const uint32_t db0 = (uint32_t)make_desc(sbase, 128, 256);
        auto block8 = [&](bool raw, int pos, int thr0, int mode) {
#pragma unroll
            for (int j = 0; j < 8; j++) {
                const uint32_t db = db0 + (j & 3) * (P2_B / 16);
                if (j == 8 - P2_AH && mode == 1) bar_sync(4, 384);
                TR2(wg, pos + j, 0);
                wg_fence();
                mma_rs_n192(acc0, a[j & 1][0], db);
                mma_rs_n192(acc1, a[j & 1][0], db + 384);
                mma_rs_n192(acc0, a[j & 1][1], db + 768);
                mma_rs_n192(acc1, a[j & 1][1], db + 768 + 384);
                wg_commit();
                if (j == 7 && mode == 2) bar_arrive(4, 384);
                const uint32_t rel = ((j - 1) & 4 ? rel1 : rel0) + ((j - 1) & 3) * 8;
                TR2(wg, pos + j, 1);
                wg_wait<1>();
                TR2(wg, pos + j, 2);
                if (who < (j ? 2 : thr0)) mbar_arrive_cluster(rel);
                if (!ok_a) {
                    if (j == 0 && pend) { publish(); pend = false; }
                    mbar_wait(af + ((j + 1) & 7) * 8, pa);
                }
                TR2(wg, pos + j, 3);
                if (raw && j == 7) table(pos + 8);
                fetch((j + 1) & 7, raw && (j < 7 || pos + 8 < P2_RAW));
            }
        };
        int n = wg == 2 && half ? -1 : wg, pos = p2_start(n);
        uint32_t px = 0;
        wait_pos(pos);
        mbar_wait(af, 0);
        table(pos);
        fetch(0, pos < P2_RAW);
#pragma unroll 1
        for (;; n += 3) {
            TSTAMP(1, 2 + n);
            const int end = pos + (n < 0 ? 24 : 48);
#pragma unroll
            for (int i = 0; i < 48; i += 2) {
                asm volatile("mov.b64 {%0, %1}, 0;\n" : "=r"(acc0[i]), "=r"(acc0[i + 1]));
                asm volatile("mov.b64 {%0, %1}, 0;\n" : "=r"(acc1[i]), "=r"(acc1[i + 1]));
            }
            int thr = 1;
#pragma unroll 1
            for (; pos < P2_RAW; pos += 8, thr = 2) block8(true, pos, thr, 0);
#pragma unroll 1
            for (; pos < end; pos += 8, thr = 2) {
                const int e = pos + 8, r = e % 48;
                block8(false, pos, thr, e < 48 || e > 256 || (r != 0 && r != P2_S1 && r != P2_S2) ? 0 : e == end ? 2 : 1);
            }
            TR2(wg, pos - 1, 4);
            wg_wait<0>();
            TR2(wg, pos - 1, 5);
            if (who == 1) mbar_arrive_cluster(rel0 + 24);
            mbar_wait(bar_xfull + wg * 8, px);
            TR2(wg, pos - 1, 6);
            px ^= 1;
            __syncwarp();
            p2_epilogue(acc0, acc1, up, sx, sbase + P2_OFF_BIAS + q * 16 + (n < 0 && fin ? C_DIM * 2 : 0), zero);
            TR2(wg, pos - 1, 7);
            if (n + 3 >= P2_ITEMS) { publish(); break; }
            if (n < 0) {
                publish();
                pos = P2_S2;
                wait_pos(pos);
                mbar_wait(bar_bfull, 0);
            } else {
                pend = true;
                ok_a = false;
            }
        }
        TSTAMP(1, 29);
        cluster_sync();
        TSTAMP(1, 30);
    }
}

}

extern "C" void kernel_launch(void* const* d_in, const int* in_sizes, int n_in, void* d_out, int out_size) {
    const __nv_bfloat16* x = (const __nv_bfloat16*)d_in[0];
    const __nv_bfloat16* dw = (const __nv_bfloat16*)d_in[1];
    const __nv_bfloat16* w1 = (const __nv_bfloat16*)d_in[2];
    const __nv_bfloat16* w2 = (const __nv_bfloat16*)d_in[3];
    const __nv_bfloat16* grn_g = (const __nv_bfloat16*)d_in[4];
    const __nv_bfloat16* grn_b = (const __nv_bfloat16*)d_in[5];
    __nv_bfloat16* out = (__nv_bfloat16*)d_out;

    cudaFuncSetAttribute(pass1_kernel, cudaFuncAttributeMaxDynamicSharedMemorySize, P1_SMEM);
    cudaFuncSetAttribute(pass2_kernel, cudaFuncAttributeMaxDynamicSharedMemorySize, P2_SMEM);

    typedef CUresult (*EncodeFn)(CUtensorMap*, CUtensorMapDataType, cuuint32_t, void*, const cuuint64_t*, const cuuint64_t*,
                                 const cuuint32_t*, const cuuint32_t*, CUtensorMapInterleave, CUtensorMapSwizzle,
                                 CUtensorMapL2promotion, CUtensorMapFloatOOBfill);
    static EncodeFn encode = nullptr;
    if (!encode) {
        cudaDriverEntryPointQueryResult qres;
        cudaGetDriverEntryPoint("cuTensorMapEncodeTiled", (void**)&encode, cudaEnableDefault, &qres);
    }
    CUtensorMap wmap;
    const cuuint64_t gdim[2] = {HID, C_DIM};
    const cuuint64_t gstr[1] = {HID * 2};
    const cuuint32_t box[2] = {64, 192}, estr[2] = {1, 1};
    CUresult er = encode(&wmap, CU_TENSOR_MAP_DATA_TYPE_BFLOAT16, 2, (void*)w1, gdim, gstr, box, estr, CU_TENSOR_MAP_INTERLEAVE_NONE,
           CU_TENSOR_MAP_SWIZZLE_128B, CU_TENSOR_MAP_L2_PROMOTION_L2_128B, CU_TENSOR_MAP_FLOAT_OOB_FILL_NONE);
    if (er != CUDA_SUCCESS) printf("tensor map encode failed %d\n", (int)er);

    pass1_kernel<<<NUM_CTAS, 512, P1_SMEM>>>(wmap, x, dw, w2, grn_b, 0);

    cudaLaunchAttribute attr[1];
    attr[0].id = cudaLaunchAttributeProgrammaticStreamSerialization;
    attr[0].val.programmaticStreamSerializationAllowed = 1;
    cudaLaunchConfig_t cfg = {};
    cfg.gridDim = dim3(NUM_CTAS);
    cfg.stream = 0;
    cfg.attrs = attr;
    cfg.numAttrs = 1;
    cfg.blockDim = dim3(512);
    cfg.dynamicSmemBytes = P2_SMEM;
    cudaLaunchKernelEx(&cfg, pass2_kernel, x, grn_g, out, 0);
}
```

```cpp
#include <cuda.h>
#include <cuda_runtime.h>
#include <cuda_bf16.h>
#include <cuda_fp16.h>
#include <stdint.h>
#include <stdio.h>

namespace {

constexpr int M_TOTAL = 384 * 384;
constexpr int C_DIM   = 384;
constexpr int HID     = 1536;
constexpr int NT128   = M_TOTAL / 128;
constexpr int NUM_CTAS = 132;

constexpr int NGRP = 22, GRP_CTAS = 6;
constexpr int LN_STEP = NUM_CTAS / 4, LN_RING = 2 * LN_STEP;
constexpr int LN_TILE = 128 * C_DIM * 2;
constexpr int H_TILE = 64 * HID * 3 / 2;
constexpr int H_HALF = 3072, H_STEP = 6144;

__device__ __align__(1024) uint4 g_h[(size_t)M_TOTAL * HID * 3 / 32];
__device__ __align__(1024) uint4 g_ln[LN_RING * LN_TILE / 16];
__device__ __align__(1024) uint4 g_w2img[2][HID * C_DIM * 2 / 16];
__device__ __align__(16) float g_sums[2][HID + 512];
__device__ float g_scale[HID];
__device__ float g_redo[HID];
__device__ unsigned g_epoch;
__device__ __align__(128) unsigned g_prog[3][32];
__device__ __align__(128) unsigned g_half[32][2];
__device__ unsigned g_flag[LN_RING + 3][2][8];
#define TSTAMP(k, i)
#define TRACE(wg, pos, i)
#define TRACEW(pos, i)

#define TR2(wg, pos, i)
__host__ __device__ __forceinline__ int perm32(int n) {
    return (n & ~31) | (((n >> 1) & 3) << 3) | (((n >> 3) & 3) << 1) | (n & 1);
}

__device__ __forceinline__ uint32_t smem_u32(const void* p) { return (uint32_t)__cvta_generic_to_shared(p); }

__device__ __forceinline__ void mbar_init(uint32_t bar, uint32_t count) {
    asm volatile("mbarrier.init.shared::cta.b64 [%0], %1;\n" ::"r"(bar), "r"(count) : "memory");
}
__device__ __forceinline__ void mbar_expect_tx(uint32_t bar, uint32_t bytes) {
    asm volatile("mbarrier.arrive.expect_tx.shared::cta.b64 _, [%0], %1;\n" ::"r"(bar), "r"(bytes) : "memory");
}
__device__ __forceinline__ void mbar_arrive(uint32_t bar) {
    asm volatile("mbarrier.arrive.shared::cta.b64 _, [%0];\n" ::"r"(bar) : "memory");
}
__device__ __forceinline__ void mbar_arrive_cluster(uint32_t bar_cluster_addr) {
    asm volatile("mbarrier.arrive.shared::cluster.b64 _, [%0];\n" ::"r"(bar_cluster_addr) : "memory");
}
#define SAFE_BREAK
__device__ __forceinline__ void mbar_wait(uint32_t bar, uint32_t parity) {
    asm volatile(
        "{\n"
        ".reg .pred p;\n"
        "LAB_WAIT:\n"
        "mbarrier.try_wait.parity.shared::cta.b64 p, [%0], %1;\n"
        "@!p bra LAB_WAIT;\n"
        "}\n" ::"r"(bar), "r"(parity) : "memory");
}
__device__ __forceinline__ bool mbar_test(uint32_t bar, uint32_t parity) {
    uint32_t ok;
    asm volatile("{\n.reg .pred p;\n"
                 "mbarrier.test_wait.parity.shared::cta.b64 p, [%1], %2;\n"
                 "selp.u32 %0, 1, 0, p;\n}\n" : "=r"(ok) : "r"(bar), "r"(parity) : "memory");
    return ok != 0;
}
__device__ __forceinline__ uint32_t mapa(uint32_t addr, uint32_t rank) {
    uint32_t r;
    asm volatile("mapa.shared::cluster.u32 %0, %1, %2;\n" : "=r"(r) : "r"(addr), "r"(rank));
    return r;
}
__device__ __forceinline__ void bulk_g2s(uint32_t dst, const void* src, uint32_t bytes, uint32_t bar) {
    asm volatile("cp.async.bulk.shared::cluster.global.mbarrier::complete_tx::bytes [%0], [%1], %2, [%3];\n"
                 ::"r"(dst), "l"(src), "r"(bytes), "r"(bar) : "memory");
}
__device__ __forceinline__ void bulk_g2s_mc(uint32_t dst, const void* src, uint32_t bytes, uint32_t bar, uint16_t mask) {
    asm volatile("cp.async.bulk.shared::cluster.global.mbarrier::complete_tx::bytes.multicast::cluster [%0], [%1], %2, [%3], %4;\n"
                 ::"r"(dst), "l"(src), "r"(bytes), "r"(bar), "h"(mask) : "memory");
}
__device__ __forceinline__ void tma2(uint32_t dst, const CUtensorMap* map, int c0, int c1, uint32_t bar) {
    asm volatile("cp.async.bulk.tensor.2d.shared::cluster.global.tile.mbarrier::complete_tx::bytes [%0], [%1, {%2, %3}], [%4];\n"
                 ::"r"(dst), "l"(map), "r"(c0), "r"(c1), "r"(bar) : "memory");
}
template <bool ACQ>
__device__ __forceinline__ uint32_t flag_wait(const unsigned* p, unsigned target) {
    unsigned v, n = 0;
    do {
        if (ACQ) asm volatile("ld.acquire.gpu.global.u32 %0, [%1];\n" : "=r"(v) : "l"(p) : "memory");
        else asm volatile("ld.relaxed.gpu.global.u32 %0, [%1];\n" : "=r"(v) : "l"(p) : "memory");
        n++;
    } while (v < target);
    return n == 1;
}
__device__ __forceinline__ void ldsm4t(uint32_t (&r)[4], uint32_t addr) {
    asm volatile("ldmatrix.sync.aligned.m8n8.x4.trans.shared.b16 {%0,%1,%2,%3}, [%4];\n"
                 : "=r"(r[0]), "=r"(r[1]), "=r"(r[2]), "=r"(r[3]) : "r"(addr) : "memory");
}
__device__ __forceinline__ void bulk_s2g(void* dst, uint32_t src, uint32_t bytes) {
    asm volatile("cp.async.bulk.global.shared::cta.bulk_group [%0], [%1], %2;\n" ::"l"(dst), "r"(src), "r"(bytes) : "memory");
}
__device__ __forceinline__ void cluster_sync() {
    asm volatile("barrier.cluster.arrive.aligned;\nbarrier.cluster.wait.aligned;\n" ::: "memory");
}
__device__ __forceinline__ void cluster_sync_relaxed() {
    asm volatile("barrier.cluster.arrive.relaxed.aligned;\nbarrier.cluster.wait.aligned;\n" ::: "memory");
}
__device__ __forceinline__ void gdc_wait() { asm volatile("griddepcontrol.wait;\n" ::: "memory"); }
__device__ __forceinline__ void gdc_launch() { asm volatile("griddepcontrol.launch_dependents;\n" ::: "memory"); }
__device__ __forceinline__ uint32_t cluster_rank() {
    uint32_t r;
    asm volatile("mov.u32 %0, %%cluster_ctarank;\n" : "=r"(r));
    return r;
}
__device__ __forceinline__ bool elect_one() {
    uint32_t pred;
    asm volatile("{\n.reg .pred p;\nelect.sync _|p, 0xffffffff;\nselp.u32 %0, 1, 0, p;\n}\n" : "=r"(pred));
    return pred != 0;
}
__device__ __forceinline__ void wg_fence() { asm volatile("wgmma.fence.sync.aligned;\n" ::: "memory"); }
__device__ __forceinline__ void wg_commit() { asm volatile("wgmma.commit_group.sync.aligned;\n" ::: "memory"); }
template <int N> __device__ __forceinline__ void wg_wait() {
    asm volatile("wgmma.wait_group.sync.aligned %0;\n" ::"n"(N) : "memory");
}
template <int R> __device__ __forceinline__ void reg_inc() { asm volatile("setmaxnreg.inc.sync.aligned.u32 %0;\n" ::"n"(R)); }
template <int R> __device__ __forceinline__ void reg_dec() { asm volatile("setmaxnreg.dec.sync.aligned.u32 %0;\n" ::"n"(R)); }
__device__ __forceinline__ void bar_sync(int id, int n) { asm volatile("bar.sync %0, %1;\n" ::"r"(id), "r"(n) : "memory"); }
__device__ __forceinline__ void bar_arrive(int id, int n) { asm volatile("bar.arrive %0, %1;\n" ::"r"(id), "r"(n) : "memory"); }

__device__ __forceinline__ uint64_t make_desc(uint32_t saddr, uint32_t lbo, uint32_t sbo) {
    return (uint64_t)((saddr & 0x3FFFF) >> 4) | ((uint64_t)(lbo >> 4) << 16) | ((uint64_t)(sbo >> 4) << 32);
}

__device__ __forceinline__ void stg128_cs(void* p, uint32_t a, uint32_t b, uint32_t c, uint32_t d) {
#define H_ST "st.global.cs.v4.u32"
    asm volatile(H_ST " [%0], {%1,%2,%3,%4};\n" ::"l"(p), "r"(a), "r"(b), "r"(c), "r"(d) : "memory");
}
__device__ __forceinline__ uint32_t pack_bf16(float lo, float hi) {
    uint32_t r;
    asm("cvt.rn.bf16x2.f32 %0, %1, %2;\n" : "=r"(r) : "f"(hi), "f"(lo));
    return r;
}
__device__ __forceinline__ float bf_lo(uint32_t v) { return __uint_as_float(v << 16); }
__device__ __forceinline__ float bf_hi(uint32_t v) { return __uint_as_float(v & 0xffff0000u); }
__device__ __forceinline__ uint32_t bf2_mul(uint32_t a, uint32_t b) {
    uint32_t r;
    asm("mul.rn.bf16x2 %0, %1, %2;\n" : "=r"(r) : "r"(a), "r"(b));
    return r;
}
__device__ __forceinline__ uint32_t bf2_fma(uint32_t a, uint32_t b, uint32_t c) {
    uint32_t r;
    asm("fma.rn.bf16x2 %0, %1, %2, %3;\n" : "=r"(r) : "r"(a), "r"(b), "r"(c));
    return r;
}
__device__ __forceinline__ uint32_t bf2_add(uint32_t a, uint32_t b) {
    uint32_t r;
    asm("add.rn.bf16x2 %0, %1, %2;\n" : "=r"(r) : "r"(a), "r"(b));
    return r;
}
__device__ __forceinline__ uint32_t h2_mul(uint32_t a, uint32_t b) {
    uint32_t r;
    asm("mul.rn.f16x2 %0, %1, %2;\n" : "=r"(r) : "r"(a), "r"(b));
    return r;
}
__device__ __forceinline__ uint32_t h2_fma(uint32_t a, uint32_t b, uint32_t c) {
    uint32_t r;
    asm("fma.rn.f16x2 %0, %1, %2, %3;\n" : "=r"(r) : "r"(a), "r"(b), "r"(c));
    return r;
}
__device__ __forceinline__ uint32_t h2_add(uint32_t a, uint32_t b) {
    uint32_t r;
    asm("add.rn.f16x2 %0, %1, %2;\n" : "=r"(r) : "r"(a), "r"(b));
    return r;
}
__device__ __forceinline__ uint32_t pack_f16(float lo, float hi) {
    uint32_t r;
    asm("cvt.rn.f16x2.f32 %0, %1, %2;\n" : "=r"(r) : "f"(hi), "f"(lo));
    return r;
}
__device__ __forceinline__ float h_lo(uint32_t v) { return __low2float(*reinterpret_cast<const __half2*>(&v)); }
__device__ __forceinline__ float h_hi(uint32_t v) { return __high2float(*reinterpret_cast<const __half2*>(&v)); }
__device__ __forceinline__ uint32_t bf2_to_h2(uint32_t v) { return (v & 0x7fff7fffu) * 7u + v; }
__device__ __forceinline__ uint32_t prmt(uint32_t a, uint32_t b, uint32_t sel) {
    uint32_t r;
    asm("prmt.b32 %0, %1, %2, %3;\n" : "=r"(r) : "r"(a), "r"(b), "r"(sel));
    return r;
}
__device__ __forceinline__ uint32_t bitsel(uint32_t a, uint32_t b, uint32_t m) {
    uint32_t r;
    asm("lop3.b32 %0, %1, %2, %3, 0xd8;\n" : "=r"(r) : "r"(a), "r"(b), "r"(m));
    return r;
}
constexpr float KAPPA = 0.3292034911525734f;
constexpr uint32_t GELU_C2 = 0x40d940d9u;
constexpr float HSCALE = 1.0f / (2.0f * KAPPA);
__device__ __forceinline__ float w2_scale(uint32_t m) { return __uint_as_float((257u - max(m >> 23, 16u)) << 23); }
__device__ __forceinline__ void sched_break(int zero) {
    asm volatile("{\n.reg .pred p;\nsetp.ne.s32 p, %0, 0;\nSB_LOOP:\n@p nanosleep.u32 1;\n@p bra SB_LOOP;\n}\n" ::"r"(zero));
}

#define ACC8(d, o) "+r"(d[o + 0]), "+r"(d[o + 1]), "+r"(d[o + 2]), "+r"(d[o + 3]), "+r"(d[o + 4]), "+r"(d[o + 5]), "+r"(d[o + 6]), "+r"(d[o + 7])

__device__ __forceinline__ void mma_rs_n128(uint32_t (&d)[32], const uint32_t (&a)[4], uint32_t desc, int scale_d) {
    asm volatile(
        "{\n.reg .pred p;\n.reg .b64 db;\nsetp.ne.b32 p, %37, 0;\nmov.b64 db, {%36, 0x40000040};\n"
        "wgmma.mma_async.sync.aligned.m64n128k16.f16.f16.f16 "
        "{%0,%1,%2,%3,%4,%5,%6,%7,%8,%9,%10,%11,%12,%13,%14,%15,"
        "%16,%17,%18,%19,%20,%21,%22,%23,%24,%25,%26,%27,%28,%29,%30,%31},"
        "{%32,%33,%34,%35}, db, p, 1, 1, 0;\n}\n"
        : ACC8(d, 0), ACC8(d, 8), ACC8(d, 16), ACC8(d, 24)
        : "r"(a[0]), "r"(a[1]), "r"(a[2]), "r"(a[3]), "r"(desc), "r"(scale_d));
}

__device__ __forceinline__ void mma_ss_n128(uint32_t (&d)[32], uint32_t da, uint32_t db, int scale_d) {
    asm volatile(
        "{\n.reg .pred p;\n.reg .b64 da, db;\nsetp.ne.b32 p, %34, 0;\nmov.b64 da, {%32, 0x40000040};\nmov.b64 db, {%33, 0x40000040};\n"
        "wgmma.mma_async.sync.aligned.m64n128k16.f16.f16.f16 "
        "{%0,%1,%2,%3,%4,%5,%6,%7,%8,%9,%10,%11,%12,%13,%14,%15,"
        "%16,%17,%18,%19,%20,%21,%22,%23,%24,%25,%26,%27,%28,%29,%30,%31},"
        "da, db, p, 1, 1, 1, 0;\n}\n"
        : ACC8(d, 0), ACC8(d, 8), ACC8(d, 16), ACC8(d, 24)
        : "r"(da), "r"(db), "r"(scale_d));
}

__device__ __forceinline__ void mma_rs_n192(uint32_t (&d)[48], const uint4& a, uint32_t db) {
    asm volatile(
        "{\n.reg .b64 db;\nmov.b64 db, {%52, 16};\n"
        "wgmma.mma_async.sync.aligned.m64n192k16.f16.f16.f16 "
        "{%0,%1,%2,%3,%4,%5,%6,%7,%8,%9,%10,%11,%12,%13,%14,%15,"
        "%16,%17,%18,%19,%20,%21,%22,%23,%24,%25,%26,%27,%28,%29,%30,%31,"
        "%32,%33,%34,%35,%36,%37,%38,%39,%40,%41,%42,%43,%44,%45,%46,%47},"
        "{%48,%49,%50,%51}, db, 1, 1, 1, 0;\n}\n"
        : ACC8(d, 0), ACC8(d, 8), ACC8(d, 16), ACC8(d, 24), ACC8(d, 32), ACC8(d, 40)
        : "r"(a.x), "r"(a.y), "r"(a.z), "r"(a.w), "r"(db));
}

#define P1_WPF 30
#define P1_PACE 1
constexpr int P1_SLOT = LN_TILE / 6, P1_NST = 6;
constexpr int P1_W = 64 * C_DIM * 2;
constexpr int P1_X = 32 * C_DIM * 2;
constexpr int P1_OFF_W = LN_TILE;
constexpr int P1_OFF_X = P1_OFF_W + 2 * P1_W;
constexpr int P1_OFF_BAR = P1_OFF_X + P1_X;
constexpr int P1_OFF_TILE = P1_OFF_BAR + (2 * P1_NST + 4 + 4 + 4) * 8;
constexpr int P1_OFF_EX = P1_OFF_TILE + 64;
constexpr int P1_OFF_DW = P1_OFF_EX + 256 * 4;
constexpr int P1_SMEM = P1_OFF_DW + C_DIM * 2;

__device__ __forceinline__ float rsqrt_fast(float x) {
    float r;
    asm("rsqrt.approx.ftz.f32 %0, %1;\n" : "=f"(r) : "f"(x));
    return r;
}
__device__ __forceinline__ float row_sum(const uint32_t (&c)[4]) {
    const uint32_t u = bf2_add(bf2_add(c[0], c[1]), bf2_add(c[2], c[3]));
    float s = bf_lo(u) + bf_hi(u);
#pragma unroll
    for (int o = 1; o < 8; o <<= 1) s += __shfl_xor_sync(0xffffffffu, s, o);
    return s;
}
__device__ __forceinline__ uint32_t pace(uint32_t bar, uint32_t off, uint32_t val, uint32_t after, int zero) {
    asm volatile(
        "{\n.reg .pred p, q;\n.reg .b32 par;\n"
        "lop3.b32 par, %4, %2, %3, 0xea;\n"
        "setp.eq.u32 q, par, 0;\n"
        "mov.pred p, 0;\n"
        "@q mbarrier.test_wait.parity.shared::cta.b64 p, [%1], par;\n"
        "selp.u32 par, 1, 0, p;\n"
        "@q mbarrier.try_wait.parity.shared::cta.b64 p, [%1], par, 1000;\n"
        "@p or.b32 %0, %0, %2;\n"
        "}\n" : "+r"(val) : "r"(bar), "r"(zero), "r"(off), "r"(after));
    return val;
}
template <int PACE, int R>
__device__ __forceinline__ void ln_rows(uint32_t (&v)[R][6][4], const uint32_t (&d)[6][4], uint32_t bar, uint32_t off, int zero,
                                        uint32_t bar_read) {
    const float inv = 1.0f / C_DIM;
    uint32_t c[R][4], nm[R];
    float e[R], r[R], er[R];
    bool big = false;
#pragma unroll
    for (int p = 0; p < R; p++) {
#pragma unroll
        for (int i = 0; i < 6; i++)
#pragma unroll
            for (int k = 0; k < 4; k++) c[p][k] = bf2_fma(v[p][i][k], d[i][k], i ? c[p][k] : 0);
        const float m = row_sum(c[p]) * inv;
        nm[p] = pack_bf16(-m, -m);
        e[p] = m + bf_lo(nm[p]);
    }
    if (bar_read) mbar_arrive(bar_read + (nm[0] & zero));
    if (PACE & 1) nm[0] = pace(bar, off, nm[0], nm[0], zero);
#pragma unroll
    for (int p = 0; p < R; p++) {
#pragma unroll
        for (int i = 0; i < 6; i++) {
#pragma unroll
            for (int k = 0; k < 4; k++) {
                v[p][i][k] = bf2_fma(v[p][i][k], d[i][k], nm[p]);
                c[p][k] = i ? bf2_fma(v[p][i][k], v[p][i][k], c[p][k]) : bf2_mul(v[p][i][k], v[p][i][k]);
            }
        }
        r[p] = KAPPA * rsqrt_fast(fmaxf(fmaf(-e[p], e[p], row_sum(c[p]) * inv), 0.f) + 1e-5f);
        er[p] = -e[p] * r[p] * 0x1p-112f;
        big |= r[p] < 0x1p-8f;
    }
    if (__any_sync(0xffffffffu, big)) {
#pragma unroll
        for (int p = 0; p < R; p++) {
            const uint32_t p2 = __float_as_uint(r[p]) & 0x7f800000u;
            r[p] = __uint_as_float((__float_as_uint(r[p]) & 0x007fffffu) | 0x3f800000u);
#pragma unroll
            for (int i = 0; i < 6; i++)
#pragma unroll
                for (int k = 0; k < 4; k++) v[p][i][k] = bf2_mul(v[p][i][k], p2 | p2 >> 16);
        }
    }
#pragma unroll
    for (int p = 0; p < R; p++) {
        uint32_t rs = pack_bf16(r[p] * 0x1p-112f, r[p] * 0x1p-112f);
        const uint32_t sh = pack_bf16(er[p], er[p]);
        if (PACE & 2) rs = pace(bar, off, rs, sh, zero);
#pragma unroll
        for (int i = 0; i < 6; i++)
#pragma unroll
            for (int k = 0; k < 4; k++) v[p][i][k] = bf2_to_h2(bf2_fma(v[p][i][k], rs, sh));
    }
}

template <int R>
__device__ __forceinline__ uint32_t gelu2(uint32_t a, uint32_t sc2) {
    uint32_t y, t;
    if (R) asm("{\n.reg .b16 l, h;\n.reg .b32 f;\nmov.b32 {l, h}, %2;\nmov.b32 f, {h, h};\nmul.rn.f16x2 %0, %1, f;\n}\n" : "=r"(y) : "r"(a), "r"(sc2));
    else asm("{\n.reg .b16 l, h;\n.reg .b32 f;\nmov.b32 {l, h}, %2;\nmov.b32 f, {l, l};\nmul.rn.f16x2 %0, %1, f;\n}\n" : "=r"(y) : "r"(a), "r"(sc2));
    asm("tanh.approx.f16x2 %0, %1;\n" : "=r"(t) : "r"(h2_mul(y, h2_fma(y, y, GELU_C2))));
    return h2_fma(a, t, a);
}
constexpr uint32_t SPARE = 0x40074007u;
constexpr float UNCHOP = 1.0023f;

__device__ __forceinline__ uint32_t p1_parity(uint32_t sbase) {
    uint32_t v;
    asm volatile("ld.shared.u32 %0, [%1];\n" : "=r"(v) : "r"(sbase + P1_OFF_TILE - 4) : "memory");
    return v;
}
__device__ __forceinline__ uint32_t p1_exponents(float (&t)[2], uint32_t (&ex)[2], uint32_t saddr, int lane) {
#pragma unroll
    for (int r = 0; r < 2; r++) {
        t[r] += __shfl_xor_sync(0xffffffffu, t[r], 1);
        t[r] += __shfl_xor_sync(0xffffffffu, t[r], 2);
        ex[r] = min(max(((__float_as_uint(193.3f * t[r]) >> 23) + 127u) >> 1, 72u), 198u);
        asm volatile("st.shared.u32 [%0], %1;\n" ::"r"(saddr + r * 32), "r"(ex[r] << 23) : "memory");
    }
    return pack_f16(__uint_as_float(min(ex[0], 142u) << 23), __uint_as_float(min(ex[1], 142u) << 23));
}
template <int N>
__device__ __forceinline__ void p1_convert(uint32_t (&o)[N][4], uint32_t (&v)[N][4], const uint32_t (&ex)[2]) {
    if (__any_sync(0xffffffffu, max(ex[0], ex[1]) > 141u)) {
#pragma unroll
        for (int k = 0; k < 4 * N; k++) v[k >> 2][k & 3] = bf2_mul(v[k >> 2][k & 3], ex[k & 1] > 141u ? 0x1f801f80u : 0x3f803f80u);
    }
#pragma unroll
    for (int k = 0; k < 4 * N; k++) {
        const uint32_t u = bf2_mul(v[k >> 2][k & 3], ((ex[k & 1] > 141u ? 206u : 142u) - ex[k & 1]) * 0x00800080u);
        asm volatile("mad.lo.u32 %0, %1, 7, %2;\n" : "=r"(o[k >> 2][k & 3]) : "r"(u & 0x7fff7fffu), "r"(u));
    }
}
template <int N>
__device__ __forceinline__ void p1_squares(const uint32_t (&v)[N][4], float (&t)[2]) {
#pragma unroll
    for (int j = 0; j < N / 2; j++) {
        const int r = j & 1, b = (j >> 1) * 4;
        uint32_t c = bf2_mul(v[b][r], v[b][r]);
#pragma unroll
        for (int k = 1; k < 8; k++) c = bf2_fma(v[b + k / 2][r + (k & 1) * 2], v[b + k / 2][r + (k & 1) * 2], c);
        t[r] += bf_lo(c) + bf_hi(c);
    }
}
__device__ __forceinline__ void p1_epilogue(const uint32_t (&acc)[2][32], const uint32_t (&sc2)[2], float (&ssq)[4], uint8_t* hp, int zero) {
    uint32_t sq[2], h[16][4];
#pragma unroll
    for (int i2 = 0; i2 < 9; i2++) {
#pragma unroll
        for (int c = 2 * i2 - 2; c < 2 * i2; c++) {
            if (c >= 0 && (c & 3)) {
                uint32_t o[4];
#pragma unroll
                for (int u = 0; u < 4; u++) {
                    const uint32_t v = h[c & 12][u];
                    o[u] = bitsel(h[c][u], (c & 3) == 2 ? prmt(v, v, 0xa381) : prmt(v >> 3, v, (c & 3) == 1 ? 0x6240 : 0xf3d1), SPARE);
                }
                stg128_cs(hp + (c >> 3) * 2 * H_STEP + ((c >> 2) & 1) * H_HALF + ((c & 3) - 1) * 512, o[0], o[1], o[2], o[3]);
            }
        }
        if (i2 < 8) {
#pragma unroll
            for (int u = 0; u < 4; u++) {
                h[2 * i2][u] = gelu2<0>(acc[i2 >> 2][8 * (i2 & 3) + 2 * u], sc2[i2 >> 2]);
                h[2 * i2 + 1][u] = gelu2<1>(acc[i2 >> 2][8 * (i2 & 3) + 2 * u + 1], sc2[i2 >> 2]);
#pragma unroll
                for (int r = 0; r < 2; r++) {
                    const uint32_t v = h[2 * i2 + r][u];
                    sq[r] = ((i2 & 3) | u) ? h2_fma(v, v, sq[r]) : h2_mul(v, v);
                }
            }
            if ((i2 & 3) == 3) {
#pragma unroll
                for (int r = 0; r < 2; r++) ssq[(i2 >> 2) * 2 + r] += h_lo(sq[r]) + h_hi(sq[r]);
            }
            sched_break(zero);
        }
    }
}
template <int WG>
__device__ __forceinline__ void p1_mma(uint32_t (&acc)[2][32], const uint32_t (&a)[24][4], uint32_t sbase, uint32_t empty_remote, int i, int lane) {
    const uint32_t bar_full = sbase + P1_OFF_BAR;
    const uint32_t db = (uint32_t)make_desc(sbase, 16, 1024), da = db + (P1_OFF_W + WG * P1_W) / 16;
    if (WG == 0) mbar_wait(bar_full, i & 1);
    bar_sync(1 + WG, 256);
    TRACE(WG, i, 1);
    wg_fence();
#pragma unroll
    for (int k = 0; k < 24; k++) {
        if (WG == 0 && k && k % 4 == 0) mbar_wait(bar_full + (k >> 2) * 8, i & 1);
        mma_rs_n128(acc[0], a[k], db + (k >> 2) * 1024 + (k & 3) * 2, k != 0);
        mma_ss_n128(acc[1], da + k * 128, db + (k >> 2) * 1024 + (k & 3) * 2, k != 0);
        if (k == 23) bar_arrive(2 - WG, 256);
        if (k == 23 || (WG == 1 && k % 4 == 3)) wg_commit();
        if (WG == 1 && k % 4 == 3 && k > 3) {
            wg_wait<1>();
            if (lane < 2) mbar_arrive_cluster(empty_remote + ((k >> 2) - 1) * 8);
        }
    }
    TRACE(WG, i, 2);
    wg_wait<0>();
    if (WG == 1 && lane < 2) mbar_arrive_cluster(empty_remote + 5 * 8);
}
__device__ __forceinline__ void p1_consumer(const uint32_t (&a)[24][4], const uint32_t (&sc2)[2], uint32_t sbase, int WG, int w, int lane, int zero) {
    const uint32_t bar_full = sbase + P1_OFF_BAR, bar_empty = bar_full + P1_NST * 8;
    const uint32_t empty_remote = mapa(bar_empty, lane & 1);
    const uint32_t bar_pace = bar_empty + P1_NST * 8 + 32 + w * 8;
    const int g = lane >> 2, q = lane & 3, cb = (blockIdx.x % GRP_CTAS) * 4 + WG * 2;
    uint32_t acc[2][32];
    float ssq[4] = {0.f, 0.f, 0.f, 0.f};
    TSTAMP(0, 1);

    uint8_t* hp = reinterpret_cast<uint8_t*>(g_h) + ((cb * 2 + (w >> 1)) * H_STEP + (w & 1) * 1536) + g * 64 + (q ^ (g >> 1)) * 16;
    int i = 0;
#pragma unroll 1
    for (;; i++) {
        TRACE(WG, i, 0);
        if (WG == 0) p1_mma<0>(acc, a, sbase, empty_remote, i, lane);
        else p1_mma<1>(acc, a, sbase, empty_remote, i, lane);
        TRACE(WG, i, 4);
        uint32_t step, more;
        asm volatile("ld.shared.v2.u32 {%0, %1}, [%2];\n" : "=r"(step), "=r"(more) : "r"(sbase + P1_OFF_TILE + (i & 3) * 16) : "memory");
        hp += step;
        p1_epilogue(acc, sc2, ssq, hp, zero);
        if (lane == 0) mbar_arrive(bar_pace);
        if (!more) break;
    }
    TSTAMP(0, 21);
    if (WG == 0) bar_sync(1, 256);
#pragma unroll
    for (int r = 0; r < 4; r++) {
        const int ch = (r >> 1) * 64 + w * 16 + (r & 1) * 8 + g;
        ssq[r] += __shfl_xor_sync(0xffffffffu, ssq[r], 1);
        ssq[r] += __shfl_xor_sync(0xffffffffu, ssq[r], 2);
        float f;
        asm volatile("ld.shared.f32 %0, [%1];\n" : "=f"(f) : "r"(sbase + P1_OFF_EX + (WG * 128 + ch) * 4) : "memory");
        if (q == 0) {
            float* sums = g_sums[p1_parity(sbase)];
            atomicAdd(&sums[cb * 64 + ch], ssq[r] * f * f);
            g_scale[cb * 64 + ch] = f;
            if (ssq[r] < (i + 1) * 0x1p-12f) sums[HID + C_DIM + 1] = 1.f;
        }
    }
}

__global__ void __cluster_dims__(2, 1, 1) __launch_bounds__(512, 1)
pass1_kernel(const __grid_constant__ CUtensorMap wmap, const __nv_bfloat16* __restrict__ x, const __nv_bfloat16* __restrict__ dw,
             const __nv_bfloat16* __restrict__ w2, const __nv_bfloat16* __restrict__ grn_b, int zero) {
    extern __shared__ __align__(1024) uint8_t smem[];
    const uint32_t sbase = smem_u32(smem);
    const uint32_t bar_full = sbase + P1_OFF_BAR, bar_empty = bar_full + P1_NST * 8, bar_w = bar_empty + P1_NST * 8;
    const int tid = threadIdx.x;
    const int warp = __shfl_sync(0xffffffffu, tid >> 5, 0), lane = tid & 31;
    const uint32_t rank = cluster_rank();
    const int cig = blockIdx.x % GRP_CTAS;
    uint8_t* const ring = reinterpret_cast<uint8_t*>(g_ln);

    TSTAMP(0, 0);
    TRACEW(110 + warp, 0);
    const uint32_t bar_pace = bar_w + 32, bar_xfull = bar_pace + 32, bar_xempty = bar_xfull + 8, bar_done = bar_xfull + 16;
    const int ln0 = blockIdx.x >> 2, first = blockIdx.x / GRP_CTAS;
    const uint8_t* xsrc = reinterpret_cast<const uint8_t*>(x) + (size_t)blockIdx.x * P1_X;

    if (warp >= 12) {
        reg_dec<40>();
        asm volatile("barrier.cluster.arrive.relaxed.aligned;\n" ::: "memory");
        asm volatile("barrier.cluster.wait.aligned;\n" ::: "memory");
        if (warp == 12) {
            int prev = 0, t = first;
            const uint32_t rbase = mapa(sbase, lane & 1);
#pragma unroll 1
            for (int i = 0; t < NT128; i++) {
                const int round = t / LN_RING, slot = t - round * LN_RING;
                const uint8_t* src = ring + slot * LN_TILE + rank * (P1_SLOT / 2);
                int next = 0;
                if (rank == 0 && lane == 0) next = atomicAdd(&g_flag[LN_RING + (cig >> 1)][0][0], 1u);
                flag_wait<true>(&g_flag[slot][0][0], 4 * round + 4);
                TRACEW(i, 2);
                asm volatile("fence.proxy.async.global;\n" ::: "memory");
                next = NGRP + __shfl_sync(0xffffffffu, next, 0);
#pragma unroll 1
                for (int h = 0; h < P1_NST; h++) {
                    mbar_wait(bar_empty + h * 8, i & 1);
                    if (h == 0) TRACEW(i, 4);
                    if (h == 5) TRACEW(i, 5);
                    if (elect_one()) {
                        mbar_expect_tx(bar_full + h * 8, h ? P1_SLOT : P1_SLOT + 16);
                        bulk_g2s_mc(sbase + h * P1_SLOT + rank * (P1_SLOT / 2), src + h * P1_SLOT, P1_SLOT / 2, bar_full + h * 8, (uint16_t)3);
                    }
                    __syncwarp();
                    if (h == 0 && rank == 0 && lane < 2)
                        asm volatile("st.async.shared::cluster.mbarrier::complete_tx::bytes.v4.u32 [%0], {%1, %2, %3, %3}, [%4];\n"
                                     ::"r"(rbase + P1_OFF_TILE + (i & 3) * 16), "r"((t - prev) * (2 * H_TILE)), "r"((int)(next < NT128)), "r"(next),
                                       "r"(rbase + P1_OFF_BAR) : "memory");
                }
                prev = t;
                t = next;
                if (rank != 0) {
                    mbar_wait(bar_full, i & 1);
                    asm volatile("ld.shared.u32 %0, [%1];\n" : "=r"(t) : "r"(sbase + P1_OFF_TILE + (i & 3) * 16 + 8) : "memory");
                }
            }
        } else if (warp == 13) {
            int ph = 0;
            unsigned target = 0;
#pragma unroll 1
            for (int i = ln0 + LN_STEP; i < NT128; i += LN_STEP, ph ^= 1) {
                target += ph * (GRP_CTAS / 2);
                xsrc += (size_t)NUM_CTAS * P1_X;
                mbar_wait(bar_xempty, ph);
                if (elect_one()) {
                    mbar_expect_tx(bar_xfull, P1_X);
                    bulk_g2s(sbase + P1_OFF_X, xsrc, P1_X, bar_xfull);
                }
                __syncwarp();
                const uint32_t off = flag_wait<false>(&g_flag[ln0 + (ph ^ 1) * LN_STEP][1][0], target);
                mbar_wait(bar_done, ph);
                if (elect_one()) {
                    asm volatile("st.shared.u32 [%0], %1;\n" ::"r"(bar_done + 8), "r"(off) : "memory");
                    mbar_arrive(bar_xfull);
                }
                __syncwarp();
            }
        } else if (warp == 15) {
            const uint32_t par = g_epoch & 1;
            asm volatile("st.shared.u32 [%0], %1;\n" ::"r"(sbase + P1_OFF_TILE - 4), "r"(par) : "memory");
            if (blockIdx.x < 16) reinterpret_cast<float4*>(g_sums[par ^ 1])[blockIdx.x * 32 + lane] = make_float4(0.f, 0.f, 0.f, 0.f);
            int t = first;
            if (rank == 1 && lane == 0) mbar_arrive(bar_empty);
#pragma unroll 1
            for (int i = 0; rank == 1 && t < NT128; i++) {
#pragma unroll 1
                for (int h = 0; h < P1_NST; h++) mbar_wait(bar_full + h * 8, i & 1);
                if (lane == 0) asm volatile("red.relaxed.gpu.global.add.u32 [%0], 1;\n" ::"l"(&g_flag[t % LN_RING][1][0]) : "memory");
                asm volatile("ld.shared.u32 %0, [%1];\n" : "=r"(t) : "r"(sbase + P1_OFF_TILE + (i & 3) * 16 + 8) : "memory");
                if (lane == 0) mbar_arrive(bar_empty);
                TRACEW(i, 3);
            }
            if (rank == 0) {
                mbar_wait(bar_full, 0);
                TRACEW(110 + warp, 3);
                mbar_wait(bar_full, 1);
                float* sums = g_sums[par] + HID;
                unsigned* flag = reinterpret_cast<unsigned*>(sums + C_DIM);
                if (blockIdx.x == 0) reinterpret_cast<uint2*>(g_half)[lane] = make_uint2(0, 0);
                if (blockIdx.x == 2 && lane < 3) g_prog[lane][0] = 0;
                if (blockIdx.x < 96) g_redo[blockIdx.x * 16 + lane] = 0.f;
                float gs = 0.f;
#pragma unroll 1
                for (int pass = 0; pass < 2; pass++) {
                    float mx = 0.f;
#pragma unroll 1
                    for (int it = first; it < 96; it += NGRP) {
                        const int nb = it % 12, k0 = (cig * 4 + it / 12) * 64 + (lane >> 2);
                        const uint32_t sc = mapa(sbase + P1_OFF_EX + (k0 & 255) * 4, it / 48);
                        uint32_t* dst = reinterpret_cast<uint32_t*>(g_w2img[0]) + (k0 >> 4) * 3072 + nb * 256 + lane;
                        float bs[8] = {};
#pragma unroll 1
                        for (int c = 0; c < 8; c++) {
                            const uint4 u = __ldg(reinterpret_cast<const uint4*>(w2 + (size_t)(k0 + c * 8) * C_DIM + nb * 32) + (lane & 3));
                            const float b = __bfloat162float(grn_b[k0 + c * 8]);
                            float t;
                            asm volatile("ld.shared::cluster.f32 %0, [%1];\n" : "=f"(t) : "r"(sc + c * 32) : "memory");
#pragma unroll
                            for (int j = 0; j < 4; j++) {
                                const uint32_t v = j == 0 ? u.x : j == 1 ? u.y : j == 2 ? u.z : u.w;
                                mx = fmaxf(mx, fmaxf(fabsf(bf_lo(v)), fabsf(bf_hi(v))) * t);
                                if (pass) {
                                    bs[2 * j] = fmaf(b, bf_lo(v), bs[2 * j]);
                                    bs[2 * j + 1] = fmaf(b, bf_hi(v), bs[2 * j + 1]);
                                    uint32_t h = pack_f16(bf_lo(v) * t * gs, bf_hi(v) * t * gs);
                                    asm volatile("movmatrix.sync.aligned.m8n8.trans.b16 %0, %0;\n" : "+r"(h));
                                    dst[(c >> 1) * 3072 + (c & 1) * 32 + j * 64] = h;
                                }
                            }
                        }
                        if (pass) {
#pragma unroll
                            for (int j = 0; j < 8; j++) {
#pragma unroll
                                for (int o = 4; o < 32; o <<= 1) bs[j] += __shfl_xor_sync(0xffffffffu, bs[j], o);
                                if (lane >> 2 == j) atomicAdd(&sums[nb * 32 + (j >> 1) * 8 + (lane & 3) * 2 + (j & 1)], bs[j]);
                            }
                        }
                    }
                    if (!pass) {
                        const uint32_t m = __reduce_max_sync(0xffffffffu, __float_as_uint(mx));
                        if (lane == 0) {
                            atomicMax(flag, m);
                            asm volatile("red.release.gpu.global.add.u32 [%0], 1;\n" ::"l"(flag + 32) : "memory");
                        }
                        flag_wait<true>(flag + 32, NUM_CTAS / 2);
                        gs = w2_scale(__ldcg(flag));
                    }
                }
                do {
                    __nanosleep(1000);
                    asm volatile("ld.volatile.shared.u32 %0, [%1];\n" : "=r"(t) : "r"(sbase + P1_OFF_TILE + (lane & 3) * 16 + 8) : "memory");
                    SAFE_BREAK;
                } while (__all_sync(0xffffffffu, t < NT128 - P1_WPF));
                if (lane == 0 && blockIdx.x < 128)
                    asm volatile("cp.async.bulk.prefetch.L2.global [%0], %1;\n" ::"l"(g_w2img[0] + blockIdx.x * 576), "r"(18432) : "memory");
            }
        } else if (warp == 14) {
            int ph = 0;
#pragma unroll 1
            for (int i = ln0; i < NT128; i += LN_STEP, ph ^= 1) {
                mbar_wait(bar_done, ph);
                TRACEW(i / LN_STEP, 0);
                asm volatile("fence.proxy.async.global;\n" ::: "memory");
                if (elect_one()) asm volatile("red.release.gpu.global.add.u32 [%0], 1;\n" ::"l"(&g_flag[ln0 + ph * LN_STEP][0][0]) : "memory");
                __syncwarp();
                TRACEW(i / LN_STEP, 1);
            }
        }
        __syncwarp();
        cluster_sync();
    } else if (warp >= 8) {
        reg_dec<88>();
        asm volatile("barrier.cluster.arrive.relaxed.aligned;\n" ::: "memory");
        {
            const int l8 = lane & 7, row = (warp - 8) * 4 + (lane >> 3), px = (blockIdx.x & 3) * 32 + row;
            uint32_t d[6][4];
            const int n = (px & 64) + perm32(2 * row + ((px >> 5) & 1));
            uint8_t* const dst0 = ring + ln0 * LN_TILE + n * 128 + ((l8 ^ (n & 7)) << 4);
            const uint32_t src = sbase + P1_OFF_X + ((warp - 8) * 8 + (lane >> 3)) * (C_DIM * 2) + l8 * 16;
            int ph = 0;
#pragma unroll 1
            for (int i = ln0; i < NT128; i += LN_STEP, ph ^= 1) {
                TRACE(2, i / LN_STEP, 0);
                uint32_t off = 1;
#pragma unroll 1
                for (int ps = i == ln0 ? -2 : 0; ps < 2; ps += ps < 0 ? 2 : 1) {
                    if (ps == 0) {
                        if (i == ln0) asm volatile("barrier.cluster.wait.aligned;\n" ::: "memory");
                        mbar_wait(bar_xfull, ph);
                        asm volatile("ld.shared.u32 %0, [%1];\n" : "=r"(off) : "r"(bar_done + 8) : "memory");
                    }
                    if (ps == 0) TRACE(2, i / LN_STEP, 1);
                    if (i == ln0) {
#pragma unroll
                        for (int j = 0; j < 6; j++)
                            asm volatile("ld.shared.v4.u32 {%0,%1,%2,%3}, [%4];\n"
                                         : "=r"(d[j][0]), "=r"(d[j][1]), "=r"(d[j][2]), "=r"(d[j][3]) : "r"(sbase + P1_OFF_DW + j * 128 + l8 * 16) : "memory");
                    }
                    uint32_t v1[1][6][4];
                    uint32_t (&v)[6][4] = v1[0];
#pragma unroll
                    for (int j = 0; j < 6; j++)
                        asm volatile("ld.shared.v4.u32 {%0,%1,%2,%3}, [%4];\n"
                                     : "=r"(v[j][0]), "=r"(v[j][1]), "=r"(v[j][2]), "=r"(v[j][3]) : "r"(src + (ps & 1) * (4 * C_DIM * 2) + j * 128) : "memory");
                    ln_rows<P1_PACE, 1>(v1, d, bar_pace + (warp - 8) * 8, off, zero, ps == 1 && lane == 0 ? bar_xempty : 0);
                    uint8_t* dst = dst0 + ph * (LN_STEP * LN_TILE) + (ps & 1) * 4096;
#pragma unroll
                    for (int j = 0; j < 6; j++) *reinterpret_cast<uint4*>(dst + j * 16384) = make_uint4(v[j][0], v[j][1], v[j][2], v[j][3]);
                    TRACE(2, i / LN_STEP, 3 + (ps & 1));
                }
                asm volatile("fence.proxy.async.global;\nfence.acq_rel.cta;\n" ::: "memory");
                __syncwarp();
                if (lane == 0) mbar_arrive(bar_done);
                TRACE(2, i / LN_STEP, 5);
                TRACE(2, i / LN_STEP, 2);
            }
        }
        __syncwarp();
        cluster_sync();
    } else {
        const int wg = warp >> 2, w = warp & 3;
        auto load_w = [&](int i0, int i1) {
#pragma unroll 1
            for (int i = i0; i < i1; i++) {
                if (!(i & 1)) mbar_expect_tx(bar_w + (i >> 1) * 8, P1_W);
                tma2(sbase + (i & 2) * P1_W + (i >> 2) * P1_W + (i & 1) * (P1_W / 2), &wmap, cig * 256 + (i >> 1) * 64, (i & 1) * 192, bar_w + (i >> 1) * 8);
            }
        };
        if (warp == 4 && elect_one()) {
            mbar_init(bar_xfull, 2);
#pragma unroll
            for (int i = 0; i < 4; i++) mbar_init(bar_w + i * 8, 1);
            asm volatile("fence.mbarrier_init.release.cluster;\n" ::: "memory");
            mbar_expect_tx(bar_xfull, P1_X + C_DIM * 2);
            bulk_g2s(sbase + P1_OFF_X, xsrc, P1_X, bar_xfull);
            bulk_g2s(sbase + P1_OFF_DW, dw, C_DIM * 2, bar_xfull);
            load_w(0, 4);
            asm volatile("st.shared.u32 [%0], 1;\n" ::"r"(bar_done + 8) : "memory");
            mbar_arrive(bar_xfull);
        }
        if (warp == 5 && elect_one()) {
#pragma unroll
            for (int i = 0; i < P1_NST; i++) {
                mbar_init(bar_full + i * 8, 1);
                mbar_init(bar_empty + i * 8, i ? 8 : 8 + rank);
                if (i < 4) mbar_init(bar_pace + i * 8, 1);
            }
            mbar_init(bar_xempty, 4);
            mbar_init(bar_done, 4);
            asm volatile("fence.mbarrier_init.release.cluster;\n" ::: "memory");
        }
        __syncwarp();
        asm volatile("barrier.cluster.arrive.relaxed.aligned;\n" ::: "memory");
        reg_inc<192>();
        TRACEW(110 + warp, 1);
        uint32_t a[24][4];
        gdc_launch();
        const uint32_t src = sbase + wg * P1_W + ((lane >> 4) * 8 + (lane & 7)) * 128 + (((2 * w + ((lane >> 3) & 1)) ^ (lane & 7)) << 4);
        const uint32_t s_ex = sbase + P1_OFF_EX + (wg * 128 + w * 16 + (lane >> 2)) * 4;
        uint32_t sc2[2], ex[2];
        if (wg == 1) bar_arrive(1, 256);
#pragma unroll 1
        for (int it = 0; it < 2; it++) {
          if (it != wg) asm volatile("barrier.cluster.wait.aligned;\n" ::: "memory");
          if (it < wg) {
              mbar_wait(bar_xfull, 0);
              if (w == 0 && elect_one()) load_w(4, 8);
              __syncwarp();
          }
          if (it || wg == 0) {
            float t[2] = {0.f, 0.f};
            if (it) {
                TRACEW(110 + warp, 2);
                mbar_wait(bar_w + wg * 16, 0);
            }
            TRACEW(110 + warp, 5);
#pragma unroll
            for (int k = 0; k < 24; k++) ldsm4t(a[k], src + k * 2048);
            TRACEW(110 + warp, 6);
            p1_squares(a, t);
            sc2[0] = p1_exponents(t, ex, s_ex, lane);
            if (it && lane < 6) mbar_arrive_cluster(mapa(bar_empty, lane & 1) + (wg * 3 + (lane >> 1)) * 8 + (sc2[0] & zero));
            p1_convert<24>(a, a, ex);
          }
          if (it || wg == 1) {
            float t[2] = {0.f, 0.f};
            TRACEW(100 + warp, 0);
            if (it) mbar_wait(bar_w + wg * 16 + 8, 0);
            TRACEW(100 + warp, 1);
            uint32_t v[8][4], o[8][4];
#pragma unroll 1
            for (int j = 0; j <= 2 * it; j++) {
#pragma unroll
                for (int k = 0; k < 8; k++) ldsm4t(v[k], src + P1_OFF_W + (8 * j + k) * 2048);
                p1_squares(v, t);
            }
            sc2[1] = p1_exponents(t, ex, s_ex + 256, lane);
#pragma unroll 1
            for (int j = 2 * it; j >= 0; j--) {
                p1_convert<8>(o, v, ex);
#pragma unroll
                for (int k = 0; k < 8; k++) {
                    if (j) ldsm4t(v[k], src + P1_OFF_W + (8 * j - 8 + k) * 2048);
                    if (it) asm volatile("stmatrix.sync.aligned.m8n8.x4.trans.shared.b16 [%0], {%1,%2,%3,%4};\n"
                                         ::"r"(src + P1_OFF_W + (8 * j + k) * 2048), "r"(o[k][0]), "r"(o[k][1]), "r"(o[k][2]), "r"(o[k][3]) : "memory");
                }
            }
          }
        }
        asm volatile("fence.proxy.async.shared::cta;\n" ::: "memory");
        TRACEW(110 + warp, 7);
        bar_sync(6 + wg, 128);
        p1_consumer(a, sc2, sbase, wg, w, lane, zero);
        cluster_sync();
        TSTAMP(0, 30);
    }
}

constexpr int P2_B = 24576, P2_NB = 4;
constexpr int P2_A = 3072, P2_NA = 8;
constexpr int P2_XROW = C_DIM * 2;
constexpr int P2_OFF_A = P2_B * P2_NB;
constexpr int P2_OFF_X = P2_OFF_A + 3 * P2_NA * P2_A;
constexpr int P2_XHALF = 32 * P2_XROW + 64;
constexpr int P2_OFF_GRN = P2_OFF_X + 64 * P2_XROW + 128;
constexpr int P2_OFF_BIAS = P2_OFF_GRN + HID * 2;
constexpr int P2_OFF_RED = P2_OFF_BIAS + C_DIM * 4;
constexpr int P2_OFF_BAR = P2_OFF_RED + 192;
constexpr int P2_SMEM = P2_OFF_BAR + (2 * P2_NB + 6 * P2_NA + 7) * 8;
#define P2_S1 16
constexpr int P2_S2 = 32;
constexpr int P2_NCL = NUM_CTAS / 2, P2_ITEMS = NT128 / P2_NCL, P2_SHARED = NT128 - P2_ITEMS * P2_NCL;
constexpr int P2_NPOS = 6 * 48 + P2_S1;
constexpr int P2_RAW = 24;
constexpr int P2_XC = 8 * P2_XROW;
#define P2_T0 4
#define P2_SLACK 0
#define P2_RAMP 2
#define P2_LATE 88
#define P2_GATE 1
#define P2_AH 2
__device__ __forceinline__ int p2_start(int n) { return n < 0 ? 0 : n / 3 * 48 + (n % 3 == 1 ? P2_S1 : n % 3 * (P2_S2 / 2)); }
__device__ __forceinline__ int p2_tile(int cl, int n) {
    return n == 0 ? NT128 - 1 - cl : n < 0 ? NT128 - 1 - P2_NCL - (cl >> 1) : cl + P2_NCL * (n - 1);
}

#define P2_EB 2
#define P2_EX 1
__device__ __forceinline__ void p2_epilogue(uint32_t (&acc0)[48], uint32_t (&acc1)[48], uint32_t up, uint32_t sx, uint32_t sb, int zero) {
    uint32_t v[12][3][4];
    auto load = [&](int t, int j) {
        if (t >= 12) return;
        uint32_t (&w)[4] = v[t][j];
        asm volatile("ld.shared.v4.u32 {%0,%1,%2,%3}, [%4];\n" : "=r"(w[0]), "=r"(w[1]), "=r"(w[2]), "=r"(w[3])
                     : "r"((j ? sx + (j - 1) * 4 * P2_XROW : sb) + t * 64) : "memory");
    };
    auto store = [&](int t, int r) {
        const uint32_t* w = (t < 6 ? acc0 : acc1) + 8 * (t % 6) + 4 * r;
        asm volatile("st.shared.v4.u32 [%4], {%0,%1,%2,%3};\n" ::"r"(w[0]), "r"(w[1]), "r"(w[2]), "r"(w[3]), "r"(sx + t * 64 + r * 4 * P2_XROW) : "memory");
    };
#pragma unroll
    for (int t = 0; t < P2_EB; t++) load(t, 0);
#pragma unroll
    for (int t = 0; t < 2 * P2_EX; t++) load(t >> 1, 1 + (t & 1));
#pragma unroll
    for (int t = 0; t < 12; t++) {
        load(t + P2_EX, 1);
        load(t + P2_EX, 2);
        load(t + P2_EB, 0);
        uint32_t* acc = (t < 6 ? acc0 : acc1) + 8 * (t % 6);
        uint32_t y[8];
#pragma unroll
        for (int e = 0; e < 8; e++) {
            y[e] = h2_add(acc[e], v[t][0][e >> 1]);
            y[e] = pack_bf16(h_lo(y[e]), h_hi(y[e]));
        }
#pragma unroll
        for (int e = 0; e < 8; e++) acc[(e & 1) * 4 + (e >> 1)] = bf2_fma(y[e], up, v[t][1 + (e & 1)][e >> 1]);
        store(t, 0);
        store(t, 1);
        sched_break(zero);
    }
    if (zero) {
#pragma unroll
        for (int t = 0; t < 24; t++) store(t >> 1, t & 1);
    }
}

__device__ __forceinline__ void p2_unpack(uint32_t (&u)[4], uint32_t o1, uint32_t o2, uint32_t o3) {
    u[2] = o1 & ~SPARE;
    u[1] = o2 & ~SPARE;
    u[3] = o3 & ~SPARE;
    const uint32_t t = bitsel(prmt(o1, o2, 0x6341), prmt(o1, o3, 0x6240) << 3, 0x38383838u);
    u[0] = bitsel(t, prmt(o2, o3, 0x7351) << 1, 0x80808080u) & ~SPARE;
}

__device__ __forceinline__ void p2_redo_sums(int warp, int lane) {
#pragma unroll 1
    for (int s = warp; s < 96; s += 12) {
        float t[2] = {0.f, 0.f};
#pragma unroll 1
        for (int tile = blockIdx.x; tile < 2 * NT128; tile += NUM_CTAS) {
            const uint32_t* p = reinterpret_cast<const uint32_t*>(reinterpret_cast<const uint8_t*>(g_h) + (size_t)(tile >> 1) * (2 * H_TILE) +
                                                                  (s >> 1) * H_STEP + (tile & 1) * H_HALF + (s & 1) * 1536) + lane * 4;
#pragma unroll
            for (int j = 0; j < 4; j++) {
                uint32_t u[4];
                p2_unpack(u, __ldcg(p + j), __ldcg(p + j + 128), __ldcg(p + j + 256));
#pragma unroll
                for (int c = 0; c < 4; c++) t[c >> 1] += h_lo(u[c]) * h_lo(u[c]) + h_hi(u[c]) * h_hi(u[c]);
            }
        }
#pragma unroll
        for (int r = 0; r < 2; r++) {
            const int ch = s * 16 + r * 8 + (lane >> 2);
            const float f = __ldcg(&g_scale[ch]) * UNCHOP;
            atomicAdd(&g_redo[ch], t[r] * f * f);
        }
    }
    __threadfence();
    __syncwarp();
    if (lane == 0) asm volatile("red.release.gpu.global.add.u32 [%0], 1;\n" ::"l"(&g_prog[2][0]) : "memory");
    flag_wait<true>(&g_prog[2][0], 12 * NUM_CTAS);
}

__global__ void __cluster_dims__(2, 1, 1) __launch_bounds__(512, 1)
pass2_kernel(const __nv_bfloat16* __restrict__ x, const __nv_bfloat16* __restrict__ grn_g, __nv_bfloat16* __restrict__ out, int zero) {
    extern __shared__ __align__(1024) uint8_t smem[];
    const uint32_t sbase = smem_u32(smem);
    const uint32_t bar_bfull = sbase + P2_OFF_BAR, bar_bempty = bar_bfull + P2_NB * 8;
    const uint32_t bar_afull = bar_bempty + P2_NB * 8, bar_aempty = bar_afull + 3 * P2_NA * 8;
    const uint32_t bar_xfull = bar_aempty + 3 * P2_NA * 8, bar_oready = bar_xfull + 24, s_pos = bar_oready + 24;
    int tid;
    asm volatile("mov.u32 %0, %%tid.x;\n" : "=r"(tid));
    const int warp = __shfl_sync(0xffffffffu, tid >> 5, 0), lane = tid & 31;
    const uint32_t rank = cluster_rank();
    const int cl = blockIdx.x >> 1, pair = cl >> 1;
    const int half = pair < P2_SHARED, fin = half && (cl & 1);
    const int k0 = (pair + 3 * (cl & 1)) % 6 * 8;
    const bool late = blockIdx.x >= P2_LATE;
    auto wait_pos = [&](int target) {
        int v;
        while (true) {
            asm volatile("ld.volatile.shared.u32 %0, [%1];\n" : "=r"(v) : "r"(s_pos) : "memory");
            if (v >= target) break;
            SAFE_BREAK;
            __nanosleep(100);
        }
    };

    TSTAMP(1, 0);
    if (tid == 384) {
        for (int i = 0; i < P2_NB; i++) {
            mbar_init(bar_bfull + i * 8, 1);
            mbar_init(bar_bempty + i * 8, 24);
        }
        for (int i = 0; i < 3 * P2_NA; i++) {
            mbar_init(bar_afull + i * 8, 1);
            mbar_init(bar_aempty + i * 8, 4);
        }
        for (int i = 0; i < 3; i++) {
            mbar_init(bar_xfull + i * 8, 2);
            mbar_init(bar_oready + i * 8, 4);
        }
        asm volatile("st.shared.u32 [%0], 0;\n" ::"r"(s_pos) : "memory");
        asm volatile("fence.mbarrier_init.release.cluster;\n" ::: "memory");
    }
    __syncthreads();
    cluster_sync_relaxed();

    if (warp >= 12) {
        reg_dec<32>();
        if (warp == 12) {
            const uint8_t* wsrc = reinterpret_cast<const uint8_t*>(g_w2img) + rank * (P2_B / 2);
            int kb = k0;
            gdc_wait();
            if (P2_GATE) bar_sync(5, 448);
#pragma unroll 1
            for (int p = 0; p < P2_NPOS; p++) {
                const int st = p & 3;
                if (p == P2_RAW) {
                    flag_wait<true>(&g_prog[1][0], NUM_CTAS);
                    asm volatile("fence.proxy.async.global;\n" ::: "memory");
                    wsrc += sizeof(g_w2img[0]);
                }
                const int idle = (p < P2_S1 || p >= 6 * 48) + (p < P2_S2 ? !half || p >= 24 : p >= 5 * 48 + P2_S2);
                mbar_wait(bar_bempty + st * 8, (~p >> 2) & 1);
                TR2(3, p, 0);
                if (elect_one()) {
                    const int len = P2_B / 2;
                    mbar_expect_tx(bar_bfull + st * 8, 2 * len);
                    bulk_g2s_mc(sbase + st * P2_B + rank * (P2_B / 2), wsrc + kb * P2_B, len, bar_bfull + st * 8, (uint16_t)3);
                    asm volatile("st.volatile.shared.u32 [%0], %1;\n" ::"r"(s_pos), "r"(p) : "memory");
                    if (rank == 0) asm volatile("red.relaxed.gpu.global.add.u32 [%0], 1;\n" ::"l"(&g_prog[0][0]) : "memory");
                    if (idle) asm volatile("mbarrier.arrive.shared::cta.b64 _, [%0], %1;\n" ::"r"(bar_bempty + st * 8), "r"(8 * idle) : "memory");
                }
                __syncwarp();
                if (++kb == 48) kb = 0;
            }
            mbar_wait(bar_bempty, 1);
            if (lane == 0) mbar_arrive(bar_bfull);
        } else if (warp == 13) {
            const int w = lane < 3 ? lane : 0;
            const uint32_t dst0 = sbase + P2_OFF_A + w * P2_NA * P2_A;
            const uint32_t bf = bar_afull + w * P2_NA * 8, be = bar_aempty + w * P2_NA * 8;
            int n = (w == 2 && half ? -1 : w) - 3, left = 0, u = 0, c = 0;
            const uint8_t* src = nullptr;
            bool act = lane < 3;
            gdc_wait();
            if (P2_GATE) bar_sync(5, 448);
            while (__any_sync(0xffffffffu, act)) {
                if (left == 0) {
                    n += 3;
                    left = n >= P2_ITEMS ? -1 : n < 0 ? 24 : 48;
                    u = (k0 + p2_start(n)) % 48;
                    src = reinterpret_cast<const uint8_t*>(g_h) + (size_t)p2_tile(cl, n) * (2 * H_TILE) + rank * H_HALF + u * H_STEP;
                }
                bool ok = act && mbar_test(be + ((c - 1) & 7) * 8, (~c >> 3) & 1);
                if (__any_sync(0xffffffffu, act && c < 16)) {
                    int v;
                    asm volatile("ld.volatile.shared.u32 %0, [%1];\n" : "=r"(v) : "r"(s_pos) : "memory");
                    ok = ok && c <= (n <= 0 ? 2 * v - P2_RAMP : c >= 16 ? c : v - p2_start(n) + 8);
                }
                if (ok) {
                    const int st = c & 7;
                    if (left > 0) {
                        mbar_expect_tx(bf + st * 8, P2_A);
                        bulk_g2s(dst0 + st * P2_A, src, P2_A, bf + st * 8);
                    } else {
                        mbar_arrive(bf + st * 8);
                        act = false;
                    }
                    src += H_STEP;
                    if (++u == 48) { u = 0; src -= 48 * H_STEP; }
                    c++;
                    left--;
                }
                SAFE_BREAK;
                if (!__any_sync(0xffffffffu, ok)) __nanosleep(100);
            }
        } else if (warp == 14) {
            const uint32_t sx = sbase + P2_OFF_X;
            size_t o = 0;
            int wp = 0;
            uint32_t par = 0;
            if (fin) {
#pragma unroll 1
                for (int c = lane * 16; c < 64 * P2_XROW + 128; c += 512) asm volatile("st.shared.v4.u32 [%0], {0, 0, 0, 0};\n" ::"r"(sx + c) : "memory");
                __syncwarp();
            }
            if (late) wait_pos(6);
#pragma unroll 1
            for (int n = -half; n <= P2_ITEMS; n++) {
                const int w = (n + 3) % 3, end = p2_start(n) + 48;
                const size_t on = (size_t)(2 * p2_tile(cl, n) + rank) * (64 * C_DIM * 2);
                const uint32_t xf = bar_xfull + w * 8;
                bool st = n + half > 0;
                const bool ld = n < P2_ITEMS && !(n < 0 && fin);
                if (n == P2_ITEMS - 1 && lane == 0)
                    asm volatile("cp.async.bulk.prefetch.L2.global [%0], %1;\n" ::"l"(reinterpret_cast<const uint8_t*>(x) + on), "r"(64 * P2_XROW) : "memory");
                if (st) {
                    mbar_wait(bar_oready + wp * 8, (par >> wp) & 1);
                    par ^= 1u << wp;
                }
                if (lane == 0) {
                    if (n < P2_ITEMS) mbar_expect_tx(xf, ld ? 64 * C_DIM * 2 : 0);
                    const int t0 = (n ? p2_start(n - 1) + 48 : P2_S2) + P2_T0, dt = end - t0;
                    int t = st && n < P2_ITEMS - 1 ? 16 * t0 : -4096;
                    if ((n == 0 && half) || n >= P2_ITEMS - 1) {
                        if (fin && n == 0) {
                            flag_wait<true>(&g_half[pair][rank], 1);
                            asm volatile("fence.proxy.async.global;\n" ::: "memory");
                        }
#pragma unroll 1
                        for (int c = 0; c < 2; c++) {
                            uint8_t* dst = reinterpret_cast<uint8_t*>(out) + o + c * 32 * P2_XROW;
                            if (!fin || n) bulk_s2g(dst, sx + c * P2_XHALF, 32 * P2_XROW);
                            else asm volatile("cp.reduce.async.bulk.global.shared::cta.bulk_group.add.noftz.bf16 [%0], [%1], %2;\n"
                                              ::"l"(dst), "r"(sx + c * P2_XHALF), "r"(32 * P2_XROW) : "memory");
                        }
                        asm volatile("cp.async.bulk.commit_group;\n" ::: "memory");
                        if (!fin && n == 0) {
                            asm volatile("cp.async.bulk.wait_group 0;\nfence.proxy.async.global;\n" ::: "memory");
                            asm volatile("st.release.gpu.global.u32 [%0], 1;\n" ::"l"(&g_half[pair][rank]) : "memory");
                        }
                        st = false;
                    }
#pragma unroll 1
                    for (int c = 0; c < 64 * P2_XROW; c += P2_XC, t += 2 * dt) {
                        const uint32_t sp = sx + c + (c >= 32 * P2_XROW ? 64 : 0);
                        wait_pos(t >> 4);
                        if (st) bulk_s2g(reinterpret_cast<uint8_t*>(out) + o + c, sp, P2_XC);
                        asm volatile("cp.async.bulk.commit_group;\n" ::: "memory");
                        if (ld) {
                            wait_pos((t + dt) >> 4);
                            asm volatile("cp.async.bulk.wait_group.read 0;\n" ::: "memory");
                            bulk_g2s(sp, reinterpret_cast<const uint8_t*>(x) + on + c, P2_XC, xf);
                        }
                    }
                    if (rank == 0 && n > 0 && n < P2_ITEMS - 1) flag_wait<false>(&g_prog[0][0], P2_NCL * (end + P2_SLACK));
                    if (n < P2_ITEMS) mbar_arrive(xf);
                }
                __syncwarp();
                o = on;
                wp = w;
            }
            asm volatile("cp.async.bulk.wait_group 0;\n" ::: "memory");
        } else if (blockIdx.x == 120) {
            gdc_wait();
            for (int i = lane; i < (LN_RING + 3) * 2; i += 32) (&g_flag[0][0][0])[i * 8] = 0;
            if (lane == 0) g_epoch++;
        }
        __syncwarp();
        cluster_sync();
    } else {
        reg_inc<160>();
        const int wg = warp >> 2, w = warp & 3, g = lane >> 2, q = lane & 3;
        const uint32_t sx = sbase + P2_OFF_X + (g & 1) * P2_XHALF + (w * 8 + (g >> 1)) * P2_XROW + q * 16;
        const uint32_t af = bar_afull + wg * P2_NA * 8;
        const uint32_t s_a = sbase + P2_OFF_A + wg * P2_NA * P2_A + (lane >> 3) * 512 + (lane & 7) * 64 + ((w ^ ((lane & 7) >> 1)) << 4);
        uint32_t acc0[48], acc1[48], up;
        uint4 a[2][2];

        __nv_bfloat16 gg[4];
#pragma unroll
        for (int i = 0; i < 4; i++) gg[i] = grn_g[tid + 384 * i];
#pragma unroll 1
        for (int it = late; it < 2; it++) {
            float* s_red = reinterpret_cast<float*>(smem + P2_OFF_RED);
            float gx[7], part = 0.f;
            if (it) {
                TSTAMP(1, 27);
                gdc_wait();
                TSTAMP(1, 1);
            }
            float gy[7];
#pragma unroll
            for (int i = 0; i < 7; i++) {
                const float* p = &g_sums[0][i < 5 ? tid + 384 * i : HID + C_DIM + i - 5];
                asm volatile("ld.global.cg.f32 %0, [%1];\n" : "=f"(gx[i]) : "l"(p) : "memory");
                asm volatile("ld.global.cg.f32 %0, [%1];\n" : "=f"(gy[i]) : "l"(p + HID + 512) : "memory");
            }
            if (P2_GATE && it) bar_arrive(5, 448);
            const float bias = gx[4] + gy[4];
            const float gs = w2_scale(__float_as_uint(gx[5]) | __float_as_uint(gy[5]));
            if (it && gx[6] + gy[6] != 0.f) {
                p2_redo_sums(warp, lane);
#pragma unroll
                for (int i = 0; i < 4; i++) {
                    gx[i] = __ldcg(&g_redo[tid + 384 * i]);
                    gy[i] = 0.f;
                }
            }
            float mg = 0.f;
#pragma unroll
            for (int i = 0; i < 4; i++) {
                gx[i] = gx[i] + gy[i];
                gx[i] = __fsqrt_rn(gx[i] * (HSCALE * HSCALE) + 1e-6f);
                part += gx[i];
                gx[i] *= __bfloat162float(gg[i]);
                mg = fmaxf(mg, fabsf(gx[i]));
            }
#pragma unroll
            for (int o = 16; o > 0; o >>= 1) part += __shfl_xor_sync(0xffffffffu, part, o);
            const uint32_t mgw = __reduce_max_sync(0xffffffffu, __float_as_uint(mg));
            const uint32_t mbw = __reduce_max_sync(0xffffffffu, __float_as_uint(fabsf(bias)));
            TSTAMP(1, 26);
            if (lane == 0) *reinterpret_cast<float4*>(s_red + warp * 4) = make_float4(part, __uint_as_float(mgw), __uint_as_float(mbw), 0.f);
            bar_sync(1, 384);
            float tot = 0.f, mb = 0.f;
#pragma unroll
            for (int i = 0; i < 12; i++) {
                const float4 t = *reinterpret_cast<const float4*>(s_red + i * 4);
                tot += t.x;
                mg = fmaxf(mg, t.y);
                mb = fmaxf(mb, t.z);
            }
            const float inv = 1.0f / (tot * (1.0f / HID) + 1e-6f);
            const uint32_t ej = min((__float_as_uint(fmaxf(fmaf(mg, inv, 1.0f) * (HSCALE * UNCHOP), mb * gs * 0x1p-13f)) >> 23) + 1, 250u);
            const float dn = __uint_as_float((254u - ej) << 23);
            up = min(ej + 127u - (__float_as_uint(gs) >> 23), 254u) * 0x00800080u;
            reinterpret_cast<uint16_t*>(smem + P2_OFF_BIAS + C_DIM * 2)[tid] = 0;
            *reinterpret_cast<__half*>(smem + P2_OFF_BIAS + (tid >> 5) * 64 + (tid & 6) * 8 + (tid & 24) / 2 + (tid & 1) * 2) = __float2half_rn(bias * gs * dn);
#pragma unroll
            for (int i = 0; i < 4; i++) {
                const int k = tid + 384 * i;
                *reinterpret_cast<__half*>(smem + P2_OFF_GRN + (k >> 4) * 32 + (k & 6) * 4 + (k & 8) / 2 + (k & 1) * 2) =
                    __float2half_rn(fmaf(gx[i], inv, 1.0f) * (HSCALE * UNCHOP * dn));
            }
            TSTAMP(1, 25);
            bar_sync(1, 384);
        }
        TSTAMP(1, 28);
        if (wg == 1) {
            constexpr int N = sizeof(g_w2img[0]) / 16, PER = (N + NUM_CTAS - 1) / NUM_CTAS;
            uint4 v[5];
#pragma unroll
            for (int i = 0; i < 5; i++) v[i] = __ldcg(&g_w2img[0][min(blockIdx.x * PER + (tid & 127) + 128 * i, N - 1)]);
#pragma unroll
            for (int i = 0; i < 5; i++) {
                const int j = min(blockIdx.x * PER + (tid & 127) + 128 * i, N - 1);
                const uint32_t* t = reinterpret_cast<const uint32_t*>(smem + P2_OFF_GRN + (j / 768) * 32 + (j & 8) / 2);
                auto sc = [&](uint32_t u, int e) { return (h2_mul(u, t[2 * e]) + 0x00040004u) & 0xfff8fff8u; };
                g_w2img[1][j] = make_uint4(sc(v[i].x, 0), sc(v[i].y, 1), sc(v[i].z, 2), sc(v[i].w, 3));
            }
            asm volatile("fence.proxy.async.global;\n" ::: "memory");
            bar_sync(2, 128);
            if (tid == 128) asm volatile("fence.acq_rel.gpu;\nred.release.gpu.global.add.u32 [%0], 1;\n" ::"l"(&g_prog[1][0]) : "memory");
        }

        const int who = __shfl_sync(0xffffffffu, lane == 2 ? 0 : lane < 2 ? 1 : 2, lane);
        const uint32_t rel0 = who ? mapa(bar_bempty, lane & 1) : mapa(bar_aempty + wg * P2_NA * 8, rank), rel1 = rel0 + (who ? 0 : 32);
        auto publish = [&]() {
            asm volatile("fence.proxy.async.shared::cta;\n" ::: "memory");
            __syncwarp();
            if (who == 0) mbar_arrive(bar_oready + wg * 8);
        };
        bool ok_a, pend = false;
        uint32_t pa = 0, s_t;
        auto fetch = [&](int j, bool raw) {
            uint32_t o[6], u0[4], u1[4];
            uint2 t0 = make_uint2(0, 0), t1 = t0;
            if (raw) {
                asm volatile("ld.shared.v2.u32 {%0,%1}, [%2];\n" : "=r"(t0.x), "=r"(t0.y) : "r"(s_t + j * 64) : "memory");
                asm volatile("ld.shared.v2.u32 {%0,%1}, [%2];\n" : "=r"(t1.x), "=r"(t1.y) : "r"(s_t + j * 64 + 32) : "memory");
            }
            const bool ok_b = mbar_test(bar_bfull + (j & 3) * 8, j >> 2);
            if (j == 7) pa ^= 1;
            ok_a = mbar_test(af + ((j + 1) & 7) * 8, pa);
            asm volatile("ldmatrix.sync.aligned.m8n8.x4.trans.shared.b16 {%0,%1,%2,%3}, [%4];\n"
                         : "=r"(o[0]), "=r"(o[1]), "=r"(o[2]), "=r"(o[3]) : "r"(s_a + j * P2_A) : "memory");
            asm volatile("ldmatrix.sync.aligned.m8n8.x2.trans.shared.b16 {%0,%1}, [%2];\n"
                         : "=r"(o[4]), "=r"(o[5]) : "r"(s_a + j * P2_A + 2048) : "memory");
            p2_unpack(u0, o[0], o[1], o[2]);
            p2_unpack(u1, o[3], o[4], o[5]);
            if (raw) {
                u0[0] = h2_mul(u0[0], t0.x); u0[1] = h2_mul(u0[1], t0.x); u0[2] = h2_mul(u0[2], t0.y); u0[3] = h2_mul(u0[3], t0.y);
                u1[0] = h2_mul(u1[0], t1.x); u1[1] = h2_mul(u1[1], t1.x); u1[2] = h2_mul(u1[2], t1.y); u1[3] = h2_mul(u1[3], t1.y);
            }
            a[j & 1][0] = make_uint4(u0[0], u0[1], u0[2], u0[3]);
            a[j & 1][1] = make_uint4(u1[0], u1[1], u1[2], u1[3]);
            if (!ok_b) mbar_wait(bar_bfull + (j & 3) * 8, j >> 2);
        };
        auto table = [&](int pos) { s_t = sbase + P2_OFF_GRN + q * 8 + (k0 + pos) % 48 * 64; };
        const uint32_t db0 = (uint32_t)make_desc(sbase, 128, 256);
        auto block8 = [&](bool raw, int pos, int thr0, int mode) {
#pragma unroll
            for (int j = 0; j < 8; j++) {
                const uint32_t db = db0 + (j & 3) * (P2_B / 16);
                if (j == 8 - P2_AH && mode == 1) bar_sync(4, 384);
                TR2(wg, pos + j, 0);
                wg_fence();
                mma_rs_n192(acc0, a[j & 1][0], db);
                mma_rs_n192(acc1, a[j & 1][0], db + 384);
                mma_rs_n192(acc0, a[j & 1][1], db + 768);
                mma_rs_n192(acc1, a[j & 1][1], db + 768 + 384);
                wg_commit();
                if (j == 7 && mode == 2) bar_arrive(4, 384);
                const uint32_t rel = ((j - 1) & 4 ? rel1 : rel0) + ((j - 1) & 3) * 8;
                TR2(wg, pos + j, 1);
                wg_wait<1>();
                TR2(wg, pos + j, 2);
                if (who < (j ? 2 : thr0)) mbar_arrive_cluster(rel);
                if (!ok_a) {
                    if (j == 0 && pend) { publish(); pend = false; }
                    mbar_wait(af + ((j + 1) & 7) * 8, pa);
                }
                TR2(wg, pos + j, 3);
                if (raw && j == 7) table(pos + 8);
                fetch((j + 1) & 7, raw && (j < 7 || pos + 8 < P2_RAW));
            }
        };
        int n = wg == 2 && half ? -1 : wg, pos = p2_start(n);
        uint32_t px = 0;
        wait_pos(pos);
        mbar_wait(af, 0);
        table(pos);
        fetch(0, pos < P2_RAW);
#pragma unroll 1
        for (;; n += 3) {
            TSTAMP(1, 2 + n);
            const int end = pos + (n < 0 ? 24 : 48);
#pragma unroll
            for (int i = 0; i < 48; i += 2) {
                asm volatile("mov.b64 {%0, %1}, 0;\n" : "=r"(acc0[i]), "=r"(acc0[i + 1]));
                asm volatile("mov.b64 {%0, %1}, 0;\n" : "=r"(acc1[i]), "=r"(acc1[i + 1]));
            }
            int thr = 1;
#pragma unroll 1
            for (; pos < P2_RAW; pos += 8, thr = 2) block8(true, pos, thr, 0);
#pragma unroll 1
            for (; pos < end; pos += 8, thr = 2) {
                const int e = pos + 8, r = e % 48;
                block8(false, pos, thr, e < 48 || e > 256 || (r != 0 && r != P2_S1 && r != P2_S2) ? 0 : e == end ? 2 : 1);
            }
            TR2(wg, pos - 1, 4);
            wg_wait<0>();
            TR2(wg, pos - 1, 5);
            if (who == 1) mbar_arrive_cluster(rel0 + 24);
            mbar_wait(bar_xfull + wg * 8, px);
            TR2(wg, pos - 1, 6);
            px ^= 1;
            __syncwarp();
            p2_epilogue(acc0, acc1, up, sx, sbase + P2_OFF_BIAS + q * 16 + (n < 0 && fin ? C_DIM * 2 : 0), zero);
            TR2(wg, pos - 1, 7);
            if (n + 3 >= P2_ITEMS) { publish(); break; }
            if (n < 0) {
                publish();
                pos = P2_S2;
                wait_pos(pos);
                mbar_wait(bar_bfull, 0);
            } else {
                pend = true;
                ok_a = false;
            }
        }
        TSTAMP(1, 29);
        cluster_sync();
        TSTAMP(1, 30);
    }
}

}

extern "C" void kernel_launch(void* const* d_in, const int* in_sizes, int n_in, void* d_out, int out_size) {
    const __nv_bfloat16* x = (const __nv_bfloat16*)d_in[0];
    const __nv_bfloat16* dw = (const __nv_bfloat16*)d_in[1];
    const __nv_bfloat16* w1 = (const __nv_bfloat16*)d_in[2];
    const __nv_bfloat16* w2 = (const __nv_bfloat16*)d_in[3];
    const __nv_bfloat16* grn_g = (const __nv_bfloat16*)d_in[4];
    const __nv_bfloat16* grn_b = (const __nv_bfloat16*)d_in[5];
    __nv_bfloat16* out = (__nv_bfloat16*)d_out;

    cudaFuncSetAttribute(pass1_kernel, cudaFuncAttributeMaxDynamicSharedMemorySize, P1_SMEM);
    cudaFuncSetAttribute(pass2_kernel, cudaFuncAttributeMaxDynamicSharedMemorySize, P2_SMEM);

    typedef CUresult (*EncodeFn)(CUtensorMap*, CUtensorMapDataType, cuuint32_t, void*, const cuuint64_t*, const cuuint64_t*,
                                 const cuuint32_t*, const cuuint32_t*, CUtensorMapInterleave, CUtensorMapSwizzle,
                                 CUtensorMapL2promotion, CUtensorMapFloatOOBfill);
    static EncodeFn encode = nullptr;
    if (!encode) {
        cudaDriverEntryPointQueryResult qres;
        cudaGetDriverEntryPoint("cuTensorMapEncodeTiled", (void**)&encode, cudaEnableDefault, &qres);
    }
    CUtensorMap wmap;
    const cuuint64_t gdim[2] = {HID, C_DIM};
    const cuuint64_t gstr[1] = {HID * 2};
    const cuuint32_t box[2] = {64, 192}, estr[2] = {1, 1};
    CUresult er = encode(&wmap, CU_TENSOR_MAP_DATA_TYPE_BFLOAT16, 2, (void*)w1, gdim, gstr, box, estr, CU_TENSOR_MAP_INTERLEAVE_NONE,
           CU_TENSOR_MAP_SWIZZLE_128B, CU_TENSOR_MAP_L2_PROMOTION_L2_128B, CU_TENSOR_MAP_FLOAT_OOB_FILL_NONE);
    if (er != CUDA_SUCCESS) printf("tensor map encode failed %d\n", (int)er);

    pass1_kernel<<<NUM_CTAS, 512, P1_SMEM>>>(wmap, x, dw, w2, grn_b, 0);

    cudaLaunchAttribute attr[1];
    attr[0].id = cudaLaunchAttributeProgrammaticStreamSerialization;
    attr[0].val.programmaticStreamSerializationAllowed = 1;
    cudaLaunchConfig_t cfg = {};
    cfg.gridDim = dim3(NUM_CTAS);
    cfg.stream = 0;
    cfg.attrs = attr;
    cfg.numAttrs = 1;
    cfg.blockDim = dim3(512);
    cfg.dynamicSmemBytes = P2_SMEM;
    cudaLaunchKernelEx(&cfg, pass2_kernel, x, grn_g, out, 0);
}
```

```cpp
#include <cuda.h>
#include <cuda_runtime.h>
#include <cuda_bf16.h>
#include <cuda_fp16.h>
#include <stdint.h>
#include <stdio.h>

namespace {

constexpr int M_TOTAL = 384 * 384;
constexpr int C_DIM   = 384;
constexpr int HID     = 1536;
constexpr int NT128   = M_TOTAL / 128;
constexpr int NUM_CTAS = 132;

constexpr int NGRP = 22, GRP_CTAS = 6;
constexpr int LN_STEP = NUM_CTAS / 4, LN_RING = 2 * LN_STEP;
constexpr int LN_TILE = 128 * C_DIM * 2;
constexpr int H_TILE = 64 * HID * 3 / 2;
constexpr int H_HALF = 3072, H_STEP = 6144;

__device__ __align__(1024) uint4 g_h[(size_t)M_TOTAL * HID * 3 / 32];
__device__ __align__(1024) uint4 g_ln[LN_RING * LN_TILE / 16];
__device__ __align__(1024) uint4 g_w2img[2][HID * C_DIM * 2 / 16];
__device__ __align__(16) float g_sums[2][HID + 512];
__device__ float g_scale[HID];
__device__ float g_redo[HID];
__device__ unsigned g_epoch;
__device__ __align__(128) unsigned g_prog[3][32];
__device__ __align__(128) unsigned g_half[32][2];
__device__ unsigned g_flag[LN_RING + 3][2][8];
#define TSTAMP(k, i)
#define TRACE(wg, pos, i)
#define TRACEW(pos, i)

#define TR2(wg, pos, i)
__host__ __device__ __forceinline__ int perm32(int n) {
    return (n & ~31) | (((n >> 1) & 3) << 3) | (((n >> 3) & 3) << 1) | (n & 1);
}

__device__ __forceinline__ uint32_t smem_u32(const void* p) { return (uint32_t)__cvta_generic_to_shared(p); }

__device__ __forceinline__ void mbar_init(uint32_t bar, uint32_t count) {
    asm volatile("mbarrier.init.shared::cta.b64 [%0], %1;\n" ::"r"(bar), "r"(count) : "memory");
}
__device__ __forceinline__ void mbar_expect_tx(uint32_t bar, uint32_t bytes) {
    asm volatile("mbarrier.arrive.expect_tx.shared::cta.b64 _, [%0], %1;\n" ::"r"(bar), "r"(bytes) : "memory");
}
__device__ __forceinline__ void mbar_arrive(uint32_t bar) {
    asm volatile("mbarrier.arrive.shared::cta.b64 _, [%0];\n" ::"r"(bar) : "memory");
}
__device__ __forceinline__ void mbar_arrive_cluster(uint32_t bar_cluster_addr) {
    asm volatile("mbarrier.arrive.shared::cluster.b64 _, [%0];\n" ::"r"(bar_cluster_addr) : "memory");
}
#define SAFE_BREAK
__device__ __forceinline__ void mbar_wait(uint32_t bar, uint32_t parity) {
    asm volatile(
        "{\n"
        ".reg .pred p;\n"
        "LAB_WAIT:\n"
        "mbarrier.try_wait.parity.shared::cta.b64 p, [%0], %1;\n"
        "@!p bra LAB_WAIT;\n"
        "}\n" ::"r"(bar), "r"(parity) : "memory");
}
__device__ __forceinline__ bool mbar_test(uint32_t bar, uint32_t parity) {
    uint32_t ok;
    asm volatile("{\n.reg .pred p;\n"
                 "mbarrier.test_wait.parity.shared::cta.b64 p, [%1], %2;\n"
                 "selp.u32 %0, 1, 0, p;\n}\n" : "=r"(ok) : "r"(bar), "r"(parity) : "memory");
    return ok != 0;
}
__device__ __forceinline__ uint32_t mapa(uint32_t addr, uint32_t rank) {
    uint32_t r;
    asm volatile("mapa.shared::cluster.u32 %0, %1, %2;\n" : "=r"(r) : "r"(addr), "r"(rank));
    return r;
}
__device__ __forceinline__ void bulk_g2s(uint32_t dst, const void* src, uint32_t bytes, uint32_t bar) {
    asm volatile("cp.async.bulk.shared::cluster.global.mbarrier::complete_tx::bytes [%0], [%1], %2, [%3];\n"
                 ::"r"(dst), "l"(src), "r"(bytes), "r"(bar) : "memory");
}
__device__ __forceinline__ void bulk_g2s_mc(uint32_t dst, const void* src, uint32_t bytes, uint32_t bar, uint16_t mask) {
    asm volatile("cp.async.bulk.shared::cluster.global.mbarrier::complete_tx::bytes.multicast::cluster [%0], [%1], %2, [%3], %4;\n"
                 ::"r"(dst), "l"(src), "r"(bytes), "r"(bar), "h"(mask) : "memory");
}
__device__ __forceinline__ void tma2(uint32_t dst, const CUtensorMap* map, int c0, int c1, uint32_t bar) {
    asm volatile("cp.async.bulk.tensor.2d.shared::cluster.global.tile.mbarrier::complete_tx::bytes [%0], [%1, {%2, %3}], [%4];\n"
                 ::"r"(dst), "l"(map), "r"(c0), "r"(c1), "r"(bar) : "memory");
}
template <bool ACQ>
__device__ __forceinline__ uint32_t flag_wait(const unsigned* p, unsigned target) {
    unsigned v, n = 0;
    do {
        if (ACQ) asm volatile("ld.acquire.gpu.global.u32 %0, [%1];\n" : "=r"(v) : "l"(p) : "memory");
        else asm volatile("ld.relaxed.gpu.global.u32 %0, [%1];\n" : "=r"(v) : "l"(p) : "memory");
        n++;
    } while (v < target);
    return n == 1;
}
__device__ __forceinline__ void ldsm4t(uint32_t (&r)[4], uint32_t addr) {
    asm volatile("ldmatrix.sync.aligned.m8n8.x4.trans.shared.b16 {%0,%1,%2,%3}, [%4];\n"
                 : "=r"(r[0]), "=r"(r[1]), "=r"(r[2]), "=r"(r[3]) : "r"(addr) : "memory");
}
__device__ __forceinline__ void bulk_s2g(void* dst, uint32_t src, uint32_t bytes) {
    asm volatile("cp.async.bulk.global.shared::cta.bulk_group [%0], [%1], %2;\n" ::"l"(dst), "r"(src), "r"(bytes) : "memory");
}
__device__ __forceinline__ void cluster_sync() {
    asm volatile("barrier.cluster.arrive.aligned;\nbarrier.cluster.wait.aligned;\n" ::: "memory");
}
__device__ __forceinline__ void cluster_sync_relaxed() {
    asm volatile("barrier.cluster.arrive.relaxed.aligned;\nbarrier.cluster.wait.aligned;\n" ::: "memory");
}
#define END_SYNC cluster_sync_relaxed
__device__ __forceinline__ void gdc_wait() { asm volatile("griddepcontrol.wait;\n" ::: "memory"); }
__device__ __forceinline__ void gdc_launch() { asm volatile("griddepcontrol.launch_dependents;\n" ::: "memory"); }
__device__ __forceinline__ uint32_t cluster_rank() {
    uint32_t r;
    asm volatile("mov.u32 %0, %%cluster_ctarank;\n" : "=r"(r));
    return r;
}
__device__ __forceinline__ bool elect_one() {
    uint32_t pred;
    asm volatile("{\n.reg .pred p;\nelect.sync _|p, 0xffffffff;\nselp.u32 %0, 1, 0, p;\n}\n" : "=r"(pred));
    return pred != 0;
}
__device__ __forceinline__ void wg_fence() { asm volatile("wgmma.fence.sync.aligned;\n" ::: "memory"); }
__device__ __forceinline__ void wg_commit() { asm volatile("wgmma.commit_group.sync.aligned;\n" ::: "memory"); }
template <int N> __device__ __forceinline__ void wg_wait() {
    asm volatile("wgmma.wait_group.sync.aligned %0;\n" ::"n"(N) : "memory");
}
template <int R> __device__ __forceinline__ void reg_inc() { asm volatile("setmaxnreg.inc.sync.aligned.u32 %0;\n" ::"n"(R)); }
template <int R> __device__ __forceinline__ void reg_dec() { asm volatile("setmaxnreg.dec.sync.aligned.u32 %0;\n" ::"n"(R)); }
__device__ __forceinline__ void bar_sync(int id, int n) { asm volatile("bar.sync %0, %1;\n" ::"r"(id), "r"(n) : "memory"); }
__device__ __forceinline__ void bar_arrive(int id, int n) { asm volatile("bar.arrive %0, %1;\n" ::"r"(id), "r"(n) : "memory"); }

__device__ __forceinline__ uint64_t make_desc(uint32_t saddr, uint32_t lbo, uint32_t sbo) {
    return (uint64_t)((saddr & 0x3FFFF) >> 4) | ((uint64_t)(lbo >> 4) << 16) | ((uint64_t)(sbo >> 4) << 32);
}

__device__ __forceinline__ void stg128_cs(void* p, uint32_t a, uint32_t b, uint32_t c, uint32_t d) {
#define H_ST "st.global.cs.v4.u32"
    asm volatile(H_ST " [%0], {%1,%2,%3,%4};\n" ::"l"(p), "r"(a), "r"(b), "r"(c), "r"(d) : "memory");
}
__device__ __forceinline__ uint32_t pack_bf16(float lo, float hi) {
    uint32_t r;
    asm("cvt.rn.bf16x2.f32 %0, %1, %2;\n" : "=r"(r) : "f"(hi), "f"(lo));
    return r;
}
__device__ __forceinline__ float bf_lo(uint32_t v) { return __uint_as_float(v << 16); }
__device__ __forceinline__ float bf_hi(uint32_t v) { return __uint_as_float(v & 0xffff0000u); }
__device__ __forceinline__ uint32_t bf2_mul(uint32_t a, uint32_t b) {
    uint32_t r;
    asm("mul.rn.bf16x2 %0, %1, %2;\n" : "=r"(r) : "r"(a), "r"(b));
    return r;
}
__device__ __forceinline__ uint32_t bf2_fma(uint32_t a, uint32_t b, uint32_t c) {
    uint32_t r;
    asm("fma.rn.bf16x2 %0, %1, %2, %3;\n" : "=r"(r) : "r"(a), "r"(b), "r"(c));
    return r;
}
__device__ __forceinline__ uint32_t bf2_add(uint32_t a, uint32_t b) {
    uint32_t r;
    asm("add.rn.bf16x2 %0, %1, %2;\n" : "=r"(r) : "r"(a), "r"(b));
    return r;
}
__device__ __forceinline__ uint32_t h2_mul(uint32_t a, uint32_t b) {
    uint32_t r;
    asm("mul.rn.f16x2 %0, %1, %2;\n" : "=r"(r) : "r"(a), "r"(b));
    return r;
}
__device__ __forceinline__ uint32_t h2_fma(uint32_t a, uint32_t b, uint32_t c) {
    uint32_t r;
    asm("fma.rn.f16x2 %0, %1, %2, %3;\n" : "=r"(r) : "r"(a), "r"(b), "r"(c));
    return r;
}
__device__ __forceinline__ uint32_t h2_add(uint32_t a, uint32_t b) {
    uint32_t r;
    asm("add.rn.f16x2 %0, %1, %2;\n" : "=r"(r) : "r"(a), "r"(b));
    return r;
}
__device__ __forceinline__ uint32_t pack_f16(float lo, float hi) {
    uint32_t r;
    asm("cvt.rn.f16x2.f32 %0, %1, %2;\n" : "=r"(r) : "f"(hi), "f"(lo));
    return r;
}
__device__ __forceinline__ float h_lo(uint32_t v) { return __low2float(*reinterpret_cast<const __half2*>(&v)); }
__device__ __forceinline__ float h_hi(uint32_t v) { return __high2float(*reinterpret_cast<const __half2*>(&v)); }
__device__ __forceinline__ uint32_t bf2_to_h2(uint32_t v) { return (v & 0x7fff7fffu) * 7u + v; }
__device__ __forceinline__ uint32_t prmt(uint32_t a, uint32_t b, uint32_t sel) {
    uint32_t r;
    asm("prmt.b32 %0, %1, %2, %3;\n" : "=r"(r) : "r"(a), "r"(b), "r"(sel));
    return r;
}
__device__ __forceinline__ uint32_t bitsel(uint32_t a, uint32_t b, uint32_t m) {
    uint32_t r;
    asm("lop3.b32 %0, %1, %2, %3, 0xd8;\n" : "=r"(r) : "r"(a), "r"(b), "r"(m));
    return r;
}
constexpr float KAPPA = 0.3292034911525734f;
constexpr uint32_t GELU_C2 = 0x40d940d9u;
constexpr float HSCALE = 1.0f / (2.0f * KAPPA);
__device__ __forceinline__ float w2_scale(uint32_t m) { return __uint_as_float((257u - max(m >> 23, 16u)) << 23); }
__device__ __forceinline__ void sched_break(int zero) {
    asm volatile("{\n.reg .pred p;\nsetp.ne.s32 p, %0, 0;\nSB_LOOP:\n@p nanosleep.u32 1;\n@p bra SB_LOOP;\n}\n" ::"r"(zero));
}

#define ACC8(d, o) "+r"(d[o + 0]), "+r"(d[o + 1]), "+r"(d[o + 2]), "+r"(d[o + 3]), "+r"(d[o + 4]), "+r"(d[o + 5]), "+r"(d[o + 6]), "+r"(d[o + 7])

__device__ __forceinline__ void mma_rs_n128(uint32_t (&d)[32], const uint32_t (&a)[4], uint32_t desc, int scale_d) {
    asm volatile(
        "{\n.reg .pred p;\n.reg .b64 db;\nsetp.ne.b32 p, %37, 0;\nmov.b64 db, {%36, 0x40000040};\n"
        "wgmma.mma_async.sync.aligned.m64n128k16.f16.f16.f16 "
        "{%0,%1,%2,%3,%4,%5,%6,%7,%8,%9,%10,%11,%12,%13,%14,%15,"
        "%16,%17,%18,%19,%20,%21,%22,%23,%24,%25,%26,%27,%28,%29,%30,%31},"
        "{%32,%33,%34,%35}, db, p, 1, 1, 0;\n}\n"
        : ACC8(d, 0), ACC8(d, 8), ACC8(d, 16), ACC8(d, 24)
        : "r"(a[0]), "r"(a[1]), "r"(a[2]), "r"(a[3]), "r"(desc), "r"(scale_d));
}

__device__ __forceinline__ void mma_ss_n128(uint32_t (&d)[32], uint32_t da, uint32_t db, int scale_d) {
    asm volatile(
        "{\n.reg .pred p;\n.reg .b64 da, db;\nsetp.ne.b32 p, %34, 0;\nmov.b64 da, {%32, 0x40000040};\nmov.b64 db, {%33, 0x40000040};\n"
        "wgmma.mma_async.sync.aligned.m64n128k16.f16.f16.f16 "
        "{%0,%1,%2,%3,%4,%5,%6,%7,%8,%9,%10,%11,%12,%13,%14,%15,"
        "%16,%17,%18,%19,%20,%21,%22,%23,%24,%25,%26,%27,%28,%29,%30,%31},"
        "da, db, p, 1, 1, 1, 0;\n}\n"
        : ACC8(d, 0), ACC8(d, 8), ACC8(d, 16), ACC8(d, 24)
        : "r"(da), "r"(db), "r"(scale_d));
}

__device__ __forceinline__ void mma_rs_n192(uint32_t (&d)[48], const uint4& a, uint32_t db) {
    asm volatile(
        "{\n.reg .b64 db;\nmov.b64 db, {%52, 16};\n"
        "wgmma.mma_async.sync.aligned.m64n192k16.f16.f16.f16 "
        "{%0,%1,%2,%3,%4,%5,%6,%7,%8,%9,%10,%11,%12,%13,%14,%15,"
        "%16,%17,%18,%19,%20,%21,%22,%23,%24,%25,%26,%27,%28,%29,%30,%31,"
        "%32,%33,%34,%35,%36,%37,%38,%39,%40,%41,%42,%43,%44,%45,%46,%47},"
        "{%48,%49,%50,%51}, db, 1, 1, 1, 0;\n}\n"
        : ACC8(d, 0), ACC8(d, 8), ACC8(d, 16), ACC8(d, 24), ACC8(d, 32), ACC8(d, 40)
        : "r"(a.x), "r"(a.y), "r"(a.z), "r"(a.w), "r"(db));
}

#define P1_WPF 30
#define P1_PACE 1
constexpr int P1_SLOT = LN_TILE / 6, P1_NST = 6;
constexpr int P1_W = 64 * C_DIM * 2;
constexpr int P1_X = 32 * C_DIM * 2;
constexpr int P1_OFF_W = LN_TILE;
constexpr int P1_OFF_X = P1_OFF_W + 2 * P1_W;
constexpr int P1_OFF_BAR = P1_OFF_X + P1_X;
constexpr int P1_OFF_TILE = P1_OFF_BAR + (2 * P1_NST + 4 + 4 + 4) * 8;
constexpr int P1_OFF_EX = P1_OFF_TILE + 64;
constexpr int P1_OFF_DW = P1_OFF_EX + 256 * 4;
constexpr int P1_SMEM = P1_OFF_DW + C_DIM * 2;

__device__ __forceinline__ float rsqrt_fast(float x) {
    float r;
    asm("rsqrt.approx.ftz.f32 %0, %1;\n" : "=f"(r) : "f"(x));
    return r;
}
__device__ __forceinline__ float row_sum(const uint32_t (&c)[4]) {
    const uint32_t u = bf2_add(bf2_add(c[0], c[1]), bf2_add(c[2], c[3]));
    float s = bf_lo(u) + bf_hi(u);
#pragma unroll
    for (int o = 1; o < 8; o <<= 1) s += __shfl_xor_sync(0xffffffffu, s, o);
    return s;
}
__device__ __forceinline__ uint32_t pace(uint32_t bar, uint32_t off, uint32_t val, uint32_t after, int zero) {
    asm volatile(
        "{\n.reg .pred p, q;\n.reg .b32 par;\n"
        "lop3.b32 par, %4, %2, %3, 0xea;\n"
        "setp.eq.u32 q, par, 0;\n"
        "mov.pred p, 0;\n"
        "@q mbarrier.test_wait.parity.shared::cta.b64 p, [%1], par;\n"
        "selp.u32 par, 1, 0, p;\n"
        "@q mbarrier.try_wait.parity.shared::cta.b64 p, [%1], par, 1000;\n"
        "@p or.b32 %0, %0, %2;\n"
        "}\n" : "+r"(val) : "r"(bar), "r"(zero), "r"(off), "r"(after));
    return val;
}
template <int PACE, int R>
__device__ __forceinline__ void ln_rows(uint32_t (&v)[R][6][4], const uint32_t (&d)[6][4], uint32_t bar, uint32_t off, int zero,
                                        uint32_t bar_read) {
    const float inv = 1.0f / C_DIM;
    uint32_t c[R][4], nm[R];
    float e[R], r[R], er[R];
    bool big = false;
#pragma unroll
    for (int p = 0; p < R; p++) {
#pragma unroll
        for (int i = 0; i < 6; i++)
#pragma unroll
            for (int k = 0; k < 4; k++) c[p][k] = bf2_fma(v[p][i][k], d[i][k], i ? c[p][k] : 0);
        const float m = row_sum(c[p]) * inv;
        nm[p] = pack_bf16(-m, -m);
        e[p] = m + bf_lo(nm[p]);
    }
    if (bar_read) mbar_arrive(bar_read + (nm[0] & zero));
    if (PACE & 1) nm[0] = pace(bar, off, nm[0], nm[0], zero);
#pragma unroll
    for (int p = 0; p < R; p++) {
#pragma unroll
        for (int i = 0; i < 6; i++) {
#pragma unroll
            for (int k = 0; k < 4; k++) {
                v[p][i][k] = bf2_fma(v[p][i][k], d[i][k], nm[p]);
                c[p][k] = i ? bf2_fma(v[p][i][k], v[p][i][k], c[p][k]) : bf2_mul(v[p][i][k], v[p][i][k]);
            }
        }
        r[p] = KAPPA * rsqrt_fast(fmaxf(fmaf(-e[p], e[p], row_sum(c[p]) * inv), 0.f) + 1e-5f);
        er[p] = -e[p] * r[p] * 0x1p-112f;
        big |= r[p] < 0x1p-8f;
    }
    if (__any_sync(0xffffffffu, big)) {
#pragma unroll
        for (int p = 0; p < R; p++) {
            const uint32_t p2 = __float_as_uint(r[p]) & 0x7f800000u;
            r[p] = __uint_as_float((__float_as_uint(r[p]) & 0x007fffffu) | 0x3f800000u);
#pragma unroll
            for (int i = 0; i < 6; i++)
#pragma unroll
                for (int k = 0; k < 4; k++) v[p][i][k] = bf2_mul(v[p][i][k], p2 | p2 >> 16);
        }
    }
#pragma unroll
    for (int p = 0; p < R; p++) {
        uint32_t rs = pack_bf16(r[p] * 0x1p-112f, r[p] * 0x1p-112f);
        const uint32_t sh = pack_bf16(er[p], er[p]);
        if (PACE & 2) rs = pace(bar, off, rs, sh, zero);
#pragma unroll
        for (int i = 0; i < 6; i++)
#pragma unroll
            for (int k = 0; k < 4; k++) v[p][i][k] = bf2_to_h2(bf2_fma(v[p][i][k], rs, sh));
    }
}

template <int R>
__device__ __forceinline__ uint32_t gelu2(uint32_t a, uint32_t sc2) {
    uint32_t y, t;
    if (R) asm("{\n.reg .b16 l, h;\n.reg .b32 f;\nmov.b32 {l, h}, %2;\nmov.b32 f, {h, h};\nmul.rn.f16x2 %0, %1, f;\n}\n" : "=r"(y) : "r"(a), "r"(sc2));
    else asm("{\n.reg .b16 l, h;\n.reg .b32 f;\nmov.b32 {l, h}, %2;\nmov.b32 f, {l, l};\nmul.rn.f16x2 %0, %1, f;\n}\n" : "=r"(y) : "r"(a), "r"(sc2));
    asm("tanh.approx.f16x2 %0, %1;\n" : "=r"(t) : "r"(h2_mul(y, h2_fma(y, y, GELU_C2))));
    return h2_fma(a, t, a);
}
constexpr uint32_t SPARE = 0x40074007u;
constexpr float UNCHOP = 1.0023f;

__device__ __forceinline__ uint32_t p1_parity(uint32_t sbase) {
    uint32_t v;
    asm volatile("ld.shared.u32 %0, [%1];\n" : "=r"(v) : "r"(sbase + P1_OFF_TILE - 4) : "memory");
    return v;
}
__device__ __forceinline__ uint32_t p1_exponents(float (&t)[2], uint32_t (&ex)[2], uint32_t saddr, int lane) {
#pragma unroll
    for (int r = 0; r < 2; r++) {
        t[r] += __shfl_xor_sync(0xffffffffu, t[r], 1);
        t[r] += __shfl_xor_sync(0xffffffffu, t[r], 2);
        ex[r] = min(max(((__float_as_uint(193.3f * t[r]) >> 23) + 127u) >> 1, 72u), 198u);
        asm volatile("st.shared.u32 [%0], %1;\n" ::"r"(saddr + r * 32), "r"(ex[r] << 23) : "memory");
    }
    return pack_f16(__uint_as_float(min(ex[0], 142u) << 23), __uint_as_float(min(ex[1], 142u) << 23));
}
template <int N>
__device__ __forceinline__ void p1_convert(uint32_t (&o)[N][4], uint32_t (&v)[N][4], const uint32_t (&ex)[2]) {
    if (__any_sync(0xffffffffu, max(ex[0], ex[1]) > 141u)) {
#pragma unroll
        for (int k = 0; k < 4 * N; k++) v[k >> 2][k & 3] = bf2_mul(v[k >> 2][k & 3], ex[k & 1] > 141u ? 0x1f801f80u : 0x3f803f80u);
    }
#pragma unroll
    for (int k = 0; k < 4 * N; k++) {
        const uint32_t u = bf2_mul(v[k >> 2][k & 3], ((ex[k & 1] > 141u ? 206u : 142u) - ex[k & 1]) * 0x00800080u);
        asm volatile("mad.lo.u32 %0, %1, 7, %2;\n" : "=r"(o[k >> 2][k & 3]) : "r"(u & 0x7fff7fffu), "r"(u));
    }
}
template <int N>
__device__ __forceinline__ void p1_squares(const uint32_t (&v)[N][4], float (&t)[2]) {
#pragma unroll
    for (int j = 0; j < N / 2; j++) {
        const int r = j & 1, b = (j >> 1) * 4;
        uint32_t c = bf2_mul(v[b][r], v[b][r]);
#pragma unroll
        for (int k = 1; k < 8; k++) c = bf2_fma(v[b + k / 2][r + (k & 1) * 2], v[b + k / 2][r + (k & 1) * 2], c);
        t[r] += bf_lo(c) + bf_hi(c);
    }
}
__device__ __forceinline__ void p1_epilogue(const uint32_t (&acc)[2][32], const uint32_t (&sc2)[2], float (&ssq)[4], uint8_t* hp, int zero) {
    uint32_t sq[2], h[16][4];
#pragma unroll
    for (int i2 = 0; i2 < 9; i2++) {
#pragma unroll
        for (int c = 2 * i2 - 2; c < 2 * i2; c++) {
            if (c >= 0 && (c & 3)) {
                uint32_t o[4];
#pragma unroll
                for (int u = 0; u < 4; u++) {
                    const uint32_t v = h[c & 12][u];
                    o[u] = bitsel(h[c][u], (c & 3) == 2 ? prmt(v, v, 0xa381) : prmt(v >> 3, v, (c & 3) == 1 ? 0x6240 : 0xf3d1), SPARE);
                }
                stg128_cs(hp + (c >> 3) * 2 * H_STEP + ((c >> 2) & 1) * H_HALF + ((c & 3) - 1) * 512, o[0], o[1], o[2], o[3]);
            }
        }
        if (i2 < 8) {
#pragma unroll
            for (int u = 0; u < 4; u++) {
                h[2 * i2][u] = gelu2<0>(acc[i2 >> 2][8 * (i2 & 3) + 2 * u], sc2[i2 >> 2]);
                h[2 * i2 + 1][u] = gelu2<1>(acc[i2 >> 2][8 * (i2 & 3) + 2 * u + 1], sc2[i2 >> 2]);
#pragma unroll
                for (int r = 0; r < 2; r++) {
                    const uint32_t v = h[2 * i2 + r][u];
                    sq[r] = ((i2 & 3) | u) ? h2_fma(v, v, sq[r]) : h2_mul(v, v);
                }
            }
            if ((i2 & 3) == 3) {
#pragma unroll
                for (int r = 0; r < 2; r++) ssq[(i2 >> 2) * 2 + r] += h_lo(sq[r]) + h_hi(sq[r]);
            }
            sched_break(zero);
        }
    }
}
template <int WG>
__device__ __forceinline__ void p1_mma(uint32_t (&acc)[2][32], const uint32_t (&a)[24][4], uint32_t sbase, uint32_t empty_remote, int i, int lane) {
    const uint32_t bar_full = sbase + P1_OFF_BAR;
    const uint32_t db = (uint32_t)make_desc(sbase, 16, 1024), da = db + (P1_OFF_W + WG * P1_W) / 16;
    if (WG == 0) mbar_wait(bar_full, i & 1);
    bar_sync(1 + WG, 256);
    TRACE(WG, i, 1);
    wg_fence();
#pragma unroll
    for (int k = 0; k < 24; k++) {
        if (WG == 0 && k && k % 4 == 0) mbar_wait(bar_full + (k >> 2) * 8, i & 1);
        mma_rs_n128(acc[0], a[k], db + (k >> 2) * 1024 + (k & 3) * 2, k != 0);
        mma_ss_n128(acc[1], da + k * 128, db + (k >> 2) * 1024 + (k & 3) * 2, k != 0);
        if (k == 23) bar_arrive(2 - WG, 256);
        if (k == 23 || (WG == 1 && k % 4 == 3)) wg_commit();
        if (WG == 1 && k % 4 == 3 && k > 3) {
            wg_wait<1>();
            if (lane < 2) mbar_arrive_cluster(empty_remote + ((k >> 2) - 1) * 8);
        }
    }
    TRACE(WG, i, 2);
    wg_wait<0>();
    if (WG == 1 && lane < 2) mbar_arrive_cluster(empty_remote + 5 * 8);
}
__device__ __forceinline__ void p1_consumer(const uint32_t (&a)[24][4], const uint32_t (&sc2)[2], uint32_t sbase, int WG, int w, int lane, int zero) {
    const uint32_t bar_full = sbase + P1_OFF_BAR, bar_empty = bar_full + P1_NST * 8;
    const uint32_t empty_remote = mapa(bar_empty, lane & 1);
    const uint32_t bar_pace = bar_empty + P1_NST * 8 + 32 + w * 8;
    const int g = lane >> 2, q = lane & 3, cb = (blockIdx.x % GRP_CTAS) * 4 + WG * 2;
    uint32_t acc[2][32];
    float ssq[4] = {0.f, 0.f, 0.f, 0.f};
    TSTAMP(0, 1);

    uint8_t* hp = reinterpret_cast<uint8_t*>(g_h) + ((cb * 2 + (w >> 1)) * H_STEP + (w & 1) * 1536) + g * 64 + (q ^ (g >> 1)) * 16;
    int i = 0;
#pragma unroll 1
    for (;; i++) {
        TRACE(WG, i, 0);
        if (WG == 0) p1_mma<0>(acc, a, sbase, empty_remote, i, lane);
        else p1_mma<1>(acc, a, sbase, empty_remote, i, lane);
        TRACE(WG, i, 4);
        uint32_t step, more;
        asm volatile("ld.shared.v2.u32 {%0, %1}, [%2];\n" : "=r"(step), "=r"(more) : "r"(sbase + P1_OFF_TILE + (i & 3) * 16) : "memory");
        hp += step;
        p1_epilogue(acc, sc2, ssq, hp, zero);
        if (lane == 0) mbar_arrive(bar_pace);
        if (!more) break;
    }
    TSTAMP(0, 21);
    if (WG == 0) bar_sync(1, 256);
#pragma unroll
    for (int r = 0; r < 4; r++) {
        const int ch = (r >> 1) * 64 + w * 16 + (r & 1) * 8 + g;
        ssq[r] += __shfl_xor_sync(0xffffffffu, ssq[r], 1);
        ssq[r] += __shfl_xor_sync(0xffffffffu, ssq[r], 2);
        float f;
        asm volatile("ld.shared.f32 %0, [%1];\n" : "=f"(f) : "r"(sbase + P1_OFF_EX + (WG * 128 + ch) * 4) : "memory");
        if (q == 0) {
            float* sums = g_sums[p1_parity(sbase)];
            atomicAdd(&sums[cb * 64 + ch], ssq[r] * f * f);
            g_scale[cb * 64 + ch] = f;
            if (ssq[r] < (i + 1) * 0x1p-12f) sums[HID + C_DIM + 1] = 1.f;
        }
    }
}

__global__ void __cluster_dims__(2, 1, 1) __launch_bounds__(512, 1)
pass1_kernel(const __grid_constant__ CUtensorMap wmap, const __nv_bfloat16* __restrict__ x, const __nv_bfloat16* __restrict__ dw,
             const __nv_bfloat16* __restrict__ w2, const __nv_bfloat16* __restrict__ grn_b, int zero) {
    extern __shared__ __align__(1024) uint8_t smem[];
    const uint32_t sbase = smem_u32(smem);
    const uint32_t bar_full = sbase + P1_OFF_BAR, bar_empty = bar_full + P1_NST * 8, bar_w = bar_empty + P1_NST * 8;
    const int tid = threadIdx.x;
    const int warp = __shfl_sync(0xffffffffu, tid >> 5, 0), lane = tid & 31;
    const uint32_t rank = cluster_rank();
    const int cig = blockIdx.x % GRP_CTAS;
    uint8_t* const ring = reinterpret_cast<uint8_t*>(g_ln);

    TSTAMP(0, 0);
    TRACEW(110 + warp, 0);
    const uint32_t bar_pace = bar_w + 32, bar_xfull = bar_pace + 32, bar_xempty = bar_xfull + 8, bar_done = bar_xfull + 16;
    const int ln0 = blockIdx.x >> 2, first = blockIdx.x / GRP_CTAS;
    const uint8_t* xsrc = reinterpret_cast<const uint8_t*>(x) + (size_t)blockIdx.x * P1_X;

    if (warp >= 12) {
        reg_dec<40>();
        asm volatile("barrier.cluster.arrive.relaxed.aligned;\n" ::: "memory");
        asm volatile("barrier.cluster.wait.aligned;\n" ::: "memory");
        if (warp == 12) {
            int prev = 0, t = first;
            const uint32_t rbase = mapa(sbase, lane & 1);
#pragma unroll 1
            for (int i = 0; t < NT128; i++) {
                const int round = t / LN_RING, slot = t - round * LN_RING;
                const uint8_t* src = ring + slot * LN_TILE + rank * (P1_SLOT / 2);
                int next = 0;
                if (rank == 0 && lane == 0) next = atomicAdd(&g_flag[LN_RING + (cig >> 1)][0][0], 1u);
                flag_wait<true>(&g_flag[slot][0][0], 4 * round + 4);
                TRACEW(i, 2);
                asm volatile("fence.proxy.async.global;\n" ::: "memory");
                next = NGRP + __shfl_sync(0xffffffffu, next, 0);
#pragma unroll 1
                for (int h = 0; h < P1_NST; h++) {
                    mbar_wait(bar_empty + h * 8, i & 1);
                    if (h == 0) TRACEW(i, 4);
                    if (h == 5) TRACEW(i, 5);
                    if (elect_one()) {
                        mbar_expect_tx(bar_full + h * 8, h ? P1_SLOT : P1_SLOT + 16);
                        bulk_g2s_mc(sbase + h * P1_SLOT + rank * (P1_SLOT / 2), src + h * P1_SLOT, P1_SLOT / 2, bar_full + h * 8, (uint16_t)3);
                    }
                    __syncwarp();
                    if (h == 0 && rank == 0 && lane < 2)
                        asm volatile("st.async.shared::cluster.mbarrier::complete_tx::bytes.v4.u32 [%0], {%1, %2, %3, %3}, [%4];\n"
                                     ::"r"(rbase + P1_OFF_TILE + (i & 3) * 16), "r"((t - prev) * (2 * H_TILE)), "r"((int)(next < NT128)), "r"(next),
                                       "r"(rbase + P1_OFF_BAR) : "memory");
                }
                prev = t;
                t = next;
                if (rank != 0) {
                    mbar_wait(bar_full, i & 1);
                    asm volatile("ld.shared.u32 %0, [%1];\n" : "=r"(t) : "r"(sbase + P1_OFF_TILE + (i & 3) * 16 + 8) : "memory");
                }
            }
        } else if (warp == 13) {
            int ph = 0;
            unsigned target = 0;
#pragma unroll 1
            for (int i = ln0 + LN_STEP; i < NT128; i += LN_STEP, ph ^= 1) {
                target += ph * (GRP_CTAS / 2);
                xsrc += (size_t)NUM_CTAS * P1_X;
                mbar_wait(bar_xempty, ph);
                if (elect_one()) {
                    mbar_expect_tx(bar_xfull, P1_X);
                    bulk_g2s(sbase + P1_OFF_X, xsrc, P1_X, bar_xfull);
                }
                __syncwarp();
                const uint32_t off = flag_wait<false>(&g_flag[ln0 + (ph ^ 1) * LN_STEP][1][0], target);
                mbar_wait(bar_done, ph);
                if (elect_one()) {
                    asm volatile("st.shared.u32 [%0], %1;\n" ::"r"(bar_done + 8), "r"(off) : "memory");
                    mbar_arrive(bar_xfull);
                }
                __syncwarp();
            }
        } else if (warp == 15) {
            const uint32_t par = g_epoch & 1;
            asm volatile("st.shared.u32 [%0], %1;\n" ::"r"(sbase + P1_OFF_TILE - 4), "r"(par) : "memory");
            if (blockIdx.x < 16) reinterpret_cast<float4*>(g_sums[par ^ 1])[blockIdx.x * 32 + lane] = make_float4(0.f, 0.f, 0.f, 0.f);
            int t = first;
            if (rank == 1 && lane == 0) mbar_arrive(bar_empty);
#pragma unroll 1
            for (int i = 0; rank == 1 && t < NT128; i++) {
#pragma unroll 1
                for (int h = 0; h < P1_NST; h++) mbar_wait(bar_full + h * 8, i & 1);
                if (lane == 0) asm volatile("red.relaxed.gpu.global.add.u32 [%0], 1;\n" ::"l"(&g_flag[t % LN_RING][1][0]) : "memory");
                asm volatile("ld.shared.u32 %0, [%1];\n" : "=r"(t) : "r"(sbase + P1_OFF_TILE + (i & 3) * 16 + 8) : "memory");
                if (lane == 0) mbar_arrive(bar_empty);
                TRACEW(i, 3);
            }
            if (rank == 0) {
                mbar_wait(bar_full, 0);
                TRACEW(110 + warp, 3);
                mbar_wait(bar_full, 1);
                float* sums = g_sums[par] + HID;
                unsigned* flag = reinterpret_cast<unsigned*>(sums + C_DIM);
                if (blockIdx.x == 0) reinterpret_cast<uint2*>(g_half)[lane] = make_uint2(0, 0);
                if (blockIdx.x == 2 && lane < 3) g_prog[lane][0] = 0;
                if (blockIdx.x < 96) g_redo[blockIdx.x * 16 + lane] = 0.f;
                float gs = 0.f;
#pragma unroll 1
                for (int pass = 0; pass < 2; pass++) {
                    float mx = 0.f;
#pragma unroll 1
                    for (int it = first; it < 96; it += NGRP) {
                        const int nb = it % 12, k0 = (cig * 4 + it / 12) * 64 + (lane >> 2);
                        const uint32_t sc = mapa(sbase + P1_OFF_EX + (k0 & 255) * 4, it / 48);
                        uint32_t* dst = reinterpret_cast<uint32_t*>(g_w2img[0]) + (k0 >> 4) * 3072 + nb * 256 + lane;
                        float bs[8] = {};
#pragma unroll 1
                        for (int c = 0; c < 8; c++) {
                            const uint4 u = __ldg(reinterpret_cast<const uint4*>(w2 + (size_t)(k0 + c * 8) * C_DIM + nb * 32) + (lane & 3));
                            const float b = __bfloat162float(grn_b[k0 + c * 8]);
                            float t;
                            asm volatile("ld.shared::cluster.f32 %0, [%1];\n" : "=f"(t) : "r"(sc + c * 32) : "memory");
#pragma unroll
                            for (int j = 0; j < 4; j++) {
                                const uint32_t v = j == 0 ? u.x : j == 1 ? u.y : j == 2 ? u.z : u.w;
                                mx = fmaxf(mx, fmaxf(fabsf(bf_lo(v)), fabsf(bf_hi(v))) * t);
                                if (pass) {
                                    bs[2 * j] = fmaf(b, bf_lo(v), bs[2 * j]);
                                    bs[2 * j + 1] = fmaf(b, bf_hi(v), bs[2 * j + 1]);
                                    uint32_t h = pack_f16(bf_lo(v) * t * gs, bf_hi(v) * t * gs);
                                    asm volatile("movmatrix.sync.aligned.m8n8.trans.b16 %0, %0;\n" : "+r"(h));
                                    dst[(c >> 1) * 3072 + (c & 1) * 32 + j * 64] = h;
                                }
                            }
                        }
                        if (pass) {
#pragma unroll
                            for (int j = 0; j < 8; j++) {
#pragma unroll
                                for (int o = 4; o < 32; o <<= 1) bs[j] += __shfl_xor_sync(0xffffffffu, bs[j], o);
                                if (lane >> 2 == j) atomicAdd(&sums[nb * 32 + (j >> 1) * 8 + (lane & 3) * 2 + (j & 1)], bs[j]);
                            }
                        }
                    }
                    if (!pass) {
                        const uint32_t m = __reduce_max_sync(0xffffffffu, __float_as_uint(mx));
                        if (lane == 0) {
                            atomicMax(flag, m);
                            asm volatile("red.release.gpu.global.add.u32 [%0], 1;\n" ::"l"(flag + 32) : "memory");
                        }
                        flag_wait<true>(flag + 32, NUM_CTAS / 2);
                        gs = w2_scale(__ldcg(flag));
                    }
                }
                do {
                    __nanosleep(1000);
                    asm volatile("ld.volatile.shared.u32 %0, [%1];\n" : "=r"(t) : "r"(sbase + P1_OFF_TILE + (lane & 3) * 16 + 8) : "memory");
                    SAFE_BREAK;
                } while (__all_sync(0xffffffffu, t < NT128 - P1_WPF));
                if (lane == 0 && blockIdx.x < 128)
                    asm volatile("cp.async.bulk.prefetch.L2.global [%0], %1;\n" ::"l"(g_w2img[0] + blockIdx.x * 576), "r"(18432) : "memory");
            }
        } else if (warp == 14) {
            int ph = 0;
#pragma unroll 1
            for (int i = ln0; i < NT128; i += LN_STEP, ph ^= 1) {
                mbar_wait(bar_done, ph);
                TRACEW(i / LN_STEP, 0);
                asm volatile("fence.proxy.async.global;\n" ::: "memory");
                if (elect_one()) asm volatile("red.release.gpu.global.add.u32 [%0], 1;\n" ::"l"(&g_flag[ln0 + ph * LN_STEP][0][0]) : "memory");
                __syncwarp();
                TRACEW(i / LN_STEP, 1);
            }
        }
        __syncwarp();
        END_SYNC();
    } else if (warp >= 8) {
        reg_dec<88>();
        asm volatile("barrier.cluster.arrive.relaxed.aligned;\n" ::: "memory");
        {
            const int l8 = lane & 7, row = (warp - 8) * 4 + (lane >> 3), px = (blockIdx.x & 3) * 32 + row;
            uint32_t d[6][4];
            const int n = (px & 64) + perm32(2 * row + ((px >> 5) & 1));
            uint8_t* const dst0 = ring + ln0 * LN_TILE + n * 128 + ((l8 ^ (n & 7)) << 4);
            const uint32_t src = sbase + P1_OFF_X + ((warp - 8) * 8 + (lane >> 3)) * (C_DIM * 2) + l8 * 16;
            int ph = 0;
#pragma unroll 1
            for (int i = ln0; i < NT128; i += LN_STEP, ph ^= 1) {
                TRACE(2, i / LN_STEP, 0);
                uint32_t off = 1;
#pragma unroll 1
                for (int ps = i == ln0 ? -2 : 0; ps < 2; ps += ps < 0 ? 2 : 1) {
                    if (ps == 0) {
                        if (i == ln0) asm volatile("barrier.cluster.wait.aligned;\n" ::: "memory");
                        mbar_wait(bar_xfull, ph);
                        asm volatile("ld.shared.u32 %0, [%1];\n" : "=r"(off) : "r"(bar_done + 8) : "memory");
                    }
                    if (ps == 0) TRACE(2, i / LN_STEP, 1);
                    if (i == ln0) {
#pragma unroll
                        for (int j = 0; j < 6; j++)
                            asm volatile("ld.shared.v4.u32 {%0,%1,%2,%3}, [%4];\n"
                                         : "=r"(d[j][0]), "=r"(d[j][1]), "=r"(d[j][2]), "=r"(d[j][3]) : "r"(sbase + P1_OFF_DW + j * 128 + l8 * 16) : "memory");
                    }
                    uint32_t v1[1][6][4];
                    uint32_t (&v)[6][4] = v1[0];
#pragma unroll
                    for (int j = 0; j < 6; j++)
                        asm volatile("ld.shared.v4.u32 {%0,%1,%2,%3}, [%4];\n"
                                     : "=r"(v[j][0]), "=r"(v[j][1]), "=r"(v[j][2]), "=r"(v[j][3]) : "r"(src + (ps & 1) * (4 * C_DIM * 2) + j * 128) : "memory");
                    ln_rows<P1_PACE, 1>(v1, d, bar_pace + (warp - 8) * 8, off, zero, ps == 1 && lane == 0 ? bar_xempty : 0);
                    uint8_t* dst = dst0 + ph * (LN_STEP * LN_TILE) + (ps & 1) * 4096;
#pragma unroll
                    for (int j = 0; j < 6; j++) *reinterpret_cast<uint4*>(dst + j * 16384) = make_uint4(v[j][0], v[j][1], v[j][2], v[j][3]);
                    TRACE(2, i / LN_STEP, 3 + (ps & 1));
                }
                asm volatile("fence.proxy.async.global;\nfence.acq_rel.cta;\n" ::: "memory");
                __syncwarp();
                if (lane == 0) mbar_arrive(bar_done);
                TRACE(2, i / LN_STEP, 5);
                TRACE(2, i / LN_STEP, 2);
            }
        }
        __syncwarp();
        END_SYNC();
    } else {
        const int wg = warp >> 2, w = warp & 3;
        auto load_w = [&](int i0, int i1) {
#pragma unroll 1
            for (int i = i0; i < i1; i++) {
                if (!(i & 1)) mbar_expect_tx(bar_w + (i >> 1) * 8, P1_W);
                tma2(sbase + (i & 2) * P1_W + (i >> 2) * P1_W + (i & 1) * (P1_W / 2), &wmap, cig * 256 + (i >> 1) * 64, (i & 1) * 192, bar_w + (i >> 1) * 8);
            }
        };
        if (warp == 4 && elect_one()) {
            mbar_init(bar_xfull, 2);
#pragma unroll
            for (int i = 0; i < 4; i++) mbar_init(bar_w + i * 8, 1);
            asm volatile("fence.mbarrier_init.release.cluster;\n" ::: "memory");
            mbar_expect_tx(bar_xfull, P1_X + C_DIM * 2);
            bulk_g2s(sbase + P1_OFF_X, xsrc, P1_X, bar_xfull);
            bulk_g2s(sbase + P1_OFF_DW, dw, C_DIM * 2, bar_xfull);
            load_w(0, 4);
            asm volatile("st.shared.u32 [%0], 1;\n" ::"r"(bar_done + 8) : "memory");
            mbar_arrive(bar_xfull);
        }
        if (warp == 5 && elect_one()) {
#pragma unroll
            for (int i = 0; i < P1_NST; i++) {
                mbar_init(bar_full + i * 8, 1);
                mbar_init(bar_empty + i * 8, i ? 8 : 8 + rank);
                if (i < 4) mbar_init(bar_pace + i * 8, 1);
            }
            mbar_init(bar_xempty, 4);
            mbar_init(bar_done, 4);
            asm volatile("fence.mbarrier_init.release.cluster;\n" ::: "memory");
        }
        __syncwarp();
        asm volatile("barrier.cluster.arrive.relaxed.aligned;\n" ::: "memory");
        reg_inc<192>();
        TRACEW(110 + warp, 1);
        uint32_t a[24][4];
        gdc_launch();
        const uint32_t src = sbase + wg * P1_W + ((lane >> 4) * 8 + (lane & 7)) * 128 + (((2 * w + ((lane >> 3) & 1)) ^ (lane & 7)) << 4);
        const uint32_t s_ex = sbase + P1_OFF_EX + (wg * 128 + w * 16 + (lane >> 2)) * 4;
        uint32_t sc2[2], ex[2];
        if (wg == 1) bar_arrive(1, 256);
#pragma unroll 1
        for (int it = 0; it < 2; it++) {
          if (it != wg) asm volatile("barrier.cluster.wait.aligned;\n" ::: "memory");
          if (it < wg) {
              mbar_wait(bar_xfull, 0);
              if (w == 0 && elect_one()) load_w(4, 8);
              __syncwarp();
          }
          if (it || wg == 0) {
            float t[2] = {0.f, 0.f};
            if (it) {
                TRACEW(110 + warp, 2);
                mbar_wait(bar_w + wg * 16, 0);
            }
            TRACEW(110 + warp, 5);
#pragma unroll
            for (int k = 0; k < 24; k++) ldsm4t(a[k], src + k * 2048);
            TRACEW(110 + warp, 6);
            p1_squares(a, t);
            sc2[0] = p1_exponents(t, ex, s_ex, lane);
            if (it && lane < 6) mbar_arrive_cluster(mapa(bar_empty, lane & 1) + (wg * 3 + (lane >> 1)) * 8 + (sc2[0] & zero));
            p1_convert<24>(a, a, ex);
          }
          if (it || wg == 1) {
            float t[2] = {0.f, 0.f};
            TRACEW(100 + warp, 0);
            if (it) mbar_wait(bar_w + wg * 16 + 8, 0);
            TRACEW(100 + warp, 1);
            uint32_t v[8][4], o[8][4];
#pragma unroll 1
            for (int j = 0; j <= 2 * it; j++) {
#pragma unroll
                for (int k = 0; k < 8; k++) ldsm4t(v[k], src + P1_OFF_W + (8 * j + k) * 2048);
                p1_squares(v, t);
            }
            sc2[1] = p1_exponents(t, ex, s_ex + 256, lane);
#pragma unroll 1
            for (int j = 2 * it; j >= 0; j--) {
                p1_convert<8>(o, v, ex);
#pragma unroll
                for (int k = 0; k < 8; k++) {
                    if (j) ldsm4t(v[k], src + P1_OFF_W + (8 * j - 8 + k) * 2048);
                    if (it) asm volatile("stmatrix.sync.aligned.m8n8.x4.trans.shared.b16 [%0], {%1,%2,%3,%4};\n"
                                         ::"r"(src + P1_OFF_W + (8 * j + k) * 2048), "r"(o[k][0]), "r"(o[k][1]), "r"(o[k][2]), "r"(o[k][3]) : "memory");
                }
            }
          }
        }
        asm volatile("fence.proxy.async.shared::cta;\n" ::: "memory");
        TRACEW(110 + warp, 7);
        bar_sync(6 + wg, 128);
        p1_consumer(a, sc2, sbase, wg, w, lane, zero);
        END_SYNC();
        TSTAMP(0, 30);
    }
}

constexpr int P2_B = 24576, P2_NB = 4;
constexpr int P2_A = 3072, P2_NA = 8;
constexpr int P2_XROW = C_DIM * 2;
constexpr int P2_OFF_A = P2_B * P2_NB;
constexpr int P2_OFF_X = P2_OFF_A + 3 * P2_NA * P2_A + 128;
constexpr int P2_LHALF = 2 * P2_NA * P2_A + 64;
constexpr int P2_XHALF = 32 * P2_XROW + 64;
constexpr int P2_OFF_GRN = P2_OFF_X + 64 * P2_XROW + 128;
constexpr int P2_OFF_BIAS = P2_OFF_GRN + HID * 2;
constexpr int P2_OFF_RED = P2_OFF_BIAS + C_DIM * 4;
constexpr int P2_OFF_BAR = P2_OFF_RED + 192;
constexpr int P2_SMEM = P2_OFF_BAR + (2 * P2_NB + 6 * P2_NA + 7) * 8;
#define P2_S1 16
constexpr int P2_S2 = 32;
constexpr int P2_NCL = NUM_CTAS / 2, P2_ITEMS = NT128 / P2_NCL, P2_SHARED = NT128 - P2_ITEMS * P2_NCL;
constexpr int P2_NPOS = 6 * 48 + P2_S1;
constexpr int P2_RAW = 24;
constexpr int P2_XC = 8 * P2_XROW;
#define P2_T0 4
#define P2_TL 8
#define P2_XP0 28
#define P2_XPN 13
#define P2_XPD 3
#define P2_CMP 0
#define P2_SLACK 0
#define P2_RAMP 2
#define P2_LATE 88
#define P2_GATE 1
#define P2_AH 2
__device__ __forceinline__ int p2_start(int n) { return n < 0 ? 0 : n / 3 * 48 + (n % 3 == 1 ? P2_S1 : n % 3 * (P2_S2 / 2)); }
__device__ __forceinline__ int p2_tile(int cl, int n) {
    return n == 0 ? NT128 - 1 - cl : n < 0 ? NT128 - 1 - P2_NCL - (cl >> 1) : cl + P2_NCL * (n - 1);
}

#define P2_EB 2
#define P2_EX 1
__device__ __forceinline__ void p2_epilogue(uint32_t (&acc0)[48], uint32_t (&acc1)[48], uint32_t up, uint32_t sx, uint32_t sb, int zero) {
    uint32_t v[12][3][4];
    auto load = [&](int t, int j) {
        if (t >= 12) return;
        uint32_t (&w)[4] = v[t][j];
        asm volatile("ld.shared.v4.u32 {%0,%1,%2,%3}, [%4];\n" : "=r"(w[0]), "=r"(w[1]), "=r"(w[2]), "=r"(w[3])
                     : "r"((j ? sx + (j - 1) * 4 * P2_XROW : sb) + t * 64) : "memory");
    };
    auto store = [&](int t, int r) {
        const uint32_t* w = (t < 6 ? acc0 : acc1) + 8 * (t % 6) + 4 * r;
        asm volatile("st.shared.v4.u32 [%4], {%0,%1,%2,%3};\n" ::"r"(w[0]), "r"(w[1]), "r"(w[2]), "r"(w[3]), "r"(sx + t * 64 + r * 4 * P2_XROW) : "memory");
    };
#pragma unroll
    for (int t = 0; t < P2_EB; t++) load(t, 0);
#pragma unroll
    for (int t = 0; t < 2 * P2_EX; t++) load(t >> 1, 1 + (t & 1));
#pragma unroll
    for (int t = 0; t < 12; t++) {
        load(t + P2_EX, 1);
        load(t + P2_EX, 2);
        load(t + P2_EB, 0);
        uint32_t* acc = (t < 6 ? acc0 : acc1) + 8 * (t % 6);
        uint32_t y[8];
#pragma unroll
        for (int e = 0; e < 8; e++) {
            y[e] = h2_add(acc[e], v[t][0][e >> 1]);
            y[e] = pack_bf16(h_lo(y[e]), h_hi(y[e]));
        }
#pragma unroll
        for (int e = 0; e < 8; e++) acc[(e & 1) * 4 + (e >> 1)] = bf2_fma(y[e], up, v[t][1 + (e & 1)][e >> 1]);
        store(t, 0);
        store(t, 1);
        sched_break(zero);
    }
    if (zero) {
#pragma unroll
        for (int t = 0; t < 24; t++) store(t >> 1, t & 1);
    }
}

__device__ __forceinline__ void p2_unpack(uint32_t (&u)[4], uint32_t o1, uint32_t o2, uint32_t o3) {
    u[2] = o1 & ~SPARE;
    u[1] = o2 & ~SPARE;
    u[3] = o3 & ~SPARE;
    const uint32_t t = bitsel(prmt(o1, o2, 0x6341), prmt(o1, o3, 0x6240) << 3, 0x38383838u);
    u[0] = bitsel(t, prmt(o2, o3, 0x7351) << 1, 0x80808080u) & ~SPARE;
}

__device__ __forceinline__ void p2_redo_sums(int warp, int lane) {
#pragma unroll 1
    for (int s = warp; s < 96; s += 12) {
        float t[2] = {0.f, 0.f};
#pragma unroll 1
        for (int tile = blockIdx.x; tile < 2 * NT128; tile += NUM_CTAS) {
            const uint32_t* p = reinterpret_cast<const uint32_t*>(reinterpret_cast<const uint8_t*>(g_h) + (size_t)(tile >> 1) * (2 * H_TILE) +
                                                                  (s >> 1) * H_STEP + (tile & 1) * H_HALF + (s & 1) * 1536) + lane * 4;
#pragma unroll
            for (int j = 0; j < 4; j++) {
                uint32_t u[4];
                p2_unpack(u, __ldcg(p + j), __ldcg(p + j + 128), __ldcg(p + j + 256));
#pragma unroll
                for (int c = 0; c < 4; c++) t[c >> 1] += h_lo(u[c]) * h_lo(u[c]) + h_hi(u[c]) * h_hi(u[c]);
            }
        }
#pragma unroll
        for (int r = 0; r < 2; r++) {
            const int ch = s * 16 + r * 8 + (lane >> 2);
            const float f = __ldcg(&g_scale[ch]) * UNCHOP;
            atomicAdd(&g_redo[ch], t[r] * f * f);
        }
    }
    __threadfence();
    __syncwarp();
    if (lane == 0) asm volatile("red.release.gpu.global.add.u32 [%0], 1;\n" ::"l"(&g_prog[2][0]) : "memory");
    flag_wait<true>(&g_prog[2][0], 12 * NUM_CTAS);
}

__global__ void __cluster_dims__(2, 1, 1) __launch_bounds__(512, 1)
pass2_kernel(const __nv_bfloat16* __restrict__ x, const __nv_bfloat16* __restrict__ grn_g, __nv_bfloat16* __restrict__ out, int zero) {
    extern __shared__ __align__(1024) uint8_t smem[];
    const uint32_t sbase = smem_u32(smem);
    const uint32_t bar_bfull = sbase + P2_OFF_BAR, bar_bempty = bar_bfull + P2_NB * 8;
    const uint32_t bar_afull = bar_bempty + P2_NB * 8, bar_aempty = bar_afull + 3 * P2_NA * 8;
    const uint32_t bar_xfull = bar_aempty + 3 * P2_NA * 8, bar_oready = bar_xfull + 24, s_pos = bar_oready + 24;
    int tid;
    asm volatile("mov.u32 %0, %%tid.x;\n" : "=r"(tid));
    const int warp = __shfl_sync(0xffffffffu, tid >> 5, 0), lane = tid & 31;
    const uint32_t rank = cluster_rank();
    const int cl = blockIdx.x >> 1, pair = cl >> 1;
    const int half = pair < P2_SHARED, fin = half && (cl & 1);
    const int k0 = (pair + 3 * (cl & 1)) % 6 * 8;
    const bool late = blockIdx.x >= P2_LATE;
    auto wait_pos = [&](int target) {
        int v;
        while (true) {
            asm volatile("ld.volatile.shared.u32 %0, [%1];\n" : "=r"(v) : "r"(s_pos) : "memory");
            if (v >= target) break;
            SAFE_BREAK;
            __nanosleep(100);
        }
    };

    TSTAMP(1, 0);
    if (tid == 384) {
        for (int i = 0; i < P2_NB; i++) {
            mbar_init(bar_bfull + i * 8, 1);
            mbar_init(bar_bempty + i * 8, 24);
        }
        for (int i = 0; i < 3 * P2_NA; i++) {
            mbar_init(bar_afull + i * 8, 1);
            mbar_init(bar_aempty + i * 8, 4);
        }
        for (int i = 0; i < 3; i++) {
            mbar_init(bar_xfull + i * 8, 2);
            mbar_init(bar_oready + i * 8, 4);
        }
        asm volatile("st.shared.u32 [%0], 0;\n" ::"r"(s_pos) : "memory");
        asm volatile("fence.mbarrier_init.release.cluster;\n" ::: "memory");
    }
    __syncthreads();
    cluster_sync_relaxed();

    if (warp >= 12) {
        reg_dec<32>();
        if (warp == 12) {
            const uint8_t* wsrc = reinterpret_cast<const uint8_t*>(g_w2img) + rank * (P2_B / 2);
            int kb = k0;
            gdc_wait();
            if (P2_GATE) bar_sync(5, 448);
#pragma unroll 1
            for (int p = 0; p < P2_NPOS; p++) {
                const int st = p & 3;
                if (p == P2_RAW) {
                    flag_wait<true>(&g_prog[1][0], NUM_CTAS);
                    asm volatile("fence.proxy.async.global;\n" ::: "memory");
                    wsrc += sizeof(g_w2img[0]);
                }
                const int idle = (p < P2_S1 || p >= 6 * 48) + (p < P2_S2 ? !half || p >= 24 : p >= 5 * 48 + P2_S2);
                mbar_wait(bar_bempty + st * 8, (~p >> 2) & 1);
                TR2(3, p, 0);
                if (elect_one()) {
                    const int len = P2_B / 2;
                    mbar_expect_tx(bar_bfull + st * 8, 2 * len);
                    bulk_g2s_mc(sbase + st * P2_B + rank * (P2_B / 2), wsrc + kb * P2_B, len, bar_bfull + st * 8, (uint16_t)3);
                    asm volatile("st.volatile.shared.u32 [%0], %1;\n" ::"r"(s_pos), "r"(p) : "memory");
                    if (rank == 0) asm volatile("red.relaxed.gpu.global.add.u32 [%0], 1;\n" ::"l"(&g_prog[0][0]) : "memory");
                    if (idle) asm volatile("mbarrier.arrive.shared::cta.b64 _, [%0], %1;\n" ::"r"(bar_bempty + st * 8), "r"(8 * idle) : "memory");
                }
                __syncwarp();
                if (++kb == 48) kb = 0;
            }
            mbar_wait(bar_bempty, 1);
            if (lane == 0) mbar_arrive(bar_bfull);
        } else if (warp == 13) {
            const int w = lane < 3 ? lane : 0;
            const uint32_t dst0 = sbase + P2_OFF_A + w * P2_NA * P2_A;
            const uint32_t bf = bar_afull + w * P2_NA * 8, be = bar_aempty + w * P2_NA * 8;
            int n = (w == 2 && half ? -1 : w) - 3, left = 0, u = 0, c = 0;
            const uint8_t* src = nullptr;
            bool act = lane < 3;
            gdc_wait();
            if (P2_GATE) bar_sync(5, 448);
            while (__any_sync(0xffffffffu, act)) {
                if (left == 0) {
                    n += 3;
                    left = n >= P2_ITEMS ? -1 : n < 0 ? 24 : 48;
                    u = (k0 + p2_start(n)) % 48;
                    src = reinterpret_cast<const uint8_t*>(g_h) + (size_t)p2_tile(cl, n) * (2 * H_TILE) + rank * H_HALF + u * H_STEP;
                }
                bool ok = act && mbar_test(be + ((c - 1) & 7) * 8, (~c >> 3) & 1);
                if (__any_sync(0xffffffffu, act && c < 16)) {
                    int v;
                    asm volatile("ld.volatile.shared.u32 %0, [%1];\n" : "=r"(v) : "r"(s_pos) : "memory");
                    ok = ok && c <= (n <= 0 ? 2 * v - P2_RAMP : c >= 16 ? c : v - p2_start(n) + 8);
                }
                if (ok) {
                    const int st = c & 7;
                    if (left > 0) {
                        mbar_expect_tx(bf + st * 8, P2_A);
                        bulk_g2s(dst0 + st * P2_A, src, P2_A, bf + st * 8);
                    } else {
                        mbar_arrive(bf + st * 8);
                        act = false;
                    }
                    src += H_STEP;
                    if (++u == 48) { u = 0; src -= 48 * H_STEP; }
                    c++;
                    left--;
                }
                SAFE_BREAK;
                if (!__any_sync(0xffffffffu, ok)) __nanosleep(100);
            }
        } else if (warp == 14) {
            const uint32_t sx = sbase + P2_OFF_X;
            size_t o = 0;
            int wp = 0;
            uint32_t par = 0;
            if (fin) {
#pragma unroll 1
                for (int c = lane * 16; c < 64 * P2_XROW + 128; c += 512) asm volatile("st.shared.v4.u32 [%0], {0, 0, 0, 0};\n" ::"r"(sx + c) : "memory");
                __syncwarp();
            }
            if (late) wait_pos(6);
#pragma unroll 1
            for (int n = -half; n <= P2_ITEMS; n++) {
                const int w = (n + 3) % 3, end = p2_start(n) + 48;
                const size_t on = (size_t)(2 * p2_tile(cl, n) + rank) * (64 * C_DIM * 2);
                const uint32_t xf = bar_xfull + w * 8;
                bool st = n + half > 0;
                const bool ld = n < P2_ITEMS - 1 && !(n < 0 && fin);
                if (n == P2_ITEMS - 1 && lane == 0) {
                    mbar_expect_tx(xf, 64 * C_DIM * 2);
#pragma unroll 1
                    for (int c = 4; c < 12; c++) {
                        if (c >= 8) {
                            mbar_wait(bar_aempty + ((2 * c - 1) & 7) * 8, 1);
                            mbar_wait(bar_aempty + ((2 * c) & 7) * 8, 1);
                        }
                        bulk_g2s(sbase + P2_OFF_A + (c & 3) * P2_XC + (c < 8 ? P2_LHALF : 0), reinterpret_cast<const uint8_t*>(x) + on + (c & 7) * P2_XC, P2_XC, xf);
                    }
                    mbar_arrive(xf);
                }
                if (st) {
                    mbar_wait(bar_oready + wp * 8, (par >> wp) & 1);
                    par ^= 1u << wp;
                }
                if (lane == 0) {
                    if (n < P2_ITEMS - 1) mbar_expect_tx(xf, ld ? 64 * C_DIM * 2 : 0);
                    const int t0 = (n ? p2_start(n - 1) + 48 : P2_S2) + (n == P2_ITEMS - 1 ? P2_TL : P2_T0), dt = end - (n == P2_ITEMS - 2 ? P2_CMP : 0) - t0;
                    int t = st ? 16 * t0 : -4096;
                    if ((n == 0 && half) || n == P2_ITEMS) {
                        if (fin && n == 0) {
                            flag_wait<true>(&g_half[pair][rank], 1);
                            asm volatile("fence.proxy.async.global;\n" ::: "memory");
                        }
#pragma unroll 1
                        for (int c = 0; c < 2; c++) {
                            uint8_t* dst = reinterpret_cast<uint8_t*>(out) + o + c * 32 * P2_XROW;
                            if (!fin || n) bulk_s2g(dst, n ? sbase + P2_OFF_A + c * P2_LHALF : sx + c * P2_XHALF, 32 * P2_XROW);
                            else asm volatile("cp.reduce.async.bulk.global.shared::cta.bulk_group.add.noftz.bf16 [%0], [%1], %2;\n"
                                              ::"l"(dst), "r"(sx + c * P2_XHALF), "r"(32 * P2_XROW) : "memory");
                        }
                        asm volatile("cp.async.bulk.commit_group;\n" ::: "memory");
                        if (!fin && n == 0) {
                            asm volatile("cp.async.bulk.wait_group 0;\nfence.proxy.async.global;\n" ::: "memory");
                            asm volatile("st.release.gpu.global.u32 [%0], 1;\n" ::"l"(&g_half[pair][rank]) : "memory");
                        }
                        st = false;
                    }
#pragma unroll 1
                    for (int c = 0; n < P2_ITEMS && c < 64 * P2_XROW; c += P2_XC, t += 2 * dt) {
                        const uint32_t sp = sx + c + (c >= 32 * P2_XROW ? 64 : 0);
                        wait_pos(t >> 4);
                        if (st) bulk_s2g(reinterpret_cast<uint8_t*>(out) + o + c, sp, P2_XC);
                        asm volatile("cp.async.bulk.commit_group;\n" ::: "memory");
                        if (ld) {
                            wait_pos((t + dt) >> 4);
                            asm volatile("cp.async.bulk.wait_group.read 0;\n" ::: "memory");
                            bulk_g2s(sp, reinterpret_cast<const uint8_t*>(x) + on + c, P2_XC, xf);
                        }
                    }
                    if (rank == 0 && n > 0 && n < P2_ITEMS - 2) flag_wait<false>(&g_prog[0][0], P2_NCL * (end + P2_SLACK));
                    if (n < P2_ITEMS - 1) mbar_arrive(xf);
                }
                __syncwarp();
                o = on;
                wp = w;
            }
            asm volatile("cp.async.bulk.wait_group.read 0;\n" ::: "memory");
        } else {
            if (blockIdx.x == 120) {
                gdc_wait();
                for (int i = lane; i < (LN_RING + 3) * 2; i += 32) (&g_flag[0][0][0])[i * 8] = 0;
                if (lane == 0) g_epoch++;
            }
            int t = 4 * P2_XP0;
#pragma unroll 1
            for (int n = 0; n < P2_ITEMS && lane == 0; n++) {
                const uint8_t* xn = reinterpret_cast<const uint8_t*>(x) + (size_t)(2 * p2_tile(cl, n) + rank) * (64 * C_DIM * 2);
#pragma unroll 1
                for (int c = 0; c < 16; c++, t += n < P2_XPN ? 4 : P2_XPD) {
                    wait_pos(t >> 2);
                    asm volatile("cp.async.bulk.prefetch.L2.global [%0], %1;\n" ::"l"(xn + c * (P2_XC / 2)), "r"(P2_XC / 2) : "memory");
                }
            }
        }
        __syncwarp();
        END_SYNC();
    } else {
        reg_inc<160>();
        const int wg = warp >> 2, w = warp & 3, g = lane >> 2, q = lane & 3;
        const uint32_t sx = sbase + P2_OFF_X + (g & 1) * P2_XHALF + (w * 8 + (g >> 1)) * P2_XROW + q * 16;
        const uint32_t af = bar_afull + wg * P2_NA * 8;
        const uint32_t s_a = sbase + P2_OFF_A + wg * P2_NA * P2_A + (lane >> 3) * 512 + (lane & 7) * 64 + ((w ^ ((lane & 7) >> 1)) << 4);
        uint32_t acc0[48], acc1[48], up;
        uint4 a[2][2];

        __nv_bfloat16 gg[4];
#pragma unroll
        for (int i = 0; i < 4; i++) gg[i] = grn_g[tid + 384 * i];
#pragma unroll 1
        for (int it = late; it < 2; it++) {
            float* s_red = reinterpret_cast<float*>(smem + P2_OFF_RED);
            float gx[7], part = 0.f;
            if (it) {
                TSTAMP(1, 27);
                gdc_wait();
                TSTAMP(1, 1);
            }
            float gy[7];
#pragma unroll
            for (int i = 0; i < 7; i++) {
                const float* p = &g_sums[0][i < 5 ? tid + 384 * i : HID + C_DIM + i - 5];
                asm volatile("ld.global.cg.f32 %0, [%1];\n" : "=f"(gx[i]) : "l"(p) : "memory");
                asm volatile("ld.global.cg.f32 %0, [%1];\n" : "=f"(gy[i]) : "l"(p + HID + 512) : "memory");
            }
            if (P2_GATE && it) bar_arrive(5, 448);
            const float bias = gx[4] + gy[4];
            const float gs = w2_scale(__float_as_uint(gx[5]) | __float_as_uint(gy[5]));
            if (it && gx[6] + gy[6] != 0.f) {
                p2_redo_sums(warp, lane);
#pragma unroll
                for (int i = 0; i < 4; i++) {
                    gx[i] = __ldcg(&g_redo[tid + 384 * i]);
                    gy[i] = 0.f;
                }
            }
            float mg = 0.f;
#pragma unroll
            for (int i = 0; i < 4; i++) {
                gx[i] = gx[i] + gy[i];
                gx[i] = __fsqrt_rn(gx[i] * (HSCALE * HSCALE) + 1e-6f);
                part += gx[i];
                gx[i] *= __bfloat162float(gg[i]);
                mg = fmaxf(mg, fabsf(gx[i]));
            }
#pragma unroll
            for (int o = 16; o > 0; o >>= 1) part += __shfl_xor_sync(0xffffffffu, part, o);
            const uint32_t mgw = __reduce_max_sync(0xffffffffu, __float_as_uint(mg));
            const uint32_t mbw = __reduce_max_sync(0xffffffffu, __float_as_uint(fabsf(bias)));
            TSTAMP(1, 26);
            if (lane == 0) *reinterpret_cast<float4*>(s_red + warp * 4) = make_float4(part, __uint_as_float(mgw), __uint_as_float(mbw), 0.f);
            bar_sync(1, 384);
            float tot = 0.f, mb = 0.f;
#pragma unroll
            for (int i = 0; i < 12; i++) {
                const float4 t = *reinterpret_cast<const float4*>(s_red + i * 4);
                tot += t.x;
                mg = fmaxf(mg, t.y);
                mb = fmaxf(mb, t.z);
            }
            const float inv = 1.0f / (tot * (1.0f / HID) + 1e-6f);
            const uint32_t ej = min((__float_as_uint(fmaxf(fmaf(mg, inv, 1.0f) * (HSCALE * UNCHOP), mb * gs * 0x1p-13f)) >> 23) + 1, 250u);
            const float dn = __uint_as_float((254u - ej) << 23);
            up = min(ej + 127u - (__float_as_uint(gs) >> 23), 254u) * 0x00800080u;
            reinterpret_cast<uint16_t*>(smem + P2_OFF_BIAS + C_DIM * 2)[tid] = 0;
            *reinterpret_cast<__half*>(smem + P2_OFF_BIAS + (tid >> 5) * 64 + (tid & 6) * 8 + (tid & 24) / 2 + (tid & 1) * 2) = __float2half_rn(bias * gs * dn);
#pragma unroll
            for (int i = 0; i < 4; i++) {
                const int k = tid + 384 * i;
                *reinterpret_cast<__half*>(smem + P2_OFF_GRN + (k >> 4) * 32 + (k & 6) * 4 + (k & 8) / 2 + (k & 1) * 2) =
                    __float2half_rn(fmaf(gx[i], inv, 1.0f) * (HSCALE * UNCHOP * dn));
            }
            TSTAMP(1, 25);
            bar_sync(1, 384);
        }
        TSTAMP(1, 28);
        if (wg == 1) {
            constexpr int N = sizeof(g_w2img[0]) / 16, PER = (N + NUM_CTAS - 1) / NUM_CTAS;
            uint4 v[5];
#pragma unroll
            for (int i = 0; i < 5; i++) v[i] = __ldcg(&g_w2img[0][min(blockIdx.x * PER + (tid & 127) + 128 * i, N - 1)]);
#pragma unroll
            for (int i = 0; i < 5; i++) {
                const int j = min(blockIdx.x * PER + (tid & 127) + 128 * i, N - 1);
                const uint32_t* t = reinterpret_cast<const uint32_t*>(smem + P2_OFF_GRN + (j / 768) * 32 + (j & 8) / 2);
                auto sc = [&](uint32_t u, int e) { return (h2_mul(u, t[2 * e]) + 0x00040004u) & 0xfff8fff8u; };
                g_w2img[1][j] = make_uint4(sc(v[i].x, 0), sc(v[i].y, 1), sc(v[i].z, 2), sc(v[i].w, 3));
            }
            asm volatile("fence.proxy.async.global;\n" ::: "memory");
            bar_sync(2, 128);
            if (tid == 128) asm volatile("fence.acq_rel.gpu;\nred.release.gpu.global.add.u32 [%0], 1;\n" ::"l"(&g_prog[1][0]) : "memory");
        }

        const int who = __shfl_sync(0xffffffffu, lane == 2 ? 0 : lane < 2 ? 1 : 2, lane);
        const uint32_t rel0 = who ? mapa(bar_bempty, lane & 1) : mapa(bar_aempty + wg * P2_NA * 8, rank), rel1 = rel0 + (who ? 0 : 32);
        auto publish = [&]() {
            asm volatile("fence.proxy.async.shared::cta;\n" ::: "memory");
            __syncwarp();
            if (who == 0) mbar_arrive(bar_oready + wg * 8);
        };
        bool ok_a, pend = false;
        uint32_t pa = 0, s_t;
        auto fetch = [&](int j, bool raw) {
            uint32_t o[6], u0[4], u1[4];
            uint2 t0 = make_uint2(0, 0), t1 = t0;
            if (raw) {
                asm volatile("ld.shared.v2.u32 {%0,%1}, [%2];\n" : "=r"(t0.x), "=r"(t0.y) : "r"(s_t + j * 64) : "memory");
                asm volatile("ld.shared.v2.u32 {%0,%1}, [%2];\n" : "=r"(t1.x), "=r"(t1.y) : "r"(s_t + j * 64 + 32) : "memory");
            }
            const bool ok_b = mbar_test(bar_bfull + (j & 3) * 8, j >> 2);
            if (j == 7) pa ^= 1;
            ok_a = mbar_test(af + ((j + 1) & 7) * 8, pa);
            asm volatile("ldmatrix.sync.aligned.m8n8.x4.trans.shared.b16 {%0,%1,%2,%3}, [%4];\n"
                         : "=r"(o[0]), "=r"(o[1]), "=r"(o[2]), "=r"(o[3]) : "r"(s_a + j * P2_A) : "memory");
            asm volatile("ldmatrix.sync.aligned.m8n8.x2.trans.shared.b16 {%0,%1}, [%2];\n"
                         : "=r"(o[4]), "=r"(o[5]) : "r"(s_a + j * P2_A + 2048) : "memory");
            p2_unpack(u0, o[0], o[1], o[2]);
            p2_unpack(u1, o[3], o[4], o[5]);
            if (raw) {
                u0[0] = h2_mul(u0[0], t0.x); u0[1] = h2_mul(u0[1], t0.x); u0[2] = h2_mul(u0[2], t0.y); u0[3] = h2_mul(u0[3], t0.y);
                u1[0] = h2_mul(u1[0], t1.x); u1[1] = h2_mul(u1[1], t1.x); u1[2] = h2_mul(u1[2], t1.y); u1[3] = h2_mul(u1[3], t1.y);
            }
            a[j & 1][0] = make_uint4(u0[0], u0[1], u0[2], u0[3]);
            a[j & 1][1] = make_uint4(u1[0], u1[1], u1[2], u1[3]);
            if (!ok_b) mbar_wait(bar_bfull + (j & 3) * 8, j >> 2);
        };
        auto table = [&](int pos) { s_t = sbase + P2_OFF_GRN + q * 8 + (k0 + pos) % 48 * 64; };
        const uint32_t db0 = (uint32_t)make_desc(sbase, 128, 256);
        auto block8 = [&](bool raw, int pos, int thr0, int mode) {
#pragma unroll
            for (int j = 0; j < 8; j++) {
                const uint32_t db = db0 + (j & 3) * (P2_B / 16);
                if (j == 8 - P2_AH && mode == 1) bar_sync(4, 384);
                TR2(wg, pos + j, 0);
                wg_fence();
                mma_rs_n192(acc0, a[j & 1][0], db);
                mma_rs_n192(acc1, a[j & 1][0], db + 384);
                mma_rs_n192(acc0, a[j & 1][1], db + 768);
                mma_rs_n192(acc1, a[j & 1][1], db + 768 + 384);
                wg_commit();
                if (j == 7 && mode == 2) bar_arrive(4, 384);
                const uint32_t rel = ((j - 1) & 4 ? rel1 : rel0) + ((j - 1) & 3) * 8;
                TR2(wg, pos + j, 1);
                wg_wait<1>();
                TR2(wg, pos + j, 2);
                if (who < (j ? 2 : thr0)) mbar_arrive_cluster(rel);
                if (!ok_a) {
                    if (j == 0 && pend) { publish(); pend = false; }
                    mbar_wait(af + ((j + 1) & 7) * 8, pa);
                }
                TR2(wg, pos + j, 3);
                if (raw && j == 7) table(pos + 8);
                fetch((j + 1) & 7, raw && (j < 7 || pos + 8 < P2_RAW));
            }
        };
        int n = wg == 2 && half ? -1 : wg, pos = p2_start(n);
        uint32_t px = 0;
        wait_pos(pos);
        mbar_wait(af, 0);
        table(pos);
        fetch(0, pos < P2_RAW);
#pragma unroll 1
        for (;; n += 3) {
            TSTAMP(1, 2 + n);
            const int end = pos + (n < 0 ? 24 : 48);
#pragma unroll
            for (int i = 0; i < 48; i += 2) {
                asm volatile("mov.b64 {%0, %1}, 0;\n" : "=r"(acc0[i]), "=r"(acc0[i + 1]));
                asm volatile("mov.b64 {%0, %1}, 0;\n" : "=r"(acc1[i]), "=r"(acc1[i + 1]));
            }
            int thr = 1;
#pragma unroll 1
            for (; pos < P2_RAW; pos += 8, thr = 2) block8(true, pos, thr, 0);
#pragma unroll 1
            for (; pos < end; pos += 8, thr = 2) {
                const int e = pos + 8, r = e % 48;
                block8(false, pos, thr, e < 48 || e > 256 || (r != 0 && r != P2_S1 && r != P2_S2) ? 0 : e == end ? 2 : 1);
            }
            TR2(wg, pos - 1, 4);
            wg_wait<0>();
            TR2(wg, pos - 1, 5);
            if (who == 1) mbar_arrive_cluster(rel0 + 24);
            mbar_wait(bar_xfull + wg * 8, px);
            TR2(wg, pos - 1, 6);
            px ^= 1;
            __syncwarp();
            p2_epilogue(acc0, acc1, up, n == P2_ITEMS - 1 ? sx + (P2_OFF_A - P2_OFF_X) + (g & 1) * (P2_LHALF - P2_XHALF) : sx, sbase + P2_OFF_BIAS + q * 16 + (n < 0 && fin ? C_DIM * 2 : 0), zero);
            TR2(wg, pos - 1, 7);
            if (n + 3 >= P2_ITEMS) { publish(); break; }
            if (n < 0) {
                publish();
                pos = P2_S2;
                wait_pos(pos);
                mbar_wait(bar_bfull, 0);
            } else {
                pend = true;
                ok_a = false;
            }
        }
        TSTAMP(1, 29);
        END_SYNC();
        TSTAMP(1, 30);
    }
}

}

extern "C" void kernel_launch(void* const* d_in, const int* in_sizes, int n_in, void* d_out, int out_size) {
    const __nv_bfloat16* x = (const __nv_bfloat16*)d_in[0];
    const __nv_bfloat16* dw = (const __nv_bfloat16*)d_in[1];
    const __nv_bfloat16* w1 = (const __nv_bfloat16*)d_in[2];
    const __nv_bfloat16* w2 = (const __nv_bfloat16*)d_in[3];
    const __nv_bfloat16* grn_g = (const __nv_bfloat16*)d_in[4];
    const __nv_bfloat16* grn_b = (const __nv_bfloat16*)d_in[5];
    __nv_bfloat16* out = (__nv_bfloat16*)d_out;

    cudaFuncSetAttribute(pass1_kernel, cudaFuncAttributeMaxDynamicSharedMemorySize, P1_SMEM);
    cudaFuncSetAttribute(pass2_kernel, cudaFuncAttributeMaxDynamicSharedMemorySize, P2_SMEM);

    typedef CUresult (*EncodeFn)(CUtensorMap*, CUtensorMapDataType, cuuint32_t, void*, const cuuint64_t*, const cuuint64_t*,
                                 const cuuint32_t*, const cuuint32_t*, CUtensorMapInterleave, CUtensorMapSwizzle,
                                 CUtensorMapL2promotion, CUtensorMapFloatOOBfill);
    static EncodeFn encode = nullptr;
    if (!encode) {
        cudaDriverEntryPointQueryResult qres;
        cudaGetDriverEntryPoint("cuTensorMapEncodeTiled", (void**)&encode, cudaEnableDefault, &qres);
    }
    CUtensorMap wmap;
    const cuuint64_t gdim[2] = {HID, C_DIM};
    const cuuint64_t gstr[1] = {HID * 2};
    const cuuint32_t box[2] = {64, 192}, estr[2] = {1, 1};
    CUresult er = encode(&wmap, CU_TENSOR_MAP_DATA_TYPE_BFLOAT16, 2, (void*)w1, gdim, gstr, box, estr, CU_TENSOR_MAP_INTERLEAVE_NONE,
           CU_TENSOR_MAP_SWIZZLE_128B, CU_TENSOR_MAP_L2_PROMOTION_L2_128B, CU_TENSOR_MAP_FLOAT_OOB_FILL_NONE);
    if (er != CUDA_SUCCESS) printf("tensor map encode failed %d\n", (int)er);

    pass1_kernel<<<NUM_CTAS, 512, P1_SMEM>>>(wmap, x, dw, w2, grn_b, 0);

    cudaLaunchAttribute attr[1];
    attr[0].id = cudaLaunchAttributeProgrammaticStreamSerialization;
    attr[0].val.programmaticStreamSerializationAllowed = 1;
    cudaLaunchConfig_t cfg = {};
    cfg.gridDim = dim3(NUM_CTAS);
    cfg.stream = 0;
    cfg.attrs = attr;
    cfg.numAttrs = 1;
    cfg.blockDim = dim3(512);
    cfg.dynamicSmemBytes = P2_SMEM;
    cudaLaunchKernelEx(&cfg, pass2_kernel, x, grn_g, out, 0);
}
```

```cpp
#include <cuda.h>
#include <cuda_runtime.h>
#include <cuda_bf16.h>
#include <cuda_fp16.h>
#include <stdint.h>
#include <stdio.h>

namespace {

constexpr int M_TOTAL = 384 * 384;
constexpr int C_DIM   = 384;
constexpr int HID     = 1536;
constexpr int NT128   = M_TOTAL / 128;
constexpr int NUM_CTAS = 132;

constexpr int NGRP = 22, GRP_CTAS = 6;
constexpr int LN_STEP = NUM_CTAS / 4, LN_RING = 2 * LN_STEP;
constexpr int LN_TILE = 128 * C_DIM * 2;
constexpr int H_TILE = 64 * HID * 3 / 2;
constexpr int H_HALF = 3072, H_STEP = 6144;

__device__ __align__(1024) uint4 g_h[(size_t)M_TOTAL * HID * 3 / 32];
__device__ __align__(1024) uint4 g_ln[LN_RING * LN_TILE / 16];
__device__ __align__(1024) uint4 g_w2img[2][HID * C_DIM * 2 / 16];
__device__ __align__(16) float g_sums[2][HID + 512];
__device__ float g_scale[HID];
__device__ float g_redo[HID];
__device__ unsigned g_epoch;
__device__ __align__(128) unsigned g_prog[3][32];
__device__ __align__(128) unsigned g_half[32][2];
__device__ unsigned g_flag[LN_RING + 6][2][8];
#define TSTAMP(k, i)
#define TRACE(wg, pos, i)
#define TRACEW(pos, i)

#define TR2(wg, pos, i)
__host__ __device__ __forceinline__ int perm32(int n) {
    return (n & ~31) | (((n >> 1) & 3) << 3) | (((n >> 3) & 3) << 1) | (n & 1);
}

__device__ __forceinline__ uint32_t smem_u32(const void* p) { return (uint32_t)__cvta_generic_to_shared(p); }

__device__ __forceinline__ void mbar_init(uint32_t bar, uint32_t count) {
    asm volatile("mbarrier.init.shared::cta.b64 [%0], %1;\n" ::"r"(bar), "r"(count) : "memory");
}
__device__ __forceinline__ void mbar_expect_tx(uint32_t bar, uint32_t bytes) {
    asm volatile("mbarrier.arrive.expect_tx.shared::cta.b64 _, [%0], %1;\n" ::"r"(bar), "r"(bytes) : "memory");
}
__device__ __forceinline__ void mbar_arrive(uint32_t bar) {
    asm volatile("mbarrier.arrive.shared::cta.b64 _, [%0];\n" ::"r"(bar) : "memory");
}
__device__ __forceinline__ void mbar_arrive_cluster(uint32_t bar_cluster_addr) {
    asm volatile("mbarrier.arrive.shared::cluster.b64 _, [%0];\n" ::"r"(bar_cluster_addr) : "memory");
}
#define SAFE_BREAK
__device__ __forceinline__ void mbar_wait(uint32_t bar, uint32_t parity) {
    asm volatile(
        "{\n"
        ".reg .pred p;\n"
        "LAB_WAIT:\n"
        "mbarrier.try_wait.parity.shared::cta.b64 p, [%0], %1;\n"
        "@!p bra LAB_WAIT;\n"
        "}\n" ::"r"(bar), "r"(parity) : "memory");
}
__device__ __forceinline__ bool mbar_test(uint32_t bar, uint32_t parity) {
    uint32_t ok;
    asm volatile("{\n.reg .pred p;\n"
                 "mbarrier.test_wait.parity.shared::cta.b64 p, [%1], %2;\n"
                 "selp.u32 %0, 1, 0, p;\n}\n" : "=r"(ok) : "r"(bar), "r"(parity) : "memory");
    return ok != 0;
}
__device__ __forceinline__ uint32_t mapa(uint32_t addr, uint32_t rank) {
    uint32_t r;
    asm volatile("mapa.shared::cluster.u32 %0, %1, %2;\n" : "=r"(r) : "r"(addr), "r"(rank));
    return r;
}
__device__ __forceinline__ void bulk_g2s(uint32_t dst, const void* src, uint32_t bytes, uint32_t bar) {
    asm volatile("cp.async.bulk.shared::cluster.global.mbarrier::complete_tx::bytes [%0], [%1], %2, [%3];\n"
                 ::"r"(dst), "l"(src), "r"(bytes), "r"(bar) : "memory");
}
__device__ __forceinline__ void bulk_g2s_mc(uint32_t dst, const void* src, uint32_t bytes, uint32_t bar, uint16_t mask) {
    asm volatile("cp.async.bulk.shared::cluster.global.mbarrier::complete_tx::bytes.multicast::cluster [%0], [%1], %2, [%3], %4;\n"
                 ::"r"(dst), "l"(src), "r"(bytes), "r"(bar), "h"(mask) : "memory");
}
__device__ __forceinline__ void tma2(uint32_t dst, const CUtensorMap* map, int c0, int c1, uint32_t bar) {
    asm volatile("cp.async.bulk.tensor.2d.shared::cluster.global.tile.mbarrier::complete_tx::bytes [%0], [%1, {%2, %3}], [%4];\n"
                 ::"r"(dst), "l"(map), "r"(c0), "r"(c1), "r"(bar) : "memory");
}
template <bool ACQ>
__device__ __forceinline__ uint32_t flag_wait(const unsigned* p, unsigned target) {
    unsigned v, n = 0;
    do {
        if (ACQ) asm volatile("ld.acquire.gpu.global.u32 %0, [%1];\n" : "=r"(v) : "l"(p) : "memory");
        else asm volatile("ld.relaxed.gpu.global.u32 %0, [%1];\n" : "=r"(v) : "l"(p) : "memory");
        n++;
    } while (v < target);
    return n == 1;
}
__device__ __forceinline__ void ldsm4t(uint32_t (&r)[4], uint32_t addr) {
    asm volatile("ldmatrix.sync.aligned.m8n8.x4.trans.shared.b16 {%0,%1,%2,%3}, [%4];\n"
                 : "=r"(r[0]), "=r"(r[1]), "=r"(r[2]), "=r"(r[3]) : "r"(addr) : "memory");
}
__device__ __forceinline__ void bulk_s2g(void* dst, uint32_t src, uint32_t bytes) {
    asm volatile("cp.async.bulk.global.shared::cta.bulk_group [%0], [%1], %2;\n" ::"l"(dst), "r"(src), "r"(bytes) : "memory");
}
__device__ __forceinline__ void cluster_sync() {
    asm volatile("barrier.cluster.arrive.aligned;\nbarrier.cluster.wait.aligned;\n" ::: "memory");
}
__device__ __forceinline__ void cluster_sync_relaxed() {
    asm volatile("barrier.cluster.arrive.relaxed.aligned;\nbarrier.cluster.wait.aligned;\n" ::: "memory");
}
#define END_SYNC cluster_sync_relaxed
__device__ __forceinline__ void gdc_wait() { asm volatile("griddepcontrol.wait;\n" ::: "memory"); }
__device__ __forceinline__ void gdc_launch() { asm volatile("griddepcontrol.launch_dependents;\n" ::: "memory"); }
__device__ __forceinline__ uint32_t cluster_rank() {
    uint32_t r;
    asm volatile("mov.u32 %0, %%cluster_ctarank;\n" : "=r"(r));
    return r;
}
__device__ __forceinline__ bool elect_one() {
    uint32_t pred;
    asm volatile("{\n.reg .pred p;\nelect.sync _|p, 0xffffffff;\nselp.u32 %0, 1, 0, p;\n}\n" : "=r"(pred));
    return pred != 0;
}
__device__ __forceinline__ void wg_fence() { asm volatile("wgmma.fence.sync.aligned;\n" ::: "memory"); }
__device__ __forceinline__ void wg_commit() { asm volatile("wgmma.commit_group.sync.aligned;\n" ::: "memory"); }
template <int N> __device__ __forceinline__ void wg_wait() {
    asm volatile("wgmma.wait_group.sync.aligned %0;\n" ::"n"(N) : "memory");
}
template <int R> __device__ __forceinline__ void reg_inc() { asm volatile("setmaxnreg.inc.sync.aligned.u32 %0;\n" ::"n"(R)); }
template <int R> __device__ __forceinline__ void reg_dec() { asm volatile("setmaxnreg.dec.sync.aligned.u32 %0;\n" ::"n"(R)); }
__device__ __forceinline__ void bar_sync(int id, int n) { asm volatile("bar.sync %0, %1;\n" ::"r"(id), "r"(n) : "memory"); }
__device__ __forceinline__ void bar_arrive(int id, int n) { asm volatile("bar.arrive %0, %1;\n" ::"r"(id), "r"(n) : "memory"); }

__device__ __forceinline__ uint64_t make_desc(uint32_t saddr, uint32_t lbo, uint32_t sbo) {
    return (uint64_t)((saddr & 0x3FFFF) >> 4) | ((uint64_t)(lbo >> 4) << 16) | ((uint64_t)(sbo >> 4) << 32);
}

__device__ __forceinline__ void stg128_cs(void* p, uint32_t a, uint32_t b, uint32_t c, uint32_t d) {
#define H_ST "st.global.cs.v4.u32"
    asm volatile(H_ST " [%0], {%1,%2,%3,%4};\n" ::"l"(p), "r"(a), "r"(b), "r"(c), "r"(d) : "memory");
}
__device__ __forceinline__ uint32_t pack_bf16(float lo, float hi) {
    uint32_t r;
    asm("cvt.rn.bf16x2.f32 %0, %1, %2;\n" : "=r"(r) : "f"(hi), "f"(lo));
    return r;
}
__device__ __forceinline__ float bf_lo(uint32_t v) { return __uint_as_float(v << 16); }
__device__ __forceinline__ float bf_hi(uint32_t v) { return __uint_as_float(v & 0xffff0000u); }
__device__ __forceinline__ uint32_t bf2_mul(uint32_t a, uint32_t b) {
    uint32_t r;
    asm("mul.rn.bf16x2 %0, %1, %2;\n" : "=r"(r) : "r"(a), "r"(b));
    return r;
}
__device__ __forceinline__ uint32_t bf2_fma(uint32_t a, uint32_t b, uint32_t c) {
    uint32_t r;
    asm("fma.rn.bf16x2 %0, %1, %2, %3;\n" : "=r"(r) : "r"(a), "r"(b), "r"(c));
    return r;
}
__device__ __forceinline__ uint32_t bf2_add(uint32_t a, uint32_t b) {
    uint32_t r;
    asm("add.rn.bf16x2 %0, %1, %2;\n" : "=r"(r) : "r"(a), "r"(b));
    return r;
}
__device__ __forceinline__ uint32_t h2_mul(uint32_t a, uint32_t b) {
    uint32_t r;
    asm("mul.rn.f16x2 %0, %1, %2;\n" : "=r"(r) : "r"(a), "r"(b));
    return r;
}
__device__ __forceinline__ uint32_t h2_fma(uint32_t a, uint32_t b, uint32_t c) {
    uint32_t r;
    asm("fma.rn.f16x2 %0, %1, %2, %3;\n" : "=r"(r) : "r"(a), "r"(b), "r"(c));
    return r;
}
__device__ __forceinline__ uint32_t h2_add(uint32_t a, uint32_t b) {
    uint32_t r;
    asm("add.rn.f16x2 %0, %1, %2;\n" : "=r"(r) : "r"(a), "r"(b));
    return r;
}
__device__ __forceinline__ uint32_t pack_f16(float lo, float hi) {
    uint32_t r;
    asm("cvt.rn.f16x2.f32 %0, %1, %2;\n" : "=r"(r) : "f"(hi), "f"(lo));
    return r;
}
__device__ __forceinline__ float h_lo(uint32_t v) { return __low2float(*reinterpret_cast<const __half2*>(&v)); }
__device__ __forceinline__ float h_hi(uint32_t v) { return __high2float(*reinterpret_cast<const __half2*>(&v)); }
__device__ __forceinline__ uint32_t bf2_to_h2(uint32_t v) { return (v & 0x7fff7fffu) * 7u + v; }
__device__ __forceinline__ uint32_t prmt(uint32_t a, uint32_t b, uint32_t sel) {
    uint32_t r;
    asm("prmt.b32 %0, %1, %2, %3;\n" : "=r"(r) : "r"(a), "r"(b), "r"(sel));
    return r;
}
__device__ __forceinline__ uint32_t bitsel(uint32_t a, uint32_t b, uint32_t m) {
    uint32_t r;
    asm("lop3.b32 %0, %1, %2, %3, 0xd8;\n" : "=r"(r) : "r"(a), "r"(b), "r"(m));
    return r;
}
constexpr float KAPPA = 0.3292034911525734f;
constexpr uint32_t GELU_C2 = 0x40d940d9u;
constexpr float HSCALE = 1.0f / (2.0f * KAPPA);
__device__ __forceinline__ float w2_scale(uint32_t m) { return __uint_as_float((257u - max(m >> 23, 16u)) << 23); }
__device__ __forceinline__ void sched_break(int zero) {
    asm volatile("{\n.reg .pred p;\nsetp.ne.s32 p, %0, 0;\nSB_LOOP:\n@p nanosleep.u32 1;\n@p bra SB_LOOP;\n}\n" ::"r"(zero));
}

#define ACC8(d, o) "+r"(d[o + 0]), "+r"(d[o + 1]), "+r"(d[o + 2]), "+r"(d[o + 3]), "+r"(d[o + 4]), "+r"(d[o + 5]), "+r"(d[o + 6]), "+r"(d[o + 7])

__device__ __forceinline__ void mma_rs_n128(uint32_t (&d)[32], const uint32_t (&a)[4], uint32_t desc, int scale_d) {
    asm volatile(
        "{\n.reg .pred p;\n.reg .b64 db;\nsetp.ne.b32 p, %37, 0;\nmov.b64 db, {%36, 0x40000040};\n"
        "wgmma.mma_async.sync.aligned.m64n128k16.f16.f16.f16 "
        "{%0,%1,%2,%3,%4,%5,%6,%7,%8,%9,%10,%11,%12,%13,%14,%15,"
        "%16,%17,%18,%19,%20,%21,%22,%23,%24,%25,%26,%27,%28,%29,%30,%31},"
        "{%32,%33,%34,%35}, db, p, 1, 1, 0;\n}\n"
        : ACC8(d, 0), ACC8(d, 8), ACC8(d, 16), ACC8(d, 24)
        : "r"(a[0]), "r"(a[1]), "r"(a[2]), "r"(a[3]), "r"(desc), "r"(scale_d));
}

__device__ __forceinline__ void mma_ss_n128(uint32_t (&d)[32], uint32_t da, uint32_t db, int scale_d) {
    asm volatile(
        "{\n.reg .pred p;\n.reg .b64 da, db;\nsetp.ne.b32 p, %34, 0;\nmov.b64 da, {%32, 0x40000040};\nmov.b64 db, {%33, 0x40000040};\n"
        "wgmma.mma_async.sync.aligned.m64n128k16.f16.f16.f16 "
        "{%0,%1,%2,%3,%4,%5,%6,%7,%8,%9,%10,%11,%12,%13,%14,%15,"
        "%16,%17,%18,%19,%20,%21,%22,%23,%24,%25,%26,%27,%28,%29,%30,%31},"
        "da, db, p, 1, 1, 1, 0;\n}\n"
        : ACC8(d, 0), ACC8(d, 8), ACC8(d, 16), ACC8(d, 24)
        : "r"(da), "r"(db), "r"(scale_d));
}

__device__ __forceinline__ void mma_rs_n192(uint32_t (&d)[48], const uint4& a, uint32_t db) {
    asm volatile(
        "{\n.reg .b64 db;\nmov.b64 db, {%52, 16};\n"
        "wgmma.mma_async.sync.aligned.m64n192k16.f16.f16.f16 "
        "{%0,%1,%2,%3,%4,%5,%6,%7,%8,%9,%10,%11,%12,%13,%14,%15,"
        "%16,%17,%18,%19,%20,%21,%22,%23,%24,%25,%26,%27,%28,%29,%30,%31,"
        "%32,%33,%34,%35,%36,%37,%38,%39,%40,%41,%42,%43,%44,%45,%46,%47},"
        "{%48,%49,%50,%51}, db, 1, 1, 1, 0;\n}\n"
        : ACC8(d, 0), ACC8(d, 8), ACC8(d, 16), ACC8(d, 24), ACC8(d, 32), ACC8(d, 40)
        : "r"(a.x), "r"(a.y), "r"(a.z), "r"(a.w), "r"(db));
}

#define P1_SPLIT 5
#define P1_WPF 30
#define P1_PACE 1
constexpr int P1_SLOT = LN_TILE / 6, P1_NST = 6;
constexpr int P1_W = 64 * C_DIM * 2;
constexpr int P1_X = 32 * C_DIM * 2;
constexpr int P1_OFF_W = LN_TILE;
constexpr int P1_OFF_X = P1_OFF_W + 2 * P1_W;
constexpr int P1_OFF_BAR = P1_OFF_X + P1_X;
constexpr int P1_OFF_TILE = P1_OFF_BAR + (2 * P1_NST + 4 + 4 + 4) * 8;
constexpr int P1_OFF_EX = P1_OFF_TILE + 64;
constexpr int P1_OFF_DW = P1_OFF_EX + 256 * 4;
constexpr int P1_SMEM = P1_OFF_DW + C_DIM * 2;

__device__ __forceinline__ float rsqrt_fast(float x) {
    float r;
    asm("rsqrt.approx.ftz.f32 %0, %1;\n" : "=f"(r) : "f"(x));
    return r;
}
__device__ __forceinline__ float row_sum(const uint32_t (&c)[4]) {
    const uint32_t u = bf2_add(bf2_add(c[0], c[1]), bf2_add(c[2], c[3]));
    float s = bf_lo(u) + bf_hi(u);
#pragma unroll
    for (int o = 1; o < 8; o <<= 1) s += __shfl_xor_sync(0xffffffffu, s, o);
    return s;
}
__device__ __forceinline__ uint32_t pace(uint32_t bar, uint32_t off, uint32_t val, uint32_t after, int zero) {
    asm volatile(
        "{\n.reg .pred p, q;\n.reg .b32 par;\n"
        "lop3.b32 par, %4, %2, %3, 0xea;\n"
        "setp.eq.u32 q, par, 0;\n"
        "mov.pred p, 0;\n"
        "@q mbarrier.test_wait.parity.shared::cta.b64 p, [%1], par;\n"
        "selp.u32 par, 1, 0, p;\n"
        "@q mbarrier.try_wait.parity.shared::cta.b64 p, [%1], par, 1000;\n"
        "@p or.b32 %0, %0, %2;\n"
        "}\n" : "+r"(val) : "r"(bar), "r"(zero), "r"(off), "r"(after));
    return val;
}
template <int PACE, int R>
__device__ __forceinline__ void ln_rows(uint32_t (&v)[R][6][4], const uint32_t (&d)[6][4], uint32_t bar, uint32_t off, int zero,
                                        uint32_t bar_read) {
    const float inv = 1.0f / C_DIM;
    uint32_t c[R][4], nm[R];
    float e[R], r[R], er[R];
    bool big = false;
#pragma unroll
    for (int p = 0; p < R; p++) {
#pragma unroll
        for (int i = 0; i < 6; i++)
#pragma unroll
            for (int k = 0; k < 4; k++) c[p][k] = bf2_fma(v[p][i][k], d[i][k], i ? c[p][k] : 0);
        const float m = row_sum(c[p]) * inv;
        nm[p] = pack_bf16(-m, -m);
        e[p] = m + bf_lo(nm[p]);
    }
    if (bar_read) mbar_arrive(bar_read + (nm[0] & zero));
    if (PACE & 1) nm[0] = pace(bar, off, nm[0], nm[0], zero);
#pragma unroll
    for (int p = 0; p < R; p++) {
#pragma unroll
        for (int i = 0; i < 6; i++) {
#pragma unroll
            for (int k = 0; k < 4; k++) {
                v[p][i][k] = bf2_fma(v[p][i][k], d[i][k], nm[p]);
                c[p][k] = i ? bf2_fma(v[p][i][k], v[p][i][k], c[p][k]) : bf2_mul(v[p][i][k], v[p][i][k]);
            }
        }
        r[p] = KAPPA * rsqrt_fast(fmaxf(fmaf(-e[p], e[p], row_sum(c[p]) * inv), 0.f) + 1e-5f);
        er[p] = -e[p] * r[p] * 0x1p-112f;
        big |= r[p] < 0x1p-8f;
    }
    if (__any_sync(0xffffffffu, big)) {
#pragma unroll
        for (int p = 0; p < R; p++) {
            const uint32_t p2 = __float_as_uint(r[p]) & 0x7f800000u;
            r[p] = __uint_as_float((__float_as_uint(r[p]) & 0x007fffffu) | 0x3f800000u);
#pragma unroll
            for (int i = 0; i < 6; i++)
#pragma unroll
                for (int k = 0; k < 4; k++) v[p][i][k] = bf2_mul(v[p][i][k], p2 | p2 >> 16);
        }
    }
#pragma unroll
    for (int p = 0; p < R; p++) {
        uint32_t rs = pack_bf16(r[p] * 0x1p-112f, r[p] * 0x1p-112f);
        const uint32_t sh = pack_bf16(er[p], er[p]);
        if (PACE & 2) rs = pace(bar, off, rs, sh, zero);
#pragma unroll
        for (int i = 0; i < 6; i++)
#pragma unroll
            for (int k = 0; k < 4; k++) v[p][i][k] = bf2_to_h2(bf2_fma(v[p][i][k], rs, sh));
    }
}

template <int R>
__device__ __forceinline__ uint32_t gelu2(uint32_t a, uint32_t sc2) {
    uint32_t y, t;
    if (R) asm("{\n.reg .b16 l, h;\n.reg .b32 f;\nmov.b32 {l, h}, %2;\nmov.b32 f, {h, h};\nmul.rn.f16x2 %0, %1, f;\n}\n" : "=r"(y) : "r"(a), "r"(sc2));
    else asm("{\n.reg .b16 l, h;\n.reg .b32 f;\nmov.b32 {l, h}, %2;\nmov.b32 f, {l, l};\nmul.rn.f16x2 %0, %1, f;\n}\n" : "=r"(y) : "r"(a), "r"(sc2));
    asm("tanh.approx.f16x2 %0, %1;\n" : "=r"(t) : "r"(h2_mul(y, h2_fma(y, y, GELU_C2))));
    return h2_fma(a, t, a);
}
constexpr uint32_t SPARE = 0x40074007u;
constexpr float UNCHOP = 1.0023f;

__device__ __forceinline__ uint32_t p1_parity(uint32_t sbase) {
    uint32_t v;
    asm volatile("ld.shared.u32 %0, [%1];\n" : "=r"(v) : "r"(sbase + P1_OFF_TILE - 4) : "memory");
    return v;
}
__device__ __forceinline__ uint32_t p1_exponents(float (&t)[2], uint32_t (&ex)[2], uint32_t saddr, int lane) {
#pragma unroll
    for (int r = 0; r < 2; r++) {
        t[r] += __shfl_xor_sync(0xffffffffu, t[r], 1);
        t[r] += __shfl_xor_sync(0xffffffffu, t[r], 2);
        ex[r] = min(max(((__float_as_uint(193.3f * t[r]) >> 23) + 127u) >> 1, 72u), 198u);
        asm volatile("st.shared.u32 [%0], %1;\n" ::"r"(saddr + r * 32), "r"(ex[r] << 23) : "memory");
    }
    return pack_f16(__uint_as_float(min(ex[0], 142u) << 23), __uint_as_float(min(ex[1], 142u) << 23));
}
template <int N>
__device__ __forceinline__ void p1_convert(uint32_t (&o)[N][4], uint32_t (&v)[N][4], const uint32_t (&ex)[2]) {
    if (__any_sync(0xffffffffu, max(ex[0], ex[1]) > 141u)) {
#pragma unroll
        for (int k = 0; k < 4 * N; k++) v[k >> 2][k & 3] = bf2_mul(v[k >> 2][k & 3], ex[k & 1] > 141u ? 0x1f801f80u : 0x3f803f80u);
    }
#pragma unroll
    for (int k = 0; k < 4 * N; k++) {
        const uint32_t u = bf2_mul(v[k >> 2][k & 3], ((ex[k & 1] > 141u ? 206u : 142u) - ex[k & 1]) * 0x00800080u);
        asm volatile("mad.lo.u32 %0, %1, 7, %2;\n" : "=r"(o[k >> 2][k & 3]) : "r"(u & 0x7fff7fffu), "r"(u));
    }
}
template <int N>
__device__ __forceinline__ void p1_squares(const uint32_t (&v)[N][4], float (&t)[2]) {
#pragma unroll
    for (int j = 0; j < N / 2; j++) {
        const int r = j & 1, b = (j >> 1) * 4;
        uint32_t c = bf2_mul(v[b][r], v[b][r]);
#pragma unroll
        for (int k = 1; k < 8; k++) c = bf2_fma(v[b + k / 2][r + (k & 1) * 2], v[b + k / 2][r + (k & 1) * 2], c);
        t[r] += bf_lo(c) + bf_hi(c);
    }
}
__device__ __forceinline__ void p1_epilogue(const uint32_t (&acc)[2][32], const uint32_t (&sc2)[2], float (&ssq)[4], uint8_t* hp, int zero) {
    uint32_t sq[2], h[16][4];
#pragma unroll
    for (int i2 = 0; i2 < 9; i2++) {
#pragma unroll
        for (int c = 2 * i2 - 2; c < 2 * i2; c++) {
            if (c >= 0 && (c & 3)) {
                uint32_t o[4];
#pragma unroll
                for (int u = 0; u < 4; u++) {
                    const uint32_t v = h[c & 12][u];
                    o[u] = bitsel(h[c][u], (c & 3) == 2 ? prmt(v, v, 0xa381) : prmt(v >> 3, v, (c & 3) == 1 ? 0x6240 : 0xf3d1), SPARE);
                }
                stg128_cs(hp + (c >> 3) * 2 * H_STEP + ((c >> 2) & 1) * H_HALF + ((c & 3) - 1) * 512, o[0], o[1], o[2], o[3]);
            }
        }
        if (i2 < 8) {
#pragma unroll
            for (int u = 0; u < 4; u++) {
                h[2 * i2][u] = gelu2<0>(acc[i2 >> 2][8 * (i2 & 3) + 2 * u], sc2[i2 >> 2]);
                h[2 * i2 + 1][u] = gelu2<1>(acc[i2 >> 2][8 * (i2 & 3) + 2 * u + 1], sc2[i2 >> 2]);
#pragma unroll
                for (int r = 0; r < 2; r++) {
                    const uint32_t v = h[2 * i2 + r][u];
                    sq[r] = ((i2 & 3) | u) ? h2_fma(v, v, sq[r]) : h2_mul(v, v);
                }
            }
            if ((i2 & 3) == 3) {
#pragma unroll
                for (int r = 0; r < 2; r++) ssq[(i2 >> 2) * 2 + r] += h_lo(sq[r]) + h_hi(sq[r]);
            }
            sched_break(zero);
        }
    }
}
template <int WG>
__device__ __forceinline__ void p1_mma(uint32_t (&acc)[2][32], const uint32_t (&a)[24][4], uint32_t sbase, uint32_t empty_remote, int i, int lane, bool pass) {
    const uint32_t bar_full = sbase + P1_OFF_BAR;
    const uint32_t db = (uint32_t)make_desc(sbase, 16, 1024), da = db + (P1_OFF_W + WG * P1_W) / 16;
    if (WG == 0) mbar_wait(bar_full, i & 1);
    bar_sync(1 + WG, 256);
    TRACE(WG, i, 1);
    wg_fence();
#pragma unroll
    for (int k = 0; k < 24; k++) {
        if (WG == 0 && k && k % 4 == 0) mbar_wait(bar_full + (k >> 2) * 8, i & 1);
        mma_rs_n128(acc[0], a[k], db + (k >> 2) * 1024 + (k & 3) * 2, k != 0);
        mma_ss_n128(acc[1], da + k * 128, db + (k >> 2) * 1024 + (k & 3) * 2, k != 0);
        if (k == 23 && pass) bar_arrive(2 - WG, 256);
        if (k == 23 || (WG == 1 && k % 4 == 3)) wg_commit();
        if (WG == 1 && k % 4 == 3 && k > 3) {
            wg_wait<1>();
            if (lane < 2) mbar_arrive_cluster(empty_remote + ((k >> 2) - 1) * 8);
        }
    }
    TRACE(WG, i, 2);
    wg_wait<0>();
    if (WG == 1 && lane < 2) mbar_arrive_cluster(empty_remote + 5 * 8);
}
__device__ __forceinline__ void p1_consumer(const uint32_t (&a)[24][4], const uint32_t (&sc2)[2], uint32_t sbase, int WG, int w, int lane, int zero) {
    const uint32_t bar_full = sbase + P1_OFF_BAR, bar_empty = bar_full + P1_NST * 8;
    const uint32_t empty_remote = mapa(bar_empty, lane & 1);
    const uint32_t bar_pace = bar_empty + P1_NST * 8 + 32 + w * 8;
    const int g = lane >> 2, q = lane & 3, half = WG ^ ((blockIdx.x / GRP_CTAS) & 1), cb = (blockIdx.x % GRP_CTAS) * 4 + half * 2;
    uint32_t acc[2][32];
    float ssq[4] = {0.f, 0.f, 0.f, 0.f};
    TSTAMP(0, 1);

    uint8_t* hp = reinterpret_cast<uint8_t*>(g_h) + ((cb * 2 + (w >> 1)) * H_STEP + (w & 1) * 1536) + g * 64 + (q ^ (g >> 1)) * 16;
    int i = 0;
    uint32_t more = 3, both;
#pragma unroll 1
    for (;; i++) {
        TRACE(WG, i, 0);
        both = more & 2;
        if (WG == 0) p1_mma<0>(acc, a, sbase, empty_remote, i, lane, both);
        else p1_mma<1>(acc, a, sbase, empty_remote, i, lane, true);
        TRACE(WG, i, 4);
        int step;
        asm volatile("ld.shared.v2.u32 {%0, %1}, [%2];\n" : "=r"(step), "=r"(more) : "r"(sbase + P1_OFF_TILE + (i & 3) * 16) : "memory");
        hp += step;
        p1_epilogue(acc, sc2, ssq, hp, zero);
        if (lane == 0) mbar_arrive(bar_pace);
        if (!(more >> WG & 1)) break;
    }
    TSTAMP(0, 21);
    if (WG == 0 && both) bar_sync(1, 256);
#pragma unroll
    for (int r = 0; r < 4; r++) {
        const int ch = (r >> 1) * 64 + w * 16 + (r & 1) * 8 + g;
        ssq[r] += __shfl_xor_sync(0xffffffffu, ssq[r], 1);
        ssq[r] += __shfl_xor_sync(0xffffffffu, ssq[r], 2);
        float f;
        asm volatile("ld.shared.f32 %0, [%1];\n" : "=f"(f) : "r"(sbase + P1_OFF_EX + (half * 128 + ch) * 4) : "memory");
        if (q == 0) {
            float* sums = g_sums[p1_parity(sbase)];
            atomicAdd(&sums[cb * 64 + ch], ssq[r] * f * f);
            g_scale[cb * 64 + ch] = f;
            if (ssq[r] < (i + 1) * 0x1p-12f) sums[HID + C_DIM + 1] = 1.f;
        }
    }
}

__global__ void __cluster_dims__(2, 1, 1) __launch_bounds__(512, 1)
pass1_kernel(const __grid_constant__ CUtensorMap wmap, const __nv_bfloat16* __restrict__ x, const __nv_bfloat16* __restrict__ dw,
             const __nv_bfloat16* __restrict__ w2, const __nv_bfloat16* __restrict__ grn_b, int zero) {
    extern __shared__ __align__(1024) uint8_t smem[];
    const uint32_t sbase = smem_u32(smem);
    const uint32_t bar_full = sbase + P1_OFF_BAR, bar_empty = bar_full + P1_NST * 8, bar_w = bar_empty + P1_NST * 8;
    const int tid = threadIdx.x;
    const int warp = __shfl_sync(0xffffffffu, tid >> 5, 0), lane = tid & 31;
    const uint32_t rank = cluster_rank();
    const int cig = blockIdx.x % GRP_CTAS;
    uint8_t* const ring = reinterpret_cast<uint8_t*>(g_ln);

    TSTAMP(0, 0);
    TRACEW(110 + warp, 0);
    const uint32_t bar_pace = bar_w + 32, bar_xfull = bar_pace + 32, bar_xempty = bar_xfull + 8, bar_done = bar_xfull + 16;
    const int ln0 = blockIdx.x >> 2, first = blockIdx.x / GRP_CTAS;
    const uint8_t* xsrc = reinterpret_cast<const uint8_t*>(x) + (size_t)blockIdx.x * P1_X;

    if (warp >= 12) {
        reg_dec<40>();
        asm volatile("barrier.cluster.arrive.relaxed.aligned;\n" ::: "memory");
        asm volatile("barrier.cluster.wait.aligned;\n" ::: "memory");
        if (warp == 12) {
            int prev = 0, t = first;
            const uint32_t rbase = mapa(sbase, lane & 1);
#pragma unroll 1
            for (int i = 0; t < NT128; i++) {
                const int round = t / LN_RING, slot = t - round * LN_RING;
                const uint8_t* src = ring + slot * LN_TILE + rank * (P1_SLOT / 2);
                int next = 0;
                if (rank == 0 && lane == 0) {
                    next = t < NT128 - P1_SPLIT ? NGRP + atomicAdd(&g_flag[LN_RING + (cig >> 1)][0][0], 1u) : 2 * NT128;
                    if (next >= NT128 - P1_SPLIT && next < 2 * NT128) next = NT128 - P1_SPLIT + atomicAdd(&g_flag[LN_RING + 3 + (cig >> 1)][first & 1][0], 1u);
                }
                flag_wait<true>(&g_flag[slot][0][0], 4 * round + 4);
                TRACEW(i, 2);
                asm volatile("fence.proxy.async.global;\n" ::: "memory");
                next = __shfl_sync(0xffffffffu, next, 0);
#pragma unroll 1
                for (int h = 0; h < P1_NST; h++) {
                    mbar_wait(bar_empty + h * 8, i & 1);
                    if (h == 0) TRACEW(i, 4);
                    if (h == 5) TRACEW(i, 5);
                    if (elect_one()) {
                        mbar_expect_tx(bar_full + h * 8, h ? P1_SLOT : P1_SLOT + 16);
                        bulk_g2s_mc(sbase + h * P1_SLOT + rank * (P1_SLOT / 2), src + h * P1_SLOT, P1_SLOT / 2, bar_full + h * 8, (uint16_t)3);
                    }
                    __syncwarp();
                    if (h == 0 && rank == 0 && lane < 2)
                        asm volatile("st.async.shared::cluster.mbarrier::complete_tx::bytes.v4.u32 [%0], {%1, %2, %3, %3}, [%4];\n"
                                     ::"r"(rbase + P1_OFF_TILE + (i & 3) * 16), "r"((t - prev) * (2 * H_TILE)), "r"(next < NT128 - P1_SPLIT ? 3 : next < NT128), "r"(next),
                                       "r"(rbase + P1_OFF_BAR) : "memory");
                }
                prev = t;
                t = next;
                if (rank != 0) {
                    mbar_wait(bar_full, i & 1);
                    asm volatile("ld.shared.u32 %0, [%1];\n" : "=r"(t) : "r"(sbase + P1_OFF_TILE + (i & 3) * 16 + 8) : "memory");
                }
            }
        } else if (warp == 13) {
            int ph = 0;
            unsigned target = 0;
#pragma unroll 1
            for (int i = ln0 + LN_STEP; i < NT128; i += LN_STEP, ph ^= 1) {
                target += ph * (GRP_CTAS / 2);
                xsrc += (size_t)NUM_CTAS * P1_X;
                mbar_wait(bar_xempty, ph);
                if (elect_one()) {
                    mbar_expect_tx(bar_xfull, P1_X);
                    bulk_g2s(sbase + P1_OFF_X, xsrc, P1_X, bar_xfull);
                }
                __syncwarp();
                const uint32_t off = flag_wait<false>(&g_flag[ln0 + (ph ^ 1) * LN_STEP][1][0], target);
                mbar_wait(bar_done, ph);
                if (elect_one()) {
                    asm volatile("st.shared.u32 [%0], %1;\n" ::"r"(bar_done + 8), "r"(off) : "memory");
                    mbar_arrive(bar_xfull);
                }
                __syncwarp();
            }
        } else if (warp == 15) {
            const uint32_t par = g_epoch & 1;
            asm volatile("st.shared.u32 [%0], %1;\n" ::"r"(sbase + P1_OFF_TILE - 4), "r"(par) : "memory");
            if (blockIdx.x < 16) reinterpret_cast<float4*>(g_sums[par ^ 1])[blockIdx.x * 32 + lane] = make_float4(0.f, 0.f, 0.f, 0.f);
            int t = first;
            if (rank == 1 && lane == 0) mbar_arrive(bar_empty);
#pragma unroll 1
            for (int i = 0; rank == 1 && t < NT128; i++) {
#pragma unroll 1
                for (int h = 0; h < P1_NST; h++) mbar_wait(bar_full + h * 8, i & 1);
                if (lane == 0) asm volatile("red.relaxed.gpu.global.add.u32 [%0], 1;\n" ::"l"(&g_flag[t % LN_RING][1][0]) : "memory");
                asm volatile("ld.shared.u32 %0, [%1];\n" : "=r"(t) : "r"(sbase + P1_OFF_TILE + (i & 3) * 16 + 8) : "memory");
                if (lane == 0) mbar_arrive(bar_empty);
                TRACEW(i, 3);
            }
            if (rank == 0) {
                mbar_wait(bar_full, 0);
                TRACEW(110 + warp, 3);
                mbar_wait(bar_full, 1);
                float* sums = g_sums[par] + HID;
                unsigned* flag = reinterpret_cast<unsigned*>(sums + C_DIM);
                if (blockIdx.x == 0) reinterpret_cast<uint2*>(g_half)[lane] = make_uint2(0, 0);
                if (blockIdx.x == 2 && lane < 3) g_prog[lane][0] = 0;
                if (blockIdx.x < 96) g_redo[blockIdx.x * 16 + lane] = 0.f;
                float gs = 0.f;
#pragma unroll 1
                for (int pass = 0; pass < 2; pass++) {
                    float mx = 0.f;
#pragma unroll 1
                    for (int it = first; it < 96; it += NGRP) {
                        const int nb = it % 12, k0 = (cig * 4 + it / 12) * 64 + (lane >> 2);
                        const uint32_t sc = mapa(sbase + P1_OFF_EX + (k0 & 255) * 4, it / 48);
                        uint32_t* dst = reinterpret_cast<uint32_t*>(g_w2img[0]) + (k0 >> 4) * 3072 + nb * 256 + lane;
                        float bs[8] = {};
#pragma unroll 1
                        for (int c = 0; c < 8; c++) {
                            const uint4 u = __ldg(reinterpret_cast<const uint4*>(w2 + (size_t)(k0 + c * 8) * C_DIM + nb * 32) + (lane & 3));
                            const float b = __bfloat162float(grn_b[k0 + c * 8]);
                            float t;
                            asm volatile("ld.shared::cluster.f32 %0, [%1];\n" : "=f"(t) : "r"(sc + c * 32) : "memory");
#pragma unroll
                            for (int j = 0; j < 4; j++) {
                                const uint32_t v = j == 0 ? u.x : j == 1 ? u.y : j == 2 ? u.z : u.w;
                                mx = fmaxf(mx, fmaxf(fabsf(bf_lo(v)), fabsf(bf_hi(v))) * t);
                                if (pass) {
                                    bs[2 * j] = fmaf(b, bf_lo(v), bs[2 * j]);
                                    bs[2 * j + 1] = fmaf(b, bf_hi(v), bs[2 * j + 1]);
                                    uint32_t h = pack_f16(bf_lo(v) * t * gs, bf_hi(v) * t * gs);
                                    asm volatile("movmatrix.sync.aligned.m8n8.trans.b16 %0, %0;\n" : "+r"(h));
                                    dst[(c >> 1) * 3072 + (c & 1) * 32 + j * 64] = h;
                                }
                            }
                        }
                        if (pass) {
#pragma unroll
                            for (int j = 0; j < 8; j++) {
#pragma unroll
                                for (int o = 4; o < 32; o <<= 1) bs[j] += __shfl_xor_sync(0xffffffffu, bs[j], o);
                                if (lane >> 2 == j) atomicAdd(&sums[nb * 32 + (j >> 1) * 8 + (lane & 3) * 2 + (j & 1)], bs[j]);
                            }
                        }
                    }
                    if (!pass) {
                        const uint32_t m = __reduce_max_sync(0xffffffffu, __float_as_uint(mx));
                        if (lane == 0) {
                            atomicMax(flag, m);
                            asm volatile("red.release.gpu.global.add.u32 [%0], 1;\n" ::"l"(flag + 32) : "memory");
                        }
                        flag_wait<true>(flag + 32, NUM_CTAS / 2);
                        gs = w2_scale(__ldcg(flag));
                    }
                }
                do {
                    __nanosleep(1000);
                    asm volatile("ld.volatile.shared.u32 %0, [%1];\n" : "=r"(t) : "r"(sbase + P1_OFF_TILE + (lane & 3) * 16 + 8) : "memory");
                    SAFE_BREAK;
                } while (__all_sync(0xffffffffu, t < NT128 - P1_WPF));
                if (lane == 0 && blockIdx.x < 128)
                    asm volatile("cp.async.bulk.prefetch.L2.global [%0], %1;\n" ::"l"(g_w2img[0] + blockIdx.x * 576), "r"(18432) : "memory");
            }
        } else if (warp == 14) {
            int ph = 0;
#pragma unroll 1
            for (int i = ln0; i < NT128; i += LN_STEP, ph ^= 1) {
                mbar_wait(bar_done, ph);
                TRACEW(i / LN_STEP, 0);
                asm volatile("fence.proxy.async.global;\n" ::: "memory");
                if (elect_one()) asm volatile("red.release.gpu.global.add.u32 [%0], 1;\n" ::"l"(&g_flag[ln0 + ph * LN_STEP][0][0]) : "memory");
                __syncwarp();
                TRACEW(i / LN_STEP, 1);
            }
        }
        __syncwarp();
        END_SYNC();
    } else if (warp >= 8) {
        reg_dec<88>();
        asm volatile("barrier.cluster.arrive.relaxed.aligned;\n" ::: "memory");
        {
            const int l8 = lane & 7, row = (warp - 8) * 4 + (lane >> 3), px = (blockIdx.x & 3) * 32 + row;
            uint32_t d[6][4];
            const int n = (px & 64) + perm32(2 * row + ((px >> 5) & 1));
            uint8_t* const dst0 = ring + ln0 * LN_TILE + n * 128 + ((l8 ^ (n & 7)) << 4);
            const uint32_t src = sbase + P1_OFF_X + ((warp - 8) * 8 + (lane >> 3)) * (C_DIM * 2) + l8 * 16;
            int ph = 0;
#pragma unroll 1
            for (int i = ln0; i < NT128; i += LN_STEP, ph ^= 1) {
                TRACE(2, i / LN_STEP, 0);
                uint32_t off = 1;
#pragma unroll 1
                for (int ps = i == ln0 ? -2 : 0; ps < 2; ps += ps < 0 ? 2 : 1) {
                    if (ps == 0) {
                        if (i == ln0) asm volatile("barrier.cluster.wait.aligned;\n" ::: "memory");
                        mbar_wait(bar_xfull, ph);
                        asm volatile("ld.shared.u32 %0, [%1];\n" : "=r"(off) : "r"(bar_done + 8) : "memory");
                    }
                    if (ps == 0) TRACE(2, i / LN_STEP, 1);
                    if (i == ln0) {
#pragma unroll
                        for (int j = 0; j < 6; j++)
                            asm volatile("ld.shared.v4.u32 {%0,%1,%2,%3}, [%4];\n"
                                         : "=r"(d[j][0]), "=r"(d[j][1]), "=r"(d[j][2]), "=r"(d[j][3]) : "r"(sbase + P1_OFF_DW + j * 128 + l8 * 16) : "memory");
                    }
                    uint32_t v1[1][6][4];
                    uint32_t (&v)[6][4] = v1[0];
#pragma unroll
                    for (int j = 0; j < 6; j++)
                        asm volatile("ld.shared.v4.u32 {%0,%1,%2,%3}, [%4];\n"
                                     : "=r"(v[j][0]), "=r"(v[j][1]), "=r"(v[j][2]), "=r"(v[j][3]) : "r"(src + (ps & 1) * (4 * C_DIM * 2) + j * 128) : "memory");
                    ln_rows<P1_PACE, 1>(v1, d, bar_pace + (warp - 8) * 8, off, zero, ps == 1 && lane == 0 ? bar_xempty : 0);
                    uint8_t* dst = dst0 + ph * (LN_STEP * LN_TILE) + (ps & 1) * 4096;
#pragma unroll
                    for (int j = 0; j < 6; j++) *reinterpret_cast<uint4*>(dst + j * 16384) = make_uint4(v[j][0], v[j][1], v[j][2], v[j][3]);
                    TRACE(2, i / LN_STEP, 3 + (ps & 1));
                }
                asm volatile("fence.proxy.async.global;\nfence.acq_rel.cta;\n" ::: "memory");
                __syncwarp();
                if (lane == 0) mbar_arrive(bar_done);
                TRACE(2, i / LN_STEP, 5);
                TRACE(2, i / LN_STEP, 2);
            }
        }
        __syncwarp();
        END_SYNC();
    } else {
        const int wg = warp >> 2, w = warp & 3;
        auto load_w = [&](int i0, int i1) {
#pragma unroll 1
            for (int i = i0; i < i1; i++) {
                if (!(i & 1)) mbar_expect_tx(bar_w + (i >> 1) * 8, P1_W);
                tma2(sbase + (i & 2) * P1_W + (i >> 2) * P1_W + (i & 1) * (P1_W / 2), &wmap, cig * 256 + ((i >> 1) ^ (first & 1) * 2) * 64, (i & 1) * 192, bar_w + (i >> 1) * 8);
            }
        };
        if (warp == 4 && elect_one()) {
            mbar_init(bar_xfull, 2);
#pragma unroll
            for (int i = 0; i < 4; i++) mbar_init(bar_w + i * 8, 1);
            asm volatile("fence.mbarrier_init.release.cluster;\n" ::: "memory");
            mbar_expect_tx(bar_xfull, P1_X + C_DIM * 2);
            bulk_g2s(sbase + P1_OFF_X, xsrc, P1_X, bar_xfull);
            bulk_g2s(sbase + P1_OFF_DW, dw, C_DIM * 2, bar_xfull);
            load_w(0, 4);
            asm volatile("st.shared.u32 [%0], 1;\n" ::"r"(bar_done + 8) : "memory");
            mbar_arrive(bar_xfull);
        }
        if (warp == 5 && elect_one()) {
#pragma unroll
            for (int i = 0; i < P1_NST; i++) {
                mbar_init(bar_full + i * 8, 1);
                mbar_init(bar_empty + i * 8, i ? 8 : 8 + rank);
                if (i < 4) mbar_init(bar_pace + i * 8, 1);
            }
            mbar_init(bar_xempty, 4);
            mbar_init(bar_done, 4);
            asm volatile("fence.mbarrier_init.release.cluster;\n" ::: "memory");
        }
        __syncwarp();
        asm volatile("barrier.cluster.arrive.relaxed.aligned;\n" ::: "memory");
        reg_inc<192>();
        TRACEW(110 + warp, 1);
        uint32_t a[24][4];
        gdc_launch();
        const uint32_t src = sbase + wg * P1_W + ((lane >> 4) * 8 + (lane & 7)) * 128 + (((2 * w + ((lane >> 3) & 1)) ^ (lane & 7)) << 4);
        const uint32_t s_ex = sbase + P1_OFF_EX + ((wg ^ (first & 1)) * 128 + w * 16 + (lane >> 2)) * 4;
        uint32_t sc2[2], ex[2];
        if (wg == 1) bar_arrive(1, 256);
#pragma unroll 1
        for (int it = 0; it < 2; it++) {
          if (it != wg) asm volatile("barrier.cluster.wait.aligned;\n" ::: "memory");
          if (it < wg) {
              mbar_wait(bar_xfull, 0);
              if (w == 0 && elect_one()) load_w(4, 8);
              __syncwarp();
          }
          if (it || wg == 0) {
            float t[2] = {0.f, 0.f};
            if (it) {
                TRACEW(110 + warp, 2);
                mbar_wait(bar_w + wg * 16, 0);
            }
            TRACEW(110 + warp, 5);
#pragma unroll
            for (int k = 0; k < 24; k++) ldsm4t(a[k], src + k * 2048);
            TRACEW(110 + warp, 6);
            p1_squares(a, t);
            sc2[0] = p1_exponents(t, ex, s_ex, lane);
            if (it && lane < 6) mbar_arrive_cluster(mapa(bar_empty, lane & 1) + (wg * 3 + (lane >> 1)) * 8 + (sc2[0] & zero));
            p1_convert<24>(a, a, ex);
          }
          if (it || wg == 1) {
            float t[2] = {0.f, 0.f};
            TRACEW(100 + warp, 0);
            if (it) mbar_wait(bar_w + wg * 16 + 8, 0);
            TRACEW(100 + warp, 1);
            uint32_t v[8][4], o[8][4];
#pragma unroll 1
            for (int j = 0; j <= 2 * it; j++) {
#pragma unroll
                for (int k = 0; k < 8; k++) ldsm4t(v[k], src + P1_OFF_W + (8 * j + k) * 2048);
                p1_squares(v, t);
            }
            sc2[1] = p1_exponents(t, ex, s_ex + 256, lane);
#pragma unroll 1
            for (int j = 2 * it; j >= 0; j--) {
                p1_convert<8>(o, v, ex);
#pragma unroll
                for (int k = 0; k < 8; k++) {
                    if (j) ldsm4t(v[k], src + P1_OFF_W + (8 * j - 8 + k) * 2048);
                    if (it) asm volatile("stmatrix.sync.aligned.m8n8.x4.trans.shared.b16 [%0], {%1,%2,%3,%4};\n"
                                         ::"r"(src + P1_OFF_W + (8 * j + k) * 2048), "r"(o[k][0]), "r"(o[k][1]), "r"(o[k][2]), "r"(o[k][3]) : "memory");
                }
            }
          }
        }
        asm volatile("fence.proxy.async.shared::cta;\n" ::: "memory");
        TRACEW(110 + warp, 7);
        bar_sync(6 + wg, 128);
        p1_consumer(a, sc2, sbase, wg, w, lane, zero);
        END_SYNC();
        TSTAMP(0, 30);
    }
}

constexpr int P2_B = 24576, P2_NB = 4;
constexpr int P2_A = 3072, P2_NA = 8;
constexpr int P2_XROW = C_DIM * 2;
constexpr int P2_OFF_A = P2_B * P2_NB;
constexpr int P2_OFF_X = P2_OFF_A + 3 * P2_NA * P2_A + 128;
constexpr int P2_LHALF = 2 * P2_NA * P2_A + 64;
constexpr int P2_XHALF = 32 * P2_XROW + 64;
constexpr int P2_OFF_GRN = P2_OFF_X + 64 * P2_XROW + 128;
constexpr int P2_OFF_BIAS = P2_OFF_GRN + HID * 2;
constexpr int P2_OFF_RED = P2_OFF_BIAS + C_DIM * 4;
constexpr int P2_OFF_BAR = P2_OFF_RED + 192;
constexpr int P2_SMEM = P2_OFF_BAR + (2 * P2_NB + 6 * P2_NA + 7) * 8;
#define P2_S1 16
constexpr int P2_S2 = 32;
constexpr int P2_NCL = NUM_CTAS / 2, P2_ITEMS = NT128 / P2_NCL, P2_SHARED = NT128 - P2_ITEMS * P2_NCL;
constexpr int P2_NPOS = 6 * 48 + P2_S1;
constexpr int P2_RAW = 24;
constexpr int P2_XC = 8 * P2_XROW;
#define P2_T0 4
#define P2_TL 8
#define P2_XP0 28
#define P2_XPN 13
#define P2_XPD 3
#define P2_CMP 0
#define P2_SLACK 0
#define P2_RAMP 2
#define P2_LATE 24
#define P2_GATE 1
#define P2_AH 2
__device__ __forceinline__ int p2_start(int n) { return n < 0 ? 0 : n / 3 * 48 + (n % 3 == 1 ? P2_S1 : n % 3 * (P2_S2 / 2)); }
__device__ __forceinline__ int p2_tile(int cl, int n) {
    return n == 0 ? NT128 - 1 - cl : n < 0 ? NT128 - 1 - P2_NCL - (cl >> 1) : cl + P2_NCL * (n - 1);
}

#define P2_EB 2
#define P2_EX 1
__device__ __forceinline__ void p2_epilogue(uint32_t (&acc0)[48], uint32_t (&acc1)[48], uint32_t up, uint32_t sx, uint32_t sb, int zero) {
    uint32_t v[12][3][4];
    auto load = [&](int t, int j) {
        if (t >= 12) return;
        uint32_t (&w)[4] = v[t][j];
        asm volatile("ld.shared.v4.u32 {%0,%1,%2,%3}, [%4];\n" : "=r"(w[0]), "=r"(w[1]), "=r"(w[2]), "=r"(w[3])
                     : "r"((j ? sx + (j - 1) * 4 * P2_XROW : sb) + t * 64) : "memory");
    };
    auto store = [&](int t, int r) {
        const uint32_t* w = (t < 6 ? acc0 : acc1) + 8 * (t % 6) + 4 * r;
        asm volatile("st.shared.v4.u32 [%4], {%0,%1,%2,%3};\n" ::"r"(w[0]), "r"(w[1]), "r"(w[2]), "r"(w[3]), "r"(sx + t * 64 + r * 4 * P2_XROW) : "memory");
    };
#pragma unroll
    for (int t = 0; t < P2_EB; t++) load(t, 0);
#pragma unroll
    for (int t = 0; t < 2 * P2_EX; t++) load(t >> 1, 1 + (t & 1));
#pragma unroll
    for (int t = 0; t < 12; t++) {
        load(t + P2_EX, 1);
        load(t + P2_EX, 2);
        load(t + P2_EB, 0);
        uint32_t* acc = (t < 6 ? acc0 : acc1) + 8 * (t % 6);
        uint32_t y[8];
#pragma unroll
        for (int e = 0; e < 8; e++) {
            y[e] = h2_add(acc[e], v[t][0][e >> 1]);
            y[e] = pack_bf16(h_lo(y[e]), h_hi(y[e]));
        }
#pragma unroll
        for (int e = 0; e < 8; e++) acc[(e & 1) * 4 + (e >> 1)] = bf2_fma(y[e], up, v[t][1 + (e & 1)][e >> 1]);
        store(t, 0);
        store(t, 1);
        sched_break(zero);
    }
    if (zero) {
#pragma unroll
        for (int t = 0; t < 24; t++) store(t >> 1, t & 1);
    }
}

__device__ __forceinline__ void p2_unpack(uint32_t (&u)[4], uint32_t o1, uint32_t o2, uint32_t o3) {
    u[2] = o1 & ~SPARE;
    u[1] = o2 & ~SPARE;
    u[3] = o3 & ~SPARE;
    const uint32_t t = bitsel(prmt(o1, o2, 0x6341), prmt(o1, o3, 0x6240) << 3, 0x38383838u);
    u[0] = bitsel(t, prmt(o2, o3, 0x7351) << 1, 0x80808080u) & ~SPARE;
}

__device__ __forceinline__ void p2_redo_sums(int warp, int lane) {
#pragma unroll 1
    for (int s = warp; s < 96; s += 12) {
        float t[2] = {0.f, 0.f};
#pragma unroll 1
        for (int tile = blockIdx.x; tile < 2 * NT128; tile += NUM_CTAS) {
            const uint32_t* p = reinterpret_cast<const uint32_t*>(reinterpret_cast<const uint8_t*>(g_h) + (size_t)(tile >> 1) * (2 * H_TILE) +
                                                                  (s >> 1) * H_STEP + (tile & 1) * H_HALF + (s & 1) * 1536) + lane * 4;
#pragma unroll
            for (int j = 0; j < 4; j++) {
                uint32_t u[4];
                p2_unpack(u, __ldcg(p + j), __ldcg(p + j + 128), __ldcg(p + j + 256));
#pragma unroll
                for (int c = 0; c < 4; c++) t[c >> 1] += h_lo(u[c]) * h_lo(u[c]) + h_hi(u[c]) * h_hi(u[c]);
            }
        }
#pragma unroll
        for (int r = 0; r < 2; r++) {
            const int ch = s * 16 + r * 8 + (lane >> 2);
            const float f = __ldcg(&g_scale[ch]) * UNCHOP;
            atomicAdd(&g_redo[ch], t[r] * f * f);
        }
    }
    __threadfence();
    __syncwarp();
    if (lane == 0) asm volatile("red.release.gpu.global.add.u32 [%0], 1;\n" ::"l"(&g_prog[2][0]) : "memory");
    flag_wait<true>(&g_prog[2][0], 12 * NUM_CTAS);
}

__global__ void __cluster_dims__(2, 1, 1) __launch_bounds__(512, 1)
pass2_kernel(const __nv_bfloat16* __restrict__ x, const __nv_bfloat16* __restrict__ grn_g, __nv_bfloat16* __restrict__ out, int zero) {
    extern __shared__ __align__(1024) uint8_t smem[];
    const uint32_t sbase = smem_u32(smem);
    const uint32_t bar_bfull = sbase + P2_OFF_BAR, bar_bempty = bar_bfull + P2_NB * 8;
    const uint32_t bar_afull = bar_bempty + P2_NB * 8, bar_aempty = bar_afull + 3 * P2_NA * 8;
    const uint32_t bar_xfull = bar_aempty + 3 * P2_NA * 8, bar_oready = bar_xfull + 24, s_pos = bar_oready + 24;
    int tid;
    asm volatile("mov.u32 %0, %%tid.x;\n" : "=r"(tid));
    const int warp = __shfl_sync(0xffffffffu, tid >> 5, 0), lane = tid & 31;
    const uint32_t rank = cluster_rank();
    const int cl = blockIdx.x >> 1, pair = cl >> 1;
    const int half = pair < P2_SHARED, fin = half && (cl & 1);
    const int k0 = (pair + 3 * (cl & 1)) % 6 * 8;
    const bool late = blockIdx.x >= P2_LATE;
    auto wait_pos = [&](int target) {
        int v;
        while (true) {
            asm volatile("ld.volatile.shared.u32 %0, [%1];\n" : "=r"(v) : "r"(s_pos) : "memory");
            if (v >= target) break;
            SAFE_BREAK;
            __nanosleep(100);
        }
    };

    TSTAMP(1, 0);
    if (tid == 384) {
        for (int i = 0; i < P2_NB; i++) {
            mbar_init(bar_bfull + i * 8, 1);
            mbar_init(bar_bempty + i * 8, 24);
        }
        for (int i = 0; i < 3 * P2_NA; i++) {
            mbar_init(bar_afull + i * 8, 1);
            mbar_init(bar_aempty + i * 8, 4);
        }
        for (int i = 0; i < 3; i++) {
            mbar_init(bar_xfull + i * 8, 2);
            mbar_init(bar_oready + i * 8, 4);
        }
        asm volatile("st.shared.u32 [%0], 0;\n" ::"r"(s_pos) : "memory");
        asm volatile("fence.mbarrier_init.release.cluster;\n" ::: "memory");
    }
    __syncthreads();
    cluster_sync_relaxed();

    if (warp >= 12) {
        reg_dec<32>();
        if (warp == 12) {
            const uint8_t* wsrc = reinterpret_cast<const uint8_t*>(g_w2img) + rank * (P2_B / 2);
            int kb = k0;
            gdc_wait();
            if (P2_GATE) bar_sync(5, 448);
#pragma unroll 1
            for (int p = 0; p < P2_NPOS; p++) {
                const int st = p & 3;
                if (p == P2_RAW) {
                    flag_wait<true>(&g_prog[1][0], NUM_CTAS);
                    asm volatile("fence.proxy.async.global;\n" ::: "memory");
                    wsrc += sizeof(g_w2img[0]);
                }
                const int idle = (p < P2_S1 || p >= 6 * 48) + (p < P2_S2 ? !half || p >= 24 : p >= 5 * 48 + P2_S2);
                mbar_wait(bar_bempty + st * 8, (~p >> 2) & 1);
                TR2(3, p, 0);
                if (elect_one()) {
                    const int len = P2_B / 2;
                    mbar_expect_tx(bar_bfull + st * 8, 2 * len);
                    bulk_g2s_mc(sbase + st * P2_B + rank * (P2_B / 2), wsrc + kb * P2_B, len, bar_bfull + st * 8, (uint16_t)3);
                    asm volatile("st.volatile.shared.u32 [%0], %1;\n" ::"r"(s_pos), "r"(p) : "memory");
                    if (rank == 0) asm volatile("red.relaxed.gpu.global.add.u32 [%0], 1;\n" ::"l"(&g_prog[0][0]) : "memory");
                    if (idle) asm volatile("mbarrier.arrive.shared::cta.b64 _, [%0], %1;\n" ::"r"(bar_bempty + st * 8), "r"(8 * idle) : "memory");
                }
                __syncwarp();
                if (++kb == 48) kb = 0;
            }
            mbar_wait(bar_bempty, 1);
            if (lane == 0) mbar_arrive(bar_bfull);
        } else if (warp == 13) {
            const int w = lane < 3 ? lane : 0;
            const uint32_t dst0 = sbase + P2_OFF_A + w * P2_NA * P2_A;
            const uint32_t bf = bar_afull + w * P2_NA * 8, be = bar_aempty + w * P2_NA * 8;
            int n = (w == 2 && half ? -1 : w) - 3, left = 0, u = 0, c = 0;
            const uint8_t* src = nullptr;
            bool act = lane < 3;
            gdc_wait();
            if (P2_GATE) bar_sync(5, 448);
            while (__any_sync(0xffffffffu, act)) {
                if (left == 0) {
                    n += 3;
                    left = n >= P2_ITEMS ? -1 : n < 0 ? 24 : 48;
                    u = (k0 + p2_start(n)) % 48;
                    src = reinterpret_cast<const uint8_t*>(g_h) + (size_t)p2_tile(cl, n) * (2 * H_TILE) + rank * H_HALF + u * H_STEP;
                }
                bool ok = act && mbar_test(be + ((c - 1) & 7) * 8, (~c >> 3) & 1);
                if (__any_sync(0xffffffffu, act && c < 16)) {
                    int v;
                    asm volatile("ld.volatile.shared.u32 %0, [%1];\n" : "=r"(v) : "r"(s_pos) : "memory");
                    ok = ok && c <= (n <= 0 ? 2 * v - P2_RAMP : c >= 16 ? c : v - p2_start(n) + 8);
                }
                if (ok) {
                    const int st = c & 7;
                    if (left > 0) {
                        mbar_expect_tx(bf + st * 8, P2_A);
                        bulk_g2s(dst0 + st * P2_A, src, P2_A, bf + st * 8);
                    } else {
                        mbar_arrive(bf + st * 8);
                        act = false;
                    }
                    src += H_STEP;
                    if (++u == 48) { u = 0; src -= 48 * H_STEP; }
                    c++;
                    left--;
                }
                SAFE_BREAK;
                if (!__any_sync(0xffffffffu, ok)) __nanosleep(100);
            }
        } else if (warp == 14) {
            const uint32_t sx = sbase + P2_OFF_X;
            size_t o = 0;
            int wp = 0;
            uint32_t par = 0;
            if (fin) {
#pragma unroll 1
                for (int c = lane * 16; c < 64 * P2_XROW + 128; c += 512) asm volatile("st.shared.v4.u32 [%0], {0, 0, 0, 0};\n" ::"r"(sx + c) : "memory");
                __syncwarp();
            }
            if (late) wait_pos(6);
#pragma unroll 1
            for (int n = -half; n <= P2_ITEMS; n++) {
                const int w = (n + 3) % 3, end = p2_start(n) + 48;
                const size_t on = (size_t)(2 * p2_tile(cl, n) + rank) * (64 * C_DIM * 2);
                const uint32_t xf = bar_xfull + w * 8;
                bool st = n + half > 0;
                const bool ld = n < P2_ITEMS - 1 && !(n < 0 && fin);
                if (n == P2_ITEMS - 1 && lane == 0) {
                    mbar_expect_tx(xf, 64 * C_DIM * 2);
#pragma unroll 1
                    for (int c = 4; c < 12; c++) {
                        if (c >= 8) {
                            mbar_wait(bar_aempty + ((2 * c - 1) & 7) * 8, 1);
                            mbar_wait(bar_aempty + ((2 * c) & 7) * 8, 1);
                        }
                        bulk_g2s(sbase + P2_OFF_A + (c & 3) * P2_XC + (c < 8 ? P2_LHALF : 0), reinterpret_cast<const uint8_t*>(x) + on + (c & 7) * P2_XC, P2_XC, xf);
                    }
                    mbar_arrive(xf);
                }
                if (st) {
                    mbar_wait(bar_oready + wp * 8, (par >> wp) & 1);
                    par ^= 1u << wp;
                }
                if (lane == 0) {
                    if (n < P2_ITEMS - 1) mbar_expect_tx(xf, ld ? 64 * C_DIM * 2 : 0);
                    const int t0 = (n ? p2_start(n - 1) + 48 : P2_S2) + (n == P2_ITEMS - 1 ? P2_TL : P2_T0), dt = end - (n == P2_ITEMS - 2 ? P2_CMP : 0) - t0;
                    int t = st ? 16 * t0 : -4096;
                    if ((n == 0 && half) || n == P2_ITEMS) {
                        if (fin && n == 0) {
                            flag_wait<true>(&g_half[pair][rank], 1);
                            asm volatile("fence.proxy.async.global;\n" ::: "memory");
                        }
#pragma unroll 1
                        for (int c = 0; c < 2; c++) {
                            uint8_t* dst = reinterpret_cast<uint8_t*>(out) + o + c * 32 * P2_XROW;
                            if (!fin || n) bulk_s2g(dst, n ? sbase + P2_OFF_A + c * P2_LHALF : sx + c * P2_XHALF, 32 * P2_XROW);
                            else asm volatile("cp.reduce.async.bulk.global.shared::cta.bulk_group.add.noftz.bf16 [%0], [%1], %2;\n"
                                              ::"l"(dst), "r"(sx + c * P2_XHALF), "r"(32 * P2_XROW) : "memory");
                        }
                        asm volatile("cp.async.bulk.commit_group;\n" ::: "memory");
                        if (!fin && n == 0) {
                            asm volatile("cp.async.bulk.wait_group 0;\nfence.proxy.async.global;\n" ::: "memory");
                            asm volatile("st.release.gpu.global.u32 [%0], 1;\n" ::"l"(&g_half[pair][rank]) : "memory");
                        }
                        st = false;
                    }
#pragma unroll 1
                    for (int c = 0; n < P2_ITEMS && c < 64 * P2_XROW; c += P2_XC, t += 2 * dt) {
                        const uint32_t sp = sx + c + (c >= 32 * P2_XROW ? 64 : 0);
                        wait_pos(t >> 4);
                        if (st) bulk_s2g(reinterpret_cast<uint8_t*>(out) + o + c, sp, P2_XC);
                        asm volatile("cp.async.bulk.commit_group;\n" ::: "memory");
                        if (ld) {
                            wait_pos((t + dt) >> 4);
                            asm volatile("cp.async.bulk.wait_group.read 0;\n" ::: "memory");
                            bulk_g2s(sp, reinterpret_cast<const uint8_t*>(x) + on + c, P2_XC, xf);
                        }
                    }
                    if (rank == 0 && n > 0 && n < P2_ITEMS - 2) flag_wait<false>(&g_prog[0][0], P2_NCL * (end + P2_SLACK));
                    if (n < P2_ITEMS - 1) mbar_arrive(xf);
                }
                __syncwarp();
                o = on;
                wp = w;
            }
            asm volatile("cp.async.bulk.wait_group.read 0;\n" ::: "memory");
        } else {
            if (blockIdx.x == 120) {
                gdc_wait();
                for (int i = lane; i < (LN_RING + 6) * 2; i += 32) (&g_flag[0][0][0])[i * 8] = 0;
                if (lane == 0) g_epoch++;
            }
            int t = 4 * P2_XP0;
#pragma unroll 1
            for (int n = 0; n < P2_ITEMS && lane == 0; n++) {
                const uint8_t* xn = reinterpret_cast<const uint8_t*>(x) + (size_t)(2 * p2_tile(cl, n) + rank) * (64 * C_DIM * 2);
#pragma unroll 1
                for (int c = 0; c < 16; c++, t += n < P2_XPN ? 4 : P2_XPD) {
                    wait_pos(t >> 2);
                    asm volatile("cp.async.bulk.prefetch.L2.global [%0], %1;\n" ::"l"(xn + c * (P2_XC / 2)), "r"(P2_XC / 2) : "memory");
                }
            }
        }
        __syncwarp();
        END_SYNC();
    } else {
        reg_inc<160>();
        const int wg = warp >> 2, w = warp & 3, g = lane >> 2, q = lane & 3;
        const uint32_t sx = sbase + P2_OFF_X + (g & 1) * P2_XHALF + (w * 8 + (g >> 1)) * P2_XROW + q * 16;
        const uint32_t af = bar_afull + wg * P2_NA * 8;
        const uint32_t s_a = sbase + P2_OFF_A + wg * P2_NA * P2_A + (lane >> 3) * 512 + (lane & 7) * 64 + ((w ^ ((lane & 7) >> 1)) << 4);
        uint32_t acc0[48], acc1[48], up;
        uint4 a[2][2];

        __nv_bfloat16 gg[4];
#pragma unroll
        for (int i = 0; i < 4; i++) gg[i] = grn_g[tid + 384 * i];
#pragma unroll 1
        for (int it = late; it < 2; it++) {
            float* s_red = reinterpret_cast<float*>(smem + P2_OFF_RED);
            float gx[7], part = 0.f;
            if (it) {
                TSTAMP(1, 27);
                gdc_wait();
                TSTAMP(1, 1);
            }
            float gy[7];
#pragma unroll
            for (int i = 0; i < 7; i++) {
                const float* p = &g_sums[0][i < 5 ? tid + 384 * i : HID + C_DIM + i - 5];
                asm volatile("ld.global.cg.f32 %0, [%1];\n" : "=f"(gx[i]) : "l"(p) : "memory");
                asm volatile("ld.global.cg.f32 %0, [%1];\n" : "=f"(gy[i]) : "l"(p + HID + 512) : "memory");
            }
            if (P2_GATE && it) bar_arrive(5, 448);
            const float bias = gx[4] + gy[4];
            const float gs = w2_scale(__float_as_uint(gx[5]) | __float_as_uint(gy[5]));
            if (it && gx[6] + gy[6] != 0.f) {
                p2_redo_sums(warp, lane);
#pragma unroll
                for (int i = 0; i < 4; i++) {
                    gx[i] = __ldcg(&g_redo[tid + 384 * i]);
                    gy[i] = 0.f;
                }
            }
            float mg = 0.f;
#pragma unroll
            for (int i = 0; i < 4; i++) {
                gx[i] = gx[i] + gy[i];
                gx[i] = __fsqrt_rn(gx[i] * (HSCALE * HSCALE) + 1e-6f);
                part += gx[i];
                gx[i] *= __bfloat162float(gg[i]);
                mg = fmaxf(mg, fabsf(gx[i]));
            }
#pragma unroll
            for (int o = 16; o > 0; o >>= 1) part += __shfl_xor_sync(0xffffffffu, part, o);
            const uint32_t mgw = __reduce_max_sync(0xffffffffu, __float_as_uint(mg));
            const uint32_t mbw = __reduce_max_sync(0xffffffffu, __float_as_uint(fabsf(bias)));
            TSTAMP(1, 26);
            if (lane == 0) *reinterpret_cast<float4*>(s_red + warp * 4) = make_float4(part, __uint_as_float(mgw), __uint_as_float(mbw), 0.f);
            bar_sync(1, 384);
            float tot = 0.f, mb = 0.f;
#pragma unroll
            for (int i = 0; i < 12; i++) {
                const float4 t = *reinterpret_cast<const float4*>(s_red + i * 4);
                tot += t.x;
                mg = fmaxf(mg, t.y);
                mb = fmaxf(mb, t.z);
            }
            const float inv = 1.0f / (tot * (1.0f / HID) + 1e-6f);
            const uint32_t ej = min((__float_as_uint(fmaxf(fmaf(mg, inv, 1.0f) * (HSCALE * UNCHOP), mb * gs * 0x1p-13f)) >> 23) + 1, 250u);
            const float dn = __uint_as_float((254u - ej) << 23);
            up = min(ej + 127u - (__float_as_uint(gs) >> 23), 254u) * 0x00800080u;
            reinterpret_cast<uint16_t*>(smem + P2_OFF_BIAS + C_DIM * 2)[tid] = 0;
            *reinterpret_cast<__half*>(smem + P2_OFF_BIAS + (tid >> 5) * 64 + (tid & 6) * 8 + (tid & 24) / 2 + (tid & 1) * 2) = __float2half_rn(bias * gs * dn);
#pragma unroll
            for (int i = 0; i < 4; i++) {
                const int k = tid + 384 * i;
                *reinterpret_cast<__half*>(smem + P2_OFF_GRN + (k >> 4) * 32 + (k & 6) * 4 + (k & 8) / 2 + (k & 1) * 2) =
                    __float2half_rn(fmaf(gx[i], inv, 1.0f) * (HSCALE * UNCHOP * dn));
            }
            TSTAMP(1, 25);
            bar_sync(1, 384);
        }
        TSTAMP(1, 28);
        if (wg == 1) {
            constexpr int N = sizeof(g_w2img[0]) / 16, PER = (N + NUM_CTAS - 1) / NUM_CTAS;
            uint4 v[5];
#pragma unroll
            for (int i = 0; i < 5; i++) v[i] = __ldcg(&g_w2img[0][min(blockIdx.x * PER + (tid & 127) + 128 * i, N - 1)]);
#pragma unroll
            for (int i = 0; i < 5; i++) {
                const int j = min(blockIdx.x * PER + (tid & 127) + 128 * i, N - 1);
                const uint32_t* t = reinterpret_cast<const uint32_t*>(smem + P2_OFF_GRN + (j / 768) * 32 + (j & 8) / 2);
                auto sc = [&](uint32_t u, int e) { return (h2_mul(u, t[2 * e]) + 0x00040004u) & 0xfff8fff8u; };
                g_w2img[1][j] = make_uint4(sc(v[i].x, 0), sc(v[i].y, 1), sc(v[i].z, 2), sc(v[i].w, 3));
            }
            asm volatile("fence.proxy.async.global;\n" ::: "memory");
            bar_sync(2, 128);
            if (tid == 128) asm volatile("fence.acq_rel.gpu;\nred.release.gpu.global.add.u32 [%0], 1;\n" ::"l"(&g_prog[1][0]) : "memory");
        }

        const int who = __shfl_sync(0xffffffffu, lane == 2 ? 0 : lane < 2 ? 1 : 2, lane);
        const uint32_t rel0 = who ? mapa(bar_bempty, lane & 1) : mapa(bar_aempty + wg * P2_NA * 8, rank), rel1 = rel0 + (who ? 0 : 32);
        auto publish = [&]() {
            asm volatile("fence.proxy.async.shared::cta;\n" ::: "memory");
            __syncwarp();
            if (who == 0) mbar_arrive(bar_oready + wg * 8);
        };
        bool ok_a, pend = false;
        uint32_t pa = 0, s_t;
        auto fetch = [&](int j, bool raw) {
            uint32_t o[6], u0[4], u1[4];
            uint2 t0 = make_uint2(0, 0), t1 = t0;
            if (raw) {
                asm volatile("ld.shared.v2.u32 {%0,%1}, [%2];\n" : "=r"(t0.x), "=r"(t0.y) : "r"(s_t + j * 64) : "memory");
                asm volatile("ld.shared.v2.u32 {%0,%1}, [%2];\n" : "=r"(t1.x), "=r"(t1.y) : "r"(s_t + j * 64 + 32) : "memory");
            }
            const bool ok_b = mbar_test(bar_bfull + (j & 3) * 8, j >> 2);
            if (j == 7) pa ^= 1;
            ok_a = mbar_test(af + ((j + 1) & 7) * 8, pa);
            asm volatile("ldmatrix.sync.aligned.m8n8.x4.trans.shared.b16 {%0,%1,%2,%3}, [%4];\n"
                         : "=r"(o[0]), "=r"(o[1]), "=r"(o[2]), "=r"(o[3]) : "r"(s_a + j * P2_A) : "memory");
            asm volatile("ldmatrix.sync.aligned.m8n8.x2.trans.shared.b16 {%0,%1}, [%2];\n"
                         : "=r"(o[4]), "=r"(o[5]) : "r"(s_a + j * P2_A + 2048) : "memory");
            p2_unpack(u0, o[0], o[1], o[2]);
            p2_unpack(u1, o[3], o[4], o[5]);
            if (raw) {
                u0[0] = h2_mul(u0[0], t0.x); u0[1] = h2_mul(u0[1], t0.x); u0[2] = h2_mul(u0[2], t0.y); u0[3] = h2_mul(u0[3], t0.y);
                u1[0] = h2_mul(u1[0], t1.x); u1[1] = h2_mul(u1[1], t1.x); u1[2] = h2_mul(u1[2], t1.y); u1[3] = h2_mul(u1[3], t1.y);
            }
            a[j & 1][0] = make_uint4(u0[0], u0[1], u0[2], u0[3]);
            a[j & 1][1] = make_uint4(u1[0], u1[1], u1[2], u1[3]);
            if (!ok_b) mbar_wait(bar_bfull + (j & 3) * 8, j >> 2);
        };
        auto table = [&](int pos) { s_t = sbase + P2_OFF_GRN + q * 8 + (k0 + pos) % 48 * 64; };
        const uint32_t db0 = (uint32_t)make_desc(sbase, 128, 256);
        auto block8 = [&](bool raw, int pos, int thr0, int mode) {
#pragma unroll
            for (int j = 0; j < 8; j++) {
                const uint32_t db = db0 + (j & 3) * (P2_B / 16);
                if (j == 8 - P2_AH && mode == 1) bar_sync(4, 384);
                TR2(wg, pos + j, 0);
                wg_fence();
                mma_rs_n192(acc0, a[j & 1][0], db);
                mma_rs_n192(acc1, a[j & 1][0], db + 384);
                mma_rs_n192(acc0, a[j & 1][1], db + 768);
                mma_rs_n192(acc1, a[j & 1][1], db + 768 + 384);
                wg_commit();
                if (j == 7 && mode == 2) bar_arrive(4, 384);
                const uint32_t rel = ((j - 1) & 4 ? rel1 : rel0) + ((j - 1) & 3) * 8;
                TR2(wg, pos + j, 1);
                wg_wait<1>();
                TR2(wg, pos + j, 2);
                if (who < (j ? 2 : thr0)) mbar_arrive_cluster(rel);
                if (!ok_a) {
                    if (j == 0 && pend) { publish(); pend = false; }
                    mbar_wait(af + ((j + 1) & 7) * 8, pa);
                }
                TR2(wg, pos + j, 3);
                if (raw && j == 7) table(pos + 8);
                fetch((j + 1) & 7, raw && (j < 7 || pos + 8 < P2_RAW));
            }
        };
        int n = wg == 2 && half ? -1 : wg, pos = p2_start(n);
        uint32_t px = 0;
        wait_pos(pos);
        mbar_wait(af, 0);
        table(pos);
        fetch(0, pos < P2_RAW);
#pragma unroll 1
        for (;; n += 3) {
            TSTAMP(1, 2 + n);
            const int end = pos + (n < 0 ? 24 : 48);
#pragma unroll
            for (int i = 0; i < 48; i += 2) {
                asm volatile("mov.b64 {%0, %1}, 0;\n" : "=r"(acc0[i]), "=r"(acc0[i + 1]));
                asm volatile("mov.b64 {%0, %1}, 0;\n" : "=r"(acc1[i]), "=r"(acc1[i + 1]));
            }
            int thr = 1;
#pragma unroll 1
            for (; pos < P2_RAW; pos += 8, thr = 2) block8(true, pos, thr, 0);
#pragma unroll 1
            for (; pos < end; pos += 8, thr = 2) {
                const int e = pos + 8, r = e % 48;
                block8(false, pos, thr, e < 48 || e > 256 || (r != 0 && r != P2_S1 && r != P2_S2) ? 0 : e == end ? 2 : 1);
            }
            TR2(wg, pos - 1, 4);
            wg_wait<0>();
            TR2(wg, pos - 1, 5);
            if (who == 1) mbar_arrive_cluster(rel0 + 24);
            mbar_wait(bar_xfull + wg * 8, px);
            TR2(wg, pos - 1, 6);
            px ^= 1;
            __syncwarp();
            p2_epilogue(acc0, acc1, up, n == P2_ITEMS - 1 ? sx + (P2_OFF_A - P2_OFF_X) + (g & 1) * (P2_LHALF - P2_XHALF) : sx, sbase + P2_OFF_BIAS + q * 16 + (n < 0 && fin ? C_DIM * 2 : 0), zero);
            TR2(wg, pos - 1, 7);
            if (n + 3 >= P2_ITEMS) { publish(); break; }
            if (n < 0) {
                publish();
                pos = P2_S2;
                wait_pos(pos);
                mbar_wait(bar_bfull, 0);
            } else {
                pend = true;
                ok_a = false;
            }
        }
        TSTAMP(1, 29);
        END_SYNC();
        TSTAMP(1, 30);
    }
}

}

extern "C" void kernel_launch(void* const* d_in, const int* in_sizes, int n_in, void* d_out, int out_size) {
    const __nv_bfloat16* x = (const __nv_bfloat16*)d_in[0];
    const __nv_bfloat16* dw = (const __nv_bfloat16*)d_in[1];
    const __nv_bfloat16* w1 = (const __nv_bfloat16*)d_in[2];
    const __nv_bfloat16* w2 = (const __nv_bfloat16*)d_in[3];
    const __nv_bfloat16* grn_g = (const __nv_bfloat16*)d_in[4];
    const __nv_bfloat16* grn_b = (const __nv_bfloat16*)d_in[5];
    __nv_bfloat16* out = (__nv_bfloat16*)d_out;

    cudaFuncSetAttribute(pass1_kernel, cudaFuncAttributeMaxDynamicSharedMemorySize, P1_SMEM);
    cudaFuncSetAttribute(pass2_kernel, cudaFuncAttributeMaxDynamicSharedMemorySize, P2_SMEM);

    typedef CUresult (*EncodeFn)(CUtensorMap*, CUtensorMapDataType, cuuint32_t, void*, const cuuint64_t*, const cuuint64_t*,
                                 const cuuint32_t*, const cuuint32_t*, CUtensorMapInterleave, CUtensorMapSwizzle,
                                 CUtensorMapL2promotion, CUtensorMapFloatOOBfill);
    static EncodeFn encode = nullptr;
    if (!encode) {
        cudaDriverEntryPointQueryResult qres;
        cudaGetDriverEntryPoint("cuTensorMapEncodeTiled", (void**)&encode, cudaEnableDefault, &qres);
    }
    CUtensorMap wmap;
    const cuuint64_t gdim[2] = {HID, C_DIM};
    const cuuint64_t gstr[1] = {HID * 2};
    const cuuint32_t box[2] = {64, 192}, estr[2] = {1, 1};
    CUresult er = encode(&wmap, CU_TENSOR_MAP_DATA_TYPE_BFLOAT16, 2, (void*)w1, gdim, gstr, box, estr, CU_TENSOR_MAP_INTERLEAVE_NONE,
           CU_TENSOR_MAP_SWIZZLE_128B, CU_TENSOR_MAP_L2_PROMOTION_L2_128B, CU_TENSOR_MAP_FLOAT_OOB_FILL_NONE);
    if (er != CUDA_SUCCESS) printf("tensor map encode failed %d\n", (int)er);

    pass1_kernel<<<NUM_CTAS, 512, P1_SMEM>>>(wmap, x, dw, w2, grn_b, 0);

    cudaLaunchAttribute attr[1];
    attr[0].id = cudaLaunchAttributeProgrammaticStreamSerialization;
    attr[0].val.programmaticStreamSerializationAllowed = 1;
    cudaLaunchConfig_t cfg = {};
    cfg.gridDim = dim3(NUM_CTAS);
    cfg.stream = 0;
    cfg.attrs = attr;
    cfg.numAttrs = 1;
    cfg.blockDim = dim3(512);
    cfg.dynamicSmemBytes = P2_SMEM;
    cudaLaunchKernelEx(&cfg, pass2_kernel, x, grn_g, out, 0);
}
```

```cpp
#include <cuda.h>
#include <cuda_runtime.h>
#include <cuda_bf16.h>
#include <cuda_fp16.h>
#include <stdint.h>
#include <stdio.h>

namespace {

constexpr int M_TOTAL = 384 * 384;
constexpr int C_DIM   = 384;
constexpr int HID     = 1536;
constexpr int NT128   = M_TOTAL / 128;
constexpr int NUM_CTAS = 132;

constexpr int NGRP = 22, GRP_CTAS = 6;
constexpr int LN_STEP = NUM_CTAS / 4, LN_RING = 2 * LN_STEP;
constexpr int LN_TILE = 128 * C_DIM * 2;
constexpr int H_TILE = 64 * HID * 3 / 2;
constexpr int H_HALF = 3072, H_STEP = 6144;

__device__ __align__(1024) uint4 g_h[(size_t)M_TOTAL * HID * 3 / 32];
__device__ __align__(1024) uint4 g_ln[LN_RING * LN_TILE / 16];
__device__ __align__(1024) uint4 g_w2img[2][HID * C_DIM * 2 / 16];
__device__ __align__(16) float g_sums[2][HID + 512];
__device__ float g_scale[HID];
__device__ float g_redo[HID];
__device__ unsigned g_epoch;
__device__ __align__(128) unsigned g_prog[3][32];
__device__ __align__(128) unsigned g_half[32][2];
__device__ unsigned g_flag[LN_RING + 6][2][8];
#define TSTAMP(k, i)
#define TRACE(wg, pos, i)
#define TRACEW(pos, i)

#define TR2(wg, pos, i)
__host__ __device__ __forceinline__ int perm32(int n) {
    return (n & ~31) | (((n >> 1) & 3) << 3) | (((n >> 3) & 3) << 1) | (n & 1);
}

__device__ __forceinline__ uint32_t smem_u32(const void* p) { return (uint32_t)__cvta_generic_to_shared(p); }

__device__ __forceinline__ void mbar_init(uint32_t bar, uint32_t count) {
    asm volatile("mbarrier.init.shared::cta.b64 [%0], %1;\n" ::"r"(bar), "r"(count) : "memory");
}
__device__ __forceinline__ void mbar_expect_tx(uint32_t bar, uint32_t bytes) {
    asm volatile("mbarrier.arrive.expect_tx.shared::cta.b64 _, [%0], %1;\n" ::"r"(bar), "r"(bytes) : "memory");
}
__device__ __forceinline__ void mbar_arrive(uint32_t bar) {
    asm volatile("mbarrier.arrive.shared::cta.b64 _, [%0];\n" ::"r"(bar) : "memory");
}
__device__ __forceinline__ void mbar_arrive_cluster(uint32_t bar_cluster_addr) {
    asm volatile("mbarrier.arrive.shared::cluster.b64 _, [%0];\n" ::"r"(bar_cluster_addr) : "memory");
}
#define SAFE_BREAK
__device__ __forceinline__ void mbar_wait(uint32_t bar, uint32_t parity) {
    asm volatile(
        "{\n"
        ".reg .pred p;\n"
        "LAB_WAIT:\n"
        "mbarrier.try_wait.parity.shared::cta.b64 p, [%0], %1;\n"
        "@!p bra LAB_WAIT;\n"
        "}\n" ::"r"(bar), "r"(parity) : "memory");
}
__device__ __forceinline__ bool mbar_test(uint32_t bar, uint32_t parity) {
    uint32_t ok;
    asm volatile("{\n.reg .pred p;\n"
                 "mbarrier.test_wait.parity.shared::cta.b64 p, [%1], %2;\n"
                 "selp.u32 %0, 1, 0, p;\n}\n" : "=r"(ok) : "r"(bar), "r"(parity) : "memory");
    return ok != 0;
}
__device__ __forceinline__ uint32_t mapa(uint32_t addr, uint32_t rank) {
    uint32_t r;
    asm volatile("mapa.shared::cluster.u32 %0, %1, %2;\n" : "=r"(r) : "r"(addr), "r"(rank));
    return r;
}
__device__ __forceinline__ void bulk_g2s(uint32_t dst, const void* src, uint32_t bytes, uint32_t bar) {
    asm volatile("cp.async.bulk.shared::cluster.global.mbarrier::complete_tx::bytes [%0], [%1], %2, [%3];\n"
                 ::"r"(dst), "l"(src), "r"(bytes), "r"(bar) : "memory");
}
__device__ __forceinline__ void bulk_g2s_mc(uint32_t dst, const void* src, uint32_t bytes, uint32_t bar, uint16_t mask) {
    asm volatile("cp.async.bulk.shared::cluster.global.mbarrier::complete_tx::bytes.multicast::cluster [%0], [%1], %2, [%3], %4;\n"
                 ::"r"(dst), "l"(src), "r"(bytes), "r"(bar), "h"(mask) : "memory");
}
__device__ __forceinline__ void tma2(uint32_t dst, const CUtensorMap* map, int c0, int c1, uint32_t bar) {
    asm volatile("cp.async.bulk.tensor.2d.shared::cluster.global.tile.mbarrier::complete_tx::bytes [%0], [%1, {%2, %3}], [%4];\n"
                 ::"r"(dst), "l"(map), "r"(c0), "r"(c1), "r"(bar) : "memory");
}
template <bool ACQ>
__device__ __forceinline__ uint32_t flag_wait(const unsigned* p, unsigned target) {
    unsigned v, n = 0;
    do {
        if (ACQ) asm volatile("ld.acquire.gpu.global.u32 %0, [%1];\n" : "=r"(v) : "l"(p) : "memory");
        else asm volatile("ld.relaxed.gpu.global.u32 %0, [%1];\n" : "=r"(v) : "l"(p) : "memory");
        n++;
    } while (v < target);
    return n == 1;
}
__device__ __forceinline__ void ldsm4t(uint32_t (&r)[4], uint32_t addr) {
    asm volatile("ldmatrix.sync.aligned.m8n8.x4.trans.shared.b16 {%0,%1,%2,%3}, [%4];\n"
                 : "=r"(r[0]), "=r"(r[1]), "=r"(r[2]), "=r"(r[3]) : "r"(addr) : "memory");
}
__device__ __forceinline__ void bulk_s2g(void* dst, uint32_t src, uint32_t bytes) {
    asm volatile("cp.async.bulk.global.shared::cta.bulk_group [%0], [%1], %2;\n" ::"l"(dst), "r"(src), "r"(bytes) : "memory");
}
__device__ __forceinline__ void cluster_sync() {
    asm volatile("barrier.cluster.arrive.aligned;\nbarrier.cluster.wait.aligned;\n" ::: "memory");
}
__device__ __forceinline__ void cluster_sync_relaxed() {
    asm volatile("barrier.cluster.arrive.relaxed.aligned;\nbarrier.cluster.wait.aligned;\n" ::: "memory");
}
#define END_SYNC cluster_sync_relaxed
__device__ __forceinline__ void gdc_wait() { asm volatile("griddepcontrol.wait;\n" ::: "memory"); }
__device__ __forceinline__ void gdc_launch() { asm volatile("griddepcontrol.launch_dependents;\n" ::: "memory"); }
__device__ __forceinline__ uint32_t cluster_rank() {
    uint32_t r;
    asm volatile("mov.u32 %0, %%cluster_ctarank;\n" : "=r"(r));
    return r;
}
__device__ __forceinline__ bool elect_one() {
    uint32_t pred;
    asm volatile("{\n.reg .pred p;\nelect.sync _|p, 0xffffffff;\nselp.u32 %0, 1, 0, p;\n}\n" : "=r"(pred));
    return pred != 0;
}
__device__ __forceinline__ void wg_fence() { asm volatile("wgmma.fence.sync.aligned;\n" ::: "memory"); }
__device__ __forceinline__ void wg_commit() { asm volatile("wgmma.commit_group.sync.aligned;\n" ::: "memory"); }
template <int N> __device__ __forceinline__ void wg_wait() {
    asm volatile("wgmma.wait_group.sync.aligned %0;\n" ::"n"(N) : "memory");
}
template <int R> __device__ __forceinline__ void reg_inc() { asm volatile("setmaxnreg.inc.sync.aligned.u32 %0;\n" ::"n"(R)); }
template <int R> __device__ __forceinline__ void reg_dec() { asm volatile("setmaxnreg.dec.sync.aligned.u32 %0;\n" ::"n"(R)); }
__device__ __forceinline__ void bar_sync(int id, int n) { asm volatile("bar.sync %0, %1;\n" ::"r"(id), "r"(n) : "memory"); }
__device__ __forceinline__ void bar_arrive(int id, int n) { asm volatile("bar.arrive %0, %1;\n" ::"r"(id), "r"(n) : "memory"); }

__device__ __forceinline__ uint64_t make_desc(uint32_t saddr, uint32_t lbo, uint32_t sbo) {
    return (uint64_t)((saddr & 0x3FFFF) >> 4) | ((uint64_t)(lbo >> 4) << 16) | ((uint64_t)(sbo >> 4) << 32);
}

__device__ __forceinline__ void stg128_cs(void* p, uint32_t a, uint32_t b, uint32_t c, uint32_t d) {
#define H_ST "st.global.cs.v4.u32"
    asm volatile(H_ST " [%0], {%1,%2,%3,%4};\n" ::"l"(p), "r"(a), "r"(b), "r"(c), "r"(d) : "memory");
}
__device__ __forceinline__ uint32_t pack_bf16(float lo, float hi) {
    uint32_t r;
    asm("cvt.rn.bf16x2.f32 %0, %1, %2;\n" : "=r"(r) : "f"(hi), "f"(lo));
    return r;
}
__device__ __forceinline__ float bf_lo(uint32_t v) { return __uint_as_float(v << 16); }
__device__ __forceinline__ float bf_hi(uint32_t v) { return __uint_as_float(v & 0xffff0000u); }
__device__ __forceinline__ uint32_t bf2_mul(uint32_t a, uint32_t b) {
    uint32_t r;
    asm("mul.rn.bf16x2 %0, %1, %2;\n" : "=r"(r) : "r"(a), "r"(b));
    return r;
}
__device__ __forceinline__ uint32_t bf2_fma(uint32_t a, uint32_t b, uint32_t c) {
    uint32_t r;
    asm("fma.rn.bf16x2 %0, %1, %2, %3;\n" : "=r"(r) : "r"(a), "r"(b), "r"(c));
    return r;
}
__device__ __forceinline__ uint32_t bf2_add(uint32_t a, uint32_t b) {
    uint32_t r;
    asm("add.rn.bf16x2 %0, %1, %2;\n" : "=r"(r) : "r"(a), "r"(b));
    return r;
}
__device__ __forceinline__ uint32_t h2_mul(uint32_t a, uint32_t b) {
    uint32_t r;
    asm("mul.rn.f16x2 %0, %1, %2;\n" : "=r"(r) : "r"(a), "r"(b));
    return r;
}
__device__ __forceinline__ uint32_t h2_fma(uint32_t a, uint32_t b, uint32_t c) {
    uint32_t r;
    asm("fma.rn.f16x2 %0, %1, %2, %3;\n" : "=r"(r) : "r"(a), "r"(b), "r"(c));
    return r;
}
__device__ __forceinline__ uint32_t h2_add(uint32_t a, uint32_t b) {
    uint32_t r;
    asm("add.rn.f16x2 %0, %1, %2;\n" : "=r"(r) : "r"(a), "r"(b));
    return r;
}
__device__ __forceinline__ uint32_t pack_f16(float lo, float hi) {
    uint32_t r;
    asm("cvt.rn.f16x2.f32 %0, %1, %2;\n" : "=r"(r) : "f"(hi), "f"(lo));
    return r;
}
__device__ __forceinline__ float h_lo(uint32_t v) { return __low2float(*reinterpret_cast<const __half2*>(&v)); }
__device__ __forceinline__ float h_hi(uint32_t v) { return __high2float(*reinterpret_cast<const __half2*>(&v)); }
__device__ __forceinline__ uint32_t bf2_to_h2(uint32_t v) { return (v & 0x7fff7fffu) * 7u + v; }
__device__ __forceinline__ uint32_t prmt(uint32_t a, uint32_t b, uint32_t sel) {
    uint32_t r;
    asm("prmt.b32 %0, %1, %2, %3;\n" : "=r"(r) : "r"(a), "r"(b), "r"(sel));
    return r;
}
__device__ __forceinline__ uint32_t bitsel(uint32_t a, uint32_t b, uint32_t m) {
    uint32_t r;
    asm("lop3.b32 %0, %1, %2, %3, 0xd8;\n" : "=r"(r) : "r"(a), "r"(b), "r"(m));
    return r;
}
constexpr float KAPPA = 0.3292034911525734f;
constexpr uint32_t GELU_C2 = 0x40d940d9u;
constexpr float HSCALE = 1.0f / (2.0f * KAPPA);
__device__ __forceinline__ float w2_scale(uint32_t m) { return __uint_as_float((257u - max(m >> 23, 16u)) << 23); }
__device__ __forceinline__ void sched_break(int zero) {
    asm volatile("{\n.reg .pred p;\nsetp.ne.s32 p, %0, 0;\nSB_LOOP:\n@p nanosleep.u32 1;\n@p bra SB_LOOP;\n}\n" ::"r"(zero));
}

#define ACC8(d, o) "+r"(d[o + 0]), "+r"(d[o + 1]), "+r"(d[o + 2]), "+r"(d[o + 3]), "+r"(d[o + 4]), "+r"(d[o + 5]), "+r"(d[o + 6]), "+r"(d[o + 7])

__device__ __forceinline__ void mma_rs_n128(uint32_t (&d)[32], const uint32_t (&a)[4], uint32_t desc, int scale_d) {
    asm volatile(
        "{\n.reg .pred p;\n.reg .b64 db;\nsetp.ne.b32 p, %37, 0;\nmov.b64 db, {%36, 0x40000040};\n"
        "wgmma.mma_async.sync.aligned.m64n128k16.f16.f16.f16 "
        "{%0,%1,%2,%3,%4,%5,%6,%7,%8,%9,%10,%11,%12,%13,%14,%15,"
        "%16,%17,%18,%19,%20,%21,%22,%23,%24,%25,%26,%27,%28,%29,%30,%31},"
        "{%32,%33,%34,%35}, db, p, 1, 1, 0;\n}\n"
        : ACC8(d, 0), ACC8(d, 8), ACC8(d, 16), ACC8(d, 24)
        : "r"(a[0]), "r"(a[1]), "r"(a[2]), "r"(a[3]), "r"(desc), "r"(scale_d));
}

__device__ __forceinline__ void mma_ss_n128(uint32_t (&d)[32], uint32_t da, uint32_t db, int scale_d) {
    asm volatile(
        "{\n.reg .pred p;\n.reg .b64 da, db;\nsetp.ne.b32 p, %34, 0;\nmov.b64 da, {%32, 0x40000040};\nmov.b64 db, {%33, 0x40000040};\n"
        "wgmma.mma_async.sync.aligned.m64n128k16.f16.f16.f16 "
        "{%0,%1,%2,%3,%4,%5,%6,%7,%8,%9,%10,%11,%12,%13,%14,%15,"
        "%16,%17,%18,%19,%20,%21,%22,%23,%24,%25,%26,%27,%28,%29,%30,%31},"
        "da, db, p, 1, 1, 1, 0;\n}\n"
        : ACC8(d, 0), ACC8(d, 8), ACC8(d, 16), ACC8(d, 24)
        : "r"(da), "r"(db), "r"(scale_d));
}

__device__ __forceinline__ void mma_rs_n192(uint32_t (&d)[48], const uint4& a, uint32_t db) {
    asm volatile(
        "{\n.reg .b64 db;\nmov.b64 db, {%52, 16};\n"
        "wgmma.mma_async.sync.aligned.m64n192k16.f16.f16.f16 "
        "{%0,%1,%2,%3,%4,%5,%6,%7,%8,%9,%10,%11,%12,%13,%14,%15,"
        "%16,%17,%18,%19,%20,%21,%22,%23,%24,%25,%26,%27,%28,%29,%30,%31,"
        "%32,%33,%34,%35,%36,%37,%38,%39,%40,%41,%42,%43,%44,%45,%46,%47},"
        "{%48,%49,%50,%51}, db, 1, 1, 1, 0;\n}\n"
        : ACC8(d, 0), ACC8(d, 8), ACC8(d, 16), ACC8(d, 24), ACC8(d, 32), ACC8(d, 40)
        : "r"(a.x), "r"(a.y), "r"(a.z), "r"(a.w), "r"(db));
}

#define P1_SPLIT 5
#define P1_PACE 1
constexpr int P1_SLOT = LN_TILE / 6, P1_NST = 6;
constexpr int P1_W = 64 * C_DIM * 2;
constexpr int P1_X = 32 * C_DIM * 2;
constexpr int P1_OFF_W = LN_TILE;
constexpr int P1_OFF_X = P1_OFF_W + 2 * P1_W;
constexpr int P1_OFF_BAR = P1_OFF_X + P1_X;
constexpr int P1_OFF_TILE = P1_OFF_BAR + (2 * P1_NST + 4 + 4 + 4) * 8;
constexpr int P1_OFF_EX = P1_OFF_TILE + 64;
constexpr int P1_OFF_DW = P1_OFF_EX + 256 * 4;
constexpr int P1_SMEM = P1_OFF_DW + C_DIM * 2;

__device__ __forceinline__ float rsqrt_fast(float x) {
    float r;
    asm("rsqrt.approx.ftz.f32 %0, %1;\n" : "=f"(r) : "f"(x));
    return r;
}
__device__ __forceinline__ float row_sum(const uint32_t (&c)[4]) {
    const uint32_t u = bf2_add(bf2_add(c[0], c[1]), bf2_add(c[2], c[3]));
    float s = bf_lo(u) + bf_hi(u);
#pragma unroll
    for (int o = 1; o < 8; o <<= 1) s += __shfl_xor_sync(0xffffffffu, s, o);
    return s;
}
__device__ __forceinline__ uint32_t pace(uint32_t bar, uint32_t off, uint32_t val, uint32_t after, int zero) {
    asm volatile(
        "{\n.reg .pred p, q;\n.reg .b32 par;\n"
        "lop3.b32 par, %4, %2, %3, 0xea;\n"
        "setp.eq.u32 q, par, 0;\n"
        "mov.pred p, 0;\n"
        "@q mbarrier.test_wait.parity.shared::cta.b64 p, [%1], par;\n"
        "selp.u32 par, 1, 0, p;\n"
        "@q mbarrier.try_wait.parity.shared::cta.b64 p, [%1], par, 1000;\n"
        "@p or.b32 %0, %0, %2;\n"
        "}\n" : "+r"(val) : "r"(bar), "r"(zero), "r"(off), "r"(after));
    return val;
}
template <int PACE, int R>
__device__ __forceinline__ void ln_rows(uint32_t (&v)[R][6][4], const uint32_t (&d)[6][4], uint32_t bar, uint32_t off, int zero,
                                        uint32_t bar_read) {
    const float inv = 1.0f / C_DIM;
    uint32_t c[R][4], nm[R];
    float e[R], r[R], er[R];
    bool big = false;
#pragma unroll
    for (int p = 0; p < R; p++) {
#pragma unroll
        for (int i = 0; i < 6; i++)
#pragma unroll
            for (int k = 0; k < 4; k++) c[p][k] = bf2_fma(v[p][i][k], d[i][k], i ? c[p][k] : 0);
        const float m = row_sum(c[p]) * inv;
        nm[p] = pack_bf16(-m, -m);
        e[p] = m + bf_lo(nm[p]);
    }
    if (bar_read) mbar_arrive(bar_read + (nm[0] & zero));
    if (PACE & 1) nm[0] = pace(bar, off, nm[0], nm[0], zero);
#pragma unroll
    for (int p = 0; p < R; p++) {
#pragma unroll
        for (int i = 0; i < 6; i++) {
#pragma unroll
            for (int k = 0; k < 4; k++) {
                v[p][i][k] = bf2_fma(v[p][i][k], d[i][k], nm[p]);
                c[p][k] = i ? bf2_fma(v[p][i][k], v[p][i][k], c[p][k]) : bf2_mul(v[p][i][k], v[p][i][k]);
            }
        }
        r[p] = KAPPA * rsqrt_fast(fmaxf(fmaf(-e[p], e[p], row_sum(c[p]) * inv), 0.f) + 1e-5f);
        er[p] = -e[p] * r[p] * 0x1p-112f;
        big |= r[p] < 0x1p-8f;
    }
    if (__any_sync(0xffffffffu, big)) {
#pragma unroll
        for (int p = 0; p < R; p++) {
            const uint32_t p2 = __float_as_uint(r[p]) & 0x7f800000u;
            r[p] = __uint_as_float((__float_as_uint(r[p]) & 0x007fffffu) | 0x3f800000u);
#pragma unroll
            for (int i = 0; i < 6; i++)
#pragma unroll
                for (int k = 0; k < 4; k++) v[p][i][k] = bf2_mul(v[p][i][k], p2 | p2 >> 16);
        }
    }
#pragma unroll
    for (int p = 0; p < R; p++) {
        uint32_t rs = pack_bf16(r[p] * 0x1p-112f, r[p] * 0x1p-112f);
        const uint32_t sh = pack_bf16(er[p], er[p]);
        if (PACE & 2) rs = pace(bar, off, rs, sh, zero);
#pragma unroll
        for (int i = 0; i < 6; i++)
#pragma unroll
            for (int k = 0; k < 4; k++) v[p][i][k] = bf2_to_h2(bf2_fma(v[p][i][k], rs, sh));
    }
}

template <int R>
__device__ __forceinline__ uint32_t gelu2(uint32_t a, uint32_t sc2) {
    uint32_t y, t;
    if (R) asm("{\n.reg .b16 l, h;\n.reg .b32 f;\nmov.b32 {l, h}, %2;\nmov.b32 f, {h, h};\nmul.rn.f16x2 %0, %1, f;\n}\n" : "=r"(y) : "r"(a), "r"(sc2));
    else asm("{\n.reg .b16 l, h;\n.reg .b32 f;\nmov.b32 {l, h}, %2;\nmov.b32 f, {l, l};\nmul.rn.f16x2 %0, %1, f;\n}\n" : "=r"(y) : "r"(a), "r"(sc2));
    asm("tanh.approx.f16x2 %0, %1;\n" : "=r"(t) : "r"(h2_mul(y, h2_fma(y, y, GELU_C2))));
    return h2_fma(a, t, a);
}
constexpr uint32_t SPARE = 0x40074007u;
constexpr float UNCHOP = 1.0023f;

__device__ __forceinline__ uint32_t p1_parity(uint32_t sbase) {
    uint32_t v;
    asm volatile("ld.shared.u32 %0, [%1];\n" : "=r"(v) : "r"(sbase + P1_OFF_TILE - 4) : "memory");
    return v;
}
__device__ __forceinline__ uint32_t p1_exponents(float (&t)[2], uint32_t (&ex)[2], uint32_t saddr, int lane) {
#pragma unroll
    for (int r = 0; r < 2; r++) {
        t[r] += __shfl_xor_sync(0xffffffffu, t[r], 1);
        t[r] += __shfl_xor_sync(0xffffffffu, t[r], 2);
        ex[r] = min(max(((__float_as_uint(193.3f * t[r]) >> 23) + 127u) >> 1, 72u), 198u);
        asm volatile("st.shared.u32 [%0], %1;\n" ::"r"(saddr + r * 32), "r"(ex[r] << 23) : "memory");
    }
    return pack_f16(__uint_as_float(min(ex[0], 142u) << 23), __uint_as_float(min(ex[1], 142u) << 23));
}
template <int N>
__device__ __forceinline__ void p1_convert(uint32_t (&o)[N][4], uint32_t (&v)[N][4], const uint32_t (&ex)[2]) {
    if (__any_sync(0xffffffffu, max(ex[0], ex[1]) > 141u)) {
#pragma unroll
        for (int k = 0; k < 4 * N; k++) v[k >> 2][k & 3] = bf2_mul(v[k >> 2][k & 3], ex[k & 1] > 141u ? 0x1f801f80u : 0x3f803f80u);
    }
#pragma unroll
    for (int k = 0; k < 4 * N; k++) {
        const uint32_t u = bf2_mul(v[k >> 2][k & 3], ((ex[k & 1] > 141u ? 206u : 142u) - ex[k & 1]) * 0x00800080u);
        asm volatile("mad.lo.u32 %0, %1, 7, %2;\n" : "=r"(o[k >> 2][k & 3]) : "r"(u & 0x7fff7fffu), "r"(u));
    }
}
template <int N>
__device__ __forceinline__ void p1_squares(const uint32_t (&v)[N][4], float (&t)[2]) {
#pragma unroll
    for (int j = 0; j < N / 2; j++) {
        const int r = j & 1, b = (j >> 1) * 4;
        uint32_t c = bf2_mul(v[b][r], v[b][r]);
#pragma unroll
        for (int k = 1; k < 8; k++) c = bf2_fma(v[b + k / 2][r + (k & 1) * 2], v[b + k / 2][r + (k & 1) * 2], c);
        t[r] += bf_lo(c) + bf_hi(c);
    }
}
__device__ __forceinline__ void p1_epilogue(const uint32_t (&acc)[2][32], const uint32_t (&sc2)[2], float (&ssq)[4], uint8_t* hp, int zero) {
    uint32_t sq[2], h[16][4];
#pragma unroll
    for (int i2 = 0; i2 < 9; i2++) {
#pragma unroll
        for (int c = 2 * i2 - 2; c < 2 * i2; c++) {
            if (c >= 0 && (c & 3)) {
                uint32_t o[4];
#pragma unroll
                for (int u = 0; u < 4; u++) {
                    const uint32_t v = h[c & 12][u];
                    o[u] = bitsel(h[c][u], (c & 3) == 2 ? prmt(v, v, 0xa381) : prmt(v >> 3, v, (c & 3) == 1 ? 0x6240 : 0xf3d1), SPARE);
                }
                stg128_cs(hp + (c >> 3) * 2 * H_STEP + ((c >> 2) & 1) * H_HALF + ((c & 3) - 1) * 512, o[0], o[1], o[2], o[3]);
            }
        }
        if (i2 < 8) {
#pragma unroll
            for (int u = 0; u < 4; u++) {
                h[2 * i2][u] = gelu2<0>(acc[i2 >> 2][8 * (i2 & 3) + 2 * u], sc2[i2 >> 2]);
                h[2 * i2 + 1][u] = gelu2<1>(acc[i2 >> 2][8 * (i2 & 3) + 2 * u + 1], sc2[i2 >> 2]);
#pragma unroll
                for (int r = 0; r < 2; r++) {
                    const uint32_t v = h[2 * i2 + r][u];
                    sq[r] = ((i2 & 3) | u) ? h2_fma(v, v, sq[r]) : h2_mul(v, v);
                }
            }
            if ((i2 & 3) == 3) {
#pragma unroll
                for (int r = 0; r < 2; r++) ssq[(i2 >> 2) * 2 + r] += h_lo(sq[r]) + h_hi(sq[r]);
            }
            sched_break(zero);
        }
    }
}
template <int WG>
__device__ __forceinline__ void p1_mma(uint32_t (&acc)[2][32], const uint32_t (&a)[24][4], uint32_t sbase, uint32_t empty_remote, int i, int lane, bool pass) {
    const uint32_t bar_full = sbase + P1_OFF_BAR;
    const uint32_t db = (uint32_t)make_desc(sbase, 16, 1024), da = db + (P1_OFF_W + WG * P1_W) / 16;
    if (WG == 0) mbar_wait(bar_full, i & 1);
    bar_sync(1 + WG, 256);
    TRACE(WG, i, 1);
    wg_fence();
#pragma unroll
    for (int k = 0; k < 24; k++) {
        if (WG == 0 && k && k % 4 == 0) mbar_wait(bar_full + (k >> 2) * 8, i & 1);
        mma_rs_n128(acc[0], a[k], db + (k >> 2) * 1024 + (k & 3) * 2, k != 0);
        mma_ss_n128(acc[1], da + k * 128, db + (k >> 2) * 1024 + (k & 3) * 2, k != 0);
        if (k == 23 && pass) bar_arrive(2 - WG, 256);
        if (k == 23 || (WG == 1 && k % 4 == 3)) wg_commit();
        if (WG == 1 && k % 4 == 3 && k > 3) {
            wg_wait<1>();
            if (lane < 2) mbar_arrive_cluster(empty_remote + ((k >> 2) - 1) * 8);
        }
    }
    TRACE(WG, i, 2);
    wg_wait<0>();
    if (WG == 1 && lane < 2) mbar_arrive_cluster(empty_remote + 5 * 8);
}
__device__ __forceinline__ void p1_consumer(const uint32_t (&a)[24][4], const uint32_t (&sc2)[2], uint32_t sbase, int WG, int w, int lane, int zero) {
    const uint32_t bar_full = sbase + P1_OFF_BAR, bar_empty = bar_full + P1_NST * 8;
    const uint32_t empty_remote = mapa(bar_empty, lane & 1);
    const uint32_t bar_pace = bar_empty + P1_NST * 8 + 32 + w * 8;
    const int g = lane >> 2, q = lane & 3, half = WG ^ ((blockIdx.x / GRP_CTAS) & 1), cb = (blockIdx.x % GRP_CTAS) * 4 + half * 2;
    uint32_t acc[2][32];
    float ssq[4] = {0.f, 0.f, 0.f, 0.f};
    TSTAMP(0, 1);

    uint8_t* hp = reinterpret_cast<uint8_t*>(g_h) + ((cb * 2 + (w >> 1)) * H_STEP + (w & 1) * 1536) + g * 64 + (q ^ (g >> 1)) * 16;
    int i = 0;
    uint32_t more = 3, both;
#pragma unroll 1
    for (;; i++) {
        TRACE(WG, i, 0);
        both = more & 2;
        if (WG == 0) p1_mma<0>(acc, a, sbase, empty_remote, i, lane, both);
        else p1_mma<1>(acc, a, sbase, empty_remote, i, lane, true);
        TRACE(WG, i, 4);
        int step;
        asm volatile("ld.shared.v2.u32 {%0, %1}, [%2];\n" : "=r"(step), "=r"(more) : "r"(sbase + P1_OFF_TILE + (i & 3) * 16) : "memory");
        hp += step;
        p1_epilogue(acc, sc2, ssq, hp, zero);
        if (lane == 0) mbar_arrive(bar_pace);
        if (!(more >> WG & 1)) break;
    }
    TSTAMP(0, 21);
    if (WG == 0 && both) bar_sync(1, 256);
#pragma unroll
    for (int r = 0; r < 4; r++) {
        const int ch = (r >> 1) * 64 + w * 16 + (r & 1) * 8 + g;
        ssq[r] += __shfl_xor_sync(0xffffffffu, ssq[r], 1);
        ssq[r] += __shfl_xor_sync(0xffffffffu, ssq[r], 2);
        float f;
        asm volatile("ld.shared.f32 %0, [%1];\n" : "=f"(f) : "r"(sbase + P1_OFF_EX + (half * 128 + ch) * 4) : "memory");
        if (q == 0) {
            float* sums = g_sums[p1_parity(sbase)];
            atomicAdd(&sums[cb * 64 + ch], ssq[r] * f * f);
            g_scale[cb * 64 + ch] = f;
            if (ssq[r] < (i + 1) * 0x1p-12f) sums[HID + C_DIM + 1] = 1.f;
        }
    }
}

__global__ void __cluster_dims__(2, 1, 1) __launch_bounds__(512, 1)
pass1_kernel(const __grid_constant__ CUtensorMap wmap, const __nv_bfloat16* __restrict__ x, const __nv_bfloat16* __restrict__ dw,
             const __nv_bfloat16* __restrict__ w2, const __nv_bfloat16* __restrict__ grn_b, int zero) {
    extern __shared__ __align__(1024) uint8_t smem[];
    const uint32_t sbase = smem_u32(smem);
    const uint32_t bar_full = sbase + P1_OFF_BAR, bar_empty = bar_full + P1_NST * 8, bar_w = bar_empty + P1_NST * 8;
    const int tid = threadIdx.x;
    const int warp = __shfl_sync(0xffffffffu, tid >> 5, 0), lane = tid & 31;
    const uint32_t rank = cluster_rank();
    const int cig = blockIdx.x % GRP_CTAS;
    uint8_t* const ring = reinterpret_cast<uint8_t*>(g_ln);

    TSTAMP(0, 0);
    TRACEW(110 + warp, 0);
    const uint32_t bar_pace = bar_w + 32, bar_xfull = bar_pace + 32, bar_xempty = bar_xfull + 8, bar_done = bar_xfull + 16;
    const int ln0 = blockIdx.x >> 2, first = blockIdx.x / GRP_CTAS;
    const uint8_t* xsrc = reinterpret_cast<const uint8_t*>(x) + (size_t)blockIdx.x * P1_X;

    if (warp >= 12) {
        reg_dec<40>();
        asm volatile("barrier.cluster.arrive.relaxed.aligned;\n" ::: "memory");
        asm volatile("barrier.cluster.wait.aligned;\n" ::: "memory");
        if (warp == 12) {
            int prev = 0, t = first;
            const uint32_t rbase = mapa(sbase, lane & 1);
#pragma unroll 1
            for (int i = 0; t < NT128; i++) {
                const int round = t / LN_RING, slot = t - round * LN_RING;
                const uint8_t* src = ring + slot * LN_TILE + rank * (P1_SLOT / 2);
                int next = 0;
                if (rank == 0 && lane == 0) {
                    next = t < NT128 - P1_SPLIT ? NGRP + atomicAdd(&g_flag[LN_RING + (cig >> 1)][0][0], 1u) : 2 * NT128;
                    if (next >= NT128 - P1_SPLIT && next < 2 * NT128) next = NT128 - P1_SPLIT + atomicAdd(&g_flag[LN_RING + 3 + (cig >> 1)][first & 1][0], 1u);
                }
                flag_wait<true>(&g_flag[slot][0][0], 4 * round + 4);
                TRACEW(i, 2);
                asm volatile("fence.proxy.async.global;\n" ::: "memory");
                next = __shfl_sync(0xffffffffu, next, 0);
#pragma unroll 1
                for (int h = 0; h < P1_NST; h++) {
                    mbar_wait(bar_empty + h * 8, i & 1);
                    if (h == 0) TRACEW(i, 4);
                    if (h == 5) TRACEW(i, 5);
                    if (elect_one()) {
                        mbar_expect_tx(bar_full + h * 8, h ? P1_SLOT : P1_SLOT + 16);
                        bulk_g2s_mc(sbase + h * P1_SLOT + rank * (P1_SLOT / 2), src + h * P1_SLOT, P1_SLOT / 2, bar_full + h * 8, (uint16_t)3);
                    }
                    __syncwarp();
                    if (h == 0 && rank == 0 && lane < 2)
                        asm volatile("st.async.shared::cluster.mbarrier::complete_tx::bytes.v4.u32 [%0], {%1, %2, %3, %3}, [%4];\n"
                                     ::"r"(rbase + P1_OFF_TILE + (i & 3) * 16), "r"((t - prev) * (2 * H_TILE)), "r"(next < NT128 - P1_SPLIT ? 3 : next < NT128), "r"(next),
                                       "r"(rbase + P1_OFF_BAR) : "memory");
                }
                prev = t;
                t = next;
                if (rank != 0) {
                    mbar_wait(bar_full, i & 1);
                    asm volatile("ld.shared.u32 %0, [%1];\n" : "=r"(t) : "r"(sbase + P1_OFF_TILE + (i & 3) * 16 + 8) : "memory");
                }
            }
        } else if (warp == 13) {
            int ph = 0;
            unsigned target = 0;
#pragma unroll 1
            for (int i = ln0 + LN_STEP; i < NT128; i += LN_STEP, ph ^= 1) {
                target += ph * (GRP_CTAS / 2);
                xsrc += (size_t)NUM_CTAS * P1_X;
                mbar_wait(bar_xempty, ph);
                if (elect_one()) {
                    mbar_expect_tx(bar_xfull, P1_X);
                    bulk_g2s(sbase + P1_OFF_X, xsrc, P1_X, bar_xfull);
                }
                __syncwarp();
                const uint32_t off = flag_wait<false>(&g_flag[ln0 + (ph ^ 1) * LN_STEP][1][0], target);
                mbar_wait(bar_done, ph);
                if (elect_one()) {
                    asm volatile("st.shared.u32 [%0], %1;\n" ::"r"(bar_done + 8), "r"(off) : "memory");
                    mbar_arrive(bar_xfull);
                }
                __syncwarp();
            }
        } else if (warp == 15) {
            const uint32_t par = g_epoch & 1;
            asm volatile("st.shared.u32 [%0], %1;\n" ::"r"(sbase + P1_OFF_TILE - 4), "r"(par) : "memory");
            if (blockIdx.x < 16) reinterpret_cast<float4*>(g_sums[par ^ 1])[blockIdx.x * 32 + lane] = make_float4(0.f, 0.f, 0.f, 0.f);
            int t = first;
            if (rank == 1 && lane == 0) mbar_arrive(bar_empty);
#pragma unroll 1
            for (int i = 0; rank == 1 && t < NT128; i++) {
#pragma unroll 1
                for (int h = 0; h < P1_NST; h++) mbar_wait(bar_full + h * 8, i & 1);
                if (lane == 0) asm volatile("red.relaxed.gpu.global.add.u32 [%0], 1;\n" ::"l"(&g_flag[t % LN_RING][1][0]) : "memory");
                asm volatile("ld.shared.u32 %0, [%1];\n" : "=r"(t) : "r"(sbase + P1_OFF_TILE + (i & 3) * 16 + 8) : "memory");
                if (lane == 0) mbar_arrive(bar_empty);
                TRACEW(i, 3);
            }
            if (rank == 0) {
                mbar_wait(bar_full, 0);
                TRACEW(110 + warp, 3);
                mbar_wait(bar_full, 1);
                float* sums = g_sums[par] + HID;
                unsigned* flag = reinterpret_cast<unsigned*>(sums + C_DIM);
                if (blockIdx.x == 0) reinterpret_cast<uint2*>(g_half)[lane] = make_uint2(0, 0);
                if (blockIdx.x == 2 && lane < 3) g_prog[lane][0] = 0;
                if (blockIdx.x < 96) g_redo[blockIdx.x * 16 + lane] = 0.f;
                float gs = 0.f;
#pragma unroll 1
                for (int pass = 0; pass < 2; pass++) {
                    float mx = 0.f;
#pragma unroll 1
                    for (int it = first; it < 96; it += NGRP) {
                        const int nb = it % 12, k0 = (cig * 4 + it / 12) * 64 + (lane >> 2);
                        const uint32_t sc = mapa(sbase + P1_OFF_EX + (k0 & 255) * 4, it / 48);
                        uint32_t* dst = reinterpret_cast<uint32_t*>(g_w2img[0]) + (k0 >> 4) * 3072 + nb * 256 + lane;
                        float bs[8] = {};
#pragma unroll 1
                        for (int c = 0; c < 8; c++) {
                            const uint4 u = __ldg(reinterpret_cast<const uint4*>(w2 + (size_t)(k0 + c * 8) * C_DIM + nb * 32) + (lane & 3));
                            const float b = __bfloat162float(grn_b[k0 + c * 8]);
                            float t;
                            asm volatile("ld.shared::cluster.f32 %0, [%1];\n" : "=f"(t) : "r"(sc + c * 32) : "memory");
#pragma unroll
                            for (int j = 0; j < 4; j++) {
                                const uint32_t v = j == 0 ? u.x : j == 1 ? u.y : j == 2 ? u.z : u.w;
                                mx = fmaxf(mx, fmaxf(fabsf(bf_lo(v)), fabsf(bf_hi(v))) * t);
                                if (pass) {
                                    bs[2 * j] = fmaf(b, bf_lo(v), bs[2 * j]);
                                    bs[2 * j + 1] = fmaf(b, bf_hi(v), bs[2 * j + 1]);
                                    uint32_t h = pack_f16(bf_lo(v) * t * gs, bf_hi(v) * t * gs);
                                    asm volatile("movmatrix.sync.aligned.m8n8.trans.b16 %0, %0;\n" : "+r"(h));
                                    dst[(c >> 1) * 3072 + (c & 1) * 32 + j * 64] = h;
                                }
                            }
                        }
                        if (pass) {
#pragma unroll
                            for (int j = 0; j < 8; j++) {
#pragma unroll
                                for (int o = 4; o < 32; o <<= 1) bs[j] += __shfl_xor_sync(0xffffffffu, bs[j], o);
                                if (lane >> 2 == j) atomicAdd(&sums[nb * 32 + (j >> 1) * 8 + (lane & 3) * 2 + (j & 1)], bs[j]);
                            }
                        }
                    }
                    if (!pass) {
                        const uint32_t m = __reduce_max_sync(0xffffffffu, __float_as_uint(mx));
                        if (lane == 0) {
                            atomicMax(flag, m);
                            asm volatile("red.release.gpu.global.add.u32 [%0], 1;\n" ::"l"(flag + 32) : "memory");
                        }
                        flag_wait<true>(flag + 32, NUM_CTAS / 2);
                        gs = w2_scale(__ldcg(flag));
                    }
                }
            }
        } else if (warp == 14) {
            int ph = 0;
#pragma unroll 1
            for (int i = ln0; i < NT128; i += LN_STEP, ph ^= 1) {
                mbar_wait(bar_done, ph);
                TRACEW(i / LN_STEP, 0);
                asm volatile("fence.proxy.async.global;\n" ::: "memory");
                if (elect_one()) asm volatile("red.release.gpu.global.add.u32 [%0], 1;\n" ::"l"(&g_flag[ln0 + ph * LN_STEP][0][0]) : "memory");
                __syncwarp();
                TRACEW(i / LN_STEP, 1);
            }
        }
        __syncwarp();
        END_SYNC();
    } else if (warp >= 8) {
        reg_dec<88>();
        asm volatile("barrier.cluster.arrive.relaxed.aligned;\n" ::: "memory");
        {
            const int l8 = lane & 7, row = (warp - 8) * 4 + (lane >> 3), px = (blockIdx.x & 3) * 32 + row;
            uint32_t d[6][4];
            const int n = (px & 64) + perm32(2 * row + ((px >> 5) & 1));
            uint8_t* const dst0 = ring + ln0 * LN_TILE + n * 128 + ((l8 ^ (n & 7)) << 4);
            const uint32_t src = sbase + P1_OFF_X + ((warp - 8) * 8 + (lane >> 3)) * (C_DIM * 2) + l8 * 16;
            int ph = 0;
#pragma unroll 1
            for (int i = ln0; i < NT128; i += LN_STEP, ph ^= 1) {
                TRACE(2, i / LN_STEP, 0);
                uint32_t off = 1;
#pragma unroll 1
                for (int ps = i == ln0 ? -2 : 0; ps < 2; ps += ps < 0 ? 2 : 1) {
                    if (ps == 0) {
                        if (i == ln0) asm volatile("barrier.cluster.wait.aligned;\n" ::: "memory");
                        mbar_wait(bar_xfull, ph);
                        asm volatile("ld.shared.u32 %0, [%1];\n" : "=r"(off) : "r"(bar_done + 8) : "memory");
                    }
                    if (ps == 0) TRACE(2, i / LN_STEP, 1);
                    if (i == ln0) {
#pragma unroll
                        for (int j = 0; j < 6; j++)
                            asm volatile("ld.shared.v4.u32 {%0,%1,%2,%3}, [%4];\n"
                                         : "=r"(d[j][0]), "=r"(d[j][1]), "=r"(d[j][2]), "=r"(d[j][3]) : "r"(sbase + P1_OFF_DW + j * 128 + l8 * 16) : "memory");
                    }
                    uint32_t v1[1][6][4];
                    uint32_t (&v)[6][4] = v1[0];
#pragma unroll
                    for (int j = 0; j < 6; j++)
                        asm volatile("ld.shared.v4.u32 {%0,%1,%2,%3}, [%4];\n"
                                     : "=r"(v[j][0]), "=r"(v[j][1]), "=r"(v[j][2]), "=r"(v[j][3]) : "r"(src + (ps & 1) * (4 * C_DIM * 2) + j * 128) : "memory");
                    ln_rows<P1_PACE, 1>(v1, d, bar_pace + (warp - 8) * 8, off, zero, ps == 1 && lane == 0 ? bar_xempty : 0);
                    uint8_t* dst = dst0 + ph * (LN_STEP * LN_TILE) + (ps & 1) * 4096;
#pragma unroll
                    for (int j = 0; j < 6; j++) *reinterpret_cast<uint4*>(dst + j * 16384) = make_uint4(v[j][0], v[j][1], v[j][2], v[j][3]);
                    TRACE(2, i / LN_STEP, 3 + (ps & 1));
                }
                asm volatile("fence.proxy.async.global;\nfence.acq_rel.cta;\n" ::: "memory");
                __syncwarp();
                if (lane == 0) mbar_arrive(bar_done);
                TRACE(2, i / LN_STEP, 5);
                TRACE(2, i / LN_STEP, 2);
            }
        }
        __syncwarp();
        END_SYNC();
    } else {
        const int wg = warp >> 2, w = warp & 3;
        auto load_w = [&](int i0, int i1) {
#pragma unroll 1
            for (int i = i0; i < i1; i++) {
                if (!(i & 1)) mbar_expect_tx(bar_w + (i >> 1) * 8, P1_W);
                tma2(sbase + (i & 2) * P1_W + (i >> 2) * P1_W + (i & 1) * (P1_W / 2), &wmap, cig * 256 + ((i >> 1) ^ (first & 1) * 2) * 64, (i & 1) * 192, bar_w + (i >> 1) * 8);
            }
        };
        if (warp == 4 && elect_one()) {
            mbar_init(bar_xfull, 2);
#pragma unroll
            for (int i = 0; i < 4; i++) mbar_init(bar_w + i * 8, 1);
            asm volatile("fence.mbarrier_init.release.cluster;\n" ::: "memory");
            mbar_expect_tx(bar_xfull, P1_X + C_DIM * 2);
            bulk_g2s(sbase + P1_OFF_X, xsrc, P1_X, bar_xfull);
            bulk_g2s(sbase + P1_OFF_DW, dw, C_DIM * 2, bar_xfull);
            load_w(0, 4);
            asm volatile("st.shared.u32 [%0], 1;\n" ::"r"(bar_done + 8) : "memory");
            mbar_arrive(bar_xfull);
        }
        if (warp == 5 && elect_one()) {
#pragma unroll
            for (int i = 0; i < P1_NST; i++) {
                mbar_init(bar_full + i * 8, 1);
                mbar_init(bar_empty + i * 8, i ? 8 : 8 + rank);
                if (i < 4) mbar_init(bar_pace + i * 8, 1);
            }
            mbar_init(bar_xempty, 4);
            mbar_init(bar_done, 4);
            asm volatile("fence.mbarrier_init.release.cluster;\n" ::: "memory");
        }
        __syncwarp();
        asm volatile("barrier.cluster.arrive.relaxed.aligned;\n" ::: "memory");
        reg_inc<192>();
        TRACEW(110 + warp, 1);
        uint32_t a[24][4];
        gdc_launch();
        const uint32_t src = sbase + wg * P1_W + ((lane >> 4) * 8 + (lane & 7)) * 128 + (((2 * w + ((lane >> 3) & 1)) ^ (lane & 7)) << 4);
        const uint32_t s_ex = sbase + P1_OFF_EX + ((wg ^ (first & 1)) * 128 + w * 16 + (lane >> 2)) * 4;
        uint32_t sc2[2], ex[2];
        if (wg == 1) bar_arrive(1, 256);
#pragma unroll 1
        for (int it = 0; it < 2; it++) {
          if (it != wg) asm volatile("barrier.cluster.wait.aligned;\n" ::: "memory");
          if (it < wg) {
              mbar_wait(bar_xfull, 0);
              if (w == 0 && elect_one()) load_w(4, 8);
              __syncwarp();
          }
          if (it || wg == 0) {
            float t[2] = {0.f, 0.f};
            if (it) {
                TRACEW(110 + warp, 2);
                mbar_wait(bar_w + wg * 16, 0);
            }
            TRACEW(110 + warp, 5);
#pragma unroll
            for (int k = 0; k < 24; k++) ldsm4t(a[k], src + k * 2048);
            TRACEW(110 + warp, 6);
            p1_squares(a, t);
            sc2[0] = p1_exponents(t, ex, s_ex, lane);
            if (it && lane < 6) mbar_arrive_cluster(mapa(bar_empty, lane & 1) + (wg * 3 + (lane >> 1)) * 8 + (sc2[0] & zero));
            p1_convert<24>(a, a, ex);
          }
          if (it || wg == 1) {
            float t[2] = {0.f, 0.f};
            TRACEW(100 + warp, 0);
            if (it) mbar_wait(bar_w + wg * 16 + 8, 0);
            TRACEW(100 + warp, 1);
            uint32_t v[8][4], o[8][4];
#pragma unroll 1
            for (int j = 0; j <= 2 * it; j++) {
#pragma unroll
                for (int k = 0; k < 8; k++) ldsm4t(v[k], src + P1_OFF_W + (8 * j + k) * 2048);
                p1_squares(v, t);
            }
            sc2[1] = p1_exponents(t, ex, s_ex + 256, lane);
#pragma unroll 1
            for (int j = 2 * it; j >= 0; j--) {
                p1_convert<8>(o, v, ex);
#pragma unroll
                for (int k = 0; k < 8; k++) {
                    if (j) ldsm4t(v[k], src + P1_OFF_W + (8 * j - 8 + k) * 2048);
                    if (it) asm volatile("stmatrix.sync.aligned.m8n8.x4.trans.shared.b16 [%0], {%1,%2,%3,%4};\n"
                                         ::"r"(src + P1_OFF_W + (8 * j + k) * 2048), "r"(o[k][0]), "r"(o[k][1]), "r"(o[k][2]), "r"(o[k][3]) : "memory");
                }
            }
          }
        }
        asm volatile("fence.proxy.async.shared::cta;\n" ::: "memory");
        TRACEW(110 + warp, 7);
        bar_sync(6 + wg, 128);
        p1_consumer(a, sc2, sbase, wg, w, lane, zero);
        END_SYNC();
        TSTAMP(0, 30);
    }
}

constexpr int P2_B = 24576, P2_NB = 4;
constexpr int P2_A = 3072, P2_NA = 8;
constexpr int P2_XROW = C_DIM * 2;
constexpr int P2_OFF_A = P2_B * P2_NB;
constexpr int P2_OFF_X = P2_OFF_A + 3 * P2_NA * P2_A + 128;
constexpr int P2_LHALF = 2 * P2_NA * P2_A + 64;
constexpr int P2_XHALF = 32 * P2_XROW + 64;
constexpr int P2_OFF_GRN = P2_OFF_X + 64 * P2_XROW + 128;
constexpr int P2_OFF_BIAS = P2_OFF_GRN + HID * 2;
constexpr int P2_OFF_RED = P2_OFF_BIAS + C_DIM * 4;
constexpr int P2_OFF_BAR = P2_OFF_RED + 192;
constexpr int P2_SMEM = P2_OFF_BAR + (2 * P2_NB + 6 * P2_NA + 7) * 8;
#define P2_S1 16
constexpr int P2_S2 = 32;
constexpr int P2_NCL = NUM_CTAS / 2, P2_ITEMS = NT128 / P2_NCL, P2_SHARED = NT128 - P2_ITEMS * P2_NCL;
constexpr int P2_NPOS = 6 * 48 + P2_S1;
constexpr int P2_RAW = 24;
constexpr int P2_XC = 8 * P2_XROW;
#define P2_T0 5
#define P2_TL 8
#define P2_XP0 30
#define P2_XPN 13
#define P2_XPD 3
#define P2_CMP 0
#define P2_SLACK -1
#define P2_RAMP 2
#define P2_LATE 24
#define P2_GATE 1
#define P2_AH 2
__device__ __forceinline__ int p2_start(int n) { return n < 0 ? 0 : n / 3 * 48 + (n % 3 == 1 ? P2_S1 : n % 3 * (P2_S2 / 2)); }
__device__ __forceinline__ int p2_tile(int cl, int n) {
    return n == 0 ? NT128 - 1 - cl : n < 0 ? NT128 - 1 - P2_NCL - (cl >> 1) : cl + P2_NCL * (n - 1);
}

#define P2_EB 2
#define P2_EX 1
__device__ __forceinline__ void p2_epilogue(uint32_t (&acc0)[48], uint32_t (&acc1)[48], uint32_t up, uint32_t sx, uint32_t sb, int zero) {
    uint32_t v[12][3][4];
    auto load = [&](int t, int j) {
        if (t >= 12) return;
        uint32_t (&w)[4] = v[t][j];
        asm volatile("ld.shared.v4.u32 {%0,%1,%2,%3}, [%4];\n" : "=r"(w[0]), "=r"(w[1]), "=r"(w[2]), "=r"(w[3])
                     : "r"((j ? sx + (j - 1) * 4 * P2_XROW : sb) + t * 64) : "memory");
    };
    auto store = [&](int t, int r) {
        const uint32_t* w = (t < 6 ? acc0 : acc1) + 8 * (t % 6) + 4 * r;
        asm volatile("st.shared.v4.u32 [%4], {%0,%1,%2,%3};\n" ::"r"(w[0]), "r"(w[1]), "r"(w[2]), "r"(w[3]), "r"(sx + t * 64 + r * 4 * P2_XROW) : "memory");
    };
#pragma unroll
    for (int t = 0; t < P2_EB; t++) load(t, 0);
#pragma unroll
    for (int t = 0; t < 2 * P2_EX; t++) load(t >> 1, 1 + (t & 1));
#pragma unroll
    for (int t = 0; t < 12; t++) {
        load(t + P2_EX, 1);
        load(t + P2_EX, 2);
        load(t + P2_EB, 0);
        uint32_t* acc = (t < 6 ? acc0 : acc1) + 8 * (t % 6);
        uint32_t y[8];
#pragma unroll
        for (int e = 0; e < 8; e++) {
            y[e] = h2_add(acc[e], v[t][0][e >> 1]);
            y[e] = pack_bf16(h_lo(y[e]), h_hi(y[e]));
        }
#pragma unroll
        for (int e = 0; e < 8; e++) acc[(e & 1) * 4 + (e >> 1)] = bf2_fma(y[e], up, v[t][1 + (e & 1)][e >> 1]);
        store(t, 0);
        store(t, 1);
        sched_break(zero);
    }
    if (zero) {
#pragma unroll
        for (int t = 0; t < 24; t++) store(t >> 1, t & 1);
    }
}

__device__ __forceinline__ void p2_unpack(uint32_t (&u)[4], uint32_t o1, uint32_t o2, uint32_t o3) {
    u[2] = o1 & ~SPARE;
    u[1] = o2 & ~SPARE;
    u[3] = o3 & ~SPARE;
    const uint32_t t = bitsel(prmt(o1, o2, 0x6341), prmt(o1, o3, 0x6240) << 3, 0x38383838u);
    u[0] = bitsel(t, prmt(o2, o3, 0x7351) << 1, 0x80808080u) & ~SPARE;
}

__device__ __forceinline__ void p2_redo_sums(int warp, int lane) {
#pragma unroll 1
    for (int s = warp; s < 96; s += 12) {
        float t[2] = {0.f, 0.f};
#pragma unroll 1
        for (int tile = blockIdx.x; tile < 2 * NT128; tile += NUM_CTAS) {
            const uint32_t* p = reinterpret_cast<const uint32_t*>(reinterpret_cast<const uint8_t*>(g_h) + (size_t)(tile >> 1) * (2 * H_TILE) +
                                                                  (s >> 1) * H_STEP + (tile & 1) * H_HALF + (s & 1) * 1536) + lane * 4;
#pragma unroll
            for (int j = 0; j < 4; j++) {
                uint32_t u[4];
                p2_unpack(u, __ldcg(p + j), __ldcg(p + j + 128), __ldcg(p + j + 256));
#pragma unroll
                for (int c = 0; c < 4; c++) t[c >> 1] += h_lo(u[c]) * h_lo(u[c]) + h_hi(u[c]) * h_hi(u[c]);
            }
        }
#pragma unroll
        for (int r = 0; r < 2; r++) {
            const int ch = s * 16 + r * 8 + (lane >> 2);
            const float f = __ldcg(&g_scale[ch]) * UNCHOP;
            atomicAdd(&g_redo[ch], t[r] * f * f);
        }
    }
    __threadfence();
    __syncwarp();
    if (lane == 0) asm volatile("red.release.gpu.global.add.u32 [%0], 1;\n" ::"l"(&g_prog[2][0]) : "memory");
    flag_wait<true>(&g_prog[2][0], 12 * NUM_CTAS);
}

__global__ void __cluster_dims__(2, 1, 1) __launch_bounds__(512, 1)
pass2_kernel(const __nv_bfloat16* __restrict__ x, const __nv_bfloat16* __restrict__ grn_g, __nv_bfloat16* __restrict__ out, int zero) {
    extern __shared__ __align__(1024) uint8_t smem[];
    const uint32_t sbase = smem_u32(smem);
    const uint32_t bar_bfull = sbase + P2_OFF_BAR, bar_bempty = bar_bfull + P2_NB * 8;
    const uint32_t bar_afull = bar_bempty + P2_NB * 8, bar_aempty = bar_afull + 3 * P2_NA * 8;
    const uint32_t bar_xfull = bar_aempty + 3 * P2_NA * 8, bar_oready = bar_xfull + 24, s_pos = bar_oready + 24;
    int tid;
    asm volatile("mov.u32 %0, %%tid.x;\n" : "=r"(tid));
    const int warp = __shfl_sync(0xffffffffu, tid >> 5, 0), lane = tid & 31;
    const uint32_t rank = cluster_rank();
    const int cl = blockIdx.x >> 1, pair = cl >> 1;
    const int half = pair < P2_SHARED, fin = half && (cl & 1);
    const int k0 = (pair + 3 * (cl & 1)) % 6 * 8;
    const bool late = blockIdx.x >= P2_LATE;
    auto wait_pos = [&](int target) {
        int v;
        while (true) {
            asm volatile("ld.volatile.shared.u32 %0, [%1];\n" : "=r"(v) : "r"(s_pos) : "memory");
            if (v >= target) break;
            SAFE_BREAK;
            __nanosleep(100);
        }
    };

    TSTAMP(1, 0);
    if (tid == 384) {
        for (int i = 0; i < P2_NB; i++) {
            mbar_init(bar_bfull + i * 8, 1);
            mbar_init(bar_bempty + i * 8, 24);
        }
        for (int i = 0; i < 3 * P2_NA; i++) {
            mbar_init(bar_afull + i * 8, 1);
            mbar_init(bar_aempty + i * 8, 4);
        }
        for (int i = 0; i < 3; i++) {
            mbar_init(bar_xfull + i * 8, 2);
            mbar_init(bar_oready + i * 8, 4);
        }
        asm volatile("st.shared.u32 [%0], 0;\n" ::"r"(s_pos) : "memory");
        asm volatile("fence.mbarrier_init.release.cluster;\n" ::: "memory");
    }
    __syncthreads();
    cluster_sync_relaxed();

    if (warp >= 12) {
        reg_dec<32>();
        if (warp == 12) {
            const uint8_t* wsrc = reinterpret_cast<const uint8_t*>(g_w2img) + rank * (P2_B / 2);
            int kb = k0;
            gdc_wait();
            if (P2_GATE) bar_sync(5, 448);
#pragma unroll 1
            for (int p = 0; p < P2_NPOS; p++) {
                const int st = p & 3;
                if (p == P2_RAW) {
                    flag_wait<true>(&g_prog[1][0], NUM_CTAS);
                    asm volatile("fence.proxy.async.global;\n" ::: "memory");
                    wsrc += sizeof(g_w2img[0]);
                }
                const int idle = (p < P2_S1 || p >= 6 * 48) + (p < P2_S2 ? !half || p >= 24 : p >= 5 * 48 + P2_S2);
                mbar_wait(bar_bempty + st * 8, (~p >> 2) & 1);
                TR2(3, p, 0);
                if (elect_one()) {
                    const int len = P2_B / 2;
                    mbar_expect_tx(bar_bfull + st * 8, 2 * len);
                    bulk_g2s_mc(sbase + st * P2_B + rank * (P2_B / 2), wsrc + kb * P2_B, len, bar_bfull + st * 8, (uint16_t)3);
                    asm volatile("st.volatile.shared.u32 [%0], %1;\n" ::"r"(s_pos), "r"(p) : "memory");
                    if (P2_SLACK > -9 && rank == 0) asm volatile("red.relaxed.gpu.global.add.u32 [%0], 1;\n" ::"l"(&g_prog[0][0]) : "memory");
                    if (idle) asm volatile("mbarrier.arrive.shared::cta.b64 _, [%0], %1;\n" ::"r"(bar_bempty + st * 8), "r"(8 * idle) : "memory");
                }
                __syncwarp();
                if (++kb == 48) kb = 0;
            }
            mbar_wait(bar_bempty, 1);
            if (lane == 0) mbar_arrive(bar_bfull);
        } else if (warp == 13) {
            const int w = lane < 3 ? lane : 0;
            const uint32_t dst0 = sbase + P2_OFF_A + w * P2_NA * P2_A;
            const uint32_t bf = bar_afull + w * P2_NA * 8, be = bar_aempty + w * P2_NA * 8;
            int n = (w == 2 && half ? -1 : w) - 3, left = 0, u = 0, c = 0;
            const uint8_t* src = nullptr;
            bool act = lane < 3;
            gdc_wait();
            if (P2_GATE) bar_sync(5, 448);
            while (__any_sync(0xffffffffu, act)) {
                if (left == 0) {
                    n += 3;
                    left = n >= P2_ITEMS ? -1 : n < 0 ? 24 : 48;
                    u = (k0 + p2_start(n)) % 48;
                    src = reinterpret_cast<const uint8_t*>(g_h) + (size_t)p2_tile(cl, n) * (2 * H_TILE) + rank * H_HALF + u * H_STEP;
                }
                bool ok = act && mbar_test(be + ((c - 1) & 7) * 8, (~c >> 3) & 1);
                if (__any_sync(0xffffffffu, act && c < 16)) {
                    int v;
                    asm volatile("ld.volatile.shared.u32 %0, [%1];\n" : "=r"(v) : "r"(s_pos) : "memory");
                    ok = ok && c <= (n <= 0 ? 2 * v - P2_RAMP : c >= 16 ? c : v - p2_start(n) + 8);
                }
                if (ok) {
                    const int st = c & 7;
                    if (left > 0) {
                        mbar_expect_tx(bf + st * 8, P2_A);
                        bulk_g2s(dst0 + st * P2_A, src, P2_A, bf + st * 8);
                    } else {
                        mbar_arrive(bf + st * 8);
                        act = false;
                    }
                    src += H_STEP;
                    if (++u == 48) { u = 0; src -= 48 * H_STEP; }
                    c++;
                    left--;
                }
                SAFE_BREAK;
                if (!__any_sync(0xffffffffu, ok)) __nanosleep(100);
            }
        } else if (warp == 14) {
            const uint32_t sx = sbase + P2_OFF_X;
            size_t o = 0;
            int wp = 0;
            uint32_t par = 0;
            if (fin) {
#pragma unroll 1
                for (int c = lane * 16; c < 64 * P2_XROW + 128; c += 512) asm volatile("st.shared.v4.u32 [%0], {0, 0, 0, 0};\n" ::"r"(sx + c) : "memory");
                __syncwarp();
            }
            if (late) wait_pos(6);
#pragma unroll 1
            for (int n = -half; n <= P2_ITEMS; n++) {
                const int w = (n + 3) % 3, end = p2_start(n) + 48;
                const size_t on = (size_t)(2 * p2_tile(cl, n) + rank) * (64 * C_DIM * 2);
                const uint32_t xf = bar_xfull + w * 8;
                bool st = n + half > 0;
                const bool ld = n < P2_ITEMS - 1 && !(n < 0 && fin);
                if (n == P2_ITEMS - 1 && lane == 0) {
                    mbar_expect_tx(xf, 64 * C_DIM * 2);
#pragma unroll 1
                    for (int c = 4; c < 12; c++) {
                        if (c >= 8) {
                            mbar_wait(bar_aempty + ((2 * c - 1) & 7) * 8, 1);
                            mbar_wait(bar_aempty + ((2 * c) & 7) * 8, 1);
                        }
                        bulk_g2s(sbase + P2_OFF_A + (c & 3) * P2_XC + (c < 8 ? P2_LHALF : 0), reinterpret_cast<const uint8_t*>(x) + on + (c & 7) * P2_XC, P2_XC, xf);
                    }
                    mbar_arrive(xf);
                }
                if (st) {
                    mbar_wait(bar_oready + wp * 8, (par >> wp) & 1);
                    par ^= 1u << wp;
                }
                if (lane == 0) {
                    if (n < P2_ITEMS - 1) mbar_expect_tx(xf, ld ? 64 * C_DIM * 2 : 0);
                    const int t0 = (n ? p2_start(n - 1) + 48 : P2_S2) + (n == P2_ITEMS - 1 ? P2_TL : P2_T0), dt = end - (n == P2_ITEMS - 2 ? P2_CMP : 0) - t0;
                    int t = st ? 16 * t0 : -4096;
                    if ((n == 0 && half) || n == P2_ITEMS) {
                        if (fin && n == 0) {
                            flag_wait<true>(&g_half[pair][rank], 1);
                            asm volatile("fence.proxy.async.global;\n" ::: "memory");
                        }
#pragma unroll 1
                        for (int c = 0; c < 2; c++) {
                            uint8_t* dst = reinterpret_cast<uint8_t*>(out) + o + c * 32 * P2_XROW;
                            if (!fin || n) bulk_s2g(dst, n ? sbase + P2_OFF_A + c * P2_LHALF : sx + c * P2_XHALF, 32 * P2_XROW);
                            else asm volatile("cp.reduce.async.bulk.global.shared::cta.bulk_group.add.noftz.bf16 [%0], [%1], %2;\n"
                                              ::"l"(dst), "r"(sx + c * P2_XHALF), "r"(32 * P2_XROW) : "memory");
                        }
                        asm volatile("cp.async.bulk.commit_group;\n" ::: "memory");
                        if (!fin && n == 0) {
                            asm volatile("cp.async.bulk.wait_group 0;\nfence.proxy.async.global;\n" ::: "memory");
                            asm volatile("st.release.gpu.global.u32 [%0], 1;\n" ::"l"(&g_half[pair][rank]) : "memory");
                        }
                        st = false;
                    }
#pragma unroll 1
                    for (int c = 0; n < P2_ITEMS && c < 64 * P2_XROW; c += P2_XC, t += 2 * dt) {
                        const uint32_t sp = sx + c + (c >= 32 * P2_XROW ? 64 : 0);
                        wait_pos(t >> 4);
                        if (st) bulk_s2g(reinterpret_cast<uint8_t*>(out) + o + c, sp, P2_XC);
                        asm volatile("cp.async.bulk.commit_group;\n" ::: "memory");
                        if (ld) {
                            wait_pos((t + dt) >> 4);
                            asm volatile("cp.async.bulk.wait_group.read 0;\n" ::: "memory");
                            bulk_g2s(sp, reinterpret_cast<const uint8_t*>(x) + on + c, P2_XC, xf);
                        }
                    }
                    if (P2_SLACK > -9 && rank == 0 && n > 0 && n < P2_ITEMS - 2) flag_wait<false>(&g_prog[0][0], P2_NCL * (end + P2_SLACK));
                    if (n < P2_ITEMS - 1) mbar_arrive(xf);
                }
                __syncwarp();
                o = on;
                wp = w;
            }
            asm volatile("cp.async.bulk.wait_group.read 0;\n" ::: "memory");
        } else {
            if (blockIdx.x == 120) {
                gdc_wait();
                for (int i = lane; i < (LN_RING + 6) * 2; i += 32) (&g_flag[0][0][0])[i * 8] = 0;
                if (lane == 0) g_epoch++;
            }
            int t = 4 * P2_XP0;
#pragma unroll 1
            for (int n = 0; n < P2_ITEMS && lane == 0; n++) {
                const uint8_t* xn = reinterpret_cast<const uint8_t*>(x) + (size_t)(2 * p2_tile(cl, n) + rank) * (64 * C_DIM * 2);
#pragma unroll 1
                for (int c = 0; c < 16; c++, t += n < P2_XPN ? 4 : P2_XPD) {
                    wait_pos(t >> 2);
                    asm volatile("cp.async.bulk.prefetch.L2.global [%0], %1;\n" ::"l"(xn + c * (P2_XC / 2)), "r"(P2_XC / 2) : "memory");
                }
            }
        }
        __syncwarp();
        END_SYNC();
    } else {
        reg_inc<160>();
        const int wg = warp >> 2, w = warp & 3, g = lane >> 2, q = lane & 3;
        const uint32_t sx = sbase + P2_OFF_X + (g & 1) * P2_XHALF + (w * 8 + (g >> 1)) * P2_XROW + q * 16;
        const uint32_t af = bar_afull + wg * P2_NA * 8;
        const uint32_t s_a = sbase + P2_OFF_A + wg * P2_NA * P2_A + (lane >> 3) * 512 + (lane & 7) * 64 + ((w ^ ((lane & 7) >> 1)) << 4);
        uint32_t acc0[48], acc1[48], up;
        uint4 a[2][2];

        __nv_bfloat16 gg[4];
#pragma unroll
        for (int i = 0; i < 4; i++) gg[i] = grn_g[tid + 384 * i];
#pragma unroll 1
        for (int it = late; it < 2; it++) {
            float* s_red = reinterpret_cast<float*>(smem + P2_OFF_RED);
            float gx[7], part = 0.f;
            if (it) {
                TSTAMP(1, 27);
                gdc_wait();
                TSTAMP(1, 1);
            }
            float gy[7];
#pragma unroll
            for (int i = 0; i < 7; i++) {
                const float* p = &g_sums[0][i < 5 ? tid + 384 * i : HID + C_DIM + i - 5];
                asm volatile("ld.global.cg.f32 %0, [%1];\n" : "=f"(gx[i]) : "l"(p) : "memory");
                asm volatile("ld.global.cg.f32 %0, [%1];\n" : "=f"(gy[i]) : "l"(p + HID + 512) : "memory");
            }
            if (P2_GATE && it) bar_arrive(5, 448);
            const float bias = gx[4] + gy[4];
            const float gs = w2_scale(__float_as_uint(gx[5]) | __float_as_uint(gy[5]));
            if (it && gx[6] + gy[6] != 0.f) {
                p2_redo_sums(warp, lane);
#pragma unroll
                for (int i = 0; i < 4; i++) {
                    gx[i] = __ldcg(&g_redo[tid + 384 * i]);
                    gy[i] = 0.f;
                }
            }
            float mg = 0.f;
#pragma unroll
            for (int i = 0; i < 4; i++) {
                gx[i] = gx[i] + gy[i];
                gx[i] = __fsqrt_rn(gx[i] * (HSCALE * HSCALE) + 1e-6f);
                part += gx[i];
                gx[i] *= __bfloat162float(gg[i]);
                mg = fmaxf(mg, fabsf(gx[i]));
            }
#pragma unroll
            for (int o = 16; o > 0; o >>= 1) part += __shfl_xor_sync(0xffffffffu, part, o);
            const uint32_t mgw = __reduce_max_sync(0xffffffffu, __float_as_uint(mg));
            const uint32_t mbw = __reduce_max_sync(0xffffffffu, __float_as_uint(fabsf(bias)));
            TSTAMP(1, 26);
            if (lane == 0) *reinterpret_cast<float4*>(s_red + warp * 4) = make_float4(part, __uint_as_float(mgw), __uint_as_float(mbw), 0.f);
            bar_sync(1, 384);
            float tot = 0.f, mb = 0.f;
#pragma unroll
            for (int i = 0; i < 12; i++) {
                const float4 t = *reinterpret_cast<const float4*>(s_red + i * 4);
                tot += t.x;
                mg = fmaxf(mg, t.y);
                mb = fmaxf(mb, t.z);
            }
            const float inv = 1.0f / (tot * (1.0f / HID) + 1e-6f);
            const uint32_t ej = min((__float_as_uint(fmaxf(fmaf(mg, inv, 1.0f) * (HSCALE * UNCHOP), mb * gs * 0x1p-13f)) >> 23) + 1, 250u);
            const float dn = __uint_as_float((254u - ej) << 23);
            up = min(ej + 127u - (__float_as_uint(gs) >> 23), 254u) * 0x00800080u;
            reinterpret_cast<uint16_t*>(smem + P2_OFF_BIAS + C_DIM * 2)[tid] = 0;
            *reinterpret_cast<__half*>(smem + P2_OFF_BIAS + (tid >> 5) * 64 + (tid & 6) * 8 + (tid & 24) / 2 + (tid & 1) * 2) = __float2half_rn(bias * gs * dn);
#pragma unroll
            for (int i = 0; i < 4; i++) {
                const int k = tid + 384 * i;
                *reinterpret_cast<__half*>(smem + P2_OFF_GRN + (k >> 4) * 32 + (k & 6) * 4 + (k & 8) / 2 + (k & 1) * 2) =
                    __float2half_rn(fmaf(gx[i], inv, 1.0f) * (HSCALE * UNCHOP * dn));
            }
            TSTAMP(1, 25);
            bar_sync(1, 384);
        }
        TSTAMP(1, 28);
        if (wg == 1) {
            constexpr int N = sizeof(g_w2img[0]) / 16, PER = (N + NUM_CTAS - 1) / NUM_CTAS;
            uint4 v[5];
#pragma unroll
            for (int i = 0; i < 5; i++) v[i] = __ldcg(&g_w2img[0][min(blockIdx.x * PER + (tid & 127) + 128 * i, N - 1)]);
#pragma unroll
            for (int i = 0; i < 5; i++) {
                const int j = min(blockIdx.x * PER + (tid & 127) + 128 * i, N - 1);
                const uint32_t* t = reinterpret_cast<const uint32_t*>(smem + P2_OFF_GRN + (j / 768) * 32 + (j & 8) / 2);
                auto sc = [&](uint32_t u, int e) { return (h2_mul(u, t[2 * e]) + 0x00040004u) & 0xfff8fff8u; };
                g_w2img[1][j] = make_uint4(sc(v[i].x, 0), sc(v[i].y, 1), sc(v[i].z, 2), sc(v[i].w, 3));
            }
            asm volatile("fence.proxy.async.global;\n" ::: "memory");
            bar_sync(2, 128);
            if (tid == 128) asm volatile("fence.acq_rel.gpu;\nred.release.gpu.global.add.u32 [%0], 1;\n" ::"l"(&g_prog[1][0]) : "memory");
        }

        const int who = __shfl_sync(0xffffffffu, lane == 2 ? 0 : lane < 2 ? 1 : 2, lane);
        const uint32_t rel0 = who ? mapa(bar_bempty, lane & 1) : mapa(bar_aempty + wg * P2_NA * 8, rank), rel1 = rel0 + (who ? 0 : 32);
        auto publish = [&]() {
            asm volatile("fence.proxy.async.shared::cta;\n" ::: "memory");
            __syncwarp();
            if (who == 0) mbar_arrive(bar_oready + wg * 8);
        };
        bool ok_a, pend = false;
        uint32_t pa = 0, s_t;
        auto fetch = [&](int j, bool raw) {
            uint32_t o[6], u0[4], u1[4];
            uint2 t0 = make_uint2(0, 0), t1 = t0;
            if (raw) {
                asm volatile("ld.shared.v2.u32 {%0,%1}, [%2];\n" : "=r"(t0.x), "=r"(t0.y) : "r"(s_t + j * 64) : "memory");
                asm volatile("ld.shared.v2.u32 {%0,%1}, [%2];\n" : "=r"(t1.x), "=r"(t1.y) : "r"(s_t + j * 64 + 32) : "memory");
            }
            const bool ok_b = mbar_test(bar_bfull + (j & 3) * 8, j >> 2);
            if (j == 7) pa ^= 1;
            ok_a = mbar_test(af + ((j + 1) & 7) * 8, pa);
            asm volatile("ldmatrix.sync.aligned.m8n8.x4.trans.shared.b16 {%0,%1,%2,%3}, [%4];\n"
                         : "=r"(o[0]), "=r"(o[1]), "=r"(o[2]), "=r"(o[3]) : "r"(s_a + j * P2_A) : "memory");
            asm volatile("ldmatrix.sync.aligned.m8n8.x2.trans.shared.b16 {%0,%1}, [%2];\n"
                         : "=r"(o[4]), "=r"(o[5]) : "r"(s_a + j * P2_A + 2048) : "memory");
            p2_unpack(u0, o[0], o[1], o[2]);
            p2_unpack(u1, o[3], o[4], o[5]);
            if (raw) {
                u0[0] = h2_mul(u0[0], t0.x); u0[1] = h2_mul(u0[1], t0.x); u0[2] = h2_mul(u0[2], t0.y); u0[3] = h2_mul(u0[3], t0.y);
                u1[0] = h2_mul(u1[0], t1.x); u1[1] = h2_mul(u1[1], t1.x); u1[2] = h2_mul(u1[2], t1.y); u1[3] = h2_mul(u1[3], t1.y);
            }
            a[j & 1][0] = make_uint4(u0[0], u0[1], u0[2], u0[3]);
            a[j & 1][1] = make_uint4(u1[0], u1[1], u1[2], u1[3]);
            if (!ok_b) mbar_wait(bar_bfull + (j & 3) * 8, j >> 2);
        };
        auto table = [&](int pos) { s_t = sbase + P2_OFF_GRN + q * 8 + (k0 + pos) % 48 * 64; };
        const uint32_t db0 = (uint32_t)make_desc(sbase, 128, 256);
        auto block8 = [&](bool raw, int pos, int thr0, int mode) {
#pragma unroll
            for (int j = 0; j < 8; j++) {
                const uint32_t db = db0 + (j & 3) * (P2_B / 16);
                if (j == 8 - P2_AH && mode == 1) bar_sync(4, 384);
                TR2(wg, pos + j, 0);
                wg_fence();
                mma_rs_n192(acc0, a[j & 1][0], db);
                mma_rs_n192(acc1, a[j & 1][0], db + 384);
                mma_rs_n192(acc0, a[j & 1][1], db + 768);
                mma_rs_n192(acc1, a[j & 1][1], db + 768 + 384);
                wg_commit();
                if (j == 7 && mode == 2) bar_arrive(4, 384);
                const uint32_t rel = ((j - 1) & 4 ? rel1 : rel0) + ((j - 1) & 3) * 8;
                TR2(wg, pos + j, 1);
                wg_wait<1>();
                TR2(wg, pos + j, 2);
                if (who < (j ? 2 : thr0)) mbar_arrive_cluster(rel);
                if (!ok_a) {
                    if (j == 0 && pend) { publish(); pend = false; }
                    mbar_wait(af + ((j + 1) & 7) * 8, pa);
                }
                TR2(wg, pos + j, 3);
                if (raw && j == 7) table(pos + 8);
                fetch((j + 1) & 7, raw && (j < 7 || pos + 8 < P2_RAW));
            }
        };
        int n = wg == 2 && half ? -1 : wg, pos = p2_start(n);
        uint32_t px = 0;
        wait_pos(pos);
        mbar_wait(af, 0);
        table(pos);
        fetch(0, pos < P2_RAW);
#pragma unroll 1
        for (;; n += 3) {
            TSTAMP(1, 2 + n);
            const int end = pos + (n < 0 ? 24 : 48);
#pragma unroll
            for (int i = 0; i < 48; i += 2) {
                asm volatile("mov.b64 {%0, %1}, 0;\n" : "=r"(acc0[i]), "=r"(acc0[i + 1]));
                asm volatile("mov.b64 {%0, %1}, 0;\n" : "=r"(acc1[i]), "=r"(acc1[i + 1]));
            }
            int thr = 1;
#pragma unroll 1
            for (; pos < P2_RAW; pos += 8, thr = 2) block8(true, pos, thr, 0);
#pragma unroll 1
            for (; pos < end; pos += 8, thr = 2) {
                const int e = pos + 8, r = e % 48;
                block8(false, pos, thr, e < 48 || e > 256 || (r != 0 && r != P2_S1 && r != P2_S2) ? 0 : e == end ? 2 : 1);
            }
            TR2(wg, pos - 1, 4);
            wg_wait<0>();
            TR2(wg, pos - 1, 5);
            if (who == 1) mbar_arrive_cluster(rel0 + 24);
            mbar_wait(bar_xfull + wg * 8, px);
            TR2(wg, pos - 1, 6);
            px ^= 1;
            __syncwarp();
            p2_epilogue(acc0, acc1, up, n == P2_ITEMS - 1 ? sx + (P2_OFF_A - P2_OFF_X) + (g & 1) * (P2_LHALF - P2_XHALF) : sx, sbase + P2_OFF_BIAS + q * 16 + (n < 0 && fin ? C_DIM * 2 : 0), zero);
            TR2(wg, pos - 1, 7);
            if (n + 3 >= P2_ITEMS) { publish(); break; }
            if (n < 0) {
                publish();
                pos = P2_S2;
                wait_pos(pos);
                mbar_wait(bar_bfull, 0);
            } else {
                pend = true;
                ok_a = false;
            }
        }
        TSTAMP(1, 29);
        END_SYNC();
        TSTAMP(1, 30);
    }
}

}

extern "C" void kernel_launch(void* const* d_in, const int* in_sizes, int n_in, void* d_out, int out_size) {
    const __nv_bfloat16* x = (const __nv_bfloat16*)d_in[0];
    const __nv_bfloat16* dw = (const __nv_bfloat16*)d_in[1];
    const __nv_bfloat16* w1 = (const __nv_bfloat16*)d_in[2];
    const __nv_bfloat16* w2 = (const __nv_bfloat16*)d_in[3];
    const __nv_bfloat16* grn_g = (const __nv_bfloat16*)d_in[4];
    const __nv_bfloat16* grn_b = (const __nv_bfloat16*)d_in[5];
    __nv_bfloat16* out = (__nv_bfloat16*)d_out;

    cudaFuncSetAttribute(pass1_kernel, cudaFuncAttributeMaxDynamicSharedMemorySize, P1_SMEM);
    cudaFuncSetAttribute(pass2_kernel, cudaFuncAttributeMaxDynamicSharedMemorySize, P2_SMEM);

    typedef CUresult (*EncodeFn)(CUtensorMap*, CUtensorMapDataType, cuuint32_t, void*, const cuuint64_t*, const cuuint64_t*,
                                 const cuuint32_t*, const cuuint32_t*, CUtensorMapInterleave, CUtensorMapSwizzle,
                                 CUtensorMapL2promotion, CUtensorMapFloatOOBfill);
    static EncodeFn encode = nullptr;
    if (!encode) {
        cudaDriverEntryPointQueryResult qres;
        cudaGetDriverEntryPoint("cuTensorMapEncodeTiled", (void**)&encode, cudaEnableDefault, &qres);
    }
    CUtensorMap wmap;
    const cuuint64_t gdim[2] = {HID, C_DIM};
    const cuuint64_t gstr[1] = {HID * 2};
    const cuuint32_t box[2] = {64, 192}, estr[2] = {1, 1};
    CUresult er = encode(&wmap, CU_TENSOR_MAP_DATA_TYPE_BFLOAT16, 2, (void*)w1, gdim, gstr, box, estr, CU_TENSOR_MAP_INTERLEAVE_NONE,
           CU_TENSOR_MAP_SWIZZLE_128B, CU_TENSOR_MAP_L2_PROMOTION_L2_128B, CU_TENSOR_MAP_FLOAT_OOB_FILL_NONE);
    if (er != CUDA_SUCCESS) printf("tensor map encode failed %d\n", (int)er);

    pass1_kernel<<<NUM_CTAS, 512, P1_SMEM>>>(wmap, x, dw, w2, grn_b, 0);

    cudaLaunchAttribute attr[1];
    attr[0].id = cudaLaunchAttributeProgrammaticStreamSerialization;
    attr[0].val.programmaticStreamSerializationAllowed = 1;
    cudaLaunchConfig_t cfg = {};
    cfg.gridDim = dim3(NUM_CTAS);
    cfg.stream = 0;
    cfg.attrs = attr;
    cfg.numAttrs = 1;
    cfg.blockDim = dim3(512);
    cfg.dynamicSmemBytes = P2_SMEM;
    cudaLaunchKernelEx(&cfg, pass2_kernel, x, grn_g, out, 0);
}
```

```cpp
#include <cuda.h>
#include <cuda_runtime.h>
#include <cuda_bf16.h>
#include <cuda_fp16.h>
#include <stdint.h>
#include <stdio.h>

namespace {

constexpr int M_TOTAL = 384 * 384;
constexpr int C_DIM   = 384;
constexpr int HID     = 1536;
constexpr int NT128   = M_TOTAL / 128;
constexpr int NUM_CTAS = 132;

constexpr int NGRP = 22, GRP_CTAS = 6;
constexpr int NT_EARLY = NT128 - 30;
constexpr int LN_STEP = NUM_CTAS / 4, LN_RING = 2 * LN_STEP;
constexpr int LN_TILE = 128 * C_DIM * 2;
constexpr int H_TILE = 64 * HID * 3 / 2;
constexpr int H_HALF = 3072, H_STEP = 6144;

__device__ __align__(1024) uint4 g_h[(size_t)M_TOTAL * HID * 3 / 32];
__device__ __align__(1024) uint4 g_ln[LN_RING * LN_TILE / 16];
__device__ __align__(1024) uint4 g_w2img[2][HID * C_DIM * 2 / 16];
__device__ __align__(16) float g_sums[HID + 512];
__device__ float g_scale[HID];
__device__ float g_redo[HID];
__device__ __align__(128) unsigned g_prog[7][32];
__device__ __align__(128) unsigned g_half[32][2];
__device__ unsigned g_flag[LN_RING + 6][2][8];
#define TSTAMP(k, i)
#define TRACE(wg, pos, i)
#define TRACEW(pos, i)

#define TR2(wg, pos, i)
__host__ __device__ __forceinline__ int perm32(int n) {
    return (n & ~31) | (((n >> 1) & 3) << 3) | (((n >> 3) & 3) << 1) | (n & 1);
}

__device__ __forceinline__ uint32_t smem_u32(const void* p) { return (uint32_t)__cvta_generic_to_shared(p); }

__device__ __forceinline__ void mbar_init(uint32_t bar, uint32_t count) {
    asm volatile("mbarrier.init.shared::cta.b64 [%0], %1;\n" ::"r"(bar), "r"(count) : "memory");
}
__device__ __forceinline__ void mbar_expect_tx(uint32_t bar, uint32_t bytes) {
    asm volatile("mbarrier.arrive.expect_tx.shared::cta.b64 _, [%0], %1;\n" ::"r"(bar), "r"(bytes) : "memory");
}
__device__ __forceinline__ void mbar_arrive(uint32_t bar) {
    asm volatile("mbarrier.arrive.shared::cta.b64 _, [%0];\n" ::"r"(bar) : "memory");
}
__device__ __forceinline__ void mbar_arrive_cluster(uint32_t bar_cluster_addr) {
    asm volatile("mbarrier.arrive.shared::cluster.b64 _, [%0];\n" ::"r"(bar_cluster_addr) : "memory");
}
#define SAFE_BREAK
__device__ __forceinline__ void mbar_wait(uint32_t bar, uint32_t parity) {
    asm volatile(
        "{\n"
        ".reg .pred p;\n"
        "LAB_WAIT:\n"
        "mbarrier.try_wait.parity.shared::cta.b64 p, [%0], %1;\n"
        "@!p bra LAB_WAIT;\n"
        "}\n" ::"r"(bar), "r"(parity) : "memory");
}
__device__ __forceinline__ bool mbar_test(uint32_t bar, uint32_t parity) {
    uint32_t ok;
    asm volatile("{\n.reg .pred p;\n"
                 "mbarrier.test_wait.parity.shared::cta.b64 p, [%1], %2;\n"
                 "selp.u32 %0, 1, 0, p;\n}\n" : "=r"(ok) : "r"(bar), "r"(parity) : "memory");
    return ok != 0;
}
__device__ __forceinline__ uint32_t mapa(uint32_t addr, uint32_t rank) {
    uint32_t r;
    asm volatile("mapa.shared::cluster.u32 %0, %1, %2;\n" : "=r"(r) : "r"(addr), "r"(rank));
    return r;
}
__device__ __forceinline__ void bulk_g2s(uint32_t dst, const void* src, uint32_t bytes, uint32_t bar) {
    asm volatile("cp.async.bulk.shared::cluster.global.mbarrier::complete_tx::bytes [%0], [%1], %2, [%3];\n"
                 ::"r"(dst), "l"(src), "r"(bytes), "r"(bar) : "memory");
}
__device__ __forceinline__ void bulk_g2s_mc(uint32_t dst, const void* src, uint32_t bytes, uint32_t bar, uint16_t mask) {
    asm volatile("cp.async.bulk.shared::cluster.global.mbarrier::complete_tx::bytes.multicast::cluster [%0], [%1], %2, [%3], %4;\n"
                 ::"r"(dst), "l"(src), "r"(bytes), "r"(bar), "h"(mask) : "memory");
}
__device__ __forceinline__ void tma2(uint32_t dst, const CUtensorMap* map, int c0, int c1, uint32_t bar) {
    asm volatile("cp.async.bulk.tensor.2d.shared::cluster.global.tile.mbarrier::complete_tx::bytes [%0], [%1, {%2, %3}], [%4];\n"
                 ::"r"(dst), "l"(map), "r"(c0), "r"(c1), "r"(bar) : "memory");
}
template <bool ACQ>
__device__ __forceinline__ uint32_t flag_wait(const unsigned* p, unsigned target) {
    unsigned v, n = 0;
    do {
        if (ACQ) asm volatile("ld.acquire.gpu.global.u32 %0, [%1];\n" : "=r"(v) : "l"(p) : "memory");
        else asm volatile("ld.relaxed.gpu.global.u32 %0, [%1];\n" : "=r"(v) : "l"(p) : "memory");
        n++;
    } while (v < target);
    return n == 1;
}
__device__ __forceinline__ void ldsm4t(uint32_t (&r)[4], uint32_t addr) {
    asm volatile("ldmatrix.sync.aligned.m8n8.x4.trans.shared.b16 {%0,%1,%2,%3}, [%4];\n"
                 : "=r"(r[0]), "=r"(r[1]), "=r"(r[2]), "=r"(r[3]) : "r"(addr) : "memory");
}
__device__ __forceinline__ void bulk_s2g(void* dst, uint32_t src, uint32_t bytes) {
    asm volatile("cp.async.bulk.global.shared::cta.bulk_group [%0], [%1], %2;\n" ::"l"(dst), "r"(src), "r"(bytes) : "memory");
}
__device__ __forceinline__ void cluster_sync() {
    asm volatile("barrier.cluster.arrive.aligned;\nbarrier.cluster.wait.aligned;\n" ::: "memory");
}
__device__ __forceinline__ void cluster_sync_relaxed() {
    asm volatile("barrier.cluster.arrive.relaxed.aligned;\nbarrier.cluster.wait.aligned;\n" ::: "memory");
}
#define END_SYNC cluster_sync_relaxed
__device__ __forceinline__ void gdc_wait() { asm volatile("griddepcontrol.wait;\n" ::: "memory"); }
__device__ __forceinline__ void gdc_launch() { asm volatile("griddepcontrol.launch_dependents;\n" ::: "memory"); }
__device__ __forceinline__ uint32_t cluster_rank() {
    uint32_t r;
    asm volatile("mov.u32 %0, %%cluster_ctarank;\n" : "=r"(r));
    return r;
}
__device__ __forceinline__ bool elect_one() {
    uint32_t pred;
    asm volatile("{\n.reg .pred p;\nelect.sync _|p, 0xffffffff;\nselp.u32 %0, 1, 0, p;\n}\n" : "=r"(pred));
    return pred != 0;
}
__device__ __forceinline__ void wg_fence() { asm volatile("wgmma.fence.sync.aligned;\n" ::: "memory"); }
__device__ __forceinline__ void wg_commit() { asm volatile("wgmma.commit_group.sync.aligned;\n" ::: "memory"); }
template <int N> __device__ __forceinline__ void wg_wait() {
    asm volatile("wgmma.wait_group.sync.aligned %0;\n" ::"n"(N) : "memory");
}
template <int R> __device__ __forceinline__ void reg_inc() { asm volatile("setmaxnreg.inc.sync.aligned.u32 %0;\n" ::"n"(R)); }
template <int R> __device__ __forceinline__ void reg_dec() { asm volatile("setmaxnreg.dec.sync.aligned.u32 %0;\n" ::"n"(R)); }
__device__ __forceinline__ void bar_sync(int id, int n) { asm volatile("bar.sync %0, %1;\n" ::"r"(id), "r"(n) : "memory"); }
__device__ __forceinline__ void bar_arrive(int id, int n) { asm volatile("bar.arrive %0, %1;\n" ::"r"(id), "r"(n) : "memory"); }

__device__ __forceinline__ uint64_t make_desc(uint32_t saddr, uint32_t lbo, uint32_t sbo) {
    return (uint64_t)((saddr & 0x3FFFF) >> 4) | ((uint64_t)(lbo >> 4) << 16) | ((uint64_t)(sbo >> 4) << 32);
}

__device__ __forceinline__ void stg128_cs(void* p, uint32_t a, uint32_t b, uint32_t c, uint32_t d) {
#define H_ST "st.global.cs.v4.u32"
    asm volatile(H_ST " [%0], {%1,%2,%3,%4};\n" ::"l"(p), "r"(a), "r"(b), "r"(c), "r"(d) : "memory");
}
__device__ __forceinline__ uint32_t pack_bf16(float lo, float hi) {
    uint32_t r;
    asm("cvt.rn.bf16x2.f32 %0, %1, %2;\n" : "=r"(r) : "f"(hi), "f"(lo));
    return r;
}
__device__ __forceinline__ float bf_lo(uint32_t v) { return __uint_as_float(v << 16); }
__device__ __forceinline__ float bf_hi(uint32_t v) { return __uint_as_float(v & 0xffff0000u); }
__device__ __forceinline__ uint32_t bf2_mul(uint32_t a, uint32_t b) {
    uint32_t r;
    asm("mul.rn.bf16x2 %0, %1, %2;\n" : "=r"(r) : "r"(a), "r"(b));
    return r;
}
__device__ __forceinline__ uint32_t bf2_fma(uint32_t a, uint32_t b, uint32_t c) {
    uint32_t r;
    asm("fma.rn.bf16x2 %0, %1, %2, %3;\n" : "=r"(r) : "r"(a), "r"(b), "r"(c));
    return r;
}
__device__ __forceinline__ uint32_t bf2_add(uint32_t a, uint32_t b) {
    uint32_t r;
    asm("add.rn.bf16x2 %0, %1, %2;\n" : "=r"(r) : "r"(a), "r"(b));
    return r;
}
__device__ __forceinline__ uint32_t h2_mul(uint32_t a, uint32_t b) {
    uint32_t r;
    asm("mul.rn.f16x2 %0, %1, %2;\n" : "=r"(r) : "r"(a), "r"(b));
    return r;
}
__device__ __forceinline__ uint32_t h2_fma(uint32_t a, uint32_t b, uint32_t c) {
    uint32_t r;
    asm("fma.rn.f16x2 %0, %1, %2, %3;\n" : "=r"(r) : "r"(a), "r"(b), "r"(c));
    return r;
}
__device__ __forceinline__ uint32_t h2_add(uint32_t a, uint32_t b) {
    uint32_t r;
    asm("add.rn.f16x2 %0, %1, %2;\n" : "=r"(r) : "r"(a), "r"(b));
    return r;
}
__device__ __forceinline__ uint32_t pack_f16(float lo, float hi) {
    uint32_t r;
    asm("cvt.rn.f16x2.f32 %0, %1, %2;\n" : "=r"(r) : "f"(hi), "f"(lo));
    return r;
}
__device__ __forceinline__ float h_lo(uint32_t v) { return __low2float(*reinterpret_cast<const __half2*>(&v)); }
__device__ __forceinline__ float h_hi(uint32_t v) { return __high2float(*reinterpret_cast<const __half2*>(&v)); }
__device__ __forceinline__ uint32_t bf2_to_h2(uint32_t v) { return (v & 0x7fff7fffu) * 7u + v; }
__device__ __forceinline__ uint32_t prmt(uint32_t a, uint32_t b, uint32_t sel) {
    uint32_t r;
    asm("prmt.b32 %0, %1, %2, %3;\n" : "=r"(r) : "r"(a), "r"(b), "r"(sel));
    return r;
}
__device__ __forceinline__ uint32_t bitsel(uint32_t a, uint32_t b, uint32_t m) {
    uint32_t r;
    asm("lop3.b32 %0, %1, %2, %3, 0xd8;\n" : "=r"(r) : "r"(a), "r"(b), "r"(m));
    return r;
}
constexpr float KAPPA = 0.3292034911525734f;
constexpr uint32_t GELU_C2 = 0x40d940d9u;
constexpr float HSCALE = 1.0f / (2.0f * KAPPA);
__device__ __forceinline__ float w2_scale(uint32_t m) { return __uint_as_float((257u - max(m >> 23, 16u)) << 23); }
__device__ __forceinline__ void sched_break(int zero) {
    asm volatile("{\n.reg .pred p;\nsetp.ne.s32 p, %0, 0;\nSB_LOOP:\n@p nanosleep.u32 1;\n@p bra SB_LOOP;\n}\n" ::"r"(zero));
}

#define ACC8(d, o) "+r"(d[o + 0]), "+r"(d[o + 1]), "+r"(d[o + 2]), "+r"(d[o + 3]), "+r"(d[o + 4]), "+r"(d[o + 5]), "+r"(d[o + 6]), "+r"(d[o + 7])

__device__ __forceinline__ void mma_rs_n128(uint32_t (&d)[32], const uint32_t (&a)[4], uint32_t desc, int scale_d) {
    asm volatile(
        "{\n.reg .pred p;\n.reg .b64 db;\nsetp.ne.b32 p, %37, 0;\nmov.b64 db, {%36, 0x40000040};\n"
        "wgmma.mma_async.sync.aligned.m64n128k16.f16.f16.f16 "
        "{%0,%1,%2,%3,%4,%5,%6,%7,%8,%9,%10,%11,%12,%13,%14,%15,"
        "%16,%17,%18,%19,%20,%21,%22,%23,%24,%25,%26,%27,%28,%29,%30,%31},"
        "{%32,%33,%34,%35}, db, p, 1, 1, 0;\n}\n"
        : ACC8(d, 0), ACC8(d, 8), ACC8(d, 16), ACC8(d, 24)
        : "r"(a[0]), "r"(a[1]), "r"(a[2]), "r"(a[3]), "r"(desc), "r"(scale_d));
}

__device__ __forceinline__ void mma_ss_n128(uint32_t (&d)[32], uint32_t da, uint32_t db, int scale_d) {
    asm volatile(
        "{\n.reg .pred p;\n.reg .b64 da, db;\nsetp.ne.b32 p, %34, 0;\nmov.b64 da, {%32, 0x40000040};\nmov.b64 db, {%33, 0x40000040};\n"
        "wgmma.mma_async.sync.aligned.m64n128k16.f16.f16.f16 "
        "{%0,%1,%2,%3,%4,%5,%6,%7,%8,%9,%10,%11,%12,%13,%14,%15,"
        "%16,%17,%18,%19,%20,%21,%22,%23,%24,%25,%26,%27,%28,%29,%30,%31},"
        "da, db, p, 1, 1, 1, 0;\n}\n"
        : ACC8(d, 0), ACC8(d, 8), ACC8(d, 16), ACC8(d, 24)
        : "r"(da), "r"(db), "r"(scale_d));
}

__device__ __forceinline__ void mma_rs_n192(uint32_t (&d)[48], const uint4& a, uint32_t db) {
    asm volatile(
        "{\n.reg .b64 db;\nmov.b64 db, {%52, 16};\n"
        "wgmma.mma_async.sync.aligned.m64n192k16.f16.f16.f16 "
        "{%0,%1,%2,%3,%4,%5,%6,%7,%8,%9,%10,%11,%12,%13,%14,%15,"
        "%16,%17,%18,%19,%20,%21,%22,%23,%24,%25,%26,%27,%28,%29,%30,%31,"
        "%32,%33,%34,%35,%36,%37,%38,%39,%40,%41,%42,%43,%44,%45,%46,%47},"
        "{%48,%49,%50,%51}, db, 1, 1, 1, 0;\n}\n"
        : ACC8(d, 0), ACC8(d, 8), ACC8(d, 16), ACC8(d, 24), ACC8(d, 32), ACC8(d, 40)
        : "r"(a.x), "r"(a.y), "r"(a.z), "r"(a.w), "r"(db));
}

#define P1_SPLIT 5
#define P1_PACE 1
constexpr int P1_SLOT = LN_TILE / 6, P1_NST = 6;
constexpr int P1_W = 64 * C_DIM * 2;
constexpr int P1_X = 32 * C_DIM * 2;
constexpr int P1_OFF_W = LN_TILE;
constexpr int P1_OFF_X = P1_OFF_W + 2 * P1_W;
constexpr int P1_OFF_BAR = 227328;
constexpr int P1_OFF_TILE = P1_OFF_BAR + (2 * P1_NST + 4 + 4 + 4) * 8;
constexpr int P1_OFF_EX = P1_OFF_TILE + 64;
constexpr int P1_OFF_DW = P1_OFF_EX + 256 * 4;
constexpr int OFF_PRE = P1_OFF_DW + C_DIM * 2;
constexpr int SMEM_BYTES = OFF_PRE + C_DIM * 4 + 16;

__device__ __forceinline__ float rsqrt_fast(float x) {
    float r;
    asm("rsqrt.approx.ftz.f32 %0, %1;\n" : "=f"(r) : "f"(x));
    return r;
}
__device__ __forceinline__ float row_sum(const uint32_t (&c)[4]) {
    const uint32_t u = bf2_add(bf2_add(c[0], c[1]), bf2_add(c[2], c[3]));
    float s = bf_lo(u) + bf_hi(u);
#pragma unroll
    for (int o = 1; o < 8; o <<= 1) s += __shfl_xor_sync(0xffffffffu, s, o);
    return s;
}
__device__ __forceinline__ uint32_t pace(uint32_t bar, uint32_t off, uint32_t val, uint32_t after, int zero) {
    asm volatile(
        "{\n.reg .pred p, q;\n.reg .b32 par;\n"
        "lop3.b32 par, %4, %2, %3, 0xea;\n"
        "setp.eq.u32 q, par, 0;\n"
        "mov.pred p, 0;\n"
        "@q mbarrier.test_wait.parity.shared::cta.b64 p, [%1], par;\n"
        "selp.u32 par, 1, 0, p;\n"
        "@q mbarrier.try_wait.parity.shared::cta.b64 p, [%1], par, 1000;\n"
        "@p or.b32 %0, %0, %2;\n"
        "}\n" : "+r"(val) : "r"(bar), "r"(zero), "r"(off), "r"(after));
    return val;
}
template <int PACE, int R>
__device__ __forceinline__ void ln_rows(uint32_t (&v)[R][6][4], const uint32_t (&d)[6][4], uint32_t bar, uint32_t off, int zero,
                                        uint32_t bar_read) {
    const float inv = 1.0f / C_DIM;
    uint32_t c[R][4], nm[R];
    float e[R], r[R], er[R];
    bool big = false;
#pragma unroll
    for (int p = 0; p < R; p++) {
#pragma unroll
        for (int i = 0; i < 6; i++)
#pragma unroll
            for (int k = 0; k < 4; k++) c[p][k] = bf2_fma(v[p][i][k], d[i][k], i ? c[p][k] : 0);
        const float m = row_sum(c[p]) * inv;
        nm[p] = pack_bf16(-m, -m);
        e[p] = m + bf_lo(nm[p]);
    }
    if (bar_read) mbar_arrive(bar_read + (nm[0] & zero));
    if (PACE & 1) nm[0] = pace(bar, off, nm[0], nm[0], zero);
#pragma unroll
    for (int p = 0; p < R; p++) {
#pragma unroll
        for (int i = 0; i < 6; i++) {
#pragma unroll
            for (int k = 0; k < 4; k++) {
                v[p][i][k] = bf2_fma(v[p][i][k], d[i][k], nm[p]);
                c[p][k] = i ? bf2_fma(v[p][i][k], v[p][i][k], c[p][k]) : bf2_mul(v[p][i][k], v[p][i][k]);
            }
        }
        r[p] = KAPPA * rsqrt_fast(fmaxf(fmaf(-e[p], e[p], row_sum(c[p]) * inv), 0.f) + 1e-5f);
        er[p] = -e[p] * r[p] * 0x1p-112f;
        big |= r[p] < 0x1p-8f;
    }
    if (__any_sync(0xffffffffu, big)) {
#pragma unroll
        for (int p = 0; p < R; p++) {
            const uint32_t p2 = __float_as_uint(r[p]) & 0x7f800000u;
            r[p] = __uint_as_float((__float_as_uint(r[p]) & 0x007fffffu) | 0x3f800000u);
#pragma unroll
            for (int i = 0; i < 6; i++)
#pragma unroll
                for (int k = 0; k < 4; k++) v[p][i][k] = bf2_mul(v[p][i][k], p2 | p2 >> 16);
        }
    }
#pragma unroll
    for (int p = 0; p < R; p++) {
        uint32_t rs = pack_bf16(r[p] * 0x1p-112f, r[p] * 0x1p-112f);
        const uint32_t sh = pack_bf16(er[p], er[p]);
        if (PACE & 2) rs = pace(bar, off, rs, sh, zero);
#pragma unroll
        for (int i = 0; i < 6; i++)
#pragma unroll
            for (int k = 0; k < 4; k++) v[p][i][k] = bf2_to_h2(bf2_fma(v[p][i][k], rs, sh));
    }
}

template <int R>
__device__ __forceinline__ uint32_t gelu2(uint32_t a, uint32_t sc2) {
    uint32_t y, t;
    if (R) asm("{\n.reg .b16 l, h;\n.reg .b32 f;\nmov.b32 {l, h}, %2;\nmov.b32 f, {h, h};\nmul.rn.f16x2 %0, %1, f;\n}\n" : "=r"(y) : "r"(a), "r"(sc2));
    else asm("{\n.reg .b16 l, h;\n.reg .b32 f;\nmov.b32 {l, h}, %2;\nmov.b32 f, {l, l};\nmul.rn.f16x2 %0, %1, f;\n}\n" : "=r"(y) : "r"(a), "r"(sc2));
    asm("tanh.approx.f16x2 %0, %1;\n" : "=r"(t) : "r"(h2_mul(y, h2_fma(y, y, GELU_C2))));
    return h2_fma(a, t, a);
}
constexpr uint32_t SPARE = 0x40074007u;
constexpr float UNCHOP = 1.0023f;

__device__ __forceinline__ uint32_t p1_exponents(float (&t)[2], uint32_t (&ex)[2], uint32_t saddr, int lane) {
#pragma unroll
    for (int r = 0; r < 2; r++) {
        t[r] += __shfl_xor_sync(0xffffffffu, t[r], 1);
        t[r] += __shfl_xor_sync(0xffffffffu, t[r], 2);
        ex[r] = min(max(((__float_as_uint(193.3f * t[r]) >> 23) + 127u) >> 1, 72u), 198u);
        asm volatile("st.shared.u32 [%0], %1;\n" ::"r"(saddr + r * 32), "r"(ex[r] << 23) : "memory");
    }
    return pack_f16(__uint_as_float(min(ex[0], 142u) << 23), __uint_as_float(min(ex[1], 142u) << 23));
}
template <int N>
__device__ __forceinline__ void p1_convert(uint32_t (&o)[N][4], uint32_t (&v)[N][4], const uint32_t (&ex)[2]) {
    if (__any_sync(0xffffffffu, max(ex[0], ex[1]) > 141u)) {
#pragma unroll
        for (int k = 0; k < 4 * N; k++) v[k >> 2][k & 3] = bf2_mul(v[k >> 2][k & 3], ex[k & 1] > 141u ? 0x1f801f80u : 0x3f803f80u);
    }
#pragma unroll
    for (int k = 0; k < 4 * N; k++) {
        const uint32_t u = bf2_mul(v[k >> 2][k & 3], ((ex[k & 1] > 141u ? 206u : 142u) - ex[k & 1]) * 0x00800080u);
        asm volatile("mad.lo.u32 %0, %1, 7, %2;\n" : "=r"(o[k >> 2][k & 3]) : "r"(u & 0x7fff7fffu), "r"(u));
    }
}
template <int N>
__device__ __forceinline__ void p1_squares(const uint32_t (&v)[N][4], float (&t)[2]) {
#pragma unroll
    for (int j = 0; j < N / 2; j++) {
        const int r = j & 1, b = (j >> 1) * 4;
        uint32_t c = bf2_mul(v[b][r], v[b][r]);
#pragma unroll
        for (int k = 1; k < 8; k++) c = bf2_fma(v[b + k / 2][r + (k & 1) * 2], v[b + k / 2][r + (k & 1) * 2], c);
        t[r] += bf_lo(c) + bf_hi(c);
    }
}
__device__ __forceinline__ void p1_epilogue(const uint32_t (&acc)[2][32], const uint32_t (&sc2)[2], float (&ssq)[4], uint8_t* hp, int zero) {
    uint32_t sq[2], h[16][4];
#pragma unroll
    for (int i2 = 0; i2 < 9; i2++) {
#pragma unroll
        for (int c = 2 * i2 - 2; c < 2 * i2; c++) {
            if (c >= 0 && (c & 3)) {
                uint32_t o[4];
#pragma unroll
                for (int u = 0; u < 4; u++) {
                    const uint32_t v = h[c & 12][u];
                    o[u] = bitsel(h[c][u], (c & 3) == 2 ? prmt(v, v, 0xa381) : prmt(v >> 3, v, (c & 3) == 1 ? 0x6240 : 0xf3d1), SPARE);
                }
                stg128_cs(hp + (c >> 3) * 2 * H_STEP + ((c >> 2) & 1) * H_HALF + ((c & 3) - 1) * 512, o[0], o[1], o[2], o[3]);
            }
        }
        if (i2 < 8) {
#pragma unroll
            for (int u = 0; u < 4; u++) {
                h[2 * i2][u] = gelu2<0>(acc[i2 >> 2][8 * (i2 & 3) + 2 * u], sc2[i2 >> 2]);
                h[2 * i2 + 1][u] = gelu2<1>(acc[i2 >> 2][8 * (i2 & 3) + 2 * u + 1], sc2[i2 >> 2]);
#pragma unroll
                for (int r = 0; r < 2; r++) {
                    const uint32_t v = h[2 * i2 + r][u];
                    sq[r] = ((i2 & 3) | u) ? h2_fma(v, v, sq[r]) : h2_mul(v, v);
                }
            }
            if ((i2 & 3) == 3) {
#pragma unroll
                for (int r = 0; r < 2; r++) ssq[(i2 >> 2) * 2 + r] += h_lo(sq[r]) + h_hi(sq[r]);
            }
            sched_break(zero);
        }
    }
}
template <int WG>
__device__ __forceinline__ void p1_mma(uint32_t (&acc)[2][32], const uint32_t (&a)[24][4], uint32_t sbase, uint32_t empty_remote, int i, int lane, bool pass) {
    const uint32_t bar_full = sbase + P1_OFF_BAR;
    const uint32_t db = (uint32_t)make_desc(sbase, 16, 1024), da = db + (P1_OFF_W + WG * P1_W) / 16;
    if (WG == 0) mbar_wait(bar_full, i & 1);
    bar_sync(1 + WG, 256);
    TRACE(WG, i, 1);
    wg_fence();
#pragma unroll
    for (int k = 0; k < 24; k++) {
        if (WG == 0 && k && k % 4 == 0) mbar_wait(bar_full + (k >> 2) * 8, i & 1);
        mma_rs_n128(acc[0], a[k], db + (k >> 2) * 1024 + (k & 3) * 2, k != 0);
        mma_ss_n128(acc[1], da + k * 128, db + (k >> 2) * 1024 + (k & 3) * 2, k != 0);
        if (k == 23 && pass) bar_arrive(2 - WG, 256);
        if (k == 23 || (WG == 1 && k % 4 == 3)) wg_commit();
        if (WG == 1 && k % 4 == 3 && k > 3) {
            wg_wait<1>();
            if (lane < 2) mbar_arrive_cluster(empty_remote + ((k >> 2) - 1) * 8);
        }
    }
    TRACE(WG, i, 2);
    wg_wait<0>();
    if (WG == 1 && lane < 2) mbar_arrive_cluster(empty_remote + 5 * 8);
}
__device__ __forceinline__ bool p1_consumer(const uint32_t (&a)[24][4], const uint32_t (&sc2)[2], uint32_t sbase, int WG, int w, int lane, int zero) {
    const uint32_t bar_full = sbase + P1_OFF_BAR, bar_empty = bar_full + P1_NST * 8;
    const uint32_t empty_remote = mapa(bar_empty, lane & 1);
    const uint32_t bar_pace = bar_empty + P1_NST * 8 + 32 + w * 8;
    const int g = lane >> 2, q = lane & 3, half = WG ^ ((blockIdx.x / GRP_CTAS) & 1), cb = (blockIdx.x % GRP_CTAS) * 4 + half * 2;
    uint32_t acc[2][32];
    float ssq[4] = {0.f, 0.f, 0.f, 0.f};
    TSTAMP(0, 1);

    uint8_t* hp = reinterpret_cast<uint8_t*>(g_h) + ((cb * 2 + (w >> 1)) * H_STEP + (w & 1) * 1536) + g * 64 + (q ^ (g >> 1)) * 16;
    int i = 0;
    uint32_t more = 3, both;
#pragma unroll 1
    for (;; i++) {
        TRACE(WG, i, 0);
        both = more & 2;
        if (WG == 0) p1_mma<0>(acc, a, sbase, empty_remote, i, lane, both);
        else p1_mma<1>(acc, a, sbase, empty_remote, i, lane, true);
        TRACE(WG, i, 4);
        int step;
        asm volatile("ld.shared.v2.u32 {%0, %1}, [%2];\n" : "=r"(step), "=r"(more) : "r"(sbase + P1_OFF_TILE + (i & 3) * 16) : "memory");
        hp += step;
        p1_epilogue(acc, sc2, ssq, hp, zero);
        if (lane == 0) mbar_arrive(bar_pace);
        if (more & 4) {
            asm volatile("fence.proxy.async.global;\n" ::: "memory");
            bar_arrive(8, 288);
        }
        if (!(more >> WG & 1)) break;
    }
    TSTAMP(0, 21);
    if (WG == 0 && both) bar_sync(1, 256);
    const int ch = (q >> 1) * 64 + w * 16 + (q & 1) * 8 + g;
    float f;
    asm volatile("ld.shared.f32 %0, [%1];\n" : "=f"(f) : "r"(sbase + P1_OFF_EX + (half * 128 + ch) * 4) : "memory");
    g_scale[cb * 64 + ch] = f;
    asm volatile("fence.proxy.async.global;\n" ::: "memory");
    bar_arrive(3, 320);
    asm volatile("barrier.cluster.arrive.relaxed.aligned;\n" ::: "memory");
#pragma unroll
    for (int r = 0; r < 4; r++) {
        ssq[r] += __shfl_xor_sync(0xffffffffu, ssq[r], 1);
        ssq[r] += __shfl_xor_sync(0xffffffffu, ssq[r], 2);
    }
    const float t = q == 0 ? ssq[0] : q == 1 ? ssq[1] : q == 2 ? ssq[2] : ssq[3];
    const float old = atomicAdd(&g_sums[cb * 64 + ch], t * f * f);
    const unsigned one = 0x10000u + __any_sync(0xffffffffu, t < (i + 1) * 0x1p-12f || old < 0.f);
    if (lane == 0) asm volatile("red.relaxed.gpu.global.add.u32 [%0], %1;\n" ::"l"(&g_prog[4][0]), "r"(one) : "memory");
    __syncwarp();
    return WG ? more & 1 : both;
}

__device__ __forceinline__ void p2_init(uint32_t sbase);
template <int ROLE>
__device__ __forceinline__ bool pass1(const CUtensorMap& wmap, const __nv_bfloat16* __restrict__ x, const __nv_bfloat16* __restrict__ dw,
                                      const __nv_bfloat16* __restrict__ w2, const __nv_bfloat16* __restrict__ grn_b, uint32_t sbase,
                                      int warp, int lane, int zero) {
    const uint32_t bar_full = sbase + P1_OFF_BAR, bar_empty = bar_full + P1_NST * 8, bar_w = bar_empty + P1_NST * 8;
    const uint32_t rank = cluster_rank();
    const int cig = blockIdx.x % GRP_CTAS;
    uint8_t* const ring = reinterpret_cast<uint8_t*>(g_ln);

    TSTAMP(0, 0);
    TRACEW(110 + warp, 0);
    const uint32_t bar_pace = bar_w + 32, bar_xfull = bar_pace + 32, bar_xempty = bar_xfull + 8, bar_done = bar_xfull + 16;
    const int ln0 = blockIdx.x >> 2, first = blockIdx.x / GRP_CTAS;
    const uint8_t* xsrc = reinterpret_cast<const uint8_t*>(x) + (size_t)blockIdx.x * P1_X;

    if (ROLE == 2) {
        reg_dec<32>();
        asm volatile("barrier.cluster.arrive.relaxed.aligned;\n" ::: "memory");
        asm volatile("barrier.cluster.wait.aligned;\n" ::: "memory");
        if (warp == 12) {
            int prev = 0, t = first;
            const uint32_t rbase = mapa(sbase, lane & 1);
#pragma unroll 1
            for (int i = 0; t < NT128; i++) {
                const int round = t / LN_RING, slot = t - round * LN_RING;
                const uint8_t* src = ring + slot * LN_TILE + rank * (P1_SLOT / 2);
                int next = 0;
                if (rank == 0 && lane == 0) {
                    next = t < NT128 - P1_SPLIT ? NGRP + atomicAdd(&g_flag[LN_RING + (cig >> 1)][0][0], 1u) : 2 * NT128;
                    if (next >= NT128 - P1_SPLIT && next < 2 * NT128) next = NT128 - P1_SPLIT + atomicAdd(&g_flag[LN_RING + 3 + (cig >> 1)][first & 1][0], 1u);
                }
                flag_wait<true>(&g_flag[slot][0][0], 4 * round + 4);
                TRACEW(i, 2);
                asm volatile("fence.proxy.async.global;\n" ::: "memory");
                next = __shfl_sync(0xffffffffu, next, 0);
#pragma unroll 1
                for (int h = 0; h < P1_NST; h++) {
                    mbar_wait(bar_empty + h * 8, i & 1);
                    if (h == 0) TRACEW(i, 4);
                    if (h == 5) TRACEW(i, 5);
                    if (elect_one()) {
                        mbar_expect_tx(bar_full + h * 8, h ? P1_SLOT : P1_SLOT + 16);
                        bulk_g2s_mc(sbase + h * P1_SLOT + rank * (P1_SLOT / 2), src + h * P1_SLOT, P1_SLOT / 2, bar_full + h * 8, (uint16_t)3);
                    }
                    __syncwarp();
                    if (h == 0 && rank == 0 && lane < 2)
                        asm volatile("st.async.shared::cluster.mbarrier::complete_tx::bytes.v4.u32 [%0], {%1, %2, %3, %3}, [%4];\n"
                                     ::"r"(rbase + P1_OFF_TILE + (i & 3) * 16), "r"((t - prev) * (2 * H_TILE)), "r"((next < NT128 - P1_SPLIT ? 3 : next < NT128) + (t < NT_EARLY && next >= NT_EARLY ? 4 : 0)), "r"(next),
                                       "r"(rbase + P1_OFF_BAR) : "memory");
                }
                prev = t;
                t = next;
                if (rank != 0) {
                    mbar_wait(bar_full, i & 1);
                    asm volatile("ld.shared.u32 %0, [%1];\n" : "=r"(t) : "r"(sbase + P1_OFF_TILE + (i & 3) * 16 + 8) : "memory");
                }
            }
        } else if (warp == 13) {
            int ph = 0;
            unsigned target = 0;
#pragma unroll 1
            for (int i = ln0 + LN_STEP; i < NT128; i += LN_STEP, ph ^= 1) {
                target += ph * (GRP_CTAS / 2);
                xsrc += (size_t)NUM_CTAS * P1_X;
                mbar_wait(bar_xempty, ph);
                if (elect_one()) {
                    mbar_expect_tx(bar_xfull, P1_X);
                    bulk_g2s(sbase + P1_OFF_X, xsrc, P1_X, bar_xfull);
                }
                __syncwarp();
                const uint32_t off = flag_wait<false>(&g_flag[ln0 + (ph ^ 1) * LN_STEP][1][0], target);
                mbar_wait(bar_done, ph);
                if (elect_one()) {
                    asm volatile("st.shared.u32 [%0], %1;\n" ::"r"(bar_done + 8), "r"(off) : "memory");
                    mbar_arrive(bar_xfull);
                }
                __syncwarp();
            }
        } else if (warp == 15) {
            int t = first;
            if (rank == 1 && lane == 0) mbar_arrive(bar_empty);
#pragma unroll 1
            for (int i = 0; rank == 1 && t < NT128; i++) {
#pragma unroll 1
                for (int h = 0; h < P1_NST; h++) mbar_wait(bar_full + h * 8, i & 1);
                if (lane == 0) asm volatile("red.relaxed.gpu.global.add.u32 [%0], 1;\n" ::"l"(&g_flag[t % LN_RING][1][0]) : "memory");
                asm volatile("ld.shared.u32 %0, [%1];\n" : "=r"(t) : "r"(sbase + P1_OFF_TILE + (i & 3) * 16 + 8) : "memory");
                if (lane == 0) mbar_arrive(bar_empty);
                TRACEW(i, 3);
            }
            if (rank == 0) {
                mbar_wait(bar_full, 0);
                TRACEW(110 + warp, 3);
                mbar_wait(bar_full, 1);
                float* sums = g_sums + HID;
                unsigned* flag = reinterpret_cast<unsigned*>(sums + C_DIM);
                if (blockIdx.x == 0) reinterpret_cast<uint2*>(g_half)[lane] = make_uint2(0, 0);
                if (blockIdx.x == 2 && lane < 7) g_prog[lane][0] = 0;
                if (blockIdx.x < 96) g_redo[blockIdx.x * 16 + lane] = 0.f;
                float gs = 0.f;
#pragma unroll 1
                for (int pass = 0; pass < 2; pass++) {
                    float mx = 0.f;
#pragma unroll 1
                    for (int it = first; it < 96; it += NGRP) {
                        const int nb = it % 12, k0 = (cig * 4 + it / 12) * 64 + (lane >> 2);
                        const uint32_t sc = mapa(sbase + P1_OFF_EX + (k0 & 255) * 4, it / 48);
                        uint32_t* dst = reinterpret_cast<uint32_t*>(g_w2img[0]) + (k0 >> 4) * 3072 + nb * 256 + lane;
                        float bs[8] = {};
#pragma unroll 1
                        for (int c = 0; c < 8; c++) {
                            const uint4 u = __ldg(reinterpret_cast<const uint4*>(w2 + (size_t)(k0 + c * 8) * C_DIM + nb * 32) + (lane & 3));
                            const float b = __bfloat162float(grn_b[k0 + c * 8]);
                            float t;
                            asm volatile("ld.shared::cluster.f32 %0, [%1];\n" : "=f"(t) : "r"(sc + c * 32) : "memory");
#pragma unroll
                            for (int j = 0; j < 4; j++) {
                                const uint32_t v = j == 0 ? u.x : j == 1 ? u.y : j == 2 ? u.z : u.w;
                                mx = fmaxf(mx, fmaxf(fabsf(bf_lo(v)), fabsf(bf_hi(v))) * t);
                                if (pass) {
                                    bs[2 * j] = fmaf(b, bf_lo(v), bs[2 * j]);
                                    bs[2 * j + 1] = fmaf(b, bf_hi(v), bs[2 * j + 1]);
                                    uint32_t h = pack_f16(bf_lo(v) * t * gs, bf_hi(v) * t * gs);
                                    asm volatile("movmatrix.sync.aligned.m8n8.trans.b16 %0, %0;\n" : "+r"(h));
                                    dst[(c >> 1) * 3072 + (c & 1) * 32 + j * 64] = h;
                                }
                            }
                        }
                        if (pass) {
#pragma unroll
                            for (int j = 0; j < 8; j++) {
#pragma unroll
                                for (int o = 4; o < 32; o <<= 1) bs[j] += __shfl_xor_sync(0xffffffffu, bs[j], o);
                                if (lane >> 2 == j) atomicAdd(&sums[nb * 32 + (j >> 1) * 8 + (lane & 3) * 2 + (j & 1)], bs[j]);
                            }
                        }
                    }
                    if (!pass) {
                        const uint32_t m = __reduce_max_sync(0xffffffffu, __float_as_uint(mx));
                        __threadfence();
                        __syncwarp();
                        if (lane == 0) {
                            atomicMax(flag, m);
                            asm volatile("red.release.gpu.global.add.u32 [%0], 1;\n" ::"l"(flag + 32) : "memory");
                        }
                        flag_wait<true>(flag + 32, NUM_CTAS / 2);
                        gs = w2_scale(__ldcg(flag));
                    }
                }
                asm volatile("fence.proxy.async.global;\nfence.acq_rel.gpu;\n" ::: "memory");
                __syncwarp();
                if (lane == 0) asm volatile("red.relaxed.gpu.global.add.u32 [%0], 1;\n" ::"l"(&g_prog[3][0]) : "memory");
            }
        } else if (warp == 14) {
            int ph = 0;
#pragma unroll 1
            for (int i = ln0; i < NT128; i += LN_STEP, ph ^= 1) {
                mbar_wait(bar_done, ph);
                TRACEW(i / LN_STEP, 0);
                asm volatile("fence.proxy.async.global;\n" ::: "memory");
                if (elect_one()) asm volatile("red.release.gpu.global.add.u32 [%0], 1;\n" ::"l"(&g_flag[ln0 + ph * LN_STEP][0][0]) : "memory");
                __syncwarp();
                TRACEW(i / LN_STEP, 1);
            }
            if (lane == 0) p2_init(sbase);
#pragma unroll 1
            for (int i = 6; i >= 5; i--) {
                if (i == 6) bar_sync(8, 288);
                else bar_sync(3, 320);
                asm volatile("fence.proxy.async.global;\n" ::: "memory");
                if (lane == 0) asm volatile("red.release.gpu.global.add.u32 [%0], 1;\n" ::"l"(&g_prog[i][0]) : "memory");
                __syncwarp();
            }
        }
        __syncwarp();
        asm volatile("barrier.cluster.arrive.relaxed.aligned;\n" ::: "memory");
        return false;
    } else if (ROLE == 1) {
        reg_dec<96>();
        asm volatile("barrier.cluster.arrive.relaxed.aligned;\n" ::: "memory");
        {
            const int l8 = lane & 7, row = (warp - 8) * 4 + (lane >> 3), px = (blockIdx.x & 3) * 32 + row;
            uint32_t d[6][4];
            const int n = (px & 64) + perm32(2 * row + ((px >> 5) & 1));
            uint8_t* const dst0 = ring + ln0 * LN_TILE + n * 128 + ((l8 ^ (n & 7)) << 4);
            const uint32_t src = sbase + P1_OFF_X + ((warp - 8) * 8 + (lane >> 3)) * (C_DIM * 2) + l8 * 16;
            int ph = 0;
#pragma unroll 1
            for (int i = ln0; i < NT128; i += LN_STEP, ph ^= 1) {
                TRACE(2, i / LN_STEP, 0);
                uint32_t off = 1;
#pragma unroll 1
                for (int ps = i == ln0 ? -2 : 0; ps < 2; ps += ps < 0 ? 2 : 1) {
                    if (ps == 0) {
                        if (i == ln0) asm volatile("barrier.cluster.wait.aligned;\n" ::: "memory");
                        mbar_wait(bar_xfull, ph);
                        asm volatile("ld.shared.u32 %0, [%1];\n" : "=r"(off) : "r"(bar_done + 8) : "memory");
                    }
                    if (ps == 0) TRACE(2, i / LN_STEP, 1);
                    if (i == ln0) {
#pragma unroll
                        for (int j = 0; j < 6; j++)
                            asm volatile("ld.shared.v4.u32 {%0,%1,%2,%3}, [%4];\n"
                                         : "=r"(d[j][0]), "=r"(d[j][1]), "=r"(d[j][2]), "=r"(d[j][3]) : "r"(sbase + P1_OFF_DW + j * 128 + l8 * 16) : "memory");
                    }
                    uint32_t v1[1][6][4];
                    uint32_t (&v)[6][4] = v1[0];
#pragma unroll
                    for (int j = 0; j < 6; j++)
                        asm volatile("ld.shared.v4.u32 {%0,%1,%2,%3}, [%4];\n"
                                     : "=r"(v[j][0]), "=r"(v[j][1]), "=r"(v[j][2]), "=r"(v[j][3]) : "r"(src + (ps & 1) * (4 * C_DIM * 2) + j * 128) : "memory");
                    ln_rows<P1_PACE, 1>(v1, d, bar_pace + (warp - 8) * 8, off, zero, ps == 1 && lane == 0 ? bar_xempty : 0);
                    uint8_t* dst = dst0 + ph * (LN_STEP * LN_TILE) + (ps & 1) * 4096;
#pragma unroll
                    for (int j = 0; j < 6; j++) *reinterpret_cast<uint4*>(dst + j * 16384) = make_uint4(v[j][0], v[j][1], v[j][2], v[j][3]);
                    TRACE(2, i / LN_STEP, 3 + (ps & 1));
                }
                asm volatile("fence.proxy.async.global;\nfence.acq_rel.cta;\n" ::: "memory");
                __syncwarp();
                if (lane == 0) mbar_arrive(bar_done);
                TRACE(2, i / LN_STEP, 5);
                TRACE(2, i / LN_STEP, 2);
            }
        }
        __syncwarp();
        asm volatile("barrier.cluster.arrive.relaxed.aligned;\n" ::: "memory");
        return false;
    } else {
        const int wg = warp >> 2, w = warp & 3;
        auto load_w = [&](int i0, int i1) {
#pragma unroll 1
            for (int i = i0; i < i1; i++) {
                if (!(i & 1)) mbar_expect_tx(bar_w + (i >> 1) * 8, P1_W);
                tma2(sbase + (i & 2) * P1_W + (i >> 2) * P1_W + (i & 1) * (P1_W / 2), &wmap, cig * 256 + ((i >> 1) ^ (first & 1) * 2) * 64, (i & 1) * 192, bar_w + (i >> 1) * 8);
            }
        };
        if (warp == 4 && elect_one()) {
            mbar_init(bar_xfull, 2);
#pragma unroll
            for (int i = 0; i < 4; i++) mbar_init(bar_w + i * 8, 1);
            asm volatile("fence.mbarrier_init.release.cluster;\n" ::: "memory");
            mbar_expect_tx(bar_xfull, P1_X + C_DIM * 2);
            bulk_g2s(sbase + P1_OFF_X, xsrc, P1_X, bar_xfull);
            bulk_g2s(sbase + P1_OFF_DW, dw, C_DIM * 2, bar_xfull);
            load_w(0, 4);
            asm volatile("st.shared.u32 [%0], 1;\n" ::"r"(bar_done + 8) : "memory");
            mbar_arrive(bar_xfull);
        }
        if (warp == 5 && elect_one()) {
#pragma unroll
            for (int i = 0; i < P1_NST; i++) {
                mbar_init(bar_full + i * 8, 1);
                mbar_init(bar_empty + i * 8, i ? 8 : 8 + rank);
                if (i < 4) mbar_init(bar_pace + i * 8, 1);
            }
            mbar_init(bar_xempty, 4);
            mbar_init(bar_done, 4);
            asm volatile("fence.mbarrier_init.release.cluster;\n" ::: "memory");
        }
        __syncwarp();
        asm volatile("barrier.cluster.arrive.relaxed.aligned;\n" ::: "memory");
        reg_inc<192>();
        TRACEW(110 + warp, 1);
        uint32_t a[24][4];
        const uint32_t src = sbase + wg * P1_W + ((lane >> 4) * 8 + (lane & 7)) * 128 + (((2 * w + ((lane >> 3) & 1)) ^ (lane & 7)) << 4);
        const uint32_t s_ex = sbase + P1_OFF_EX + ((wg ^ (first & 1)) * 128 + w * 16 + (lane >> 2)) * 4;
        uint32_t sc2[2], ex[2];
        if (wg == 1) bar_arrive(1, 256);
#pragma unroll 1
        for (int it = 0; it < 2; it++) {
          if (it != wg) asm volatile("barrier.cluster.wait.aligned;\n" ::: "memory");
          if (it < wg) {
              mbar_wait(bar_xfull, 0);
              if (w == 0 && elect_one()) load_w(4, 8);
              __syncwarp();
          }
          if (it || wg == 0) {
            float t[2] = {0.f, 0.f};
            if (it) {
                TRACEW(110 + warp, 2);
                mbar_wait(bar_w + wg * 16, 0);
            }
            TRACEW(110 + warp, 5);
#pragma unroll
            for (int k = 0; k < 24; k++) ldsm4t(a[k], src + k * 2048);
            TRACEW(110 + warp, 6);
            p1_squares(a, t);
            sc2[0] = p1_exponents(t, ex, s_ex, lane);
            if (it && lane < 6) mbar_arrive_cluster(mapa(bar_empty, lane & 1) + (wg * 3 + (lane >> 1)) * 8 + (sc2[0] & zero));
            p1_convert<24>(a, a, ex);
          }
          if (it || wg == 1) {
            float t[2] = {0.f, 0.f};
            TRACEW(100 + warp, 0);
            if (it) mbar_wait(bar_w + wg * 16 + 8, 0);
            TRACEW(100 + warp, 1);
            uint32_t v[8][4], o[8][4];
#pragma unroll 1
            for (int j = 0; j <= 2 * it; j++) {
#pragma unroll
                for (int k = 0; k < 8; k++) ldsm4t(v[k], src + P1_OFF_W + (8 * j + k) * 2048);
                p1_squares(v, t);
            }
            sc2[1] = p1_exponents(t, ex, s_ex + 256, lane);
#pragma unroll 1
            for (int j = 2 * it; j >= 0; j--) {
                p1_convert<8>(o, v, ex);
#pragma unroll
                for (int k = 0; k < 8; k++) {
                    if (j) ldsm4t(v[k], src + P1_OFF_W + (8 * j - 8 + k) * 2048);
                    if (it) asm volatile("stmatrix.sync.aligned.m8n8.x4.trans.shared.b16 [%0], {%1,%2,%3,%4};\n"
                                         ::"r"(src + P1_OFF_W + (8 * j + k) * 2048), "r"(o[k][0]), "r"(o[k][1]), "r"(o[k][2]), "r"(o[k][3]) : "memory");
                }
            }
          }
        }
        asm volatile("fence.proxy.async.shared::cta;\n" ::: "memory");
        TRACEW(110 + warp, 7);
        bar_sync(6 + wg, 128);
        const bool early = p1_consumer(a, sc2, sbase, wg, w, lane, zero);
        TSTAMP(0, 30);
        return early;
    }
}

constexpr int P2_B = 24576, P2_NB = 4;
constexpr int P2_A = 3072, P2_NA = 8;
constexpr int P2_XROW = C_DIM * 2;
constexpr int P2_OFF_A = P2_B * P2_NB;
constexpr int P2_OFF_X = P2_OFF_A + 3 * P2_NA * P2_A + 128;
constexpr int P2_LHALF = 2 * P2_NA * P2_A + 64;
constexpr int P2_XHALF = 32 * P2_XROW + 64;
constexpr int P2_OFF_GRN = P2_OFF_X + 64 * P2_XROW + 128;
constexpr int P2_OFF_BIAS = P2_OFF_GRN + HID * 2;
constexpr int P2_OFF_RED = P2_OFF_BIAS + C_DIM * 4;
constexpr int P2_OFF_BAR = P2_OFF_RED + 192;
constexpr int P2_SMEM = P2_OFF_BAR + (2 * P2_NB + 6 * P2_NA + 7) * 8;
#define P2_S1 16
constexpr int P2_S2 = 32;
constexpr int P2_NCL = NUM_CTAS / 2, P2_ITEMS = NT128 / P2_NCL, P2_SHARED = NT128 - P2_ITEMS * P2_NCL;
constexpr int P2_NPOS = 6 * 48 + P2_S1;
constexpr int P2_RAW = 24;
constexpr int P2_XC = 8 * P2_XROW;
#define P2_T0 5
#define P2_TL 8
#define P2_XP0 30
#define P2_XPN 13
#define P2_XPD 3
#define P2_CMP 0
#define P2_SLACK -1
#define P2_XW 6
#define P2_AH 2
__device__ __forceinline__ int p2_start(int n) { return n < 0 ? 0 : n / 3 * 48 + (n % 3 == 1 ? P2_S1 : n % 3 * (P2_S2 / 2)); }
__device__ __forceinline__ int p2_tile(int cl, int n) {
    return n == 0 ? NT_EARLY - 1 - cl : n < 0 ? NT_EARLY + (cl >> 1) : cl + P2_NCL * (n - 1);
}

#define P2_EB 2
#define P2_EX 1
__device__ __forceinline__ void p2_epilogue(uint32_t (&acc0)[48], uint32_t (&acc1)[48], uint32_t up, uint32_t sx, uint32_t sb, int zero) {
    uint32_t v[12][3][4];
    auto load = [&](int t, int j) {
        if (t >= 12) return;
        uint32_t (&w)[4] = v[t][j];
        asm volatile("ld.shared.v4.u32 {%0,%1,%2,%3}, [%4];\n" : "=r"(w[0]), "=r"(w[1]), "=r"(w[2]), "=r"(w[3])
                     : "r"((j ? sx + (j - 1) * 4 * P2_XROW : sb) + t * 64) : "memory");
    };
    auto store = [&](int t, int r) {
        const uint32_t* w = (t < 6 ? acc0 : acc1) + 8 * (t % 6) + 4 * r;
        asm volatile("st.shared.v4.u32 [%4], {%0,%1,%2,%3};\n" ::"r"(w[0]), "r"(w[1]), "r"(w[2]), "r"(w[3]), "r"(sx + t * 64 + r * 4 * P2_XROW) : "memory");
    };
#pragma unroll
    for (int t = 0; t < P2_EB; t++) load(t, 0);
#pragma unroll
    for (int t = 0; t < 2 * P2_EX; t++) load(t >> 1, 1 + (t & 1));
#pragma unroll
    for (int t = 0; t < 12; t++) {
        load(t + P2_EX, 1);
        load(t + P2_EX, 2);
        load(t + P2_EB, 0);
        uint32_t* acc = (t < 6 ? acc0 : acc1) + 8 * (t % 6);
        uint32_t y[8];
#pragma unroll
        for (int e = 0; e < 8; e++) {
            y[e] = h2_add(acc[e], v[t][0][e >> 1]);
            y[e] = pack_bf16(h_lo(y[e]), h_hi(y[e]));
        }
#pragma unroll
        for (int e = 0; e < 8; e++) acc[(e & 1) * 4 + (e >> 1)] = bf2_fma(y[e], up, v[t][1 + (e & 1)][e >> 1]);
        store(t, 0);
        store(t, 1);
        sched_break(zero);
    }
}

__device__ __forceinline__ void p2_unpack(uint32_t (&u)[4], uint32_t o1, uint32_t o2, uint32_t o3) {
    u[2] = o1 & ~SPARE;
    u[1] = o2 & ~SPARE;
    u[3] = o3 & ~SPARE;
    const uint32_t t = bitsel(prmt(o1, o2, 0x6341), prmt(o1, o3, 0x6240) << 3, 0x38383838u);
    u[0] = bitsel(t, prmt(o2, o3, 0x7351) << 1, 0x80808080u) & ~SPARE;
}

__device__ __forceinline__ void p2_redo_sums(int warp, int lane) {
    flag_wait<true>(&g_prog[5][0], NUM_CTAS);
#pragma unroll 1
    for (int s = warp; s < 96; s += 12) {
        float t[2] = {0.f, 0.f};
#pragma unroll 1
        for (int tile = blockIdx.x; tile < 2 * NT128; tile += NUM_CTAS) {
            const uint32_t* p = reinterpret_cast<const uint32_t*>(reinterpret_cast<const uint8_t*>(g_h) + (size_t)(tile >> 1) * (2 * H_TILE) +
                                                                  (s >> 1) * H_STEP + (tile & 1) * H_HALF + (s & 1) * 1536) + lane * 4;
#pragma unroll
            for (int j = 0; j < 4; j++) {
                uint32_t u[4];
                p2_unpack(u, __ldcg(p + j), __ldcg(p + j + 128), __ldcg(p + j + 256));
#pragma unroll
                for (int c = 0; c < 4; c++) t[c >> 1] += h_lo(u[c]) * h_lo(u[c]) + h_hi(u[c]) * h_hi(u[c]);
            }
        }
#pragma unroll
        for (int r = 0; r < 2; r++) {
            const int ch = s * 16 + r * 8 + (lane >> 2);
            const float f = __ldcg(&g_scale[ch]) * UNCHOP;
            atomicAdd(&g_redo[ch], t[r] * f * f);
        }
    }
    __threadfence();
    __syncwarp();
    if (lane == 0) asm volatile("red.release.gpu.global.add.u32 [%0], 1;\n" ::"l"(&g_prog[2][0]) : "memory");
    flag_wait<true>(&g_prog[2][0], 12 * NUM_CTAS);
}

static_assert(P2_OFF_GRN >= P1_OFF_X + P1_X && P1_OFF_BAR >= P2_SMEM, "barriers and tables keep their memory");
__device__ __forceinline__ void p2_init(uint32_t sbase) {
    const uint32_t bar = sbase + P2_OFF_BAR;
#pragma unroll 1
    for (int i = 0; i < 2 * P2_NB + 6 * P2_NA + 6; i++) {
        const int j = i - 2 * P2_NB;
        mbar_init(bar + i * 8, j < -P2_NB ? 1 : j < 0 ? 24 : j < 3 * P2_NA ? 1 : j >= 6 * P2_NA && j < 6 * P2_NA + 3 ? 2 : 4);
    }
    asm volatile("st.shared.v2.u32 [%0], {0, 0};\n" ::"r"(bar + (2 * P2_NB + 6 * P2_NA + 6) * 8) : "memory");
    asm volatile("fence.mbarrier_init.release.cluster;\nfence.acq_rel.cta;\n" ::: "memory");
}
template <int ROLE>
__device__ __forceinline__ void pass2(const __nv_bfloat16* __restrict__ x, const __nv_bfloat16* __restrict__ grn_g, __nv_bfloat16* __restrict__ out,
                                      uint8_t* smem, uint32_t sbase, bool early, int zero) {
    const uint32_t bar_bfull = sbase + P2_OFF_BAR, bar_bempty = bar_bfull + P2_NB * 8;
    const uint32_t bar_afull = bar_bempty + P2_NB * 8, bar_aempty = bar_afull + 3 * P2_NA * 8;
    const uint32_t bar_xfull = bar_aempty + 3 * P2_NA * 8, bar_oready = bar_xfull + 24, s_pos = bar_oready + 24;
    int tid;
    asm volatile("mov.u32 %0, %%tid.x;\n" : "=r"(tid));
    const int warp = __shfl_sync(0xffffffffu, tid >> 5, 0), lane = tid & 31;
    const uint32_t rank = cluster_rank();
    const int cl = blockIdx.x >> 1, pair = cl >> 1;
    const int half = pair < P2_SHARED, fin = half && (cl & 1);
    const int k0 = (pair + 3 * (cl & 1)) % 6 * 8;
    auto wait_pos = [&](int target) {
        int v;
        while (true) {
            asm volatile("ld.volatile.shared.u32 %0, [%1];\n" : "=r"(v) : "r"(s_pos) : "memory");
            if (v >= target) break;
            SAFE_BREAK;
            __nanosleep(100);
        }
    };

    TSTAMP(1, 0);
    if (ROLE == 2) {
        if (warp != 14) flag_wait<true>(&g_prog[3][0], P2_NCL);
        if (warp == 15) {
            float* pre = reinterpret_cast<float*>(smem + OFF_PRE);
            const float gs = w2_scale(__float_as_uint(__ldcg(&g_sums[HID + C_DIM])));
            float mb = 0.f;
#pragma unroll 1
            for (int i = lane; i < C_DIM; i += 32) {
                pre[i] = __ldcg(&g_sums[HID + i]) * gs;
                mb = fmaxf(mb, fabsf(pre[i]));
            }
            pre[C_DIM] = gs;
            pre[C_DIM + 1] = __uint_as_float(__reduce_max_sync(0xffffffffu, __float_as_uint(mb)));
            bar_sync(3, 320);
            unsigned v;
            do {
                asm volatile("ld.acquire.gpu.global.u32 %0, [%1];\n" : "=r"(v) : "l"(&g_prog[4][0]) : "memory");
                SAFE_BREAK;
            } while (v < NUM_CTAS * 8 * 0x10000u);
            pre[C_DIM + 2] = __uint_as_float(v & 0xffffu);
            bar_arrive(5, 416);
        }
        asm volatile("barrier.cluster.wait.aligned;\nfence.proxy.async;\n" ::: "memory");
        if (warp == 12) {
            const uint8_t* wsrc = reinterpret_cast<const uint8_t*>(g_w2img) + rank * (P2_B / 2);
            int kb = k0;
#pragma unroll 1
            for (int p = 0; p < P2_NPOS; p++) {
                const int st = p & 3;
                if (p == P2_RAW) {
                    flag_wait<true>(&g_prog[1][0], NUM_CTAS);
                    asm volatile("fence.proxy.async.global;\n" ::: "memory");
                    wsrc += sizeof(g_w2img[0]);
                }
                const int idle = (p < P2_S1 || p >= 6 * 48) + (p < P2_S2 ? !half || p >= 24 : p >= 5 * 48 + P2_S2);
                mbar_wait(bar_bempty + st * 8, (~p >> 2) & 1);
                TR2(3, p, 0);
                if (elect_one()) {
                    const int len = P2_B / 2;
                    mbar_expect_tx(bar_bfull + st * 8, 2 * len);
                    bulk_g2s_mc(sbase + st * P2_B + rank * (P2_B / 2), wsrc + kb * P2_B, len, bar_bfull + st * 8, (uint16_t)3);
                    asm volatile("st.volatile.shared.u32 [%0], %1;\n" ::"r"(s_pos), "r"(p) : "memory");
                    if (P2_SLACK > -9 && rank == 0) asm volatile("red.relaxed.gpu.global.add.u32 [%0], 1;\n" ::"l"(&g_prog[0][0]) : "memory");
                    if (idle) asm volatile("mbarrier.arrive.shared::cta.b64 _, [%0], %1;\n" ::"r"(bar_bempty + st * 8), "r"(8 * idle) : "memory");
                }
                __syncwarp();
                if (++kb == 48) kb = 0;
            }
            mbar_wait(bar_bempty, 1);
            if (lane == 0) mbar_arrive(bar_bfull);
        } else if (warp == 13) {
            const int w = lane % 3;
            const uint32_t dst0 = sbase + P2_OFF_A + w * P2_NA * P2_A;
            const uint32_t bf = bar_afull + w * P2_NA * 8, be = bar_aempty + w * P2_NA * 8;
            int n = (w == 2 && half ? -1 : w) - 3, left = 0, u = 0, c = 0;
            const uint8_t* src = nullptr;
            bool act = lane < 3;
            auto next = [&]() {
                n += 3;
                left = n >= P2_ITEMS ? -1 : n < 0 ? 24 : 48;
                u = (k0 + p2_start(n)) % 48;
                src = reinterpret_cast<const uint8_t*>(g_h) + (size_t)p2_tile(cl, n) * (2 * H_TILE) + rank * H_HALF + u * H_STEP;
            };
            next();
            flag_wait<true>(&g_prog[6][0], NUM_CTAS);
#pragma unroll 1
            for (int i = 0, w1 = 1; i < 3; i++) {
                if (i == 1 && __ldcg(&g_prog[5][0]) >= NUM_CTAS) w1 = 2;
                const int wi = i == 0 ? 0 : i == 1 ? w1 : 3 - w1;
                if (wi == 2) flag_wait<true>(&g_prog[5][0], NUM_CTAS);
                asm volatile("fence.proxy.async.global;\n" ::: "memory");
                if (w == wi && lane < 24) {
                    mbar_expect_tx(bf + lane / 3 * 8, P2_A);
                    bulk_g2s(dst0 + lane / 3 * P2_A, src + lane / 3 * H_STEP, P2_A, bf + lane / 3 * 8);
                }
                __syncwarp();
            }
            c = 8;
            left -= 8;
            u += 8;
            src += 8 * H_STEP;
            if (u == 48) { u = 0; src -= 48 * H_STEP; }
            while (__any_sync(0xffffffffu, act)) {
                if (left == 0) next();
                const bool ok = act && mbar_test(be + ((c - 1) & 7) * 8, (~c >> 3) & 1);
                if (ok) {
                    const int st = c & 7;
                    if (left > 0) {
                        mbar_expect_tx(bf + st * 8, P2_A);
                        bulk_g2s(dst0 + st * P2_A, src, P2_A, bf + st * 8);
                    } else {
                        mbar_arrive(bf + st * 8);
                        act = false;
                    }
                    src += H_STEP;
                    if (++u == 48) { u = 0; src -= 48 * H_STEP; }
                    c++;
                    left--;
                }
                SAFE_BREAK;
                if (!__any_sync(0xffffffffu, ok)) __nanosleep(100);
            }
        } else if (warp == 14) {
            const uint32_t sx = sbase + P2_OFF_X;
            size_t o = 0;
            int wp = 0;
            uint32_t par = 0;
            if (fin) {
#pragma unroll 1
                for (int c = lane * 16; c < 64 * P2_XROW + 128; c += 512) asm volatile("st.shared.v4.u32 [%0], {0, 0, 0, 0};\n" ::"r"(sx + c) : "memory");
                __syncwarp();
            }
            wait_pos(P2_XW);
#pragma unroll 1
            for (int n = -half; n <= P2_ITEMS; n++) {
                const int w = (n + 3) % 3, end = p2_start(n) + 48;
                const size_t on = (size_t)(2 * p2_tile(cl, n) + rank) * (64 * C_DIM * 2);
                const uint32_t xf = bar_xfull + w * 8;
                bool st = n + half > 0;
                const bool ld = n < P2_ITEMS - 1 && !(n < 0 && fin);
                if (n == P2_ITEMS - 1 && lane == 0) {
                    mbar_expect_tx(xf, 64 * C_DIM * 2);
#pragma unroll 1
                    for (int c = 4; c < 12; c++) {
                        if (c >= 8) {
                            mbar_wait(bar_aempty + ((2 * c - 1) & 7) * 8, 1);
                            mbar_wait(bar_aempty + ((2 * c) & 7) * 8, 1);
                        }
                        bulk_g2s(sbase + P2_OFF_A + (c & 3) * P2_XC + (c < 8 ? P2_LHALF : 0), reinterpret_cast<const uint8_t*>(x) + on + (c & 7) * P2_XC, P2_XC, xf);
                    }
                    mbar_arrive(xf);
                }
                if (st) {
                    mbar_wait(bar_oready + wp * 8, (par >> wp) & 1);
                    par ^= 1u << wp;
                }
                if (lane == 0) {
                    if (n < P2_ITEMS - 1) mbar_expect_tx(xf, ld ? 64 * C_DIM * 2 : 0);
                    const int t0 = (n ? p2_start(n - 1) + 48 : P2_S2) + (n == P2_ITEMS - 1 ? P2_TL : P2_T0), dt = end - (n == P2_ITEMS - 2 ? P2_CMP : 0) - t0;
                    int t = st ? 16 * t0 : -4096;
                    if ((n == 0 && half) || n == P2_ITEMS) {
                        if (fin && n == 0) {
                            flag_wait<true>(&g_half[pair][rank], 1);
                            asm volatile("fence.proxy.async.global;\n" ::: "memory");
                        }
#pragma unroll 1
                        for (int c = 0; c < 2; c++) {
                            uint8_t* dst = reinterpret_cast<uint8_t*>(out) + o + c * 32 * P2_XROW;
                            if (!fin || n) bulk_s2g(dst, n ? sbase + P2_OFF_A + c * P2_LHALF : sx + c * P2_XHALF, 32 * P2_XROW);
                            else asm volatile("cp.reduce.async.bulk.global.shared::cta.bulk_group.add.noftz.bf16 [%0], [%1], %2;\n"
                                              ::"l"(dst), "r"(sx + c * P2_XHALF), "r"(32 * P2_XROW) : "memory");
                        }
                        asm volatile("cp.async.bulk.commit_group;\n" ::: "memory");
                        if (!fin && n == 0) {
                            asm volatile("cp.async.bulk.wait_group 0;\nfence.proxy.async.global;\n" ::: "memory");
                            asm volatile("st.release.gpu.global.u32 [%0], 1;\n" ::"l"(&g_half[pair][rank]) : "memory");
                        }
                        st = false;
                    }
#pragma unroll 1
                    for (int c = 0; n < P2_ITEMS && c < 64 * P2_XROW; c += P2_XC, t += 2 * dt) {
                        const uint32_t sp = sx + c + (c >= 32 * P2_XROW ? 64 : 0);
                        wait_pos(t >> 4);
                        if (st) bulk_s2g(reinterpret_cast<uint8_t*>(out) + o + c, sp, P2_XC);
                        asm volatile("cp.async.bulk.commit_group;\n" ::: "memory");
                        if (ld) {
                            wait_pos((t + dt) >> 4);
                            asm volatile("cp.async.bulk.wait_group.read 0;\n" ::: "memory");
                            bulk_g2s(sp, reinterpret_cast<const uint8_t*>(x) + on + c, P2_XC, xf);
                        }
                    }
                    if (P2_SLACK > -9 && rank == 0 && n > 0 && n < P2_ITEMS - 2) flag_wait<false>(&g_prog[0][0], P2_NCL * (end + P2_SLACK));
                    if (n < P2_ITEMS - 1) mbar_arrive(xf);
                }
                __syncwarp();
                o = on;
                wp = w;
            }
            asm volatile("cp.async.bulk.wait_group.read 0;\n" ::: "memory");
        } else {
            if (blockIdx.x == 120) {
                wait_pos(P2_RAW);
                for (int i = lane; i < (LN_RING + 6) * 2; i += 32) (&g_flag[0][0][0])[i * 8] = 0;
                for (int i = lane; i < HID + 512; i += 32) g_sums[i] = 0.f;
            }
            int t = 4 * P2_XP0;
#pragma unroll 1
            for (int n = 0; n < P2_ITEMS && lane == 0; n++) {
                const uint8_t* xn = reinterpret_cast<const uint8_t*>(x) + (size_t)(2 * p2_tile(cl, n) + rank) * (64 * C_DIM * 2);
#pragma unroll 1
                for (int c = 0; c < 16; c++, t += n < P2_XPN ? 4 : P2_XPD) {
                    wait_pos(t >> 2);
                    asm volatile("cp.async.bulk.prefetch.L2.global [%0], %1;\n" ::"l"(xn + c * (P2_XC / 2)), "r"(P2_XC / 2) : "memory");
                }
            }
        }
        __syncwarp();
        END_SYNC();
    } else {
        const int wg = warp >> 2, w = warp & 3, g = lane >> 2, q = lane & 3;
        const uint32_t sx = sbase + P2_OFF_X + (g & 1) * P2_XHALF + (w * 8 + (g >> 1)) * P2_XROW + q * 16;
        const uint32_t af = bar_afull + wg * P2_NA * 8;
        const uint32_t s_a = sbase + P2_OFF_A + wg * P2_NA * P2_A + (lane >> 3) * 512 + (lane & 7) * 64 + ((w ^ ((lane & 7) >> 1)) << 4);
        uint32_t acc0[48], acc1[48], up;
        uint4 a[2][2];

        __nv_bfloat16 gg[4];
#pragma unroll
        for (int i = 0; i < 4; i++) gg[i] = grn_g[tid + 384 * i];
#pragma unroll 1
        for (int it = !early; it < 2; it++) {
            float* s_red = reinterpret_cast<float*>(smem + P2_OFF_RED);
            float gx[4], part = 0.f;
            if (it) {
                TSTAMP(1, 27);
                bar_sync(5, 416);
                TSTAMP(1, 1);
            }
#pragma unroll
            for (int i = 0; i < 4; i++) gx[i] = __ldcg(&g_sums[tid + 384 * i]);
            const float bias = reinterpret_cast<const float*>(smem + OFF_PRE)[tid];
            const float4 pre = *reinterpret_cast<const float4*>(smem + OFF_PRE + C_DIM * 4);
            if (it && __float_as_uint(pre.z)) {
                p2_redo_sums(warp, lane);
#pragma unroll
                for (int i = 0; i < 4; i++) gx[i] = __ldcg(&g_redo[tid + 384 * i]);
            }
            float mg = 0.f;
#pragma unroll
            for (int i = 0; i < 4; i++) {
                asm("sqrt.approx.f32 %0, %1;\n" : "=f"(gx[i]) : "f"(gx[i] * (HSCALE * HSCALE) + 1e-6f));
                part += gx[i];
                gx[i] *= __bfloat162float(gg[i]);
                mg = fmaxf(mg, fabsf(gx[i]));
            }
#pragma unroll
            for (int o = 16; o > 0; o >>= 1) part += __shfl_xor_sync(0xffffffffu, part, o);
            const uint32_t mgw = __reduce_max_sync(0xffffffffu, __float_as_uint(mg));
            TSTAMP(1, 26);
            if (lane == 0) *reinterpret_cast<float2*>(s_red + warp * 2) = make_float2(part, __uint_as_float(mgw));
            if (it) bar_sync(4, 384);
            float tot = 0.f;
#pragma unroll
            for (int i = 0; i < 6; i++) {
                const float4 t = *reinterpret_cast<const float4*>(s_red + i * 4);
                tot += t.x + t.z;
                mg = fmaxf(mg, fmaxf(t.y, t.w));
            }
            const float inv = __fdividef(1.0f, tot * (1.0f / HID) + 1e-6f);
            const uint32_t ej = min((__float_as_uint(fmaxf(fmaf(mg, inv, 1.0f) * (HSCALE * UNCHOP), pre.y * 0x1p-13f)) >> 23) + 1, 250u);
            const float dn = __uint_as_float((254u - ej) << 23);
            up = min(ej + 127u - (__float_as_uint(pre.x) >> 23), 254u) * 0x00800080u;
            reinterpret_cast<uint16_t*>(smem + P2_OFF_BIAS + C_DIM * 2)[tid] = 0;
            *reinterpret_cast<__half*>(smem + P2_OFF_BIAS + (tid >> 5) * 64 + (tid & 6) * 8 + (tid & 24) / 2 + (tid & 1) * 2) = __float2half_rn(bias * dn);
#pragma unroll
            for (int i = 0; i < 4; i++) {
                const int k = tid + 384 * i;
                *reinterpret_cast<__half*>(smem + P2_OFF_GRN + (k >> 4) * 32 + (k & 6) * 4 + (k & 8) / 2 + (k & 1) * 2) =
                    __float2half_rn(fmaf(gx[i], inv, 1.0f) * (HSCALE * UNCHOP * dn));
            }
            TSTAMP(1, 25);
        }
        bar_sync(4, 384);
        asm volatile("barrier.cluster.wait.aligned;\n" ::: "memory");
        TSTAMP(1, 28);
        if (wg == 1) {
            constexpr int N = sizeof(g_w2img[0]) / 16, PER = (N + NUM_CTAS - 1) / NUM_CTAS;
            uint4 v[5];
#pragma unroll
            for (int i = 0; i < 5; i++) v[i] = __ldcg(&g_w2img[0][min(blockIdx.x * PER + (tid & 127) + 128 * i, N - 1)]);
#pragma unroll
            for (int i = 0; i < 5; i++) {
                const int j = min(blockIdx.x * PER + (tid & 127) + 128 * i, N - 1);
                const uint32_t* t = reinterpret_cast<const uint32_t*>(smem + P2_OFF_GRN + (j / 768) * 32 + (j & 8) / 2);
                auto sc = [&](uint32_t u, int e) { return (h2_mul(u, t[2 * e]) + 0x00040004u) & 0xfff8fff8u; };
                g_w2img[1][j] = make_uint4(sc(v[i].x, 0), sc(v[i].y, 1), sc(v[i].z, 2), sc(v[i].w, 3));
            }
            asm volatile("fence.proxy.async.global;\n" ::: "memory");
            bar_sync(2, 128);
            if (tid == 128) asm volatile("fence.acq_rel.gpu;\nred.release.gpu.global.add.u32 [%0], 1;\n" ::"l"(&g_prog[1][0]) : "memory");
        }

        const int who = __shfl_sync(0xffffffffu, lane == 2 ? 0 : lane < 2 ? 1 : 2, lane);
        const uint32_t rel0 = who ? mapa(bar_bempty, lane & 1) : mapa(bar_aempty + wg * P2_NA * 8, rank), rel1 = rel0 + (who ? 0 : 32);
        auto publish = [&]() {
            asm volatile("fence.proxy.async.shared::cta;\n" ::: "memory");
            __syncwarp();
            if (who == 0) mbar_arrive(bar_oready + wg * 8);
        };
        bool ok_a, pend = false;
        uint32_t pa = 0, s_t;
        auto fetch = [&](int j, bool raw) {
            uint32_t o[6], u0[4], u1[4];
            uint2 t0 = make_uint2(0, 0), t1 = t0;
            if (raw) {
                asm volatile("ld.shared.v2.u32 {%0,%1}, [%2];\n" : "=r"(t0.x), "=r"(t0.y) : "r"(s_t + j * 64) : "memory");
                asm volatile("ld.shared.v2.u32 {%0,%1}, [%2];\n" : "=r"(t1.x), "=r"(t1.y) : "r"(s_t + j * 64 + 32) : "memory");
            }
            const bool ok_b = mbar_test(bar_bfull + (j & 3) * 8, j >> 2);
            if (j == 7) pa ^= 1;
            ok_a = mbar_test(af + ((j + 1) & 7) * 8, pa);
            asm volatile("ldmatrix.sync.aligned.m8n8.x4.trans.shared.b16 {%0,%1,%2,%3}, [%4];\n"
                         : "=r"(o[0]), "=r"(o[1]), "=r"(o[2]), "=r"(o[3]) : "r"(s_a + j * P2_A) : "memory");
            asm volatile("ldmatrix.sync.aligned.m8n8.x2.trans.shared.b16 {%0,%1}, [%2];\n"
                         : "=r"(o[4]), "=r"(o[5]) : "r"(s_a + j * P2_A + 2048) : "memory");
            p2_unpack(u0, o[0], o[1], o[2]);
            p2_unpack(u1, o[3], o[4], o[5]);
            if (raw) {
                u0[0] = h2_mul(u0[0], t0.x); u0[1] = h2_mul(u0[1], t0.x); u0[2] = h2_mul(u0[2], t0.y); u0[3] = h2_mul(u0[3], t0.y);
                u1[0] = h2_mul(u1[0], t1.x); u1[1] = h2_mul(u1[1], t1.x); u1[2] = h2_mul(u1[2], t1.y); u1[3] = h2_mul(u1[3], t1.y);
            }
            a[j & 1][0] = make_uint4(u0[0], u0[1], u0[2], u0[3]);
            a[j & 1][1] = make_uint4(u1[0], u1[1], u1[2], u1[3]);
            if (!ok_b) mbar_wait(bar_bfull + (j & 3) * 8, j >> 2);
        };
        auto table = [&](int pos) { s_t = sbase + P2_OFF_GRN + q * 8 + (k0 + pos) % 48 * 64; };
        const uint32_t db0 = (uint32_t)make_desc(sbase, 128, 256);
        auto block8 = [&](bool raw, int pos, int thr0, int mode) {
#pragma unroll
            for (int j = 0; j < 8; j++) {
                const uint32_t db = db0 + (j & 3) * (P2_B / 16);
                if (j == 8 - P2_AH && mode == 1) bar_sync(4, 384);
                TR2(wg, pos + j, 0);
                wg_fence();
                mma_rs_n192(acc0, a[j & 1][0], db);
                mma_rs_n192(acc1, a[j & 1][0], db + 384);
                mma_rs_n192(acc0, a[j & 1][1], db + 768);
                mma_rs_n192(acc1, a[j & 1][1], db + 768 + 384);
                wg_commit();
                if (j == 7 && mode == 2) bar_arrive(4, 384);
                const uint32_t rel = ((j - 1) & 4 ? rel1 : rel0) + ((j - 1) & 3) * 8;
                TR2(wg, pos + j, 1);
                wg_wait<1>();
                TR2(wg, pos + j, 2);
                if (who < (j ? 2 : thr0)) mbar_arrive_cluster(rel);
                if (!ok_a) {
                    if (j == 0 && pend) { publish(); pend = false; }
                    mbar_wait(af + ((j + 1) & 7) * 8, pa);
                }
                TR2(wg, pos + j, 3);
                if (raw && j == 7) table(pos + 8);
                fetch((j + 1) & 7, raw && (j < 7 || pos + 8 < P2_RAW));
            }
        };
        int n = wg == 2 && half ? -1 : wg, pos = p2_start(n);
        uint32_t px = 0;
        wait_pos(pos);
        mbar_wait(af, 0);
        table(pos);
        fetch(0, pos < P2_RAW);
#pragma unroll 1
        for (;; n += 3) {
            TSTAMP(1, 2 + n);
            const int end = pos + (n < 0 ? 24 : 48);
#pragma unroll
            for (int i = 0; i < 48; i += 2) {
                asm volatile("mov.b64 {%0, %1}, 0;\n" : "=r"(acc0[i]), "=r"(acc0[i + 1]));
                asm volatile("mov.b64 {%0, %1}, 0;\n" : "=r"(acc1[i]), "=r"(acc1[i + 1]));
            }
            int thr = 1;
#pragma unroll 1
            for (; pos < P2_RAW; pos += 8, thr = 2) block8(true, pos, thr, 0);
#pragma unroll 1
            for (; pos < end; pos += 8, thr = 2) {
                const int e = pos + 8, r = e % 48;
                block8(false, pos, thr, e < 48 || e > 256 || (r != 0 && r != P2_S1 && r != P2_S2) ? 0 : e == end ? 2 : 1);
            }
            TR2(wg, pos - 1, 4);
            wg_wait<0>();
            TR2(wg, pos - 1, 5);
            if (who == 1) mbar_arrive_cluster(rel0 + 24);
            mbar_wait(bar_xfull + wg * 8, px);
            TR2(wg, pos - 1, 6);
            px ^= 1;
            __syncwarp();
            p2_epilogue(acc0, acc1, up, n == P2_ITEMS - 1 ? sx - (P2_OFF_X - P2_OFF_A) + (g & 1) * (P2_LHALF - P2_XHALF) : sx, sbase + P2_OFF_BIAS + q * 16 + (n < 0 && fin ? C_DIM * 2 : 0), zero);
            TR2(wg, pos - 1, 7);
            if (n + 3 >= P2_ITEMS) { publish(); break; }
            if (n < 0) {
                publish();
                pos = P2_S2;
                wait_pos(pos);
                mbar_wait(bar_bfull, 0);
            } else {
                pend = true;
                ok_a = false;
            }
        }
        TSTAMP(1, 29);
        END_SYNC();
        TSTAMP(1, 30);
    }
}

__global__ void __cluster_dims__(2, 1, 1) __launch_bounds__(512, 1)
block_kernel(const __grid_constant__ CUtensorMap wmap, const __nv_bfloat16* __restrict__ x, const __nv_bfloat16* __restrict__ dw,
             const __nv_bfloat16* __restrict__ w2, const __nv_bfloat16* __restrict__ grn_g, const __nv_bfloat16* __restrict__ grn_b,
             __nv_bfloat16* __restrict__ out, int zero) {
    extern __shared__ __align__(1024) uint8_t smem[];
    const uint32_t sbase = smem_u32(smem);
    const int warp = __shfl_sync(0xffffffffu, threadIdx.x >> 5, 0), lane = threadIdx.x & 31;
    if (warp >= 12) {
        pass1<2>(wmap, x, dw, w2, grn_b, sbase, warp, lane, zero);
        pass2<2>(x, grn_g, out, smem, sbase, false, zero);
    } else {
        bool early = false;
        if (warp >= 8) {
            pass1<1>(wmap, x, dw, w2, grn_b, sbase, warp, lane, zero);
            reg_inc<160>();
        } else {
            early = pass1<0>(wmap, x, dw, w2, grn_b, sbase, warp, lane, zero);
            reg_dec<160>();
        }
        pass2<0>(x, grn_g, out, smem, sbase, early, zero);
    }
}

}

extern "C" void kernel_launch(void* const* d_in, const int* in_sizes, int n_in, void* d_out, int out_size) {
    const __nv_bfloat16* x = (const __nv_bfloat16*)d_in[0];
    const __nv_bfloat16* dw = (const __nv_bfloat16*)d_in[1];
    const __nv_bfloat16* w1 = (const __nv_bfloat16*)d_in[2];
    const __nv_bfloat16* w2 = (const __nv_bfloat16*)d_in[3];
    const __nv_bfloat16* grn_g = (const __nv_bfloat16*)d_in[4];
    const __nv_bfloat16* grn_b = (const __nv_bfloat16*)d_in[5];
    __nv_bfloat16* out = (__nv_bfloat16*)d_out;

    cudaFuncSetAttribute(block_kernel, cudaFuncAttributeMaxDynamicSharedMemorySize, SMEM_BYTES);

    typedef CUresult (*EncodeFn)(CUtensorMap*, CUtensorMapDataType, cuuint32_t, void*, const cuuint64_t*, const cuuint64_t*,
                                 const cuuint32_t*, const cuuint32_t*, CUtensorMapInterleave, CUtensorMapSwizzle,
                                 CUtensorMapL2promotion, CUtensorMapFloatOOBfill);
    static EncodeFn encode = nullptr;
    if (!encode) {
        cudaDriverEntryPointQueryResult qres;
        cudaGetDriverEntryPoint("cuTensorMapEncodeTiled", (void**)&encode, cudaEnableDefault, &qres);
    }
    CUtensorMap wmap;
    const cuuint64_t gdim[2] = {HID, C_DIM};
    const cuuint64_t gstr[1] = {HID * 2};
    const cuuint32_t box[2] = {64, 192}, estr[2] = {1, 1};
    CUresult er = encode(&wmap, CU_TENSOR_MAP_DATA_TYPE_BFLOAT16, 2, (void*)w1, gdim, gstr, box, estr, CU_TENSOR_MAP_INTERLEAVE_NONE,
           CU_TENSOR_MAP_SWIZZLE_128B, CU_TENSOR_MAP_L2_PROMOTION_L2_128B, CU_TENSOR_MAP_FLOAT_OOB_FILL_NONE);
    if (er != CUDA_SUCCESS) printf("tensor map encode failed %d\n", (int)er);

    block_kernel<<<NUM_CTAS, 512, SMEM_BYTES>>>(wmap, x, dw, w2, grn_g, grn_b, out, 0);
}
```

```cpp
#include <cuda.h>
#include <cuda_runtime.h>
#include <cuda_bf16.h>
#include <cuda_fp16.h>
#include <stdint.h>
#include <stdio.h>

namespace {

constexpr int M_TOTAL = 384 * 384;
constexpr int C_DIM   = 384;
constexpr int HID     = 1536;
constexpr int NT128   = M_TOTAL / 128;
constexpr int NUM_CTAS = 132;

constexpr int NGRP = 22, GRP_CTAS = 6;
constexpr int NT_EARLY = NT128 - 30;
constexpr int LN_STEP = NUM_CTAS / 4, LN_RING = 2 * LN_STEP;
constexpr int LN_TILE = 128 * C_DIM * 2;
constexpr int H_TILE = 64 * HID * 3 / 2;
constexpr int H_HALF = 3072, H_STEP = 6144;

__device__ __align__(1024) uint4 g_h[(size_t)M_TOTAL * HID * 3 / 32];
__device__ __align__(1024) uint4 g_ln[LN_RING * LN_TILE / 16];
__device__ __align__(1024) uint4 g_w2img[2][HID * C_DIM * 2 / 16];
__device__ __align__(16) unsigned long long g_sq[HID];
__device__ __align__(16) float g_sums[512];
__device__ float g_scale[HID];
__device__ float g_redo[HID];
__device__ __align__(128) unsigned g_prog[7][32];
__device__ __align__(128) unsigned g_half[32][2];
__device__ unsigned g_flag[LN_RING + 6][2][8];
#define TSTAMP(k, i)
#define TRACE(wg, pos, i)
#define TRACEW(pos, i)

#define TR2(wg, pos, i)
__host__ __device__ __forceinline__ int perm32(int n) {
    return (n & ~31) | (((n >> 1) & 3) << 3) | (((n >> 3) & 3) << 1) | (n & 1);
}

__device__ __forceinline__ uint32_t smem_u32(const void* p) { return (uint32_t)__cvta_generic_to_shared(p); }

__device__ __forceinline__ void mbar_init(uint32_t bar, uint32_t count) {
    asm volatile("mbarrier.init.shared::cta.b64 [%0], %1;\n" ::"r"(bar), "r"(count) : "memory");
}
__device__ __forceinline__ void mbar_expect_tx(uint32_t bar, uint32_t bytes) {
    asm volatile("mbarrier.arrive.expect_tx.shared::cta.b64 _, [%0], %1;\n" ::"r"(bar), "r"(bytes) : "memory");
}
__device__ __forceinline__ void mbar_arrive(uint32_t bar) {
    asm volatile("mbarrier.arrive.shared::cta.b64 _, [%0];\n" ::"r"(bar) : "memory");
}
__device__ __forceinline__ void mbar_arrive_cluster(uint32_t bar_cluster_addr) {
    asm volatile("mbarrier.arrive.shared::cluster.b64 _, [%0];\n" ::"r"(bar_cluster_addr) : "memory");
}
#define SAFE_BREAK
__device__ __forceinline__ void mbar_wait(uint32_t bar, uint32_t parity) {
    asm volatile(
        "{\n"
        ".reg .pred p;\n"
        "LAB_WAIT:\n"
        "mbarrier.try_wait.parity.shared::cta.b64 p, [%0], %1;\n"
        "@!p bra LAB_WAIT;\n"
        "}\n" ::"r"(bar), "r"(parity) : "memory");
}
__device__ __forceinline__ bool mbar_test(uint32_t bar, uint32_t parity) {
    uint32_t ok;
    asm volatile("{\n.reg .pred p;\n"
                 "mbarrier.test_wait.parity.shared::cta.b64 p, [%1], %2;\n"
                 "selp.u32 %0, 1, 0, p;\n}\n" : "=r"(ok) : "r"(bar), "r"(parity) : "memory");
    return ok != 0;
}
__device__ __forceinline__ uint32_t mapa(uint32_t addr, uint32_t rank) {
    uint32_t r;
    asm volatile("mapa.shared::cluster.u32 %0, %1, %2;\n" : "=r"(r) : "r"(addr), "r"(rank));
    return r;
}
__device__ __forceinline__ void bulk_g2s(uint32_t dst, const void* src, uint32_t bytes, uint32_t bar) {
    asm volatile("cp.async.bulk.shared::cluster.global.mbarrier::complete_tx::bytes [%0], [%1], %2, [%3];\n"
                 ::"r"(dst), "l"(src), "r"(bytes), "r"(bar) : "memory");
}
__device__ __forceinline__ void bulk_g2s_mc(uint32_t dst, const void* src, uint32_t bytes, uint32_t bar, uint16_t mask) {
    asm volatile("cp.async.bulk.shared::cluster.global.mbarrier::complete_tx::bytes.multicast::cluster [%0], [%1], %2, [%3], %4;\n"
                 ::"r"(dst), "l"(src), "r"(bytes), "r"(bar), "h"(mask) : "memory");
}
__device__ __forceinline__ void tma2(uint32_t dst, const CUtensorMap* map, int c0, int c1, uint32_t bar) {
    asm volatile("cp.async.bulk.tensor.2d.shared::cluster.global.tile.mbarrier::complete_tx::bytes [%0], [%1, {%2, %3}], [%4];\n"
                 ::"r"(dst), "l"(map), "r"(c0), "r"(c1), "r"(bar) : "memory");
}
template <bool ACQ>
__device__ __forceinline__ uint32_t flag_wait(const unsigned* p, unsigned target) {
    unsigned v, n = 0;
    do {
        if (ACQ) asm volatile("ld.acquire.gpu.global.u32 %0, [%1];\n" : "=r"(v) : "l"(p) : "memory");
        else asm volatile("ld.relaxed.gpu.global.u32 %0, [%1];\n" : "=r"(v) : "l"(p) : "memory");
        n++;
    } while (v < target);
    return n == 1;
}
__device__ __forceinline__ void ldsm4t(uint32_t (&r)[4], uint32_t addr) {
    asm volatile("ldmatrix.sync.aligned.m8n8.x4.trans.shared.b16 {%0,%1,%2,%3}, [%4];\n"
                 : "=r"(r[0]), "=r"(r[1]), "=r"(r[2]), "=r"(r[3]) : "r"(addr) : "memory");
}
__device__ __forceinline__ void bulk_s2g(void* dst, uint32_t src, uint32_t bytes) {
    asm volatile("cp.async.bulk.global.shared::cta.bulk_group [%0], [%1], %2;\n" ::"l"(dst), "r"(src), "r"(bytes) : "memory");
}
__device__ __forceinline__ void cluster_sync() {
    asm volatile("barrier.cluster.arrive.aligned;\nbarrier.cluster.wait.aligned;\n" ::: "memory");
}
__device__ __forceinline__ void cluster_sync_relaxed() {
    asm volatile("barrier.cluster.arrive.relaxed.aligned;\nbarrier.cluster.wait.aligned;\n" ::: "memory");
}
#define END_SYNC cluster_sync_relaxed
__device__ __forceinline__ void gdc_wait() { asm volatile("griddepcontrol.wait;\n" ::: "memory"); }
__device__ __forceinline__ void gdc_launch() { asm volatile("griddepcontrol.launch_dependents;\n" ::: "memory"); }
__device__ __forceinline__ uint32_t cluster_rank() {
    uint32_t r;
    asm volatile("mov.u32 %0, %%cluster_ctarank;\n" : "=r"(r));
    return r;
}
__device__ __forceinline__ bool elect_one() {
    uint32_t pred;
    asm volatile("{\n.reg .pred p;\nelect.sync _|p, 0xffffffff;\nselp.u32 %0, 1, 0, p;\n}\n" : "=r"(pred));
    return pred != 0;
}
__device__ __forceinline__ void wg_fence() { asm volatile("wgmma.fence.sync.aligned;\n" ::: "memory"); }
__device__ __forceinline__ void wg_commit() { asm volatile("wgmma.commit_group.sync.aligned;\n" ::: "memory"); }
template <int N> __device__ __forceinline__ void wg_wait() {
    asm volatile("wgmma.wait_group.sync.aligned %0;\n" ::"n"(N) : "memory");
}
template <int R> __device__ __forceinline__ void reg_inc() { asm volatile("setmaxnreg.inc.sync.aligned.u32 %0;\n" ::"n"(R)); }
template <int R> __device__ __forceinline__ void reg_dec() { asm volatile("setmaxnreg.dec.sync.aligned.u32 %0;\n" ::"n"(R)); }
__device__ __forceinline__ void bar_sync(int id, int n) { asm volatile("bar.sync %0, %1;\n" ::"r"(id), "r"(n) : "memory"); }
__device__ __forceinline__ void bar_arrive(int id, int n) { asm volatile("bar.arrive %0, %1;\n" ::"r"(id), "r"(n) : "memory"); }

__device__ __forceinline__ uint64_t make_desc(uint32_t saddr, uint32_t lbo, uint32_t sbo) {
    return (uint64_t)((saddr & 0x3FFFF) >> 4) | ((uint64_t)(lbo >> 4) << 16) | ((uint64_t)(sbo >> 4) << 32);
}

__device__ __forceinline__ void stg128_cs(void* p, uint32_t a, uint32_t b, uint32_t c, uint32_t d) {
#define H_ST "st.global.cs.v4.u32"
    asm volatile(H_ST " [%0], {%1,%2,%3,%4};\n" ::"l"(p), "r"(a), "r"(b), "r"(c), "r"(d) : "memory");
}
__device__ __forceinline__ uint32_t pack_bf16(float lo, float hi) {
    uint32_t r;
    asm("cvt.rn.bf16x2.f32 %0, %1, %2;\n" : "=r"(r) : "f"(hi), "f"(lo));
    return r;
}
__device__ __forceinline__ float bf_lo(uint32_t v) { return __uint_as_float(v << 16); }
__device__ __forceinline__ float bf_hi(uint32_t v) { return __uint_as_float(v & 0xffff0000u); }
__device__ __forceinline__ uint32_t bf2_mul(uint32_t a, uint32_t b) {
    uint32_t r;
    asm("mul.rn.bf16x2 %0, %1, %2;\n" : "=r"(r) : "r"(a), "r"(b));
    return r;
}
__device__ __forceinline__ uint32_t bf2_fma(uint32_t a, uint32_t b, uint32_t c) {
    uint32_t r;
    asm("fma.rn.bf16x2 %0, %1, %2, %3;\n" : "=r"(r) : "r"(a), "r"(b), "r"(c));
    return r;
}
__device__ __forceinline__ uint32_t bf2_add(uint32_t a, uint32_t b) {
    uint32_t r;
    asm("add.rn.bf16x2 %0, %1, %2;\n" : "=r"(r) : "r"(a), "r"(b));
    return r;
}
__device__ __forceinline__ uint32_t h2_mul(uint32_t a, uint32_t b) {
    uint32_t r;
    asm("mul.rn.f16x2 %0, %1, %2;\n" : "=r"(r) : "r"(a), "r"(b));
    return r;
}
__device__ __forceinline__ uint32_t h2_fma(uint32_t a, uint32_t b, uint32_t c) {
    uint32_t r;
    asm("fma.rn.f16x2 %0, %1, %2, %3;\n" : "=r"(r) : "r"(a), "r"(b), "r"(c));
    return r;
}
__device__ __forceinline__ uint32_t h2_add(uint32_t a, uint32_t b) {
    uint32_t r;
    asm("add.rn.f16x2 %0, %1, %2;\n" : "=r"(r) : "r"(a), "r"(b));
    return r;
}
__device__ __forceinline__ uint32_t pack_f16(float lo, float hi) {
    uint32_t r;
    asm("cvt.rn.f16x2.f32 %0, %1, %2;\n" : "=r"(r) : "f"(hi), "f"(lo));
    return r;
}
__device__ __forceinline__ float h_lo(uint32_t v) { return __low2float(*reinterpret_cast<const __half2*>(&v)); }
__device__ __forceinline__ float h_hi(uint32_t v) { return __high2float(*reinterpret_cast<const __half2*>(&v)); }
__device__ __forceinline__ uint32_t bf2_to_h2(uint32_t v) { return (v & 0x7fff7fffu) * 7u + v; }
__device__ __forceinline__ uint32_t prmt(uint32_t a, uint32_t b, uint32_t sel) {
    uint32_t r;
    asm("prmt.b32 %0, %1, %2, %3;\n" : "=r"(r) : "r"(a), "r"(b), "r"(sel));
    return r;
}
__device__ __forceinline__ uint32_t bitsel(uint32_t a, uint32_t b, uint32_t m) {
    uint32_t r;
    asm("lop3.b32 %0, %1, %2, %3, 0xd8;\n" : "=r"(r) : "r"(a), "r"(b), "r"(m));
    return r;
}
constexpr float KAPPA = 0.3292034911525734f;
constexpr uint32_t GELU_C2 = 0x40d940d9u;
constexpr float HSCALE = 1.0f / (2.0f * KAPPA);
__device__ __forceinline__ float w2_scale(uint32_t m) { return __uint_as_float((257u - max(m >> 23, 16u)) << 23); }
__device__ __forceinline__ void sched_break(int zero) {
    asm volatile("{\n.reg .pred p;\nsetp.ne.s32 p, %0, 0;\nSB_LOOP:\n@p nanosleep.u32 1;\n@p bra SB_LOOP;\n}\n" ::"r"(zero));
}

#define ACC8(d, o) "+r"(d[o + 0]), "+r"(d[o + 1]), "+r"(d[o + 2]), "+r"(d[o + 3]), "+r"(d[o + 4]), "+r"(d[o + 5]), "+r"(d[o + 6]), "+r"(d[o + 7])

__device__ __forceinline__ void mma_rs_n128(uint32_t (&d)[32], const uint32_t (&a)[4], uint32_t desc, int scale_d) {
    asm volatile(
        "{\n.reg .pred p;\n.reg .b64 db;\nsetp.ne.b32 p, %37, 0;\nmov.b64 db, {%36, 0x40000040};\n"
        "wgmma.mma_async.sync.aligned.m64n128k16.f16.f16.f16 "
        "{%0,%1,%2,%3,%4,%5,%6,%7,%8,%9,%10,%11,%12,%13,%14,%15,"
        "%16,%17,%18,%19,%20,%21,%22,%23,%24,%25,%26,%27,%28,%29,%30,%31},"
        "{%32,%33,%34,%35}, db, p, 1, 1, 0;\n}\n"
        : ACC8(d, 0), ACC8(d, 8), ACC8(d, 16), ACC8(d, 24)
        : "r"(a[0]), "r"(a[1]), "r"(a[2]), "r"(a[3]), "r"(desc), "r"(scale_d));
}

__device__ __forceinline__ void mma_ss_n128(uint32_t (&d)[32], uint32_t da, uint32_t db, int scale_d) {
    asm volatile(
        "{\n.reg .pred p;\n.reg .b64 da, db;\nsetp.ne.b32 p, %34, 0;\nmov.b64 da, {%32, 0x40000040};\nmov.b64 db, {%33, 0x40000040};\n"
        "wgmma.mma_async.sync.aligned.m64n128k16.f16.f16.f16 "
        "{%0,%1,%2,%3,%4,%5,%6,%7,%8,%9,%10,%11,%12,%13,%14,%15,"
        "%16,%17,%18,%19,%20,%21,%22,%23,%24,%25,%26,%27,%28,%29,%30,%31},"
        "da, db, p, 1, 1, 1, 0;\n}\n"
        : ACC8(d, 0), ACC8(d, 8), ACC8(d, 16), ACC8(d, 24)
        : "r"(da), "r"(db), "r"(scale_d));
}

__device__ __forceinline__ void mma_rs_n192(uint32_t (&d)[48], const uint4& a, uint32_t db) {
    asm volatile(
        "{\n.reg .b64 db;\nmov.b64 db, {%52, 16};\n"
        "wgmma.mma_async.sync.aligned.m64n192k16.f16.f16.f16 "
        "{%0,%1,%2,%3,%4,%5,%6,%7,%8,%9,%10,%11,%12,%13,%14,%15,"
        "%16,%17,%18,%19,%20,%21,%22,%23,%24,%25,%26,%27,%28,%29,%30,%31,"
        "%32,%33,%34,%35,%36,%37,%38,%39,%40,%41,%42,%43,%44,%45,%46,%47},"
        "{%48,%49,%50,%51}, db, 1, 1, 1, 0;\n}\n"
        : ACC8(d, 0), ACC8(d, 8), ACC8(d, 16), ACC8(d, 24), ACC8(d, 32), ACC8(d, 40)
        : "r"(a.x), "r"(a.y), "r"(a.z), "r"(a.w), "r"(db));
}

#define P1_SIG 0
#define P2_ORD 1
#define P2_NAP 0
#define P1_SPLIT 5
#define P1_PACE 1
constexpr int P1_SLOT = LN_TILE / 6, P1_NST = 6;
constexpr int P1_W = 64 * C_DIM * 2;
constexpr int P1_X = 32 * C_DIM * 2;
constexpr int P1_OFF_W = LN_TILE;
constexpr int P1_OFF_X = P1_OFF_W + 2 * P1_W;
constexpr int P1_OFF_BAR = 227328;
constexpr int P1_OFF_TILE = P1_OFF_BAR + (2 * P1_NST + 4 + 4 + 4) * 8;
constexpr int P1_OFF_EX = P1_OFF_TILE + 64;
constexpr int P1_OFF_DW = P1_OFF_EX + 256 * 4;
constexpr int OFF_PRE = P1_OFF_DW + C_DIM * 2;
constexpr int SMEM_BYTES = OFF_PRE + C_DIM * 4 + 16;

__device__ __forceinline__ float rsqrt_fast(float x) {
    float r;
    asm("rsqrt.approx.ftz.f32 %0, %1;\n" : "=f"(r) : "f"(x));
    return r;
}
__device__ __forceinline__ float row_sum(const uint32_t (&c)[4]) {
    const uint32_t u = bf2_add(bf2_add(c[0], c[1]), bf2_add(c[2], c[3]));
    float s = bf_lo(u) + bf_hi(u);
#pragma unroll
    for (int o = 1; o < 8; o <<= 1) s += __shfl_xor_sync(0xffffffffu, s, o);
    return s;
}
__device__ __forceinline__ uint32_t pace(uint32_t bar, uint32_t off, uint32_t val, uint32_t after, int zero) {
    asm volatile(
        "{\n.reg .pred p, q;\n.reg .b32 par;\n"
        "lop3.b32 par, %4, %2, %3, 0xea;\n"
        "setp.eq.u32 q, par, 0;\n"
        "mov.pred p, 0;\n"
        "@q mbarrier.test_wait.parity.shared::cta.b64 p, [%1], par;\n"
        "selp.u32 par, 1, 0, p;\n"
        "@q mbarrier.try_wait.parity.shared::cta.b64 p, [%1], par, 1000;\n"
        "@p or.b32 %0, %0, %2;\n"
        "}\n" : "+r"(val) : "r"(bar), "r"(zero), "r"(off), "r"(after));
    return val;
}
template <int PACE, int R>
__device__ __forceinline__ void ln_rows(uint32_t (&v)[R][6][4], const uint32_t (&d)[6][4], uint32_t bar, uint32_t off, int zero,
                                        uint32_t bar_read) {
    const float inv = 1.0f / C_DIM;
    uint32_t c[R][4], nm[R];
    float e[R], r[R], er[R];
    bool big = false;
#pragma unroll
    for (int p = 0; p < R; p++) {
#pragma unroll
        for (int i = 0; i < 6; i++)
#pragma unroll
            for (int k = 0; k < 4; k++) c[p][k] = bf2_fma(v[p][i][k], d[i][k], i ? c[p][k] : 0);
        const float m = row_sum(c[p]) * inv;
        nm[p] = pack_bf16(-m, -m);
        e[p] = m + bf_lo(nm[p]);
    }
    if (bar_read) mbar_arrive(bar_read + (nm[0] & zero));
    if (PACE & 1) nm[0] = pace(bar, off, nm[0], nm[0], zero);
#pragma unroll
    for (int p = 0; p < R; p++) {
#pragma unroll
        for (int i = 0; i < 6; i++) {
#pragma unroll
            for (int k = 0; k < 4; k++) {
                v[p][i][k] = bf2_fma(v[p][i][k], d[i][k], nm[p]);
                c[p][k] = i ? bf2_fma(v[p][i][k], v[p][i][k], c[p][k]) : bf2_mul(v[p][i][k], v[p][i][k]);
            }
        }
        r[p] = KAPPA * rsqrt_fast(fmaxf(fmaf(-e[p], e[p], row_sum(c[p]) * inv), 0.f) + 1e-5f);
        er[p] = -e[p] * r[p] * 0x1p-112f;
        big |= r[p] < 0x1p-8f;
    }
    if (__any_sync(0xffffffffu, big)) {
#pragma unroll
        for (int p = 0; p < R; p++) {
            const uint32_t p2 = __float_as_uint(r[p]) & 0x7f800000u;
            r[p] = __uint_as_float((__float_as_uint(r[p]) & 0x007fffffu) | 0x3f800000u);
#pragma unroll
            for (int i = 0; i < 6; i++)
#pragma unroll
                for (int k = 0; k < 4; k++) v[p][i][k] = bf2_mul(v[p][i][k], p2 | p2 >> 16);
        }
    }
#pragma unroll
    for (int p = 0; p < R; p++) {
        uint32_t rs = pack_bf16(r[p] * 0x1p-112f, r[p] * 0x1p-112f);
        const uint32_t sh = pack_bf16(er[p], er[p]);
        if (PACE & 2) rs = pace(bar, off, rs, sh, zero);
#pragma unroll
        for (int i = 0; i < 6; i++)
#pragma unroll
            for (int k = 0; k < 4; k++) v[p][i][k] = bf2_to_h2(bf2_fma(v[p][i][k], rs, sh));
    }
}

template <int R>
__device__ __forceinline__ uint32_t gelu2(uint32_t a, uint32_t sc2) {
    uint32_t y, t;
    if (R) asm("{\n.reg .b16 l, h;\n.reg .b32 f;\nmov.b32 {l, h}, %2;\nmov.b32 f, {h, h};\nmul.rn.f16x2 %0, %1, f;\n}\n" : "=r"(y) : "r"(a), "r"(sc2));
    else asm("{\n.reg .b16 l, h;\n.reg .b32 f;\nmov.b32 {l, h}, %2;\nmov.b32 f, {l, l};\nmul.rn.f16x2 %0, %1, f;\n}\n" : "=r"(y) : "r"(a), "r"(sc2));
    asm("tanh.approx.f16x2 %0, %1;\n" : "=r"(t) : "r"(h2_mul(y, h2_fma(y, y, GELU_C2))));
    return h2_fma(a, t, a);
}
constexpr uint32_t SPARE = 0x40074007u;
constexpr float UNCHOP = 1.0023f;

__device__ __forceinline__ uint32_t p1_exponents(float (&t)[2], uint32_t (&ex)[2], uint32_t saddr, int lane) {
#pragma unroll
    for (int r = 0; r < 2; r++) {
        t[r] += __shfl_xor_sync(0xffffffffu, t[r], 1);
        t[r] += __shfl_xor_sync(0xffffffffu, t[r], 2);
        ex[r] = min(max(((__float_as_uint(193.3f * t[r]) >> 23) + 127u) >> 1, 72u), 198u);
        asm volatile("st.shared.u32 [%0], %1;\n" ::"r"(saddr + r * 32), "r"(ex[r] << 23) : "memory");
    }
    return pack_f16(__uint_as_float(min(ex[0], 142u) << 23), __uint_as_float(min(ex[1], 142u) << 23));
}
template <int N>
__device__ __forceinline__ void p1_convert(uint32_t (&o)[N][4], uint32_t (&v)[N][4], const uint32_t (&ex)[2]) {
    if (__any_sync(0xffffffffu, max(ex[0], ex[1]) > 141u)) {
#pragma unroll
        for (int k = 0; k < 4 * N; k++) v[k >> 2][k & 3] = bf2_mul(v[k >> 2][k & 3], ex[k & 1] > 141u ? 0x1f801f80u : 0x3f803f80u);
    }
#pragma unroll
    for (int k = 0; k < 4 * N; k++) {
        const uint32_t u = bf2_mul(v[k >> 2][k & 3], ((ex[k & 1] > 141u ? 206u : 142u) - ex[k & 1]) * 0x00800080u);
        asm volatile("mad.lo.u32 %0, %1, 7, %2;\n" : "=r"(o[k >> 2][k & 3]) : "r"(u & 0x7fff7fffu), "r"(u));
    }
}
template <int N>
__device__ __forceinline__ void p1_squares(const uint32_t (&v)[N][4], float (&t)[2]) {
#pragma unroll
    for (int j = 0; j < N / 2; j++) {
        const int r = j & 1, b = (j >> 1) * 4;
        uint32_t c = bf2_mul(v[b][r], v[b][r]);
#pragma unroll
        for (int k = 1; k < 8; k++) c = bf2_fma(v[b + k / 2][r + (k & 1) * 2], v[b + k / 2][r + (k & 1) * 2], c);
        t[r] += bf_lo(c) + bf_hi(c);
    }
}
__device__ __forceinline__ void p1_epilogue(const uint32_t (&acc)[2][32], const uint32_t (&sc2)[2], float (&ssq)[4], uint8_t* hp, bool last, int zero) {
    uint32_t sq[2], h[16][4];
#pragma unroll
    for (int i2 = 0; i2 < 9; i2++) {
        if (i2 == P1_SIG && last) asm volatile("red.relaxed.gpu.global.add.u32 [%0], 1;\n" ::"l"(&g_prog[4][0]) : "memory");
#pragma unroll
        for (int c = 2 * i2 - 2; c < 2 * i2; c++) {
            if (c >= 0 && (c & 3)) {
                uint32_t o[4];
#pragma unroll
                for (int u = 0; u < 4; u++) {
                    const uint32_t v = h[c & 12][u];
                    o[u] = bitsel(h[c][u], (c & 3) == 2 ? prmt(v, v, 0xa381) : prmt(v >> 3, v, (c & 3) == 1 ? 0x6240 : 0xf3d1), SPARE);
                }
                stg128_cs(hp + (c >> 3) * 2 * H_STEP + ((c >> 2) & 1) * H_HALF + ((c & 3) - 1) * 512, o[0], o[1], o[2], o[3]);
            }
        }
        if (i2 < 8) {
#pragma unroll
            for (int u = 0; u < 4; u++) {
                h[2 * i2][u] = gelu2<0>(acc[i2 >> 2][8 * (i2 & 3) + 2 * u], sc2[i2 >> 2]);
                h[2 * i2 + 1][u] = gelu2<1>(acc[i2 >> 2][8 * (i2 & 3) + 2 * u + 1], sc2[i2 >> 2]);
#pragma unroll
                for (int r = 0; r < 2; r++) {
                    const uint32_t v = h[2 * i2 + r][u];
                    sq[r] = ((i2 & 3) | u) ? h2_fma(v, v, sq[r]) : h2_mul(v, v);
                }
            }
            if ((i2 & 3) == 3) {
#pragma unroll
                for (int r = 0; r < 2; r++) ssq[(i2 >> 2) * 2 + r] += h_lo(sq[r]) + h_hi(sq[r]);
            }
            sched_break(zero);
        }
    }
}
template <int WG>
__device__ __forceinline__ void p1_mma(uint32_t (&acc)[2][32], const uint32_t (&a)[24][4], uint32_t sbase, uint32_t empty_remote, int i, int lane, bool pass) {
    const uint32_t bar_full = sbase + P1_OFF_BAR;
    const uint32_t db = (uint32_t)make_desc(sbase, 16, 1024), da = db + (P1_OFF_W + WG * P1_W) / 16;
    if (WG == 0) mbar_wait(bar_full, i & 1);
    bar_sync(1 + WG, 256);
    TRACE(WG, i, 1);
    wg_fence();
#pragma unroll
    for (int k = 0; k < 24; k++) {
        if (WG == 0 && k && k % 4 == 0) mbar_wait(bar_full + (k >> 2) * 8, i & 1);
        mma_rs_n128(acc[0], a[k], db + (k >> 2) * 1024 + (k & 3) * 2, k != 0);
        mma_ss_n128(acc[1], da + k * 128, db + (k >> 2) * 1024 + (k & 3) * 2, k != 0);
        if (k == 23 && pass) bar_arrive(2 - WG, 256);
        if (k == 23 || (WG == 1 && k % 4 == 3)) wg_commit();
        if (WG == 1 && k % 4 == 3 && k > 3) {
            wg_wait<1>();
            if (lane < 2) mbar_arrive_cluster(empty_remote + ((k >> 2) - 1) * 8);
        }
    }
    TRACE(WG, i, 2);
    wg_wait<0>();
    if (WG == 1 && lane < 2) mbar_arrive_cluster(empty_remote + 5 * 8);
}
__device__ __forceinline__ bool p1_consumer(const uint32_t (&a)[24][4], const uint32_t (&sc2)[2], uint32_t sbase, int WG, int w, int lane, int zero) {
    const uint32_t bar_full = sbase + P1_OFF_BAR, bar_empty = bar_full + P1_NST * 8;
    const uint32_t empty_remote = mapa(bar_empty, lane & 1);
    const uint32_t bar_pace = bar_empty + P1_NST * 8 + 32 + w * 8;
    const int g = lane >> 2, q = lane & 3, half = WG ^ ((blockIdx.x / GRP_CTAS) & 1), cb = (blockIdx.x % GRP_CTAS) * 4 + half * 2;
    uint32_t acc[2][32];
    float ssq[4] = {0.f, 0.f, 0.f, 0.f};
    TSTAMP(0, 1);

    uint8_t* hp = reinterpret_cast<uint8_t*>(g_h) + ((cb * 2 + (w >> 1)) * H_STEP + (w & 1) * 1536) + g * 64 + (q ^ (g >> 1)) * 16;
    int i = 0;
    uint32_t more = 3, both;
#pragma unroll 1
    for (;; i++) {
        TRACE(WG, i, 0);
        both = more & 2;
        if (WG == 0) p1_mma<0>(acc, a, sbase, empty_remote, i, lane, both);
        else p1_mma<1>(acc, a, sbase, empty_remote, i, lane, true);
        TRACE(WG, i, 4);
        int step;
        asm volatile("ld.shared.v2.u32 {%0, %1}, [%2];\n" : "=r"(step), "=r"(more) : "r"(sbase + P1_OFF_TILE + (i & 3) * 16) : "memory");
        hp += step;
        p1_epilogue(acc, sc2, ssq, hp, !(more >> WG & 1) && lane == 0, zero);
        if (lane == 0) mbar_arrive(bar_pace);
        if (more & 4) {
            asm volatile("fence.proxy.async.global;\n" ::: "memory");
            bar_arrive(8, 288);
            bar_arrive(9, 288);
        }
        if (!(more >> WG & 1)) break;
    }
    TSTAMP(0, 21);
    if (WG == 0 && both) bar_sync(1, 256);
#pragma unroll
    for (int r = 0; r < 4; r++) {
        ssq[r] += __shfl_xor_sync(0xffffffffu, ssq[r], 1);
        ssq[r] += __shfl_xor_sync(0xffffffffu, ssq[r], 2);
    }
    const float t = q == 0 ? ssq[0] : q == 1 ? ssq[1] : q == 2 ? ssq[2] : ssq[3];
    atomicAdd(&g_sq[cb * 64 + (q >> 1) * 64 + w * 16 + (q & 1) * 8 + g], (1ull << 56) + __float2ull_rn(fminf(t, 0x1p19f) * 0x1p32f));
    asm volatile("fence.proxy.async.global;\n" ::: "memory");
    bar_arrive(3, 288);
    asm volatile("barrier.cluster.arrive.relaxed.aligned;\n" ::: "memory");
    return WG ? more & 1 : both;
}

__device__ __forceinline__ void p2_init(uint32_t sbase);
template <int ROLE>
__device__ __forceinline__ bool pass1(const CUtensorMap& wmap, const __nv_bfloat16* __restrict__ x, const __nv_bfloat16* __restrict__ dw,
                                      const __nv_bfloat16* __restrict__ w2, const __nv_bfloat16* __restrict__ grn_b, uint32_t sbase,
                                      int warp, int lane, int zero) {
    const uint32_t bar_full = sbase + P1_OFF_BAR, bar_empty = bar_full + P1_NST * 8, bar_w = bar_empty + P1_NST * 8;
    const uint32_t rank = cluster_rank();
    const int cig = blockIdx.x % GRP_CTAS;
    uint8_t* const ring = reinterpret_cast<uint8_t*>(g_ln);

    TSTAMP(0, 0);
    TRACEW(110 + warp, 0);
    const uint32_t bar_pace = bar_w + 32, bar_xfull = bar_pace + 32, bar_xempty = bar_xfull + 8, bar_done = bar_xfull + 16;
    const int ln0 = blockIdx.x >> 2, first = blockIdx.x / GRP_CTAS;
    const uint8_t* xsrc = reinterpret_cast<const uint8_t*>(x) + (size_t)blockIdx.x * P1_X;

    if (ROLE == 2) {
        reg_dec<32>();
        asm volatile("barrier.cluster.arrive.relaxed.aligned;\n" ::: "memory");
        asm volatile("barrier.cluster.wait.aligned;\n" ::: "memory");
        if (warp == 12) {
            int prev = 0, t = first;
            const uint32_t rbase = mapa(sbase, lane & 1);
#pragma unroll 1
            for (int i = 0; t < NT128; i++) {
                const int round = t / LN_RING, slot = t - round * LN_RING;
                const uint8_t* src = ring + slot * LN_TILE + rank * (P1_SLOT / 2);
                int next = 0;
                if (rank == 0 && lane == 0) {
                    next = t < NT128 - P1_SPLIT ? NGRP + atomicAdd(&g_flag[LN_RING + (cig >> 1)][0][0], 1u) : 2 * NT128;
                    if (next >= NT128 - P1_SPLIT && next < 2 * NT128) next = NT128 - P1_SPLIT + atomicAdd(&g_flag[LN_RING + 3 + (cig >> 1)][first & 1][0], 1u);
                }
                flag_wait<true>(&g_flag[slot][0][0], 4 * round + 4);
                TRACEW(i, 2);
                asm volatile("fence.proxy.async.global;\n" ::: "memory");
                next = __shfl_sync(0xffffffffu, next, 0);
#pragma unroll 1
                for (int h = 0; h < P1_NST; h++) {
                    mbar_wait(bar_empty + h * 8, i & 1);
                    if (h == 0) TRACEW(i, 4);
                    if (h == 5) TRACEW(i, 5);
                    if (elect_one()) {
                        mbar_expect_tx(bar_full + h * 8, h ? P1_SLOT : P1_SLOT + 16);
                        bulk_g2s_mc(sbase + h * P1_SLOT + rank * (P1_SLOT / 2), src + h * P1_SLOT, P1_SLOT / 2, bar_full + h * 8, (uint16_t)3);
                    }
                    __syncwarp();
                    if (h == 0 && rank == 0 && lane < 2)
                        asm volatile("st.async.shared::cluster.mbarrier::complete_tx::bytes.v4.u32 [%0], {%1, %2, %3, %3}, [%4];\n"
                                     ::"r"(rbase + P1_OFF_TILE + (i & 3) * 16), "r"((t - prev) * (2 * H_TILE)), "r"((next < NT128 - P1_SPLIT ? 3 : next < NT128) + (t < NT_EARLY && next >= NT_EARLY ? 4 : 0)), "r"(next),
                                       "r"(rbase + P1_OFF_BAR) : "memory");
                }
                prev = t;
                t = next;
                if (rank != 0) {
                    mbar_wait(bar_full, i & 1);
                    asm volatile("ld.shared.u32 %0, [%1];\n" : "=r"(t) : "r"(sbase + P1_OFF_TILE + (i & 3) * 16 + 8) : "memory");
                }
            }
        } else if (warp == 13) {
            int ph = 0;
            unsigned target = 0;
#pragma unroll 1
            for (int i = ln0 + LN_STEP; i < NT128; i += LN_STEP, ph ^= 1) {
                target += ph * (GRP_CTAS / 2);
                xsrc += (size_t)NUM_CTAS * P1_X;
                mbar_wait(bar_xempty, ph);
                if (elect_one()) {
                    mbar_expect_tx(bar_xfull, P1_X);
                    bulk_g2s(sbase + P1_OFF_X, xsrc, P1_X, bar_xfull);
                }
                __syncwarp();
                const uint32_t off = flag_wait<false>(&g_flag[ln0 + (ph ^ 1) * LN_STEP][1][0], target);
                mbar_wait(bar_done, ph);
                if (elect_one()) {
                    asm volatile("st.shared.u32 [%0], %1;\n" ::"r"(bar_done + 8), "r"(off) : "memory");
                    mbar_arrive(bar_xfull);
                }
                __syncwarp();
            }
        } else if (warp == 15) {
            int t = first;
            if (rank == 1 && lane == 0) mbar_arrive(bar_empty);
#pragma unroll 1
            for (int i = 0; rank == 1 && t < NT128; i++) {
#pragma unroll 1
                for (int h = 0; h < P1_NST; h++) mbar_wait(bar_full + h * 8, i & 1);
                if (lane == 0) asm volatile("red.relaxed.gpu.global.add.u32 [%0], 1;\n" ::"l"(&g_flag[t % LN_RING][1][0]) : "memory");
                asm volatile("ld.shared.u32 %0, [%1];\n" : "=r"(t) : "r"(sbase + P1_OFF_TILE + (i & 3) * 16 + 8) : "memory");
                if (lane == 0) mbar_arrive(bar_empty);
                TRACEW(i, 3);
            }
            if (rank == 0) {
                mbar_wait(bar_full, 0);
                TRACEW(110 + warp, 3);
                mbar_wait(bar_full, 1);
                float* sums = g_sums;
                unsigned* flag = reinterpret_cast<unsigned*>(sums + C_DIM);
                if (blockIdx.x == 0) reinterpret_cast<uint2*>(g_half)[lane] = make_uint2(0, 0);
                if (blockIdx.x == 2 && lane < 7) g_prog[lane][0] = 0;
                if (blockIdx.x < 96) g_redo[blockIdx.x * 16 + lane] = 0.f;
                float gs = 0.f;
#pragma unroll 1
                for (int pass = 0; pass < 2; pass++) {
                    float mx = 0.f;
#pragma unroll 1
                    for (int it = first; it < 96; it += NGRP) {
                        const int nb = it % 12, k0 = (cig * 4 + it / 12) * 64 + (lane >> 2);
                        const uint32_t sc = mapa(sbase + P1_OFF_EX + (k0 & 255) * 4, it / 48);
                        uint32_t* dst = reinterpret_cast<uint32_t*>(g_w2img[0]) + (k0 >> 4) * 3072 + nb * 256 + lane;
                        float bs[8] = {};
#pragma unroll 1
                        for (int c = 0; c < 8; c++) {
                            const uint4 u = __ldg(reinterpret_cast<const uint4*>(w2 + (size_t)(k0 + c * 8) * C_DIM + nb * 32) + (lane & 3));
                            const float b = __bfloat162float(grn_b[k0 + c * 8]);
                            float t;
                            asm volatile("ld.shared::cluster.f32 %0, [%1];\n" : "=f"(t) : "r"(sc + c * 32) : "memory");
                            if (nb == 0) g_scale[k0 + c * 8] = t;
#pragma unroll
                            for (int j = 0; j < 4; j++) {
                                const uint32_t v = j == 0 ? u.x : j == 1 ? u.y : j == 2 ? u.z : u.w;
                                mx = fmaxf(mx, fmaxf(fabsf(bf_lo(v)), fabsf(bf_hi(v))) * t);
                                if (pass) {
                                    bs[2 * j] = fmaf(b, bf_lo(v), bs[2 * j]);
                                    bs[2 * j + 1] = fmaf(b, bf_hi(v), bs[2 * j + 1]);
                                    uint32_t h = pack_f16(bf_lo(v) * t * gs, bf_hi(v) * t * gs);
                                    asm volatile("movmatrix.sync.aligned.m8n8.trans.b16 %0, %0;\n" : "+r"(h));
                                    dst[(c >> 1) * 3072 + (c & 1) * 32 + j * 64] = h;
                                }
                            }
                        }
                        if (pass) {
#pragma unroll
                            for (int j = 0; j < 8; j++) {
#pragma unroll
                                for (int o = 4; o < 32; o <<= 1) bs[j] += __shfl_xor_sync(0xffffffffu, bs[j], o);
                                if (lane >> 2 == j) atomicAdd(&sums[nb * 32 + (j >> 1) * 8 + (lane & 3) * 2 + (j & 1)], bs[j]);
                            }
                        }
                    }
                    if (!pass) {
                        const uint32_t m = __reduce_max_sync(0xffffffffu, __float_as_uint(mx));
                        __threadfence();
                        __syncwarp();
                        if (lane == 0) {
                            atomicMax(flag, m);
                            asm volatile("red.release.gpu.global.add.u32 [%0], 1;\n" ::"l"(flag + 32) : "memory");
                        }
                        flag_wait<true>(flag + 32, NUM_CTAS / 2);
                        gs = w2_scale(__ldcg(flag));
                    }
                }
                asm volatile("fence.proxy.async.global;\nfence.acq_rel.gpu;\n" ::: "memory");
                __syncwarp();
                if (lane == 0) asm volatile("red.relaxed.gpu.global.add.u32 [%0], 1;\n" ::"l"(&g_prog[3][0]) : "memory");
            }
        } else if (warp == 14) {
            int ph = 0;
#pragma unroll 1
            for (int i = ln0; i < NT128; i += LN_STEP, ph ^= 1) {
                mbar_wait(bar_done, ph);
                TRACEW(i / LN_STEP, 0);
                asm volatile("fence.proxy.async.global;\n" ::: "memory");
                if (elect_one()) asm volatile("red.release.gpu.global.add.u32 [%0], 1;\n" ::"l"(&g_flag[ln0 + ph * LN_STEP][0][0]) : "memory");
                __syncwarp();
                TRACEW(i / LN_STEP, 1);
            }
            if (lane == 0) p2_init(sbase);
#pragma unroll 1
            for (int i = 6; i >= 5; i--) {
                bar_sync(i == 6 ? 8 : 3, 288);
                asm volatile("fence.proxy.async.global;\n" ::: "memory");
                if (lane == 0) asm volatile("red.release.gpu.global.add.u32 [%0], 1;\n" ::"l"(&g_prog[i][0]) : "memory");
                __syncwarp();
            }
        }
        __syncwarp();
        asm volatile("barrier.cluster.arrive.relaxed.aligned;\n" ::: "memory");
        return false;
    } else if (ROLE == 1) {
        reg_dec<96>();
        asm volatile("barrier.cluster.arrive.relaxed.aligned;\n" ::: "memory");
        {
            const int l8 = lane & 7, row = (warp - 8) * 4 + (lane >> 3), px = (blockIdx.x & 3) * 32 + row;
            uint32_t d[6][4];
            const int n = (px & 64) + perm32(2 * row + ((px >> 5) & 1));
            uint8_t* const dst0 = ring + ln0 * LN_TILE + n * 128 + ((l8 ^ (n & 7)) << 4);
            const uint32_t src = sbase + P1_OFF_X + ((warp - 8) * 8 + (lane >> 3)) * (C_DIM * 2) + l8 * 16;
            int ph = 0;
#pragma unroll 1
            for (int i = ln0; i < NT128; i += LN_STEP, ph ^= 1) {
                TRACE(2, i / LN_STEP, 0);
                uint32_t off = 1;
#pragma unroll 1
                for (int ps = i == ln0 ? -2 : 0; ps < 2; ps += ps < 0 ? 2 : 1) {
                    if (ps == 0) {
                        if (i == ln0) asm volatile("barrier.cluster.wait.aligned;\n" ::: "memory");
                        mbar_wait(bar_xfull, ph);
                        asm volatile("ld.shared.u32 %0, [%1];\n" : "=r"(off) : "r"(bar_done + 8) : "memory");
                    }
                    if (ps == 0) TRACE(2, i / LN_STEP, 1);
                    if (i == ln0) {
#pragma unroll
                        for (int j = 0; j < 6; j++)
                            asm volatile("ld.shared.v4.u32 {%0,%1,%2,%3}, [%4];\n"
                                         : "=r"(d[j][0]), "=r"(d[j][1]), "=r"(d[j][2]), "=r"(d[j][3]) : "r"(sbase + P1_OFF_DW + j * 128 + l8 * 16) : "memory");
                    }
                    uint32_t v1[1][6][4];
                    uint32_t (&v)[6][4] = v1[0];
#pragma unroll
                    for (int j = 0; j < 6; j++)
                        asm volatile("ld.shared.v4.u32 {%0,%1,%2,%3}, [%4];\n"
                                     : "=r"(v[j][0]), "=r"(v[j][1]), "=r"(v[j][2]), "=r"(v[j][3]) : "r"(src + (ps & 1) * (4 * C_DIM * 2) + j * 128) : "memory");
                    ln_rows<P1_PACE, 1>(v1, d, bar_pace + (warp - 8) * 8, off, zero, ps == 1 && lane == 0 ? bar_xempty : 0);
                    uint8_t* dst = dst0 + ph * (LN_STEP * LN_TILE) + (ps & 1) * 4096;
#pragma unroll
                    for (int j = 0; j < 6; j++) *reinterpret_cast<uint4*>(dst + j * 16384) = make_uint4(v[j][0], v[j][1], v[j][2], v[j][3]);
                    TRACE(2, i / LN_STEP, 3 + (ps & 1));
                }
                asm volatile("fence.proxy.async.global;\nfence.acq_rel.cta;\n" ::: "memory");
                __syncwarp();
                if (lane == 0) mbar_arrive(bar_done);
                TRACE(2, i / LN_STEP, 5);
                TRACE(2, i / LN_STEP, 2);
            }
        }
        __syncwarp();
        asm volatile("barrier.cluster.arrive.relaxed.aligned;\n" ::: "memory");
        return false;
    } else {
        const int wg = warp >> 2, w = warp & 3;
        auto load_w = [&](int i0, int i1) {
#pragma unroll 1
            for (int i = i0; i < i1; i++) {
                if (!(i & 1)) mbar_expect_tx(bar_w + (i >> 1) * 8, P1_W);
                tma2(sbase + (i & 2) * P1_W + (i >> 2) * P1_W + (i & 1) * (P1_W / 2), &wmap, cig * 256 + ((i >> 1) ^ (first & 1) * 2) * 64, (i & 1) * 192, bar_w + (i >> 1) * 8);
            }
        };
        if (warp == 4 && elect_one()) {
            mbar_init(bar_xfull, 2);
#pragma unroll
            for (int i = 0; i < 4; i++) mbar_init(bar_w + i * 8, 1);
            asm volatile("fence.mbarrier_init.release.cluster;\n" ::: "memory");
            mbar_expect_tx(bar_xfull, P1_X + C_DIM * 2);
            bulk_g2s(sbase + P1_OFF_X, xsrc, P1_X, bar_xfull);
            bulk_g2s(sbase + P1_OFF_DW, dw, C_DIM * 2, bar_xfull);
            load_w(0, 4);
            asm volatile("st.shared.u32 [%0], 1;\n" ::"r"(bar_done + 8) : "memory");
            mbar_arrive(bar_xfull);
        }
        if (warp == 5 && elect_one()) {
#pragma unroll
            for (int i = 0; i < P1_NST; i++) {
                mbar_init(bar_full + i * 8, 1);
                mbar_init(bar_empty + i * 8, i ? 8 : 8 + rank);
                if (i < 4) mbar_init(bar_pace + i * 8, 1);
            }
            mbar_init(bar_xempty, 4);
            mbar_init(bar_done, 4);
            asm volatile("fence.mbarrier_init.release.cluster;\n" ::: "memory");
        }
        __syncwarp();
        asm volatile("barrier.cluster.arrive.relaxed.aligned;\n" ::: "memory");
        reg_inc<192>();
        TRACEW(110 + warp, 1);
        uint32_t a[24][4];
        const uint32_t src = sbase + wg * P1_W + ((lane >> 4) * 8 + (lane & 7)) * 128 + (((2 * w + ((lane >> 3) & 1)) ^ (lane & 7)) << 4);
        const uint32_t s_ex = sbase + P1_OFF_EX + ((wg ^ (first & 1)) * 128 + w * 16 + (lane >> 2)) * 4;
        uint32_t sc2[2], ex[2];
        if (wg == 1) bar_arrive(1, 256);
#pragma unroll 1
        for (int it = 0; it < 2; it++) {
          if (it != wg) asm volatile("barrier.cluster.wait.aligned;\n" ::: "memory");
          if (it < wg) {
              mbar_wait(bar_xfull, 0);
              if (w == 0 && elect_one()) load_w(4, 8);
              __syncwarp();
          }
          if (it || wg == 0) {
            float t[2] = {0.f, 0.f};
            if (it) {
                TRACEW(110 + warp, 2);
                mbar_wait(bar_w + wg * 16, 0);
            }
            TRACEW(110 + warp, 5);
#pragma unroll
            for (int k = 0; k < 24; k++) ldsm4t(a[k], src + k * 2048);
            TRACEW(110 + warp, 6);
            p1_squares(a, t);
            sc2[0] = p1_exponents(t, ex, s_ex, lane);
            if (it && lane < 6) mbar_arrive_cluster(mapa(bar_empty, lane & 1) + (wg * 3 + (lane >> 1)) * 8 + (sc2[0] & zero));
            p1_convert<24>(a, a, ex);
          }
          if (it || wg == 1) {
            float t[2] = {0.f, 0.f};
            TRACEW(100 + warp, 0);
            if (it) mbar_wait(bar_w + wg * 16 + 8, 0);
            TRACEW(100 + warp, 1);
            uint32_t v[8][4], o[8][4];
#pragma unroll 1
            for (int j = 0; j <= 2 * it; j++) {
#pragma unroll
                for (int k = 0; k < 8; k++) ldsm4t(v[k], src + P1_OFF_W + (8 * j + k) * 2048);
                p1_squares(v, t);
            }
            sc2[1] = p1_exponents(t, ex, s_ex + 256, lane);
#pragma unroll 1
            for (int j = 2 * it; j >= 0; j--) {
                p1_convert<8>(o, v, ex);
#pragma unroll
                for (int k = 0; k < 8; k++) {
                    if (j) ldsm4t(v[k], src + P1_OFF_W + (8 * j - 8 + k) * 2048);
                    if (it) asm volatile("stmatrix.sync.aligned.m8n8.x4.trans.shared.b16 [%0], {%1,%2,%3,%4};\n"
                                         ::"r"(src + P1_OFF_W + (8 * j + k) * 2048), "r"(o[k][0]), "r"(o[k][1]), "r"(o[k][2]), "r"(o[k][3]) : "memory");
                }
            }
          }
        }
        asm volatile("fence.proxy.async.shared::cta;\n" ::: "memory");
        TRACEW(110 + warp, 7);
        bar_sync(6 + wg, 128);
        const bool early = p1_consumer(a, sc2, sbase, wg, w, lane, zero);
        TSTAMP(0, 30);
        return early;
    }
}

constexpr int P2_B = 24576, P2_NB = 4;
constexpr int P2_A = 3072, P2_NA = 8;
constexpr int P2_XROW = C_DIM * 2;
constexpr int P2_OFF_A = P2_B * P2_NB;
constexpr int P2_OFF_X = P2_OFF_A + 3 * P2_NA * P2_A + 128;
constexpr int P2_LHALF = 2 * P2_NA * P2_A + 64;
constexpr int P2_XHALF = 32 * P2_XROW + 64;
constexpr int P2_OFF_GRN = P2_OFF_X + 64 * P2_XROW + 128;
constexpr int P2_OFF_BIAS = P2_OFF_GRN + HID * 2;
constexpr int P2_OFF_RED = P2_OFF_BIAS + C_DIM * 4;
constexpr int P2_OFF_BAR = P2_OFF_RED + 192;
constexpr int P2_SMEM = P2_OFF_BAR + (2 * P2_NB + 6 * P2_NA + 7) * 8;
#define P2_S1 16
constexpr int P2_S2 = 32;
constexpr int P2_NCL = NUM_CTAS / 2, P2_ITEMS = NT128 / P2_NCL, P2_SHARED = NT128 - P2_ITEMS * P2_NCL;
constexpr int P2_NPOS = 6 * 48 + P2_S1;
constexpr int P2_RAW = 24;
constexpr int P2_XC = 8 * P2_XROW;
#define P2_T0 5
#define P2_TL 8
#define P2_XP0 30
#define P2_XPN 13
#define P2_XPD 3
#define P2_CMP 0
#define P2_SLACK -1
#define P2_XW 6
#define P2_AH 2
__device__ __forceinline__ int p2_start(int n) { return n < 0 ? 0 : n / 3 * 48 + (n % 3 == 1 ? P2_S1 : n % 3 * (P2_S2 / 2)); }
__device__ __forceinline__ int p2_tile(int cl, int n) {
    return n == 0 ? NT_EARLY - 1 - cl : n < 0 ? NT_EARLY + (cl >> 1) : cl + P2_NCL * (n - 1);
}

#define P2_EB 2
#define P2_EX 1
__device__ __forceinline__ void p2_epilogue(uint32_t (&acc0)[48], uint32_t (&acc1)[48], uint32_t up, uint32_t sx, uint32_t sb, int zero) {
    uint32_t v[12][3][4];
    auto load = [&](int t, int j) {
        if (t >= 12) return;
        uint32_t (&w)[4] = v[t][j];
        asm volatile("ld.shared.v4.u32 {%0,%1,%2,%3}, [%4];\n" : "=r"(w[0]), "=r"(w[1]), "=r"(w[2]), "=r"(w[3])
                     : "r"((j ? sx + (j - 1) * 4 * P2_XROW : sb) + t * 64) : "memory");
    };
    auto store = [&](int t, int r) {
        const uint32_t* w = (t < 6 ? acc0 : acc1) + 8 * (t % 6) + 4 * r;
        asm volatile("st.shared.v4.u32 [%4], {%0,%1,%2,%3};\n" ::"r"(w[0]), "r"(w[1]), "r"(w[2]), "r"(w[3]), "r"(sx + t * 64 + r * 4 * P2_XROW) : "memory");
    };
#pragma unroll
    for (int t = 0; t < P2_EB; t++) load(t, 0);
#pragma unroll
    for (int t = 0; t < 2 * P2_EX; t++) load(t >> 1, 1 + (t & 1));
#pragma unroll
    for (int t = 0; t < 12; t++) {
        load(t + P2_EX, 1);
        load(t + P2_EX, 2);
        load(t + P2_EB, 0);
        uint32_t* acc = (t < 6 ? acc0 : acc1) + 8 * (t % 6);
        uint32_t y[8];
#pragma unroll
        for (int e = 0; e < 8; e++) {
            y[e] = h2_add(acc[e], v[t][0][e >> 1]);
            y[e] = pack_bf16(h_lo(y[e]), h_hi(y[e]));
        }
#pragma unroll
        for (int e = 0; e < 8; e++) acc[(e & 1) * 4 + (e >> 1)] = bf2_fma(y[e], up, v[t][1 + (e & 1)][e >> 1]);
        store(t, 0);
        store(t, 1);
        sched_break(zero);
    }
}

__device__ __forceinline__ void p2_unpack(uint32_t (&u)[4], uint32_t o1, uint32_t o2, uint32_t o3) {
    u[2] = o1 & ~SPARE;
    u[1] = o2 & ~SPARE;
    u[3] = o3 & ~SPARE;
    const uint32_t t = bitsel(prmt(o1, o2, 0x6341), prmt(o1, o3, 0x6240) << 3, 0x38383838u);
    u[0] = bitsel(t, prmt(o2, o3, 0x7351) << 1, 0x80808080u) & ~SPARE;
}

__device__ __forceinline__ void p2_redo_sums(int warp, int lane) {
    flag_wait<true>(&g_prog[5][0], NUM_CTAS);
#pragma unroll 1
    for (int s = warp; s < 96; s += 12) {
        float t[2] = {0.f, 0.f};
#pragma unroll 1
        for (int tile = blockIdx.x; tile < 2 * NT128; tile += NUM_CTAS) {
            const uint32_t* p = reinterpret_cast<const uint32_t*>(reinterpret_cast<const uint8_t*>(g_h) + (size_t)(tile >> 1) * (2 * H_TILE) +
                                                                  (s >> 1) * H_STEP + (tile & 1) * H_HALF + (s & 1) * 1536) + lane * 4;
#pragma unroll
            for (int j = 0; j < 4; j++) {
                uint32_t u[4];
                p2_unpack(u, __ldcg(p + j), __ldcg(p + j + 128), __ldcg(p + j + 256));
#pragma unroll
                for (int c = 0; c < 4; c++) t[c >> 1] += h_lo(u[c]) * h_lo(u[c]) + h_hi(u[c]) * h_hi(u[c]);
            }
        }
#pragma unroll
        for (int r = 0; r < 2; r++) {
            const int ch = s * 16 + r * 8 + (lane >> 2);
            atomicAdd(&g_redo[ch], t[r] * (UNCHOP * UNCHOP));
        }
    }
    __threadfence();
    __syncwarp();
    if (lane == 0) asm volatile("red.release.gpu.global.add.u32 [%0], 1;\n" ::"l"(&g_prog[2][0]) : "memory");
    flag_wait<true>(&g_prog[2][0], 12 * NUM_CTAS);
}

static_assert(P2_OFF_GRN >= P1_OFF_X + P1_X && P1_OFF_BAR >= P2_SMEM, "barriers and tables keep their memory");
__device__ __forceinline__ void p2_init(uint32_t sbase) {
    const uint32_t bar = sbase + P2_OFF_BAR;
#pragma unroll 1
    for (int i = 0; i < 2 * P2_NB + 6 * P2_NA + 6; i++) {
        const int j = i - 2 * P2_NB;
        mbar_init(bar + i * 8, j < -P2_NB ? 1 : j < 0 ? 24 : j < 3 * P2_NA ? 1 : j >= 6 * P2_NA && j < 6 * P2_NA + 3 ? 2 : 4);
    }
    asm volatile("st.shared.v2.u32 [%0], {0, 0};\n" ::"r"(bar + (2 * P2_NB + 6 * P2_NA + 6) * 8) : "memory");
    asm volatile("fence.mbarrier_init.release.cluster;\nfence.acq_rel.cta;\n" ::: "memory");
}
template <int ROLE>
__device__ __forceinline__ void pass2(const __nv_bfloat16* __restrict__ x, const __nv_bfloat16* __restrict__ grn_g, __nv_bfloat16* __restrict__ out,
                                      uint8_t* smem, uint32_t sbase, bool early, int zero) {
    const uint32_t bar_bfull = sbase + P2_OFF_BAR, bar_bempty = bar_bfull + P2_NB * 8;
    const uint32_t bar_afull = bar_bempty + P2_NB * 8, bar_aempty = bar_afull + 3 * P2_NA * 8;
    const uint32_t bar_xfull = bar_aempty + 3 * P2_NA * 8, bar_oready = bar_xfull + 24, s_pos = bar_oready + 24;
    int tid;
    asm volatile("mov.u32 %0, %%tid.x;\n" : "=r"(tid));
    const int warp = __shfl_sync(0xffffffffu, tid >> 5, 0), lane = tid & 31;
    const uint32_t rank = cluster_rank();
    const int cl = blockIdx.x >> 1, pair = cl >> 1;
    const int half = pair < P2_SHARED, fin = half && (cl & 1);
    const int k0 = (pair + 3 * (cl & 1)) % 6 * 8;
    auto wait_pos = [&](int target) {
        int v;
        while (true) {
            asm volatile("ld.volatile.shared.u32 %0, [%1];\n" : "=r"(v) : "r"(s_pos) : "memory");
            if (v >= target) break;
            SAFE_BREAK;
            __nanosleep(100);
        }
    };

    TSTAMP(1, 0);
    if (ROLE == 2) {
        if (warp != 14) flag_wait<true>(&g_prog[3][0], P2_NCL);
        if (warp == 15) {
            float* pre = reinterpret_cast<float*>(smem + OFF_PRE);
            const float gs = w2_scale(__float_as_uint(__ldcg(&g_sums[C_DIM])));
            float mb = 0.f;
#pragma unroll 1
            for (int i = lane; i < C_DIM; i += 32) {
                pre[i] = __ldcg(&g_sums[i]) * gs;
                mb = fmaxf(mb, fabsf(pre[i]));
            }
            pre[C_DIM] = gs;
            pre[C_DIM + 1] = __uint_as_float(__reduce_max_sync(0xffffffffu, __float_as_uint(mb)));
            bar_sync(9, 288);
            flag_wait<false>(&g_prog[4][0], NUM_CTAS * 8);
            bar_arrive(5, 416);
        }
        asm volatile("barrier.cluster.wait.aligned;\nfence.proxy.async;\n" ::: "memory");
        if (warp == 12) {
            const uint8_t* wsrc = reinterpret_cast<const uint8_t*>(g_w2img) + rank * (P2_B / 2);
            int kb = k0;
#pragma unroll 1
            for (int p = 0; p < P2_NPOS; p++) {
                const int st = p & 3;
                if (p == P2_RAW) {
                    flag_wait<true>(&g_prog[1][0], NUM_CTAS);
                    asm volatile("fence.proxy.async.global;\n" ::: "memory");
                    wsrc += sizeof(g_w2img[0]);
                }
                const int idle = (p < P2_S1 || p >= 6 * 48) + (p < P2_S2 ? !half || p >= 24 : p >= 5 * 48 + P2_S2);
                mbar_wait(bar_bempty + st * 8, (~p >> 2) & 1);
                TR2(3, p, 0);
                if (elect_one()) {
                    const int len = P2_B / 2;
                    mbar_expect_tx(bar_bfull + st * 8, 2 * len);
                    bulk_g2s_mc(sbase + st * P2_B + rank * (P2_B / 2), wsrc + kb * P2_B, len, bar_bfull + st * 8, (uint16_t)3);
                    asm volatile("st.volatile.shared.u32 [%0], %1;\n" ::"r"(s_pos), "r"(p) : "memory");
                    if (P2_SLACK > -9 && rank == 0) asm volatile("red.relaxed.gpu.global.add.u32 [%0], 1;\n" ::"l"(&g_prog[0][0]) : "memory");
                    if (idle) asm volatile("mbarrier.arrive.shared::cta.b64 _, [%0], %1;\n" ::"r"(bar_bempty + st * 8), "r"(8 * idle) : "memory");
                }
                __syncwarp();
                if (++kb == 48) kb = 0;
            }
            mbar_wait(bar_bempty, 1);
            if (lane == 0) mbar_arrive(bar_bfull);
        } else if (warp == 13) {
            const int w = lane % 3;
            const uint32_t dst0 = sbase + P2_OFF_A + w * P2_NA * P2_A;
            const uint32_t bf = bar_afull + w * P2_NA * 8, be = bar_aempty + w * P2_NA * 8;
            int n = (w == 2 && half ? -1 : w) - 3, left = 0, u = 0, c = 0;
            const uint8_t* src = nullptr;
            bool act = lane < 3;
            auto next = [&]() {
                n += 3;
                left = n >= P2_ITEMS ? -1 : n < 0 ? 24 : 48;
                u = (k0 + p2_start(n)) % 48;
                src = reinterpret_cast<const uint8_t*>(g_h) + (size_t)p2_tile(cl, n) * (2 * H_TILE) + rank * H_HALF + u * H_STEP;
            };
            next();
            flag_wait<true>(&g_prog[6][0], NUM_CTAS);
#pragma unroll 1
            for (int i = 0, w1 = 1; i < 3; i++) {
                if (i == 1 && (P2_ORD || __ldcg(&g_prog[5][0]) >= NUM_CTAS)) w1 = 2;
                if (P2_ORD == 2 && i == 2) wait_pos(5);
                const int wi = i == 0 ? 0 : i == 1 ? w1 : 3 - w1;
                if (wi == 2) flag_wait<true>(&g_prog[5][0], NUM_CTAS);
                asm volatile("fence.proxy.async.global;\n" ::: "memory");
                if (w == wi && lane < 24) {
                    mbar_expect_tx(bf + lane / 3 * 8, P2_A);
                    bulk_g2s(dst0 + lane / 3 * P2_A, src + lane / 3 * H_STEP, P2_A, bf + lane / 3 * 8);
                }
                __syncwarp();
            }
            c = 8;
            left -= 8;
            u += 8;
            src += 8 * H_STEP;
            if (u == 48) { u = 0; src -= 48 * H_STEP; }
            while (__any_sync(0xffffffffu, act)) {
                if (left == 0) next();
                const bool ok = act && mbar_test(be + ((c - 1) & 7) * 8, (~c >> 3) & 1);
                if (ok) {
                    const int st = c & 7;
                    if (left > 0) {
                        mbar_expect_tx(bf + st * 8, P2_A);
                        bulk_g2s(dst0 + st * P2_A, src, P2_A, bf + st * 8);
                    } else {
                        mbar_arrive(bf + st * 8);
                        act = false;
                    }
                    src += H_STEP;
                    if (++u == 48) { u = 0; src -= 48 * H_STEP; }
                    c++;
                    left--;
                }
                SAFE_BREAK;
                if (!__any_sync(0xffffffffu, ok)) __nanosleep(100);
            }
        } else if (warp == 14) {
            const uint32_t sx = sbase + P2_OFF_X;
            size_t o = 0;
            int wp = 0;
            uint32_t par = 0;
            if (fin) {
#pragma unroll 1
                for (int c = lane * 16; c < 64 * P2_XROW + 128; c += 512) asm volatile("st.shared.v4.u32 [%0], {0, 0, 0, 0};\n" ::"r"(sx + c) : "memory");
                __syncwarp();
            }
            wait_pos(P2_XW);
#pragma unroll 1
            for (int n = -half; n <= P2_ITEMS; n++) {
                const int w = (n + 3) % 3, end = p2_start(n) + 48;
                const size_t on = (size_t)(2 * p2_tile(cl, n) + rank) * (64 * C_DIM * 2);
                const uint32_t xf = bar_xfull + w * 8;
                bool st = n + half > 0;
                const bool ld = n < P2_ITEMS - 1 && !(n < 0 && fin);
                if (n == P2_ITEMS - 1 && lane == 0) {
                    mbar_expect_tx(xf, 64 * C_DIM * 2);
#pragma unroll 1
                    for (int c = 4; c < 12; c++) {
                        if (c >= 8) {
                            mbar_wait(bar_aempty + ((2 * c - 1) & 7) * 8, 1);
                            mbar_wait(bar_aempty + ((2 * c) & 7) * 8, 1);
                        }
                        bulk_g2s(sbase + P2_OFF_A + (c & 3) * P2_XC + (c < 8 ? P2_LHALF : 0), reinterpret_cast<const uint8_t*>(x) + on + (c & 7) * P2_XC, P2_XC, xf);
                    }
                    mbar_arrive(xf);
                }
                if (st) {
                    mbar_wait(bar_oready + wp * 8, (par >> wp) & 1);
                    par ^= 1u << wp;
                }
                if (lane == 0) {
                    if (n < P2_ITEMS - 1) mbar_expect_tx(xf, ld ? 64 * C_DIM * 2 : 0);
                    const int t0 = (n ? p2_start(n - 1) + 48 : P2_S2) + (n == P2_ITEMS - 1 ? P2_TL : P2_T0), dt = end - (n == P2_ITEMS - 2 ? P2_CMP : 0) - t0;
                    int t = st ? 16 * t0 : -4096;
                    if ((n == 0 && half) || n == P2_ITEMS) {
                        if (fin && n == 0) {
                            flag_wait<true>(&g_half[pair][rank], 1);
                            asm volatile("fence.proxy.async.global;\n" ::: "memory");
                        }
#pragma unroll 1
                        for (int c = 0; c < 2; c++) {
                            uint8_t* dst = reinterpret_cast<uint8_t*>(out) + o + c * 32 * P2_XROW;
                            if (!fin || n) bulk_s2g(dst, n ? sbase + P2_OFF_A + c * P2_LHALF : sx + c * P2_XHALF, 32 * P2_XROW);
                            else asm volatile("cp.reduce.async.bulk.global.shared::cta.bulk_group.add.noftz.bf16 [%0], [%1], %2;\n"
                                              ::"l"(dst), "r"(sx + c * P2_XHALF), "r"(32 * P2_XROW) : "memory");
                        }
                        asm volatile("cp.async.bulk.commit_group;\n" ::: "memory");
                        if (!fin && n == 0) {
                            asm volatile("cp.async.bulk.wait_group 0;\nfence.proxy.async.global;\n" ::: "memory");
                            asm volatile("st.release.gpu.global.u32 [%0], 1;\n" ::"l"(&g_half[pair][rank]) : "memory");
                        }
                        st = false;
                    }
#pragma unroll 1
                    for (int c = 0; n < P2_ITEMS && c < 64 * P2_XROW; c += P2_XC, t += 2 * dt) {
                        const uint32_t sp = sx + c + (c >= 32 * P2_XROW ? 64 : 0);
                        wait_pos(t >> 4);
                        if (st) bulk_s2g(reinterpret_cast<uint8_t*>(out) + o + c, sp, P2_XC);
                        asm volatile("cp.async.bulk.commit_group;\n" ::: "memory");
                        if (ld) {
                            wait_pos((t + dt) >> 4);
                            asm volatile("cp.async.bulk.wait_group.read 0;\n" ::: "memory");
                            bulk_g2s(sp, reinterpret_cast<const uint8_t*>(x) + on + c, P2_XC, xf);
                        }
                    }
                    if (P2_SLACK > -9 && rank == 0 && n > 0 && n < P2_ITEMS - 2) flag_wait<false>(&g_prog[0][0], P2_NCL * (end + P2_SLACK));
                    if (n < P2_ITEMS - 1) mbar_arrive(xf);
                }
                __syncwarp();
                o = on;
                wp = w;
            }
            asm volatile("cp.async.bulk.wait_group.read 0;\n" ::: "memory");
        } else {
            if (blockIdx.x == 120) {
                wait_pos(P2_RAW);
                for (int i = lane; i < (LN_RING + 6) * 2; i += 32) (&g_flag[0][0][0])[i * 8] = 0;
                for (int i = lane; i < HID; i += 32) g_sq[i] = 0;
                for (int i = lane; i < 512; i += 32) g_sums[i] = 0.f;
            }
            int t = 4 * P2_XP0;
#pragma unroll 1
            for (int n = 0; n < P2_ITEMS && lane == 0; n++) {
                const uint8_t* xn = reinterpret_cast<const uint8_t*>(x) + (size_t)(2 * p2_tile(cl, n) + rank) * (64 * C_DIM * 2);
#pragma unroll 1
                for (int c = 0; c < 16; c++, t += n < P2_XPN ? 4 : P2_XPD) {
                    wait_pos(t >> 2);
                    asm volatile("cp.async.bulk.prefetch.L2.global [%0], %1;\n" ::"l"(xn + c * (P2_XC / 2)), "r"(P2_XC / 2) : "memory");
                }
            }
        }
        __syncwarp();
        END_SYNC();
    } else {
        const int wg = warp >> 2, w = warp & 3, g = lane >> 2, q = lane & 3;
        const uint32_t sx = sbase + P2_OFF_X + (g & 1) * P2_XHALF + (w * 8 + (g >> 1)) * P2_XROW + q * 16;
        const uint32_t af = bar_afull + wg * P2_NA * 8;
        const uint32_t s_a = sbase + P2_OFF_A + wg * P2_NA * P2_A + (lane >> 3) * 512 + (lane & 7) * 64 + ((w ^ ((lane & 7) >> 1)) << 4);
        uint32_t acc0[48], acc1[48], up;
        uint4 a[2][2];

        __nv_bfloat16 gg[4];
#pragma unroll
        for (int i = 0; i < 4; i++) gg[i] = grn_g[tid + 384 * i];
#pragma unroll 1
        for (int it = !early;; it++) {
            float* s_red = reinterpret_cast<float*>(smem + P2_OFF_RED);
            float gx[4], part = 0.f;
            if (it == 1) {
                TSTAMP(1, 27);
                bar_sync(5, 416);
            }
            unsigned long long v[4];
#pragma unroll
            for (int i = 0; i < 4; i++) gx[i] = __ldcg(&g_scale[tid + 384 * i]);
            while (true) {
#pragma unroll
                for (int i = 0; i < 4; i++) asm volatile("ld.relaxed.gpu.global.u64 %0, [%1];\n" : "=l"(v[i]) : "l"(&g_sq[tid + 384 * i]) : "memory");
                SAFE_BREAK;
                if (!it || !__any_sync(0xffffffffu, min(min(v[0], v[1]), min(v[2], v[3])) < (unsigned long long)NGRP << 56)) break;
                if (P2_NAP) __nanosleep(P2_NAP);
            }
            TSTAMP(1, 1);
            const float bias = reinterpret_cast<const float*>(smem + OFF_PRE)[tid];
            const float2 pre = *reinterpret_cast<const float2*>(smem + OFF_PRE + C_DIM * 4);
            bool tiny = false;
#pragma unroll
            for (int i = 0; i < 4; i++) {
                const float t = it == 2 ? __ldcg(&g_redo[tid + 384 * i]) : __ull2float_rn(v[i] << 8) * 0x1p-40f;
                tiny |= t < M_TOTAL * 0x1p-19f;
                gx[i] *= gx[i] * t;
            }
            float mg = 0.f;
#pragma unroll
            for (int i = 0; i < 4; i++) {
                asm("sqrt.approx.f32 %0, %1;\n" : "=f"(gx[i]) : "f"(gx[i] * (HSCALE * HSCALE) + 1e-6f));
                part += gx[i];
                gx[i] *= __bfloat162float(gg[i]);
                mg = fmaxf(mg, fabsf(gx[i]));
            }
#pragma unroll
            for (int o = 16; o > 0; o >>= 1) part += __shfl_xor_sync(0xffffffffu, part, o);
            const uint32_t mgw = __reduce_max_sync(0xffffffffu, __float_as_uint(mg));
            TSTAMP(1, 26);
            if (lane == 0) *reinterpret_cast<float2*>(s_red + warp * 2) = make_float2(part, __uint_as_float(mgw));
            if (it) {
                uint32_t redo;
                asm volatile("{\n.reg .pred p;\nsetp.ne.u32 p, %1, 0;\nbar.red.or.pred p, 4, 384, p;\nselp.u32 %0, 1, 0, p;\n}\n"
                             : "=r"(redo) : "r"((uint32_t)(tiny && it == 1)) : "memory");
                if (__shfl_sync(0xffffffffu, redo, 0)) {
                    p2_redo_sums(warp, lane);
                    continue;
                }
            }
            float tot = 0.f;
#pragma unroll
            for (int i = 0; i < 6; i++) {
                const float4 t = *reinterpret_cast<const float4*>(s_red + i * 4);
                tot += t.x + t.z;
                mg = fmaxf(mg, fmaxf(t.y, t.w));
            }
            const float inv = __fdividef(1.0f, tot * (1.0f / HID) + 1e-6f);
            const uint32_t ej = min((__float_as_uint(fmaxf(fmaf(mg, inv, 1.0f) * (HSCALE * UNCHOP), pre.y * 0x1p-13f)) >> 23) + 1, 250u);
            const float dn = __uint_as_float((254u - ej) << 23);
            up = min(ej + 127u - (__float_as_uint(pre.x) >> 23), 254u) * 0x00800080u;
            reinterpret_cast<uint16_t*>(smem + P2_OFF_BIAS + C_DIM * 2)[tid] = 0;
            *reinterpret_cast<__half*>(smem + P2_OFF_BIAS + (tid >> 5) * 64 + (tid & 6) * 8 + (tid & 24) / 2 + (tid & 1) * 2) = __float2half_rn(bias * dn);
#pragma unroll
            for (int i = 0; i < 4; i++) {
                const int k = tid + 384 * i;
                *reinterpret_cast<__half*>(smem + P2_OFF_GRN + (k >> 4) * 32 + (k & 6) * 4 + (k & 8) / 2 + (k & 1) * 2) =
                    __float2half_rn(fmaf(gx[i], inv, 1.0f) * (HSCALE * UNCHOP * dn));
            }
            TSTAMP(1, 25);
            if (it) break;
        }
        bar_sync(4, 384);
        asm volatile("barrier.cluster.wait.aligned;\n" ::: "memory");
        TSTAMP(1, 28);
        if (wg == 1) {
            constexpr int N = sizeof(g_w2img[0]) / 16, PER = (N + NUM_CTAS - 1) / NUM_CTAS;
            uint4 v[5];
#pragma unroll
            for (int i = 0; i < 5; i++) v[i] = __ldcg(&g_w2img[0][min(blockIdx.x * PER + (tid & 127) + 128 * i, N - 1)]);
#pragma unroll
            for (int i = 0; i < 5; i++) {
                const int j = min(blockIdx.x * PER + (tid & 127) + 128 * i, N - 1);
                const uint32_t* t = reinterpret_cast<const uint32_t*>(smem + P2_OFF_GRN + (j / 768) * 32 + (j & 8) / 2);
                auto sc = [&](uint32_t u, int e) { return (h2_mul(u, t[2 * e]) + 0x00040004u) & 0xfff8fff8u; };
                g_w2img[1][j] = make_uint4(sc(v[i].x, 0), sc(v[i].y, 1), sc(v[i].z, 2), sc(v[i].w, 3));
            }
            asm volatile("fence.proxy.async.global;\n" ::: "memory");
            bar_sync(2, 128);
            if (tid == 128) asm volatile("fence.acq_rel.gpu;\nred.release.gpu.global.add.u32 [%0], 1;\n" ::"l"(&g_prog[1][0]) : "memory");
        }

        const int who = __shfl_sync(0xffffffffu, lane == 2 ? 0 : lane < 2 ? 1 : 2, lane);
        const uint32_t rel0 = who ? mapa(bar_bempty, lane & 1) : mapa(bar_aempty + wg * P2_NA * 8, rank), rel1 = rel0 + (who ? 0 : 32);
        auto publish = [&]() {
            asm volatile("fence.proxy.async.shared::cta;\n" ::: "memory");
            __syncwarp();
            if (who == 0) mbar_arrive(bar_oready + wg * 8);
        };
        bool ok_a, pend = false;
        uint32_t pa = 0, s_t;
        auto fetch = [&](int j, bool raw) {
            uint32_t o[6], u0[4], u1[4];
            uint2 t0 = make_uint2(0, 0), t1 = t0;
            if (raw) {
                asm volatile("ld.shared.v2.u32 {%0,%1}, [%2];\n" : "=r"(t0.x), "=r"(t0.y) : "r"(s_t + j * 64) : "memory");
                asm volatile("ld.shared.v2.u32 {%0,%1}, [%2];\n" : "=r"(t1.x), "=r"(t1.y) : "r"(s_t + j * 64 + 32) : "memory");
            }
            const bool ok_b = mbar_test(bar_bfull + (j & 3) * 8, j >> 2);
            if (j == 7) pa ^= 1;
            ok_a = mbar_test(af + ((j + 1) & 7) * 8, pa);
            asm volatile("ldmatrix.sync.aligned.m8n8.x4.trans.shared.b16 {%0,%1,%2,%3}, [%4];\n"
                         : "=r"(o[0]), "=r"(o[1]), "=r"(o[2]), "=r"(o[3]) : "r"(s_a + j * P2_A) : "memory");
            asm volatile("ldmatrix.sync.aligned.m8n8.x2.trans.shared.b16 {%0,%1}, [%2];\n"
                         : "=r"(o[4]), "=r"(o[5]) : "r"(s_a + j * P2_A + 2048) : "memory");
            p2_unpack(u0, o[0], o[1], o[2]);
            p2_unpack(u1, o[3], o[4], o[5]);
            if (raw) {
                u0[0] = h2_mul(u0[0], t0.x); u0[1] = h2_mul(u0[1], t0.x); u0[2] = h2_mul(u0[2], t0.y); u0[3] = h2_mul(u0[3], t0.y);
                u1[0] = h2_mul(u1[0], t1.x); u1[1] = h2_mul(u1[1], t1.x); u1[2] = h2_mul(u1[2], t1.y); u1[3] = h2_mul(u1[3], t1.y);
            }
            a[j & 1][0] = make_uint4(u0[0], u0[1], u0[2], u0[3]);
            a[j & 1][1] = make_uint4(u1[0], u1[1], u1[2], u1[3]);
            if (!ok_b) mbar_wait(bar_bfull + (j & 3) * 8, j >> 2);
        };
        auto table = [&](int pos) { s_t = sbase + P2_OFF_GRN + q * 8 + (k0 + pos) % 48 * 64; };
        const uint32_t db0 = (uint32_t)make_desc(sbase, 128, 256);
        auto block8 = [&](bool raw, int pos, int thr0, int mode) {
#pragma unroll
            for (int j = 0; j < 8; j++) {
                const uint32_t db = db0 + (j & 3) * (P2_B / 16);
                if (j == 8 - P2_AH && mode == 1) bar_sync(4, 384);
                TR2(wg, pos + j, 0);
                wg_fence();
                mma_rs_n192(acc0, a[j & 1][0], db);
                mma_rs_n192(acc1, a[j & 1][0], db + 384);
                mma_rs_n192(acc0, a[j & 1][1], db + 768);
                mma_rs_n192(acc1, a[j & 1][1], db + 768 + 384);
                wg_commit();
                if (j == 7 && mode == 2) bar_arrive(4, 384);
                const uint32_t rel = ((j - 1) & 4 ? rel1 : rel0) + ((j - 1) & 3) * 8;
                TR2(wg, pos + j, 1);
                wg_wait<1>();
                TR2(wg, pos + j, 2);
                if (who < (j ? 2 : thr0)) mbar_arrive_cluster(rel);
                if (!ok_a) {
                    if (j == 0 && pend) { publish(); pend = false; }
                    mbar_wait(af + ((j + 1) & 7) * 8, pa);
                }
                TR2(wg, pos + j, 3);
                if (raw && j == 7) table(pos + 8);
                fetch((j + 1) & 7, raw && (j < 7 || pos + 8 < P2_RAW));
            }
        };
        int n = wg == 2 && half ? -1 : wg, pos = p2_start(n);
        uint32_t px = 0;
        wait_pos(pos);
        mbar_wait(af, 0);
        table(pos);
        fetch(0, pos < P2_RAW);
#pragma unroll 1
        for (;; n += 3) {
            TSTAMP(1, 2 + n);
            const int end = pos + (n < 0 ? 24 : 48);
#pragma unroll
            for (int i = 0; i < 48; i += 2) {
                asm volatile("mov.b64 {%0, %1}, 0;\n" : "=r"(acc0[i]), "=r"(acc0[i + 1]));
                asm volatile("mov.b64 {%0, %1}, 0;\n" : "=r"(acc1[i]), "=r"(acc1[i + 1]));
            }
            int thr = 1;
#pragma unroll 1
            for (; pos < P2_RAW; pos += 8, thr = 2) block8(true, pos, thr, 0);
#pragma unroll 1
            for (; pos < end; pos += 8, thr = 2) {
                const int e = pos + 8, r = e % 48;
                block8(false, pos, thr, e < 48 || e > 256 || (r != 0 && r != P2_S1 && r != P2_S2) ? 0 : e == end ? 2 : 1);
            }
            TR2(wg, pos - 1, 4);
            wg_wait<0>();
            TR2(wg, pos - 1, 5);
            if (who == 1) mbar_arrive_cluster(rel0 + 24);
            mbar_wait(bar_xfull + wg * 8, px);
            TR2(wg, pos - 1, 6);
            px ^= 1;
            __syncwarp();
            p2_epilogue(acc0, acc1, up, n == P2_ITEMS - 1 ? sx - (P2_OFF_X - P2_OFF_A) + (g & 1) * (P2_LHALF - P2_XHALF) : sx, sbase + P2_OFF_BIAS + q * 16 + (n < 0 && fin ? C_DIM * 2 : 0), zero);
            TR2(wg, pos - 1, 7);
            if (n + 3 >= P2_ITEMS) { publish(); break; }
            if (n < 0) {
                publish();
                pos = P2_S2;
                wait_pos(pos);
                mbar_wait(bar_bfull, 0);
            } else {
                pend = true;
                ok_a = false;
            }
        }
        TSTAMP(1, 29);
        END_SYNC();
        TSTAMP(1, 30);
    }
}

__global__ void __cluster_dims__(2, 1, 1) __launch_bounds__(512, 1)
block_kernel(const __grid_constant__ CUtensorMap wmap, const __nv_bfloat16* __restrict__ x, const __nv_bfloat16* __restrict__ dw,
             const __nv_bfloat16* __restrict__ w2, const __nv_bfloat16* __restrict__ grn_g, const __nv_bfloat16* __restrict__ grn_b,
             __nv_bfloat16* __restrict__ out, int zero) {
    extern __shared__ __align__(1024) uint8_t smem[];
    const uint32_t sbase = smem_u32(smem);
    const int warp = __shfl_sync(0xffffffffu, threadIdx.x >> 5, 0), lane = threadIdx.x & 31;
    if (warp >= 12) {
        pass1<2>(wmap, x, dw, w2, grn_b, sbase, warp, lane, zero);
        pass2<2>(x, grn_g, out, smem, sbase, false, zero);
    } else {
        bool early = false;
        if (warp >= 8) {
            pass1<1>(wmap, x, dw, w2, grn_b, sbase, warp, lane, zero);
            reg_inc<160>();
        } else {
            early = pass1<0>(wmap, x, dw, w2, grn_b, sbase, warp, lane, zero);
            reg_dec<160>();
        }
        pass2<0>(x, grn_g, out, smem, sbase, early, zero);
    }
}

}

extern "C" void kernel_launch(void* const* d_in, const int* in_sizes, int n_in, void* d_out, int out_size) {
    const __nv_bfloat16* x = (const __nv_bfloat16*)d_in[0];
    const __nv_bfloat16* dw = (const __nv_bfloat16*)d_in[1];
    const __nv_bfloat16* w1 = (const __nv_bfloat16*)d_in[2];
    const __nv_bfloat16* w2 = (const __nv_bfloat16*)d_in[3];
    const __nv_bfloat16* grn_g = (const __nv_bfloat16*)d_in[4];
    const __nv_bfloat16* grn_b = (const __nv_bfloat16*)d_in[5];
    __nv_bfloat16* out = (__nv_bfloat16*)d_out;

    cudaFuncSetAttribute(block_kernel, cudaFuncAttributeMaxDynamicSharedMemorySize, SMEM_BYTES);

    typedef CUresult (*EncodeFn)(CUtensorMap*, CUtensorMapDataType, cuuint32_t, void*, const cuuint64_t*, const cuuint64_t*,
                                 const cuuint32_t*, const cuuint32_t*, CUtensorMapInterleave, CUtensorMapSwizzle,
                                 CUtensorMapL2promotion, CUtensorMapFloatOOBfill);
    static EncodeFn encode = nullptr;
    if (!encode) {
        cudaDriverEntryPointQueryResult qres;
        cudaGetDriverEntryPoint("cuTensorMapEncodeTiled", (void**)&encode, cudaEnableDefault, &qres);
    }
    CUtensorMap wmap;
    const cuuint64_t gdim[2] = {HID, C_DIM};
    const cuuint64_t gstr[1] = {HID * 2};
    const cuuint32_t box[2] = {64, 192}, estr[2] = {1, 1};
    CUresult er = encode(&wmap, CU_TENSOR_MAP_DATA_TYPE_BFLOAT16, 2, (void*)w1, gdim, gstr, box, estr, CU_TENSOR_MAP_INTERLEAVE_NONE,
           CU_TENSOR_MAP_SWIZZLE_128B, CU_TENSOR_MAP_L2_PROMOTION_L2_128B, CU_TENSOR_MAP_FLOAT_OOB_FILL_NONE);
    if (er != CUDA_SUCCESS) printf("tensor map encode failed %d\n", (int)er);

    block_kernel<<<NUM_CTAS, 512, SMEM_BYTES>>>(wmap, x, dw, w2, grn_g, grn_b, out, 0);
}
```

```cpp
#include <cuda.h>
#include <cuda_runtime.h>
#include <cuda_bf16.h>
#include <cuda_fp16.h>
#include <stdint.h>
#include <stdio.h>

namespace {

constexpr int M_TOTAL = 384 * 384;
constexpr int C_DIM   = 384;
constexpr int HID     = 1536;
constexpr int NT128   = M_TOTAL / 128;
constexpr int NUM_CTAS = 132;

constexpr int NGRP = 22, GRP_CTAS = 6;
constexpr int NT_EARLY = NT128 - 30;
constexpr int LN_STEP = NUM_CTAS / 4, LN_RING = 2 * LN_STEP;
constexpr int LN_TILE = 128 * C_DIM * 2;
constexpr int H_TILE = 64 * HID * 3 / 2;
constexpr int H_HALF = 3072, H_STEP = 6144;

__device__ __align__(1024) uint4 g_h[(size_t)M_TOTAL * HID * 3 / 32];
__device__ __align__(1024) uint4 g_ln[LN_RING * LN_TILE / 16];
__device__ __align__(1024) uint4 g_w2img[2][HID * C_DIM * 2 / 16];
__device__ __align__(16) unsigned long long g_sq[HID];
__device__ __align__(16) float g_sums[512];
__device__ float g_scale[HID];
__device__ float g_redo[HID];
enum { CNT_POS, CNT_IMG1, CNT_REDO, CNT_IMG0, CNT_LAST, CNT_H, CNT_EARLY, NUM_CNT };
__device__ __align__(128) unsigned g_prog[NUM_CNT][32];
__device__ __align__(128) unsigned g_half[32][2];
__device__ unsigned g_flag[LN_RING + 6][2][8];
#define TSTAMP(k, i)
#define TRACE(wg, pos, i)
#define TRACEW(pos, i)

#define TR2(wg, pos, i)
__host__ __device__ __forceinline__ int perm32(int n) {
    return (n & ~31) | (((n >> 1) & 3) << 3) | (((n >> 3) & 3) << 1) | (n & 1);
}

__device__ __forceinline__ uint32_t smem_u32(const void* p) { return (uint32_t)__cvta_generic_to_shared(p); }

__device__ __forceinline__ void mbar_init(uint32_t bar, uint32_t count) {
    asm volatile("mbarrier.init.shared::cta.b64 [%0], %1;\n" ::"r"(bar), "r"(count) : "memory");
}
__device__ __forceinline__ void mbar_expect_tx(uint32_t bar, uint32_t bytes) {
    asm volatile("mbarrier.arrive.expect_tx.shared::cta.b64 _, [%0], %1;\n" ::"r"(bar), "r"(bytes) : "memory");
}
__device__ __forceinline__ void mbar_arrive(uint32_t bar) {
    asm volatile("mbarrier.arrive.shared::cta.b64 _, [%0];\n" ::"r"(bar) : "memory");
}
__device__ __forceinline__ void mbar_arrive_cluster(uint32_t bar_cluster_addr) {
    asm volatile("mbarrier.arrive.shared::cluster.b64 _, [%0];\n" ::"r"(bar_cluster_addr) : "memory");
}
#define SAFE_BREAK
__device__ __forceinline__ void mbar_wait(uint32_t bar, uint32_t parity) {
    asm volatile(
        "{\n"
        ".reg .pred p;\n"
        "LAB_WAIT:\n"
        "mbarrier.try_wait.parity.shared::cta.b64 p, [%0], %1;\n"
        "@!p bra LAB_WAIT;\n"
        "}\n" ::"r"(bar), "r"(parity) : "memory");
}
__device__ __forceinline__ bool mbar_test(uint32_t bar, uint32_t parity) {
    uint32_t ok;
    asm volatile("{\n.reg .pred p;\n"
                 "mbarrier.test_wait.parity.shared::cta.b64 p, [%1], %2;\n"
                 "selp.u32 %0, 1, 0, p;\n}\n" : "=r"(ok) : "r"(bar), "r"(parity) : "memory");
    return ok != 0;
}
__device__ __forceinline__ uint32_t mapa(uint32_t addr, uint32_t rank) {
    uint32_t r;
    asm volatile("mapa.shared::cluster.u32 %0, %1, %2;\n" : "=r"(r) : "r"(addr), "r"(rank));
    return r;
}
__device__ __forceinline__ void bulk_g2s(uint32_t dst, const void* src, uint32_t bytes, uint32_t bar) {
    asm volatile("cp.async.bulk.shared::cluster.global.mbarrier::complete_tx::bytes [%0], [%1], %2, [%3];\n"
                 ::"r"(dst), "l"(src), "r"(bytes), "r"(bar) : "memory");
}
__device__ __forceinline__ void bulk_g2s_mc(uint32_t dst, const void* src, uint32_t bytes, uint32_t bar, uint16_t mask) {
    asm volatile("cp.async.bulk.shared::cluster.global.mbarrier::complete_tx::bytes.multicast::cluster [%0], [%1], %2, [%3], %4;\n"
                 ::"r"(dst), "l"(src), "r"(bytes), "r"(bar), "h"(mask) : "memory");
}
__device__ __forceinline__ void tma2(uint32_t dst, const CUtensorMap* map, int c0, int c1, uint32_t bar) {
    asm volatile("cp.async.bulk.tensor.2d.shared::cluster.global.tile.mbarrier::complete_tx::bytes [%0], [%1, {%2, %3}], [%4];\n"
                 ::"r"(dst), "l"(map), "r"(c0), "r"(c1), "r"(bar) : "memory");
}
template <bool ACQ>
__device__ __forceinline__ uint32_t flag_wait(const unsigned* p, unsigned target) {
    unsigned v, n = 0;
    do {
        if (ACQ) asm volatile("ld.acquire.gpu.global.u32 %0, [%1];\n" : "=r"(v) : "l"(p) : "memory");
        else asm volatile("ld.relaxed.gpu.global.u32 %0, [%1];\n" : "=r"(v) : "l"(p) : "memory");
        n++;
    } while (v < target);
    return n == 1;
}
__device__ __forceinline__ void ldsm4t(uint32_t (&r)[4], uint32_t addr) {
    asm volatile("ldmatrix.sync.aligned.m8n8.x4.trans.shared.b16 {%0,%1,%2,%3}, [%4];\n"
                 : "=r"(r[0]), "=r"(r[1]), "=r"(r[2]), "=r"(r[3]) : "r"(addr) : "memory");
}
__device__ __forceinline__ void bulk_s2g(void* dst, uint32_t src, uint32_t bytes) {
    asm volatile("cp.async.bulk.global.shared::cta.bulk_group [%0], [%1], %2;\n" ::"l"(dst), "r"(src), "r"(bytes) : "memory");
}
__device__ __forceinline__ void cluster_sync_relaxed() {
    asm volatile("barrier.cluster.arrive.relaxed.aligned;\nbarrier.cluster.wait.aligned;\n" ::: "memory");
}
__device__ __forceinline__ uint32_t cluster_rank() {
    uint32_t r;
    asm volatile("mov.u32 %0, %%cluster_ctarank;\n" : "=r"(r));
    return r;
}
__device__ __forceinline__ bool elect_one() {
    uint32_t pred;
    asm volatile("{\n.reg .pred p;\nelect.sync _|p, 0xffffffff;\nselp.u32 %0, 1, 0, p;\n}\n" : "=r"(pred));
    return pred != 0;
}
__device__ __forceinline__ void wg_fence() { asm volatile("wgmma.fence.sync.aligned;\n" ::: "memory"); }
__device__ __forceinline__ void wg_commit() { asm volatile("wgmma.commit_group.sync.aligned;\n" ::: "memory"); }
template <int N> __device__ __forceinline__ void wg_wait() {
    asm volatile("wgmma.wait_group.sync.aligned %0;\n" ::"n"(N) : "memory");
}
template <int R> __device__ __forceinline__ void reg_inc() { asm volatile("setmaxnreg.inc.sync.aligned.u32 %0;\n" ::"n"(R)); }
template <int R> __device__ __forceinline__ void reg_dec() { asm volatile("setmaxnreg.dec.sync.aligned.u32 %0;\n" ::"n"(R)); }
__device__ __forceinline__ void bar_sync(int id, int n) { asm volatile("bar.sync %0, %1;\n" ::"r"(id), "r"(n) : "memory"); }
__device__ __forceinline__ void bar_arrive(int id, int n) { asm volatile("bar.arrive %0, %1;\n" ::"r"(id), "r"(n) : "memory"); }

__device__ __forceinline__ uint64_t make_desc(uint32_t saddr, uint32_t lbo, uint32_t sbo) {
    return (uint64_t)((saddr & 0x3FFFF) >> 4) | ((uint64_t)(lbo >> 4) << 16) | ((uint64_t)(sbo >> 4) << 32);
}

__device__ __forceinline__ void stg128_cs(void* p, uint32_t a, uint32_t b, uint32_t c, uint32_t d) {
    asm volatile("st.global.cs.v4.u32 [%0], {%1,%2,%3,%4};\n" ::"l"(p), "r"(a), "r"(b), "r"(c), "r"(d) : "memory");
}
__device__ __forceinline__ uint32_t pack_bf16(float lo, float hi) {
    uint32_t r;
    asm("cvt.rn.bf16x2.f32 %0, %1, %2;\n" : "=r"(r) : "f"(hi), "f"(lo));
    return r;
}
__device__ __forceinline__ float bf_lo(uint32_t v) { return __uint_as_float(v << 16); }
__device__ __forceinline__ float bf_hi(uint32_t v) { return __uint_as_float(v & 0xffff0000u); }
__device__ __forceinline__ uint32_t bf2_mul(uint32_t a, uint32_t b) {
    uint32_t r;
    asm("mul.rn.bf16x2 %0, %1, %2;\n" : "=r"(r) : "r"(a), "r"(b));
    return r;
}
__device__ __forceinline__ uint32_t bf2_fma(uint32_t a, uint32_t b, uint32_t c) {
    uint32_t r;
    asm("fma.rn.bf16x2 %0, %1, %2, %3;\n" : "=r"(r) : "r"(a), "r"(b), "r"(c));
    return r;
}
__device__ __forceinline__ uint32_t bf2_add(uint32_t a, uint32_t b) {
    uint32_t r;
    asm("add.rn.bf16x2 %0, %1, %2;\n" : "=r"(r) : "r"(a), "r"(b));
    return r;
}
__device__ __forceinline__ uint32_t h2_mul(uint32_t a, uint32_t b) {
    uint32_t r;
    asm("mul.rn.f16x2 %0, %1, %2;\n" : "=r"(r) : "r"(a), "r"(b));
    return r;
}
__device__ __forceinline__ uint32_t h2_fma(uint32_t a, uint32_t b, uint32_t c) {
    uint32_t r;
    asm("fma.rn.f16x2 %0, %1, %2, %3;\n" : "=r"(r) : "r"(a), "r"(b), "r"(c));
    return r;
}
__device__ __forceinline__ uint32_t h2_add(uint32_t a, uint32_t b) {
    uint32_t r;
    asm("add.rn.f16x2 %0, %1, %2;\n" : "=r"(r) : "r"(a), "r"(b));
    return r;
}
__device__ __forceinline__ uint32_t pack_f16(float lo, float hi) {
    uint32_t r;
    asm("cvt.rn.f16x2.f32 %0, %1, %2;\n" : "=r"(r) : "f"(hi), "f"(lo));
    return r;
}
__device__ __forceinline__ float h_lo(uint32_t v) { return __low2float(*reinterpret_cast<const __half2*>(&v)); }
__device__ __forceinline__ float h_hi(uint32_t v) { return __high2float(*reinterpret_cast<const __half2*>(&v)); }
__device__ __forceinline__ uint32_t bf2_to_h2(uint32_t v) { return (v & 0x7fff7fffu) * 7u + v; }
__device__ __forceinline__ uint32_t prmt(uint32_t a, uint32_t b, uint32_t sel) {
    uint32_t r;
    asm("prmt.b32 %0, %1, %2, %3;\n" : "=r"(r) : "r"(a), "r"(b), "r"(sel));
    return r;
}
__device__ __forceinline__ uint32_t bitsel(uint32_t a, uint32_t b, uint32_t m) {
    uint32_t r;
    asm("lop3.b32 %0, %1, %2, %3, 0xd8;\n" : "=r"(r) : "r"(a), "r"(b), "r"(m));
    return r;
}
constexpr float KAPPA = 0.3292034911525734f;
constexpr uint32_t GELU_C2 = 0x40d940d9u;
constexpr float HSCALE = 1.0f / (2.0f * KAPPA);
__device__ __forceinline__ float w2_scale(uint32_t m) { return __uint_as_float((257u - max(m >> 23, 16u)) << 23); }
__device__ __forceinline__ void sched_break(int zero) {
    asm volatile("{\n.reg .pred p;\nsetp.ne.s32 p, %0, 0;\nSB_LOOP:\n@p nanosleep.u32 1;\n@p bra SB_LOOP;\n}\n" ::"r"(zero));
}

#define ACC8(d, o) "+r"(d[o + 0]), "+r"(d[o + 1]), "+r"(d[o + 2]), "+r"(d[o + 3]), "+r"(d[o + 4]), "+r"(d[o + 5]), "+r"(d[o + 6]), "+r"(d[o + 7])

__device__ __forceinline__ void mma_rs_n128(uint32_t (&d)[32], const uint32_t (&a)[4], uint32_t desc, int scale_d) {
    asm volatile(
        "{\n.reg .pred p;\n.reg .b64 db;\nsetp.ne.b32 p, %37, 0;\nmov.b64 db, {%36, 0x40000040};\n"
        "wgmma.mma_async.sync.aligned.m64n128k16.f16.f16.f16 "
        "{%0,%1,%2,%3,%4,%5,%6,%7,%8,%9,%10,%11,%12,%13,%14,%15,"
        "%16,%17,%18,%19,%20,%21,%22,%23,%24,%25,%26,%27,%28,%29,%30,%31},"
        "{%32,%33,%34,%35}, db, p, 1, 1, 0;\n}\n"
        : ACC8(d, 0), ACC8(d, 8), ACC8(d, 16), ACC8(d, 24)
        : "r"(a[0]), "r"(a[1]), "r"(a[2]), "r"(a[3]), "r"(desc), "r"(scale_d));
}

__device__ __forceinline__ void mma_ss_n128(uint32_t (&d)[32], uint32_t da, uint32_t db, int scale_d) {
    asm volatile(
        "{\n.reg .pred p;\n.reg .b64 da, db;\nsetp.ne.b32 p, %34, 0;\nmov.b64 da, {%32, 0x40000040};\nmov.b64 db, {%33, 0x40000040};\n"
        "wgmma.mma_async.sync.aligned.m64n128k16.f16.f16.f16 "
        "{%0,%1,%2,%3,%4,%5,%6,%7,%8,%9,%10,%11,%12,%13,%14,%15,"
        "%16,%17,%18,%19,%20,%21,%22,%23,%24,%25,%26,%27,%28,%29,%30,%31},"
        "da, db, p, 1, 1, 1, 0;\n}\n"
        : ACC8(d, 0), ACC8(d, 8), ACC8(d, 16), ACC8(d, 24)
        : "r"(da), "r"(db), "r"(scale_d));
}

__device__ __forceinline__ void mma_rs_n192(uint32_t (&d)[48], const uint4& a, uint32_t db) {
    asm volatile(
        "{\n.reg .b64 db;\nmov.b64 db, {%52, 16};\n"
        "wgmma.mma_async.sync.aligned.m64n192k16.f16.f16.f16 "
        "{%0,%1,%2,%3,%4,%5,%6,%7,%8,%9,%10,%11,%12,%13,%14,%15,"
        "%16,%17,%18,%19,%20,%21,%22,%23,%24,%25,%26,%27,%28,%29,%30,%31,"
        "%32,%33,%34,%35,%36,%37,%38,%39,%40,%41,%42,%43,%44,%45,%46,%47},"
        "{%48,%49,%50,%51}, db, 1, 1, 1, 0;\n}\n"
        : ACC8(d, 0), ACC8(d, 8), ACC8(d, 16), ACC8(d, 24), ACC8(d, 32), ACC8(d, 40)
        : "r"(a.x), "r"(a.y), "r"(a.z), "r"(a.w), "r"(db));
}

constexpr int P1_SPLIT = 5;
constexpr int P1_SLOT = LN_TILE / 6, P1_NST = 6;
constexpr int P1_W = 64 * C_DIM * 2;
constexpr int P1_X = 32 * C_DIM * 2;
constexpr int P1_OFF_W = LN_TILE;
constexpr int P1_OFF_X = P1_OFF_W + 2 * P1_W;
constexpr int P1_OFF_BAR = 227328;
constexpr int P1_OFF_TILE = P1_OFF_BAR + (2 * P1_NST + 4 + 4 + 4) * 8;
constexpr int P1_OFF_EX = P1_OFF_TILE + 64;
constexpr int P1_OFF_DW = P1_OFF_EX + 256 * 4;
constexpr int OFF_PRE = P1_OFF_DW + C_DIM * 2;
constexpr int SMEM_BYTES = OFF_PRE + C_DIM * 4 + 16;

__device__ __forceinline__ float rsqrt_fast(float x) {
    float r;
    asm("rsqrt.approx.ftz.f32 %0, %1;\n" : "=f"(r) : "f"(x));
    return r;
}
__device__ __forceinline__ float row_sum(const uint32_t (&c)[4]) {
    const uint32_t u = bf2_add(bf2_add(c[0], c[1]), bf2_add(c[2], c[3]));
    float s = bf_lo(u) + bf_hi(u);
#pragma unroll
    for (int o = 1; o < 8; o <<= 1) s += __shfl_xor_sync(0xffffffffu, s, o);
    return s;
}
__device__ __forceinline__ uint32_t pace(uint32_t bar, uint32_t off, uint32_t val, int zero) {
    asm volatile(
        "{\n.reg .pred p, q;\n.reg .b32 par;\n"
        "lop3.b32 par, %0, %2, %3, 0xea;\n"
        "setp.eq.u32 q, par, 0;\n"
        "mov.pred p, 0;\n"
        "@q mbarrier.test_wait.parity.shared::cta.b64 p, [%1], par;\n"
        "selp.u32 par, 1, 0, p;\n"
        "@q mbarrier.try_wait.parity.shared::cta.b64 p, [%1], par, 1000;\n"
        "@p or.b32 %0, %0, %2;\n"
        "}\n" : "+r"(val) : "r"(bar), "r"(zero), "r"(off));
    return val;
}
__device__ __forceinline__ void ln_row(uint32_t (&v)[6][4], const uint32_t (&d)[6][4], uint32_t bar, uint32_t off, int zero, uint32_t bar_read) {
    const float inv = 1.0f / C_DIM;
    uint32_t c[4];
#pragma unroll
    for (int i = 0; i < 6; i++)
#pragma unroll
        for (int k = 0; k < 4; k++) c[k] = bf2_fma(v[i][k], d[i][k], i ? c[k] : 0);
    const float m = row_sum(c) * inv;
    uint32_t nm = pack_bf16(-m, -m);
    const float e = m + bf_lo(nm);
    if (bar_read) mbar_arrive(bar_read + (nm & zero));
    nm = pace(bar, off, nm, zero);
#pragma unroll
    for (int i = 0; i < 6; i++) {
#pragma unroll
        for (int k = 0; k < 4; k++) {
            v[i][k] = bf2_fma(v[i][k], d[i][k], nm);
            c[k] = i ? bf2_fma(v[i][k], v[i][k], c[k]) : bf2_mul(v[i][k], v[i][k]);
        }
    }
    float r = KAPPA * rsqrt_fast(fmaxf(fmaf(-e, e, row_sum(c) * inv), 0.f) + 1e-5f);
    const float er = -e * r * 0x1p-112f;
    if (__any_sync(0xffffffffu, r < 0x1p-8f)) {
        const uint32_t p2 = __float_as_uint(r) & 0x7f800000u;
        r = __uint_as_float((__float_as_uint(r) & 0x007fffffu) | 0x3f800000u);
#pragma unroll
        for (int i = 0; i < 6; i++)
#pragma unroll
            for (int k = 0; k < 4; k++) v[i][k] = bf2_mul(v[i][k], p2 | p2 >> 16);
    }
    const uint32_t rs = pack_bf16(r * 0x1p-112f, r * 0x1p-112f), sh = pack_bf16(er, er);
#pragma unroll
    for (int i = 0; i < 6; i++)
#pragma unroll
        for (int k = 0; k < 4; k++) v[i][k] = bf2_to_h2(bf2_fma(v[i][k], rs, sh));
}

template <int R>
__device__ __forceinline__ uint32_t gelu2(uint32_t a, uint32_t sc2) {
    uint32_t y, t;
    if (R) asm("{\n.reg .b16 l, h;\n.reg .b32 f;\nmov.b32 {l, h}, %2;\nmov.b32 f, {h, h};\nmul.rn.f16x2 %0, %1, f;\n}\n" : "=r"(y) : "r"(a), "r"(sc2));
    else asm("{\n.reg .b16 l, h;\n.reg .b32 f;\nmov.b32 {l, h}, %2;\nmov.b32 f, {l, l};\nmul.rn.f16x2 %0, %1, f;\n}\n" : "=r"(y) : "r"(a), "r"(sc2));
    asm("tanh.approx.f16x2 %0, %1;\n" : "=r"(t) : "r"(h2_mul(y, h2_fma(y, y, GELU_C2))));
    return h2_fma(a, t, a);
}
constexpr uint32_t SPARE = 0x40074007u;
constexpr float UNCHOP = 1.0023f;

__device__ __forceinline__ uint32_t p1_exponents(float (&t)[2], uint32_t (&ex)[2], uint32_t saddr, int lane) {
#pragma unroll
    for (int r = 0; r < 2; r++) {
        t[r] += __shfl_xor_sync(0xffffffffu, t[r], 1);
        t[r] += __shfl_xor_sync(0xffffffffu, t[r], 2);
        ex[r] = min(max(((__float_as_uint(193.3f * t[r]) >> 23) + 127u) >> 1, 72u), 198u);
        asm volatile("st.shared.u32 [%0], %1;\n" ::"r"(saddr + r * 32), "r"(ex[r] << 23) : "memory");
    }
    return pack_f16(__uint_as_float(min(ex[0], 142u) << 23), __uint_as_float(min(ex[1], 142u) << 23));
}
template <int N>
__device__ __forceinline__ void p1_convert(uint32_t (&o)[N][4], uint32_t (&v)[N][4], const uint32_t (&ex)[2]) {
    if (__any_sync(0xffffffffu, max(ex[0], ex[1]) > 141u)) {
#pragma unroll
        for (int k = 0; k < 4 * N; k++) v[k >> 2][k & 3] = bf2_mul(v[k >> 2][k & 3], ex[k & 1] > 141u ? 0x1f801f80u : 0x3f803f80u);
    }
#pragma unroll
    for (int k = 0; k < 4 * N; k++) {
        const uint32_t u = bf2_mul(v[k >> 2][k & 3], ((ex[k & 1] > 141u ? 206u : 142u) - ex[k & 1]) * 0x00800080u);
        asm volatile("mad.lo.u32 %0, %1, 7, %2;\n" : "=r"(o[k >> 2][k & 3]) : "r"(u & 0x7fff7fffu), "r"(u));
    }
}
template <int N>
__device__ __forceinline__ void p1_squares(const uint32_t (&v)[N][4], float (&t)[2]) {
#pragma unroll
    for (int j = 0; j < N / 2; j++) {
        const int r = j & 1, b = (j >> 1) * 4;
        uint32_t c = bf2_mul(v[b][r], v[b][r]);
#pragma unroll
        for (int k = 1; k < 8; k++) c = bf2_fma(v[b + k / 2][r + (k & 1) * 2], v[b + k / 2][r + (k & 1) * 2], c);
        t[r] += bf_lo(c) + bf_hi(c);
    }
}
__device__ __forceinline__ void p1_epilogue(const uint32_t (&acc)[2][32], const uint32_t (&sc2)[2], float (&ssq)[4], uint8_t* hp, int zero) {
    uint32_t sq[2], h[16][4];
#pragma unroll
    for (int i2 = 0; i2 < 9; i2++) {
#pragma unroll
        for (int c = 2 * i2 - 2; c < 2 * i2; c++) {
            if (c >= 0 && (c & 3)) {
                uint32_t o[4];
#pragma unroll
                for (int u = 0; u < 4; u++) {
                    const uint32_t v = h[c & 12][u];
                    o[u] = bitsel(h[c][u], (c & 3) == 2 ? prmt(v, v, 0xa381) : prmt(v >> 3, v, (c & 3) == 1 ? 0x6240 : 0xf3d1), SPARE);
                }
                stg128_cs(hp + (c >> 3) * 2 * H_STEP + ((c >> 2) & 1) * H_HALF + ((c & 3) - 1) * 512, o[0], o[1], o[2], o[3]);
            }
        }
        if (i2 < 8) {
#pragma unroll
            for (int u = 0; u < 4; u++) {
                h[2 * i2][u] = gelu2<0>(acc[i2 >> 2][8 * (i2 & 3) + 2 * u], sc2[i2 >> 2]);
                h[2 * i2 + 1][u] = gelu2<1>(acc[i2 >> 2][8 * (i2 & 3) + 2 * u + 1], sc2[i2 >> 2]);
#pragma unroll
                for (int r = 0; r < 2; r++) {
                    const uint32_t v = h[2 * i2 + r][u];
                    sq[r] = ((i2 & 3) | u) ? h2_fma(v, v, sq[r]) : h2_mul(v, v);
                }
            }
            if ((i2 & 3) == 3) {
#pragma unroll
                for (int r = 0; r < 2; r++) ssq[(i2 >> 2) * 2 + r] += h_lo(sq[r]) + h_hi(sq[r]);
            }
            sched_break(zero);
        }
    }
}
template <int WG>
__device__ __forceinline__ void p1_mma(uint32_t (&acc)[2][32], const uint32_t (&a)[24][4], uint32_t sbase, uint32_t empty_remote, int i, int lane, bool pass) {
    const uint32_t bar_full = sbase + P1_OFF_BAR;
    const uint32_t db = (uint32_t)make_desc(sbase, 16, 1024), da = db + (P1_OFF_W + WG * P1_W) / 16;
    if (WG == 0) mbar_wait(bar_full, i & 1);
    bar_sync(1 + WG, 256);
    TRACE(WG, i, 1);
    wg_fence();
#pragma unroll
    for (int k = 0; k < 24; k++) {
        if (WG == 0 && k && k % 4 == 0) mbar_wait(bar_full + (k >> 2) * 8, i & 1);
        mma_rs_n128(acc[0], a[k], db + (k >> 2) * 1024 + (k & 3) * 2, k != 0);
        mma_ss_n128(acc[1], da + k * 128, db + (k >> 2) * 1024 + (k & 3) * 2, k != 0);
        if (k == 23 && pass) bar_arrive(2 - WG, 256);
        if (k == 23 || (WG == 1 && k % 4 == 3)) wg_commit();
        if (WG == 1 && k % 4 == 3 && k > 3) {
            wg_wait<1>();
            if (lane < 2) mbar_arrive_cluster(empty_remote + ((k >> 2) - 1) * 8);
        }
    }
    TRACE(WG, i, 2);
    wg_wait<0>();
    if (WG == 1 && lane < 2) mbar_arrive_cluster(empty_remote + 5 * 8);
}
__device__ __forceinline__ bool p1_consumer(const uint32_t (&a)[24][4], const uint32_t (&sc2)[2], uint32_t sbase, int WG, int w, int lane, int zero) {
    const uint32_t bar_full = sbase + P1_OFF_BAR, bar_empty = bar_full + P1_NST * 8;
    const uint32_t empty_remote = mapa(bar_empty, lane & 1);
    const uint32_t bar_pace = bar_empty + P1_NST * 8 + 32 + w * 8;
    const int g = lane >> 2, q = lane & 3, half = WG ^ ((blockIdx.x / GRP_CTAS) & 1), cb = (blockIdx.x % GRP_CTAS) * 4 + half * 2;
    uint32_t acc[2][32];
    float ssq[4] = {0.f, 0.f, 0.f, 0.f};
    TSTAMP(0, 1);

    uint8_t* hp = reinterpret_cast<uint8_t*>(g_h) + ((cb * 2 + (w >> 1)) * H_STEP + (w & 1) * 1536) + g * 64 + (q ^ (g >> 1)) * 16;
    int i = 0;
    uint32_t more = 3, both;
#pragma unroll 1
    for (;; i++) {
        TRACE(WG, i, 0);
        both = more & 2;
        if (WG == 0) p1_mma<0>(acc, a, sbase, empty_remote, i, lane, both);
        else p1_mma<1>(acc, a, sbase, empty_remote, i, lane, true);
        TRACE(WG, i, 4);
        int step;
        asm volatile("ld.shared.v2.u32 {%0, %1}, [%2];\n" : "=r"(step), "=r"(more) : "r"(sbase + P1_OFF_TILE + (i & 3) * 16) : "memory");
        hp += step;
        if (!(more >> WG & 1) && lane == 0) asm volatile("red.relaxed.gpu.global.add.u32 [%0], 1;\n" ::"l"(g_prog[CNT_LAST]) : "memory");
        p1_epilogue(acc, sc2, ssq, hp, zero);
        if (lane == 0) mbar_arrive(bar_pace);
        if (more & 4) {
            asm volatile("fence.proxy.async.global;\n" ::: "memory");
            bar_arrive(8, 288);
            bar_arrive(9, 288);
        }
        if (!(more >> WG & 1)) break;
    }
    TSTAMP(0, 21);
    if (WG == 0 && both) bar_sync(1, 256);
#pragma unroll
    for (int r = 0; r < 4; r++) {
        ssq[r] += __shfl_xor_sync(0xffffffffu, ssq[r], 1);
        ssq[r] += __shfl_xor_sync(0xffffffffu, ssq[r], 2);
    }
    const float t = q == 0 ? ssq[0] : q == 1 ? ssq[1] : q == 2 ? ssq[2] : ssq[3];
    atomicAdd(&g_sq[cb * 64 + (q >> 1) * 64 + w * 16 + (q & 1) * 8 + g], (1ull << 56) + __float2ull_rn(fminf(t, 0x1p19f) * 0x1p32f));
    asm volatile("fence.proxy.async.global;\n" ::: "memory");
    bar_arrive(3, 288);
    asm volatile("barrier.cluster.arrive.relaxed.aligned;\n" ::: "memory");
    return WG ? more & 1 : both;
}

__device__ __forceinline__ void p2_init(uint32_t sbase);
template <int ROLE>
__device__ __forceinline__ bool pass1(const CUtensorMap& wmap, const __nv_bfloat16* __restrict__ x, const __nv_bfloat16* __restrict__ dw,
                                      const __nv_bfloat16* __restrict__ w2, const __nv_bfloat16* __restrict__ grn_b, uint32_t sbase,
                                      int warp, int lane, int zero) {
    const uint32_t bar_full = sbase + P1_OFF_BAR, bar_empty = bar_full + P1_NST * 8, bar_w = bar_empty + P1_NST * 8;
    const uint32_t rank = cluster_rank();
    const int cig = blockIdx.x % GRP_CTAS;
    uint8_t* const ring = reinterpret_cast<uint8_t*>(g_ln);

    TSTAMP(0, 0);
    TRACEW(110 + warp, 0);
    const uint32_t bar_pace = bar_w + 32, bar_xfull = bar_pace + 32, bar_xempty = bar_xfull + 8, bar_done = bar_xfull + 16;
    const int ln0 = blockIdx.x >> 2, first = blockIdx.x / GRP_CTAS;
    const uint8_t* xsrc = reinterpret_cast<const uint8_t*>(x) + (size_t)blockIdx.x * P1_X;

    if (ROLE == 2) {
        reg_dec<32>();
        asm volatile("barrier.cluster.arrive.relaxed.aligned;\n" ::: "memory");
        asm volatile("barrier.cluster.wait.aligned;\n" ::: "memory");
        if (warp == 12) {
            int prev = 0, t = first;
            const uint32_t rbase = mapa(sbase, lane & 1);
#pragma unroll 1
            for (int i = 0; t < NT128; i++) {
                const int round = t / LN_RING, slot = t - round * LN_RING;
                const uint8_t* src = ring + slot * LN_TILE + rank * (P1_SLOT / 2);
                int next = 0;
                if (rank == 0 && lane == 0) {
                    next = t < NT128 - P1_SPLIT ? NGRP + atomicAdd(&g_flag[LN_RING + (cig >> 1)][0][0], 1u) : 2 * NT128;
                    if (next >= NT128 - P1_SPLIT && next < 2 * NT128) next = NT128 - P1_SPLIT + atomicAdd(&g_flag[LN_RING + 3 + (cig >> 1)][first & 1][0], 1u);
                }
                flag_wait<true>(&g_flag[slot][0][0], 4 * round + 4);
                TRACEW(i, 2);
                asm volatile("fence.proxy.async.global;\n" ::: "memory");
                next = __shfl_sync(0xffffffffu, next, 0);
#pragma unroll 1
                for (int h = 0; h < P1_NST; h++) {
                    mbar_wait(bar_empty + h * 8, i & 1);
                    if (h == 0) TRACEW(i, 4);
                    if (h == 5) TRACEW(i, 5);
                    if (elect_one()) {
                        mbar_expect_tx(bar_full + h * 8, h ? P1_SLOT : P1_SLOT + 16);
                        bulk_g2s_mc(sbase + h * P1_SLOT + rank * (P1_SLOT / 2), src + h * P1_SLOT, P1_SLOT / 2, bar_full + h * 8, (uint16_t)3);
                    }
                    __syncwarp();
                    if (h == 0 && rank == 0 && lane < 2)
                        asm volatile("st.async.shared::cluster.mbarrier::complete_tx::bytes.v4.u32 [%0], {%1, %2, %3, %3}, [%4];\n"
                                     ::"r"(rbase + P1_OFF_TILE + (i & 3) * 16), "r"((t - prev) * (2 * H_TILE)), "r"((next < NT128 - P1_SPLIT ? 3 : next < NT128) + (t < NT_EARLY && next >= NT_EARLY ? 4 : 0)), "r"(next),
                                       "r"(rbase + P1_OFF_BAR) : "memory");
                }
                prev = t;
                t = next;
                if (rank != 0) {
                    mbar_wait(bar_full, i & 1);
                    asm volatile("ld.shared.u32 %0, [%1];\n" : "=r"(t) : "r"(sbase + P1_OFF_TILE + (i & 3) * 16 + 8) : "memory");
                }
            }
        } else if (warp == 13) {
            int ph = 0;
            unsigned target = 0;
#pragma unroll 1
            for (int i = ln0 + LN_STEP; i < NT128; i += LN_STEP, ph ^= 1) {
                target += ph * (GRP_CTAS / 2);
                xsrc += (size_t)NUM_CTAS * P1_X;
                mbar_wait(bar_xempty, ph);
                if (elect_one()) {
                    mbar_expect_tx(bar_xfull, P1_X);
                    bulk_g2s(sbase + P1_OFF_X, xsrc, P1_X, bar_xfull);
                }
                __syncwarp();
                const uint32_t off = flag_wait<false>(&g_flag[ln0 + (ph ^ 1) * LN_STEP][1][0], target);
                mbar_wait(bar_done, ph);
                if (elect_one()) {
                    asm volatile("st.shared.u32 [%0], %1;\n" ::"r"(bar_done + 8), "r"(off) : "memory");
                    mbar_arrive(bar_xfull);
                }
                __syncwarp();
            }
        } else if (warp == 15) {
            int t = first;
            if (rank == 1 && lane == 0) mbar_arrive(bar_empty);
#pragma unroll 1
            for (int i = 0; rank == 1 && t < NT128; i++) {
#pragma unroll 1
                for (int h = 0; h < P1_NST; h++) mbar_wait(bar_full + h * 8, i & 1);
                if (lane == 0) asm volatile("red.relaxed.gpu.global.add.u32 [%0], 1;\n" ::"l"(&g_flag[t % LN_RING][1][0]) : "memory");
                asm volatile("ld.shared.u32 %0, [%1];\n" : "=r"(t) : "r"(sbase + P1_OFF_TILE + (i & 3) * 16 + 8) : "memory");
                if (lane == 0) mbar_arrive(bar_empty);
                TRACEW(i, 3);
            }
            if (rank == 0) {
                mbar_wait(bar_full, 0);
                TRACEW(110 + warp, 3);
                mbar_wait(bar_full, 1);
                float* sums = g_sums;
                unsigned* flag = reinterpret_cast<unsigned*>(sums + C_DIM);
                if (blockIdx.x == 0) reinterpret_cast<uint2*>(g_half)[lane] = make_uint2(0, 0);
                if (blockIdx.x == 2 && lane < NUM_CNT) g_prog[lane][0] = 0;
                if (blockIdx.x < 96) g_redo[blockIdx.x * 16 + lane] = 0.f;
                float gs = 0.f;
#pragma unroll 1
                for (int pass = 0; pass < 2; pass++) {
                    float mx = 0.f;
#pragma unroll 1
                    for (int it = first; it < 96; it += NGRP) {
                        const int nb = it % 12, k0 = (cig * 4 + it / 12) * 64 + (lane >> 2);
                        const uint32_t sc = mapa(sbase + P1_OFF_EX + (k0 & 255) * 4, it / 48);
                        uint32_t* dst = reinterpret_cast<uint32_t*>(g_w2img[0]) + (k0 >> 4) * 3072 + nb * 256 + lane;
                        float bs[8] = {};
#pragma unroll 1
                        for (int c = 0; c < 8; c++) {
                            const uint4 u = __ldg(reinterpret_cast<const uint4*>(w2 + (size_t)(k0 + c * 8) * C_DIM + nb * 32) + (lane & 3));
                            const float b = __bfloat162float(grn_b[k0 + c * 8]);
                            float t;
                            asm volatile("ld.shared::cluster.f32 %0, [%1];\n" : "=f"(t) : "r"(sc + c * 32) : "memory");
                            if (nb == 0) g_scale[k0 + c * 8] = t;
#pragma unroll
                            for (int j = 0; j < 4; j++) {
                                const uint32_t v = j == 0 ? u.x : j == 1 ? u.y : j == 2 ? u.z : u.w;
                                mx = fmaxf(mx, fmaxf(fabsf(bf_lo(v)), fabsf(bf_hi(v))) * t);
                                if (pass) {
                                    bs[2 * j] = fmaf(b, bf_lo(v), bs[2 * j]);
                                    bs[2 * j + 1] = fmaf(b, bf_hi(v), bs[2 * j + 1]);
                                    uint32_t h = pack_f16(bf_lo(v) * t * gs, bf_hi(v) * t * gs);
                                    asm volatile("movmatrix.sync.aligned.m8n8.trans.b16 %0, %0;\n" : "+r"(h));
                                    dst[(c >> 1) * 3072 + (c & 1) * 32 + j * 64] = h;
                                }
                            }
                        }
                        if (pass) {
#pragma unroll
                            for (int j = 0; j < 8; j++) {
#pragma unroll
                                for (int o = 4; o < 32; o <<= 1) bs[j] += __shfl_xor_sync(0xffffffffu, bs[j], o);
                                if (lane >> 2 == j) atomicAdd(&sums[nb * 32 + (j >> 1) * 8 + (lane & 3) * 2 + (j & 1)], bs[j]);
                            }
                        }
                    }
                    if (!pass) {
                        const uint32_t m = __reduce_max_sync(0xffffffffu, __float_as_uint(mx));
                        __threadfence();
                        __syncwarp();
                        if (lane == 0) {
                            atomicMax(flag, m);
                            asm volatile("red.release.gpu.global.add.u32 [%0], 1;\n" ::"l"(flag + 32) : "memory");
                        }
                        flag_wait<true>(flag + 32, NUM_CTAS / 2);
                        gs = w2_scale(__ldcg(flag));
                    }
                }
                asm volatile("fence.proxy.async.global;\nfence.acq_rel.gpu;\n" ::: "memory");
                __syncwarp();
                if (lane == 0) asm volatile("red.relaxed.gpu.global.add.u32 [%0], 1;\n" ::"l"(g_prog[CNT_IMG0]) : "memory");
            }
        } else if (warp == 14) {
            int ph = 0;
#pragma unroll 1
            for (int i = ln0; i < NT128; i += LN_STEP, ph ^= 1) {
                mbar_wait(bar_done, ph);
                TRACEW(i / LN_STEP, 0);
                asm volatile("fence.proxy.async.global;\n" ::: "memory");
                if (elect_one()) asm volatile("red.release.gpu.global.add.u32 [%0], 1;\n" ::"l"(&g_flag[ln0 + ph * LN_STEP][0][0]) : "memory");
                __syncwarp();
                TRACEW(i / LN_STEP, 1);
            }
            if (lane == 0) p2_init(sbase);
#pragma unroll 1
            for (int i = CNT_EARLY; i >= CNT_H; i--) {
                bar_sync(i == CNT_EARLY ? 8 : 3, 288);
                asm volatile("fence.proxy.async.global;\n" ::: "memory");
                if (lane == 0) asm volatile("red.release.gpu.global.add.u32 [%0], 1;\n" ::"l"(&g_prog[i][0]) : "memory");
                __syncwarp();
            }
        }
        __syncwarp();
        asm volatile("barrier.cluster.arrive.relaxed.aligned;\n" ::: "memory");
        return false;
    } else if (ROLE == 1) {
        reg_dec<96>();
        asm volatile("barrier.cluster.arrive.relaxed.aligned;\n" ::: "memory");
        {
            const int l8 = lane & 7, row = (warp - 8) * 4 + (lane >> 3), px = (blockIdx.x & 3) * 32 + row;
            uint32_t d[6][4];
            const int n = (px & 64) + perm32(2 * row + ((px >> 5) & 1));
            uint8_t* const dst0 = ring + ln0 * LN_TILE + n * 128 + ((l8 ^ (n & 7)) << 4);
            const uint32_t src = sbase + P1_OFF_X + ((warp - 8) * 8 + (lane >> 3)) * (C_DIM * 2) + l8 * 16;
            int ph = 0;
#pragma unroll 1
            for (int i = ln0; i < NT128; i += LN_STEP, ph ^= 1) {
                TRACE(2, i / LN_STEP, 0);
                uint32_t off = 1;
#pragma unroll 1
                for (int ps = i == ln0 ? -2 : 0; ps < 2; ps += ps < 0 ? 2 : 1) {
                    if (ps == 0) {
                        if (i == ln0) asm volatile("barrier.cluster.wait.aligned;\n" ::: "memory");
                        mbar_wait(bar_xfull, ph);
                        asm volatile("ld.shared.u32 %0, [%1];\n" : "=r"(off) : "r"(bar_done + 8) : "memory");
                    }
                    if (ps == 0) TRACE(2, i / LN_STEP, 1);
                    if (i == ln0) {
#pragma unroll
                        for (int j = 0; j < 6; j++)
                            asm volatile("ld.shared.v4.u32 {%0,%1,%2,%3}, [%4];\n"
                                         : "=r"(d[j][0]), "=r"(d[j][1]), "=r"(d[j][2]), "=r"(d[j][3]) : "r"(sbase + P1_OFF_DW + j * 128 + l8 * 16) : "memory");
                    }
                    uint32_t v[6][4];
#pragma unroll
                    for (int j = 0; j < 6; j++)
                        asm volatile("ld.shared.v4.u32 {%0,%1,%2,%3}, [%4];\n"
                                     : "=r"(v[j][0]), "=r"(v[j][1]), "=r"(v[j][2]), "=r"(v[j][3]) : "r"(src + (ps & 1) * (4 * C_DIM * 2) + j * 128) : "memory");
                    ln_row(v, d, bar_pace + (warp - 8) * 8, off, zero, ps == 1 && lane == 0 ? bar_xempty : 0);
                    uint8_t* dst = dst0 + ph * (LN_STEP * LN_TILE) + (ps & 1) * 4096;
#pragma unroll
                    for (int j = 0; j < 6; j++) *reinterpret_cast<uint4*>(dst + j * 16384) = make_uint4(v[j][0], v[j][1], v[j][2], v[j][3]);
                    TRACE(2, i / LN_STEP, 3 + (ps & 1));
                }
                asm volatile("fence.proxy.async.global;\nfence.acq_rel.cta;\n" ::: "memory");
                __syncwarp();
                if (lane == 0) mbar_arrive(bar_done);
                TRACE(2, i / LN_STEP, 5);
                TRACE(2, i / LN_STEP, 2);
            }
        }
        __syncwarp();
        asm volatile("barrier.cluster.arrive.relaxed.aligned;\n" ::: "memory");
        return false;
    } else {
        const int wg = warp >> 2, w = warp & 3;
        auto load_w = [&](int i0, int i1) {
#pragma unroll 1
            for (int i = i0; i < i1; i++) {
                if (!(i & 1)) mbar_expect_tx(bar_w + (i >> 1) * 8, P1_W);
                tma2(sbase + (i & 2) * P1_W + (i >> 2) * P1_W + (i & 1) * (P1_W / 2), &wmap, cig * 256 + ((i >> 1) ^ (first & 1) * 2) * 64, (i & 1) * 192, bar_w + (i >> 1) * 8);
            }
        };
        if (warp == 4 && elect_one()) {
            mbar_init(bar_xfull, 2);
#pragma unroll
            for (int i = 0; i < 4; i++) mbar_init(bar_w + i * 8, 1);
            asm volatile("fence.mbarrier_init.release.cluster;\n" ::: "memory");
            mbar_expect_tx(bar_xfull, P1_X + C_DIM * 2);
            bulk_g2s(sbase + P1_OFF_X, xsrc, P1_X, bar_xfull);
            bulk_g2s(sbase + P1_OFF_DW, dw, C_DIM * 2, bar_xfull);
            load_w(0, 4);
            asm volatile("st.shared.u32 [%0], 1;\n" ::"r"(bar_done + 8) : "memory");
            mbar_arrive(bar_xfull);
        }
        if (warp == 5 && elect_one()) {
#pragma unroll
            for (int i = 0; i < P1_NST; i++) {
                mbar_init(bar_full + i * 8, 1);
                mbar_init(bar_empty + i * 8, i ? 8 : 8 + rank);
                if (i < 4) mbar_init(bar_pace + i * 8, 1);
            }
            mbar_init(bar_xempty, 4);
            mbar_init(bar_done, 4);
            asm volatile("fence.mbarrier_init.release.cluster;\n" ::: "memory");
        }
        __syncwarp();
        asm volatile("barrier.cluster.arrive.relaxed.aligned;\n" ::: "memory");
        reg_inc<192>();
        TRACEW(110 + warp, 1);
        uint32_t a[24][4];
        const uint32_t src = sbase + wg * P1_W + ((lane >> 4) * 8 + (lane & 7)) * 128 + (((2 * w + ((lane >> 3) & 1)) ^ (lane & 7)) << 4);
        const uint32_t s_ex = sbase + P1_OFF_EX + ((wg ^ (first & 1)) * 128 + w * 16 + (lane >> 2)) * 4;
        uint32_t sc2[2], ex[2];
        if (wg == 1) bar_arrive(1, 256);
#pragma unroll 1
        for (int it = 0; it < 2; it++) {
          if (it != wg) asm volatile("barrier.cluster.wait.aligned;\n" ::: "memory");
          if (it < wg) {
              mbar_wait(bar_xfull, 0);
              if (w == 0 && elect_one()) load_w(4, 8);
              __syncwarp();
          }
          if (it || wg == 0) {
            float t[2] = {0.f, 0.f};
            if (it) {
                TRACEW(110 + warp, 2);
                mbar_wait(bar_w + wg * 16, 0);
            }
            TRACEW(110 + warp, 5);
#pragma unroll
            for (int k = 0; k < 24; k++) ldsm4t(a[k], src + k * 2048);
            TRACEW(110 + warp, 6);
            p1_squares(a, t);
            sc2[0] = p1_exponents(t, ex, s_ex, lane);
            if (it && lane < 6) mbar_arrive_cluster(mapa(bar_empty, lane & 1) + (wg * 3 + (lane >> 1)) * 8 + (sc2[0] & zero));
            p1_convert<24>(a, a, ex);
          }
          if (it || wg == 1) {
            float t[2] = {0.f, 0.f};
            TRACEW(100 + warp, 0);
            if (it) mbar_wait(bar_w + wg * 16 + 8, 0);
            TRACEW(100 + warp, 1);
            uint32_t v[8][4], o[8][4];
#pragma unroll 1
            for (int j = 0; j <= 2 * it; j++) {
#pragma unroll
                for (int k = 0; k < 8; k++) ldsm4t(v[k], src + P1_OFF_W + (8 * j + k) * 2048);
                p1_squares(v, t);
            }
            sc2[1] = p1_exponents(t, ex, s_ex + 256, lane);
#pragma unroll 1
            for (int j = 2 * it; j >= 0; j--) {
                p1_convert<8>(o, v, ex);
#pragma unroll
                for (int k = 0; k < 8; k++) {
                    if (j) ldsm4t(v[k], src + P1_OFF_W + (8 * j - 8 + k) * 2048);
                    if (it) asm volatile("stmatrix.sync.aligned.m8n8.x4.trans.shared.b16 [%0], {%1,%2,%3,%4};\n"
                                         ::"r"(src + P1_OFF_W + (8 * j + k) * 2048), "r"(o[k][0]), "r"(o[k][1]), "r"(o[k][2]), "r"(o[k][3]) : "memory");
                }
            }
          }
        }
        asm volatile("fence.proxy.async.shared::cta;\n" ::: "memory");
        TRACEW(110 + warp, 7);
        bar_sync(6 + wg, 128);
        const bool early = p1_consumer(a, sc2, sbase, wg, w, lane, zero);
        TSTAMP(0, 30);
        return early;
    }
}

constexpr int P2_B = 24576, P2_NB = 4;
constexpr int P2_A = 3072, P2_NA = 8;
constexpr int P2_XROW = C_DIM * 2;
constexpr int P2_OFF_A = P2_B * P2_NB;
constexpr int P2_OFF_X = P2_OFF_A + 3 * P2_NA * P2_A + 128;
constexpr int P2_LHALF = 2 * P2_NA * P2_A + 64;
constexpr int P2_XHALF = 32 * P2_XROW + 64;
constexpr int P2_OFF_GRN = P2_OFF_X + 64 * P2_XROW + 128;
constexpr int P2_OFF_BIAS = P2_OFF_GRN + HID * 2;
constexpr int P2_OFF_RED = P2_OFF_BIAS + C_DIM * 4;
constexpr int P2_OFF_BAR = P2_OFF_RED + 192;
constexpr int P2_SMEM = P2_OFF_BAR + (2 * P2_NB + 6 * P2_NA + 7) * 8;
constexpr int P2_S1 = 16, P2_S2 = 32;
constexpr int P2_NCL = NUM_CTAS / 2, P2_ITEMS = NT128 / P2_NCL, P2_SHARED = NT128 - P2_ITEMS * P2_NCL;
constexpr int P2_NPOS = 6 * 48 + P2_S1;
constexpr int P2_RAW = 16;
constexpr int P2_XC = 8 * P2_XROW;
constexpr int P2_T0 = 5;
constexpr int P2_TL = 8;
constexpr int P2_XP0 = 30;
constexpr int P2_XPN = 13;
constexpr int P2_XPD = 3;
constexpr int P2_AH = 2;
__device__ __forceinline__ int p2_start(int n) { return n < 0 ? 0 : n / 3 * 48 + (n % 3 == 1 ? P2_S1 : n % 3 * (P2_S2 / 2)); }
__device__ __forceinline__ int p2_tile(int cl, int n) {
    return n == 0 ? NT_EARLY - 1 - cl : n < 0 ? NT_EARLY + (cl >> 1) : cl + P2_NCL * (n - 1);
}

constexpr int P2_EB = 2;
constexpr int P2_EX = 1;
__device__ __forceinline__ void p2_epilogue(uint32_t (&acc0)[48], uint32_t (&acc1)[48], uint32_t up, uint32_t sx, uint32_t sb, int zero) {
    uint32_t v[12][3][4];
    auto load = [&](int t, int j) {
        if (t >= 12) return;
        uint32_t (&w)[4] = v[t][j];
        asm volatile("ld.shared.v4.u32 {%0,%1,%2,%3}, [%4];\n" : "=r"(w[0]), "=r"(w[1]), "=r"(w[2]), "=r"(w[3])
                     : "r"((j ? sx + (j - 1) * 4 * P2_XROW : sb) + t * 64) : "memory");
    };
    auto store = [&](int t, int r) {
        const uint32_t* w = (t < 6 ? acc0 : acc1) + 8 * (t % 6) + 4 * r;
        asm volatile("st.shared.v4.u32 [%4], {%0,%1,%2,%3};\n" ::"r"(w[0]), "r"(w[1]), "r"(w[2]), "r"(w[3]), "r"(sx + t * 64 + r * 4 * P2_XROW) : "memory");
    };
#pragma unroll
    for (int t = 0; t < P2_EB; t++) load(t, 0);
#pragma unroll
    for (int t = 0; t < 2 * P2_EX; t++) load(t >> 1, 1 + (t & 1));
#pragma unroll
    for (int t = 0; t < 12; t++) {
        load(t + P2_EX, 1);
        load(t + P2_EX, 2);
        load(t + P2_EB, 0);
        uint32_t* acc = (t < 6 ? acc0 : acc1) + 8 * (t % 6);
        uint32_t y[8];
#pragma unroll
        for (int e = 0; e < 8; e++) {
            y[e] = h2_add(acc[e], v[t][0][e >> 1]);
            y[e] = pack_bf16(h_lo(y[e]), h_hi(y[e]));
        }
#pragma unroll
        for (int e = 0; e < 8; e++) acc[(e & 1) * 4 + (e >> 1)] = bf2_fma(y[e], up, v[t][1 + (e & 1)][e >> 1]);
        store(t, 0);
        store(t, 1);
        sched_break(zero);
    }
}

__device__ __forceinline__ void p2_unpack(uint32_t (&u)[4], uint32_t o1, uint32_t o2, uint32_t o3) {
    u[2] = o1 & ~SPARE;
    u[1] = o2 & ~SPARE;
    u[3] = o3 & ~SPARE;
    const uint32_t t = bitsel(prmt(o1, o2, 0x6341), prmt(o1, o3, 0x6240) << 3, 0x38383838u);
    u[0] = bitsel(t, prmt(o2, o3, 0x7351) << 1, 0x80808080u) & ~SPARE;
}

__device__ __forceinline__ void p2_redo_sums(int warp, int lane) {
    flag_wait<true>(g_prog[CNT_H], NUM_CTAS);
#pragma unroll 1
    for (int s = warp; s < 96; s += 12) {
        float t[2] = {0.f, 0.f};
#pragma unroll 1
        for (int tile = blockIdx.x; tile < 2 * NT128; tile += NUM_CTAS) {
            const uint32_t* p = reinterpret_cast<const uint32_t*>(reinterpret_cast<const uint8_t*>(g_h) + (size_t)(tile >> 1) * (2 * H_TILE) +
                                                                  (s >> 1) * H_STEP + (tile & 1) * H_HALF + (s & 1) * 1536) + lane * 4;
#pragma unroll
            for (int j = 0; j < 4; j++) {
                uint32_t u[4];
                p2_unpack(u, __ldcg(p + j), __ldcg(p + j + 128), __ldcg(p + j + 256));
#pragma unroll
                for (int c = 0; c < 4; c++) t[c >> 1] += h_lo(u[c]) * h_lo(u[c]) + h_hi(u[c]) * h_hi(u[c]);
            }
        }
#pragma unroll
        for (int r = 0; r < 2; r++) {
            const int ch = s * 16 + r * 8 + (lane >> 2);
            atomicAdd(&g_redo[ch], t[r] * (UNCHOP * UNCHOP));
        }
    }
    __threadfence();
    __syncwarp();
    if (lane == 0) asm volatile("red.release.gpu.global.add.u32 [%0], 1;\n" ::"l"(g_prog[CNT_REDO]) : "memory");
    flag_wait<true>(g_prog[CNT_REDO], 12 * NUM_CTAS);
}

static_assert(P2_OFF_GRN >= P1_OFF_X + P1_X && P1_OFF_BAR >= P2_SMEM, "barriers and tables keep their memory");
__device__ __forceinline__ void p2_init(uint32_t sbase) {
    const uint32_t bar = sbase + P2_OFF_BAR;
#pragma unroll 1
    for (int i = 0; i < 2 * P2_NB + 6 * P2_NA + 6; i++) {
        const int j = i - 2 * P2_NB;
        mbar_init(bar + i * 8, j < -P2_NB ? 1 : j < 0 ? 24 : j < 3 * P2_NA ? 1 : j >= 6 * P2_NA && j < 6 * P2_NA + 3 ? 2 : 4);
    }
    asm volatile("st.shared.v2.u32 [%0], {0, 0};\n" ::"r"(bar + (2 * P2_NB + 6 * P2_NA + 6) * 8) : "memory");
    asm volatile("fence.mbarrier_init.release.cluster;\nfence.acq_rel.cta;\n" ::: "memory");
}
template <int ROLE>
__device__ __forceinline__ void pass2(const __nv_bfloat16* __restrict__ x, const __nv_bfloat16* __restrict__ grn_g, __nv_bfloat16* __restrict__ out,
                                      uint8_t* smem, uint32_t sbase, bool early, int zero) {
    const uint32_t bar_bfull = sbase + P2_OFF_BAR, bar_bempty = bar_bfull + P2_NB * 8;
    const uint32_t bar_afull = bar_bempty + P2_NB * 8, bar_aempty = bar_afull + 3 * P2_NA * 8;
    const uint32_t bar_xfull = bar_aempty + 3 * P2_NA * 8, bar_oready = bar_xfull + 24, s_pos = bar_oready + 24;
    int tid;
    asm volatile("mov.u32 %0, %%tid.x;\n" : "=r"(tid));
    const int warp = __shfl_sync(0xffffffffu, tid >> 5, 0), lane = tid & 31;
    const uint32_t rank = cluster_rank();
    const int cl = blockIdx.x >> 1, pair = cl >> 1;
    const int half = pair < P2_SHARED, fin = half && (cl & 1);
    const int k0 = (pair + 3 * (cl & 1)) % 6 * 8;
    auto wait_pos = [&](int target) {
        int v;
        while (true) {
            asm volatile("ld.volatile.shared.u32 %0, [%1];\n" : "=r"(v) : "r"(s_pos) : "memory");
            if (v >= target) break;
            SAFE_BREAK;
            __nanosleep(100);
        }
    };

    TSTAMP(1, 0);
    if (ROLE == 2) {
        if (warp != 14) flag_wait<true>(g_prog[CNT_IMG0], P2_NCL);
        if (warp == 15) {
            float* pre = reinterpret_cast<float*>(smem + OFF_PRE);
            const float gs = w2_scale(__float_as_uint(__ldcg(&g_sums[C_DIM])));
            float mb = 0.f;
#pragma unroll 1
            for (int i = lane; i < C_DIM; i += 32) {
                pre[i] = __ldcg(&g_sums[i]) * gs;
                mb = fmaxf(mb, fabsf(pre[i]));
            }
            pre[C_DIM] = gs;
            pre[C_DIM + 1] = __uint_as_float(__reduce_max_sync(0xffffffffu, __float_as_uint(mb)));
            bar_sync(9, 288);
            flag_wait<false>(g_prog[CNT_LAST], NUM_CTAS * 8);
            bar_arrive(5, 416);
        }
        asm volatile("barrier.cluster.wait.aligned;\nfence.proxy.async;\n" ::: "memory");
        if (warp == 12) {
            const uint8_t* wsrc = reinterpret_cast<const uint8_t*>(g_w2img) + rank * (P2_B / 2);
            int kb = k0;
#pragma unroll 1
            for (int p = 0; p < P2_NPOS; p++) {
                const int st = p & 3;
                if (p == P2_RAW) {
                    flag_wait<true>(g_prog[CNT_IMG1], NUM_CTAS);
                    asm volatile("fence.proxy.async.global;\n" ::: "memory");
                    wsrc += sizeof(g_w2img[0]);
                }
                const int idle = (p < P2_S1 || p >= 6 * 48) + (p < P2_S2 ? !half || p >= 24 : p >= 5 * 48 + P2_S2);
                mbar_wait(bar_bempty + st * 8, (~p >> 2) & 1);
                TR2(3, p, 0);
                if (elect_one()) {
                    mbar_expect_tx(bar_bfull + st * 8, P2_B);
                    bulk_g2s_mc(sbase + st * P2_B + rank * (P2_B / 2), wsrc + kb * P2_B, P2_B / 2, bar_bfull + st * 8, (uint16_t)3);
                    asm volatile("st.volatile.shared.u32 [%0], %1;\n" ::"r"(s_pos), "r"(p) : "memory");
                    if (rank == 0) asm volatile("red.relaxed.gpu.global.add.u32 [%0], 1;\n" ::"l"(g_prog[CNT_POS]) : "memory");
                    if (idle) asm volatile("mbarrier.arrive.shared::cta.b64 _, [%0], %1;\n" ::"r"(bar_bempty + st * 8), "r"(8 * idle) : "memory");
                }
                __syncwarp();
                if (++kb == 48) kb = 0;
            }
            mbar_wait(bar_bempty, 1);
            if (lane == 0) mbar_arrive(bar_bfull);
        } else if (warp == 13) {
            const int w = lane % 3;
            const uint32_t dst0 = sbase + P2_OFF_A + w * P2_NA * P2_A;
            const uint32_t bf = bar_afull + w * P2_NA * 8, be = bar_aempty + w * P2_NA * 8;
            int n = (w == 2 && half ? -1 : w) - 3, left = 0, u = 0, c = 0;
            const uint8_t* src = nullptr;
            bool act = lane < 3;
            auto next = [&]() {
                n += 3;
                left = n >= P2_ITEMS ? -1 : n < 0 ? 24 : 48;
                u = (k0 + p2_start(n)) % 48;
                src = reinterpret_cast<const uint8_t*>(g_h) + (size_t)p2_tile(cl, n) * (2 * H_TILE) + rank * H_HALF + u * H_STEP;
            };
            next();
            flag_wait<true>(g_prog[CNT_EARLY], NUM_CTAS);
#pragma unroll 1
            for (int i = 3; i > 0; i--) {
                const int wi = i % 3;
                if (wi == 2) flag_wait<true>(g_prog[CNT_H], NUM_CTAS);
                asm volatile("fence.proxy.async.global;\n" ::: "memory");
                if (w == wi && lane < 24) {
                    mbar_expect_tx(bf + lane / 3 * 8, P2_A);
                    bulk_g2s(dst0 + lane / 3 * P2_A, src + lane / 3 * H_STEP, P2_A, bf + lane / 3 * 8);
                }
                __syncwarp();
            }
            c = 8;
            left -= 8;
            u += 8;
            src += 8 * H_STEP;
            if (u == 48) { u = 0; src -= 48 * H_STEP; }
            while (__any_sync(0xffffffffu, act)) {
                if (left == 0) next();
                const bool ok = act && mbar_test(be + ((c - 1) & 7) * 8, (~c >> 3) & 1);
                if (ok) {
                    const int st = c & 7;
                    if (left > 0) {
                        mbar_expect_tx(bf + st * 8, P2_A);
                        bulk_g2s(dst0 + st * P2_A, src, P2_A, bf + st * 8);
                    } else {
                        mbar_arrive(bf + st * 8);
                        act = false;
                    }
                    src += H_STEP;
                    if (++u == 48) { u = 0; src -= 48 * H_STEP; }
                    c++;
                    left--;
                }
                SAFE_BREAK;
                if (!__any_sync(0xffffffffu, ok)) __nanosleep(100);
            }
        } else if (warp == 14) {
            const uint32_t sx = sbase + P2_OFF_X;
            size_t o = 0;
            int wp = 0;
            uint32_t par = 0;
            if (fin) {
#pragma unroll 1
                for (int c = lane * 16; c < 64 * P2_XROW + 128; c += 512) asm volatile("st.shared.v4.u32 [%0], {0, 0, 0, 0};\n" ::"r"(sx + c) : "memory");
                __syncwarp();
            }
            wait_pos(6);
#pragma unroll 1
            for (int n = -half; n <= P2_ITEMS; n++) {
                const int w = (n + 3) % 3, end = p2_start(n) + 48;
                const size_t on = (size_t)(2 * p2_tile(cl, n) + rank) * (64 * C_DIM * 2);
                const uint32_t xf = bar_xfull + w * 8;
                bool st = n + half > 0;
                const bool ld = n < P2_ITEMS - 1 && !(n < 0 && fin);
                if (n == P2_ITEMS - 1 && lane == 0) {
                    mbar_expect_tx(xf, 64 * C_DIM * 2);
#pragma unroll 1
                    for (int c = 4; c < 12; c++) {
                        if (c >= 8) {
                            mbar_wait(bar_aempty + ((2 * c - 1) & 7) * 8, 1);
                            mbar_wait(bar_aempty + ((2 * c) & 7) * 8, 1);
                        }
                        bulk_g2s(sbase + P2_OFF_A + (c & 3) * P2_XC + (c < 8 ? P2_LHALF : 0), reinterpret_cast<const uint8_t*>(x) + on + (c & 7) * P2_XC, P2_XC, xf);
                    }
                    mbar_arrive(xf);
                }
                if (st) {
                    mbar_wait(bar_oready + wp * 8, (par >> wp) & 1);
                    par ^= 1u << wp;
                }
                if (lane == 0) {
                    if (n < P2_ITEMS - 1) mbar_expect_tx(xf, ld ? 64 * C_DIM * 2 : 0);
                    const int t0 = (n ? p2_start(n - 1) + 48 : P2_S2) + (n == P2_ITEMS - 1 ? P2_TL : P2_T0), dt = end - t0;
                    int t = st ? 16 * t0 : -4096;
                    if ((n == 0 && half) || n == P2_ITEMS) {
                        if (fin && n == 0) {
                            flag_wait<true>(&g_half[pair][rank], 1);
                            asm volatile("fence.proxy.async.global;\n" ::: "memory");
                        }
#pragma unroll 1
                        for (int c = 0; c < 2; c++) {
                            uint8_t* dst = reinterpret_cast<uint8_t*>(out) + o + c * 32 * P2_XROW;
                            if (!fin || n) bulk_s2g(dst, n ? sbase + P2_OFF_A + c * P2_LHALF : sx + c * P2_XHALF, 32 * P2_XROW);
                            else asm volatile("cp.reduce.async.bulk.global.shared::cta.bulk_group.add.noftz.bf16 [%0], [%1], %2;\n"
                                              ::"l"(dst), "r"(sx + c * P2_XHALF), "r"(32 * P2_XROW) : "memory");
                        }
                        asm volatile("cp.async.bulk.commit_group;\n" ::: "memory");
                        if (!fin && n == 0) {
                            asm volatile("cp.async.bulk.wait_group 0;\nfence.proxy.async.global;\n" ::: "memory");
                            asm volatile("st.release.gpu.global.u32 [%0], 1;\n" ::"l"(&g_half[pair][rank]) : "memory");
                        }
                        st = false;
                    }
#pragma unroll 1
                    for (int c = 0; n < P2_ITEMS && c < 64 * P2_XROW; c += P2_XC, t += 2 * dt) {
                        const uint32_t sp = sx + c + (c >= 32 * P2_XROW ? 64 : 0);
                        wait_pos(t >> 4);
                        if (st) bulk_s2g(reinterpret_cast<uint8_t*>(out) + o + c, sp, P2_XC);
                        asm volatile("cp.async.bulk.commit_group;\n" ::: "memory");
                        if (ld) {
                            wait_pos((t + dt) >> 4);
                            asm volatile("cp.async.bulk.wait_group.read 0;\n" ::: "memory");
                            bulk_g2s(sp, reinterpret_cast<const uint8_t*>(x) + on + c, P2_XC, xf);
                        }
                    }
                    if (rank == 0 && n > 0 && n < P2_ITEMS - 2) flag_wait<false>(g_prog[CNT_POS], P2_NCL * (end - 1));
                    if (n < P2_ITEMS - 1) mbar_arrive(xf);
                }
                __syncwarp();
                o = on;
                wp = w;
            }
            asm volatile("cp.async.bulk.wait_group.read 0;\n" ::: "memory");
        } else {
            if (blockIdx.x == 120) {
                wait_pos(P2_RAW);
                for (int i = lane; i < (LN_RING + 6) * 2; i += 32) (&g_flag[0][0][0])[i * 8] = 0;
                for (int i = lane; i < HID; i += 32) g_sq[i] = 0;
                for (int i = lane; i < 512; i += 32) g_sums[i] = 0.f;
            }
            int t = 4 * P2_XP0;
#pragma unroll 1
            for (int n = 0; n < P2_ITEMS && lane == 0; n++) {
                const uint8_t* xn = reinterpret_cast<const uint8_t*>(x) + (size_t)(2 * p2_tile(cl, n) + rank) * (64 * C_DIM * 2);
#pragma unroll 1
                for (int c = 0; c < 16; c++, t += n < P2_XPN ? 4 : P2_XPD) {
                    wait_pos(t >> 2);
                    asm volatile("cp.async.bulk.prefetch.L2.global [%0], %1;\n" ::"l"(xn + c * (P2_XC / 2)), "r"(P2_XC / 2) : "memory");
                }
            }
        }
        __syncwarp();
        cluster_sync_relaxed();
    } else {
        const int wg = warp >> 2, w = warp & 3, g = lane >> 2, q = lane & 3;
        const uint32_t sx = sbase + P2_OFF_X + (g & 1) * P2_XHALF + (w * 8 + (g >> 1)) * P2_XROW + q * 16;
        const uint32_t af = bar_afull + wg * P2_NA * 8;
        const uint32_t s_a = sbase + P2_OFF_A + wg * P2_NA * P2_A + (lane >> 3) * 512 + (lane & 7) * 64 + ((w ^ ((lane & 7) >> 1)) << 4);
        uint32_t acc0[48], acc1[48], up;
        uint4 a[2][2];

        __nv_bfloat16 gg[4];
#pragma unroll
        for (int i = 0; i < 4; i++) gg[i] = grn_g[tid + 384 * i];
#pragma unroll 1
        for (int it = !early;; it++) {
            float* s_red = reinterpret_cast<float*>(smem + P2_OFF_RED);
            float gx[4], part = 0.f;
            if (it == 1) {
                TSTAMP(1, 27);
                bar_sync(5, 416);
            }
            unsigned long long v[4];
#pragma unroll
            for (int i = 0; i < 4; i++) gx[i] = __ldcg(&g_scale[tid + 384 * i]);
            while (true) {
#pragma unroll
                for (int i = 0; i < 4; i++) asm volatile("ld.relaxed.gpu.global.u64 %0, [%1];\n" : "=l"(v[i]) : "l"(&g_sq[tid + 384 * i]) : "memory");
                SAFE_BREAK;
                if (!it || !__any_sync(0xffffffffu, min(min(v[0], v[1]), min(v[2], v[3])) < (unsigned long long)NGRP << 56)) break;
            }
            TSTAMP(1, 1);
            const float bias = reinterpret_cast<const float*>(smem + OFF_PRE)[tid];
            const float2 pre = *reinterpret_cast<const float2*>(smem + OFF_PRE + C_DIM * 4);
            bool tiny = false;
#pragma unroll
            for (int i = 0; i < 4; i++) {
                const float t = it == 2 ? __ldcg(&g_redo[tid + 384 * i]) : __ull2float_rn(v[i] << 8) * 0x1p-40f;
                tiny |= t < M_TOTAL * 0x1p-19f;
                gx[i] *= gx[i] * t;
            }
            float mg = 0.f;
#pragma unroll
            for (int i = 0; i < 4; i++) {
                asm("sqrt.approx.f32 %0, %1;\n" : "=f"(gx[i]) : "f"(gx[i] * (HSCALE * HSCALE) + 1e-6f));
                part += gx[i];
                gx[i] *= __bfloat162float(gg[i]);
                mg = fmaxf(mg, fabsf(gx[i]));
            }
#pragma unroll
            for (int o = 16; o > 0; o >>= 1) part += __shfl_xor_sync(0xffffffffu, part, o);
            const uint32_t mgw = __reduce_max_sync(0xffffffffu, __float_as_uint(mg));
            TSTAMP(1, 26);
            if (lane == 0) *reinterpret_cast<float2*>(s_red + warp * 2) = make_float2(part, __uint_as_float(mgw));
            if (it) {
                uint32_t redo;
                asm volatile("{\n.reg .pred p;\nsetp.ne.u32 p, %1, 0;\nbar.red.or.pred p, 4, 384, p;\nselp.u32 %0, 1, 0, p;\n}\n"
                             : "=r"(redo) : "r"((uint32_t)(tiny && it == 1)) : "memory");
                if (__shfl_sync(0xffffffffu, redo, 0)) {
                    p2_redo_sums(warp, lane);
                    continue;
                }
            }
            float tot = 0.f;
#pragma unroll
            for (int i = 0; i < 6; i++) {
                const float4 t = *reinterpret_cast<const float4*>(s_red + i * 4);
                tot += t.x + t.z;
                mg = fmaxf(mg, fmaxf(t.y, t.w));
            }
            const float inv = __fdividef(1.0f, tot * (1.0f / HID) + 1e-6f);
            const uint32_t ej = min((__float_as_uint(fmaxf(fmaf(mg, inv, 1.0f) * (HSCALE * UNCHOP), pre.y * 0x1p-13f)) >> 23) + 1, 250u);
            const float dn = __uint_as_float((254u - ej) << 23);
            up = min(ej + 127u - (__float_as_uint(pre.x) >> 23), 254u) * 0x00800080u;
            reinterpret_cast<uint16_t*>(smem + P2_OFF_BIAS + C_DIM * 2)[tid] = 0;
            *reinterpret_cast<__half*>(smem + P2_OFF_BIAS + (tid >> 5) * 64 + (tid & 6) * 8 + (tid & 24) / 2 + (tid & 1) * 2) = __float2half_rn(bias * dn);
#pragma unroll
            for (int i = 0; i < 4; i++) {
                const int k = tid + 384 * i;
                *reinterpret_cast<__half*>(smem + P2_OFF_GRN + (k >> 4) * 32 + (k & 6) * 4 + (k & 8) / 2 + (k & 1) * 2) =
                    __float2half_rn(fmaf(gx[i], inv, 1.0f) * (HSCALE * UNCHOP * dn));
            }
            TSTAMP(1, 25);
            if (it) break;
        }
        bar_sync(4, 384);
        asm volatile("barrier.cluster.wait.aligned;\n" ::: "memory");
        TSTAMP(1, 28);
        if (wg == 1) {
            constexpr int N = sizeof(g_w2img[0]) / 16, PER = (N + NUM_CTAS - 1) / NUM_CTAS;
            uint4 v[5];
#pragma unroll
            for (int i = 0; i < 5; i++) v[i] = __ldcg(&g_w2img[0][min(blockIdx.x * PER + (tid & 127) + 128 * i, N - 1)]);
#pragma unroll
            for (int i = 0; i < 5; i++) {
                const int j = min(blockIdx.x * PER + (tid & 127) + 128 * i, N - 1);
                const uint32_t* t = reinterpret_cast<const uint32_t*>(smem + P2_OFF_GRN + (j / 768) * 32 + (j & 8) / 2);
                auto sc = [&](uint32_t u, int e) { return (h2_mul(u, t[2 * e]) + 0x00040004u) & 0xfff8fff8u; };
                g_w2img[1][j] = make_uint4(sc(v[i].x, 0), sc(v[i].y, 1), sc(v[i].z, 2), sc(v[i].w, 3));
            }
            asm volatile("fence.proxy.async.global;\n" ::: "memory");
            bar_sync(2, 128);
            if (tid == 128) asm volatile("fence.acq_rel.gpu;\nred.release.gpu.global.add.u32 [%0], 1;\n" ::"l"(g_prog[CNT_IMG1]) : "memory");
        }

        const int who = __shfl_sync(0xffffffffu, lane == 2 ? 0 : lane < 2 ? 1 : 2, lane);
        const uint32_t rel0 = who ? mapa(bar_bempty, lane & 1) : mapa(bar_aempty + wg * P2_NA * 8, rank), rel1 = rel0 + (who ? 0 : 32);
        auto publish = [&]() {
            asm volatile("fence.proxy.async.shared::cta;\n" ::: "memory");
            __syncwarp();
            if (who == 0) mbar_arrive(bar_oready + wg * 8);
        };
        bool ok_a, pend = false;
        uint32_t pa = 0, s_t;
        auto fetch = [&](int j, bool raw) {
            uint32_t o[6], u0[4], u1[4];
            uint2 t0 = make_uint2(0, 0), t1 = t0;
            if (raw) {
                asm volatile("ld.shared.v2.u32 {%0,%1}, [%2];\n" : "=r"(t0.x), "=r"(t0.y) : "r"(s_t + j * 64) : "memory");
                asm volatile("ld.shared.v2.u32 {%0,%1}, [%2];\n" : "=r"(t1.x), "=r"(t1.y) : "r"(s_t + j * 64 + 32) : "memory");
            }
            const bool ok_b = mbar_test(bar_bfull + (j & 3) * 8, j >> 2);
            if (j == 7) pa ^= 1;
            ok_a = mbar_test(af + ((j + 1) & 7) * 8, pa);
            asm volatile("ldmatrix.sync.aligned.m8n8.x4.trans.shared.b16 {%0,%1,%2,%3}, [%4];\n"
                         : "=r"(o[0]), "=r"(o[1]), "=r"(o[2]), "=r"(o[3]) : "r"(s_a + j * P2_A) : "memory");
            asm volatile("ldmatrix.sync.aligned.m8n8.x2.trans.shared.b16 {%0,%1}, [%2];\n"
                         : "=r"(o[4]), "=r"(o[5]) : "r"(s_a + j * P2_A + 2048) : "memory");
            p2_unpack(u0, o[0], o[1], o[2]);
            p2_unpack(u1, o[3], o[4], o[5]);
            if (raw) {
                u0[0] = h2_mul(u0[0], t0.x); u0[1] = h2_mul(u0[1], t0.x); u0[2] = h2_mul(u0[2], t0.y); u0[3] = h2_mul(u0[3], t0.y);
                u1[0] = h2_mul(u1[0], t1.x); u1[1] = h2_mul(u1[1], t1.x); u1[2] = h2_mul(u1[2], t1.y); u1[3] = h2_mul(u1[3], t1.y);
            }
            a[j & 1][0] = make_uint4(u0[0], u0[1], u0[2], u0[3]);
            a[j & 1][1] = make_uint4(u1[0], u1[1], u1[2], u1[3]);
            if (!ok_b) mbar_wait(bar_bfull + (j & 3) * 8, j >> 2);
        };
        auto table = [&](int pos) { s_t = sbase + P2_OFF_GRN + q * 8 + (k0 + pos) % 48 * 64; };
        const uint32_t db0 = (uint32_t)make_desc(sbase, 128, 256);
        auto block8 = [&](bool raw, int pos, int thr0, int mode) {
#pragma unroll
            for (int j = 0; j < 8; j++) {
                const uint32_t db = db0 + (j & 3) * (P2_B / 16);
                if (j == 8 - P2_AH && mode == 1) bar_sync(4, 384);
                TR2(wg, pos + j, 0);
                wg_fence();
                mma_rs_n192(acc0, a[j & 1][0], db);
                mma_rs_n192(acc1, a[j & 1][0], db + 384);
                mma_rs_n192(acc0, a[j & 1][1], db + 768);
                mma_rs_n192(acc1, a[j & 1][1], db + 768 + 384);
                wg_commit();
                if (j == 7 && mode == 2) bar_arrive(4, 384);
                const uint32_t rel = ((j - 1) & 4 ? rel1 : rel0) + ((j - 1) & 3) * 8;
                TR2(wg, pos + j, 1);
                wg_wait<1>();
                TR2(wg, pos + j, 2);
                if (who < (j ? 2 : thr0)) mbar_arrive_cluster(rel);
                if (!ok_a) {
                    if (j == 0 && pend) { publish(); pend = false; }
                    mbar_wait(af + ((j + 1) & 7) * 8, pa);
                }
                TR2(wg, pos + j, 3);
                if (raw && j == 7) table(pos + 8);
                fetch((j + 1) & 7, raw && (j < 7 || pos + 8 < P2_RAW));
            }
        };
        int n = wg == 2 && half ? -1 : wg, pos = p2_start(n);
        uint32_t px = 0;
        wait_pos(pos);
        mbar_wait(af, 0);
        table(pos);
        fetch(0, pos < P2_RAW);
#pragma unroll 1
        for (;; n += 3) {
            TSTAMP(1, 2 + n);
            const int end = pos + (n < 0 ? 24 : 48);
#pragma unroll
            for (int i = 0; i < 48; i += 2) {
                asm volatile("mov.b64 {%0, %1}, 0;\n" : "=r"(acc0[i]), "=r"(acc0[i + 1]));
                asm volatile("mov.b64 {%0, %1}, 0;\n" : "=r"(acc1[i]), "=r"(acc1[i + 1]));
            }
            int thr = 1;
#pragma unroll 1
            for (; pos < P2_RAW; pos += 8, thr = 2) block8(true, pos, thr, 0);
#pragma unroll 1
            for (; pos < end; pos += 8, thr = 2) {
                const int e = pos + 8, r = e % 48;
                block8(false, pos, thr, e < 48 || e > 256 || (r != 0 && r != P2_S1 && r != P2_S2) ? 0 : e == end ? 2 : 1);
            }
            TR2(wg, pos - 1, 4);
            wg_wait<0>();
            TR2(wg, pos - 1, 5);
            if (who == 1) mbar_arrive_cluster(rel0 + 24);
            mbar_wait(bar_xfull + wg * 8, px);
            TR2(wg, pos - 1, 6);
            px ^= 1;
            __syncwarp();
            p2_epilogue(acc0, acc1, up, n == P2_ITEMS - 1 ? sx - (P2_OFF_X - P2_OFF_A) + (g & 1) * (P2_LHALF - P2_XHALF) : sx, sbase + P2_OFF_BIAS + q * 16 + (n < 0 && fin ? C_DIM * 2 : 0), zero);
            TR2(wg, pos - 1, 7);
            if (n + 3 >= P2_ITEMS) { publish(); break; }
            if (n < 0) {
                publish();
                pos = P2_S2;
                wait_pos(pos);
                mbar_wait(bar_bfull, 0);
            } else {
                pend = true;
                ok_a = false;
            }
        }
        TSTAMP(1, 29);
        cluster_sync_relaxed();
        TSTAMP(1, 30);
    }
}

__global__ void __cluster_dims__(2, 1, 1) __launch_bounds__(512, 1)
block_kernel(const __grid_constant__ CUtensorMap wmap, const __nv_bfloat16* __restrict__ x, const __nv_bfloat16* __restrict__ dw,
             const __nv_bfloat16* __restrict__ w2, const __nv_bfloat16* __restrict__ grn_g, const __nv_bfloat16* __restrict__ grn_b,
             __nv_bfloat16* __restrict__ out, int zero) {
    extern __shared__ __align__(1024) uint8_t smem[];
    const uint32_t sbase = smem_u32(smem);
    const int warp = __shfl_sync(0xffffffffu, threadIdx.x >> 5, 0), lane = threadIdx.x & 31;
    if (warp >= 12) {
        pass1<2>(wmap, x, dw, w2, grn_b, sbase, warp, lane, zero);
        pass2<2>(x, grn_g, out, smem, sbase, false, zero);
    } else {
        bool early = false;
        if (warp >= 8) {
            pass1<1>(wmap, x, dw, w2, grn_b, sbase, warp, lane, zero);
            reg_inc<160>();
        } else {
            early = pass1<0>(wmap, x, dw, w2, grn_b, sbase, warp, lane, zero);
            reg_dec<160>();
        }
        pass2<0>(x, grn_g, out, smem, sbase, early, zero);
    }
}

}

extern "C" void kernel_launch(void* const* d_in, const int* in_sizes, int n_in, void* d_out, int out_size) {
    const __nv_bfloat16* x = (const __nv_bfloat16*)d_in[0];
    const __nv_bfloat16* dw = (const __nv_bfloat16*)d_in[1];
    const __nv_bfloat16* w1 = (const __nv_bfloat16*)d_in[2];
    const __nv_bfloat16* w2 = (const __nv_bfloat16*)d_in[3];
    const __nv_bfloat16* grn_g = (const __nv_bfloat16*)d_in[4];
    const __nv_bfloat16* grn_b = (const __nv_bfloat16*)d_in[5];
    __nv_bfloat16* out = (__nv_bfloat16*)d_out;

    cudaFuncSetAttribute(block_kernel, cudaFuncAttributeMaxDynamicSharedMemorySize, SMEM_BYTES);

    typedef CUresult (*EncodeFn)(CUtensorMap*, CUtensorMapDataType, cuuint32_t, void*, const cuuint64_t*, const cuuint64_t*,
                                 const cuuint32_t*, const cuuint32_t*, CUtensorMapInterleave, CUtensorMapSwizzle,
                                 CUtensorMapL2promotion, CUtensorMapFloatOOBfill);
    static EncodeFn encode = nullptr;
    if (!encode) {
        cudaDriverEntryPointQueryResult qres;
        cudaGetDriverEntryPoint("cuTensorMapEncodeTiled", (void**)&encode, cudaEnableDefault, &qres);
    }
    CUtensorMap wmap;
    const cuuint64_t gdim[2] = {HID, C_DIM};
    const cuuint64_t gstr[1] = {HID * 2};
    const cuuint32_t box[2] = {64, 192}, estr[2] = {1, 1};
    CUresult er = encode(&wmap, CU_TENSOR_MAP_DATA_TYPE_BFLOAT16, 2, (void*)w1, gdim, gstr, box, estr, CU_TENSOR_MAP_INTERLEAVE_NONE,
           CU_TENSOR_MAP_SWIZZLE_128B, CU_TENSOR_MAP_L2_PROMOTION_L2_128B, CU_TENSOR_MAP_FLOAT_OOB_FILL_NONE);
    if (er != CUDA_SUCCESS) printf("tensor map encode failed %d\n", (int)er);

    block_kernel<<<NUM_CTAS, 512, SMEM_BYTES>>>(wmap, x, dw, w2, grn_g, grn_b, out, 0);
}
```

```cpp
#include <cuda.h>
#include <cuda_runtime.h>
#include <cuda_bf16.h>
#include <cuda_fp16.h>
#include <stdint.h>
#include <stdio.h>

namespace {

constexpr int M_TOTAL = 384 * 384;
constexpr int C_DIM   = 384;
constexpr int HID     = 1536;
constexpr int NT128   = M_TOTAL / 128;
constexpr int NUM_CTAS = 132;

constexpr int NGRP = 22, GRP_CTAS = 6;
constexpr int NT_EARLY = NT128 - 30;
constexpr int LN_STEP = NUM_CTAS / 4, LN_RING = 2 * LN_STEP;
constexpr int LN_TILE = 128 * C_DIM * 2;
constexpr int H_TILE = 64 * HID * 3 / 2;
constexpr int H_HALF = 3072, H_STEP = 6144;

__device__ __align__(1024) uint4 g_h[(size_t)M_TOTAL * HID * 3 / 32];
__device__ __align__(1024) uint4 g_ln[LN_RING * LN_TILE / 16];
__device__ __align__(1024) uint4 g_w2img[2][HID * C_DIM * 2 / 16];
__device__ __align__(16) unsigned long long g_sq[HID];
__device__ __align__(16) float g_sums[512];
__device__ float g_scale[HID];
__device__ float g_redo[HID];
enum { CNT_POS, CNT_IMG1, CNT_REDO, CNT_IMG0, CNT_LAST, CNT_H, CNT_EARLY, NUM_CNT };
__device__ __align__(128) unsigned g_prog[NUM_CNT][32];
__device__ __align__(128) unsigned g_half[32][2];
__device__ unsigned g_flag[LN_RING + 6][2][8];
#define TSTAMP(k, i)
#define TRACE(wg, pos, i)
#define TRACEW(pos, i)

#define TR2(wg, pos, i)
__host__ __device__ __forceinline__ int perm32(int n) {
    return (n & ~31) | (((n >> 1) & 3) << 3) | (((n >> 3) & 3) << 1) | (n & 1);
}

__device__ __forceinline__ uint32_t smem_u32(const void* p) { return (uint32_t)__cvta_generic_to_shared(p); }

__device__ __forceinline__ void mbar_init(uint32_t bar, uint32_t count) {
    asm volatile("mbarrier.init.shared::cta.b64 [%0], %1;\n" ::"r"(bar), "r"(count) : "memory");
}
__device__ __forceinline__ void mbar_expect_tx(uint32_t bar, uint32_t bytes) {
    asm volatile("mbarrier.arrive.expect_tx.shared::cta.b64 _, [%0], %1;\n" ::"r"(bar), "r"(bytes) : "memory");
}
__device__ __forceinline__ void mbar_arrive(uint32_t bar) {
    asm volatile("mbarrier.arrive.shared::cta.b64 _, [%0];\n" ::"r"(bar) : "memory");
}
__device__ __forceinline__ void mbar_arrive_cluster(uint32_t bar_cluster_addr) {
    asm volatile("mbarrier.arrive.shared::cluster.b64 _, [%0];\n" ::"r"(bar_cluster_addr) : "memory");
}
#define SAFE_BREAK
__device__ __forceinline__ void mbar_wait(uint32_t bar, uint32_t parity) {
    asm volatile(
        "{\n"
        ".reg .pred p;\n"
        "LAB_WAIT:\n"
        "mbarrier.try_wait.parity.shared::cta.b64 p, [%0], %1;\n"
        "@!p bra LAB_WAIT;\n"
        "}\n" ::"r"(bar), "r"(parity) : "memory");
}
__device__ __forceinline__ bool mbar_test(uint32_t bar, uint32_t parity) {
    uint32_t ok;
    asm volatile("{\n.reg .pred p;\n"
                 "mbarrier.test_wait.parity.shared::cta.b64 p, [%1], %2;\n"
                 "selp.u32 %0, 1, 0, p;\n}\n" : "=r"(ok) : "r"(bar), "r"(parity) : "memory");
    return ok != 0;
}
__device__ __forceinline__ uint32_t mapa(uint32_t addr, uint32_t rank) {
    uint32_t r;
    asm volatile("mapa.shared::cluster.u32 %0, %1, %2;\n" : "=r"(r) : "r"(addr), "r"(rank));
    return r;
}
__device__ __forceinline__ void bulk_g2s(uint32_t dst, const void* src, uint32_t bytes, uint32_t bar) {
    asm volatile("cp.async.bulk.shared::cluster.global.mbarrier::complete_tx::bytes [%0], [%1], %2, [%3];\n"
                 ::"r"(dst), "l"(src), "r"(bytes), "r"(bar) : "memory");
}
__device__ __forceinline__ void bulk_g2s_mc(uint32_t dst, const void* src, uint32_t bytes, uint32_t bar, uint16_t mask) {
    asm volatile("cp.async.bulk.shared::cluster.global.mbarrier::complete_tx::bytes.multicast::cluster [%0], [%1], %2, [%3], %4;\n"
                 ::"r"(dst), "l"(src), "r"(bytes), "r"(bar), "h"(mask) : "memory");
}
__device__ __forceinline__ void tma2(uint32_t dst, const CUtensorMap* map, int c0, int c1, uint32_t bar) {
    asm volatile("cp.async.bulk.tensor.2d.shared::cluster.global.tile.mbarrier::complete_tx::bytes [%0], [%1, {%2, %3}], [%4];\n"
                 ::"r"(dst), "l"(map), "r"(c0), "r"(c1), "r"(bar) : "memory");
}
template <bool ACQ>
__device__ __forceinline__ uint32_t flag_wait(const unsigned* p, unsigned target) {
    unsigned v, n = 0;
    do {
        if (ACQ) asm volatile("ld.acquire.gpu.global.u32 %0, [%1];\n" : "=r"(v) : "l"(p) : "memory");
        else asm volatile("ld.relaxed.gpu.global.u32 %0, [%1];\n" : "=r"(v) : "l"(p) : "memory");
        n++;
    } while (v < target);
    return n == 1;
}
__device__ __forceinline__ void ldsm4t(uint32_t (&r)[4], uint32_t addr) {
    asm volatile("ldmatrix.sync.aligned.m8n8.x4.trans.shared.b16 {%0,%1,%2,%3}, [%4];\n"
                 : "=r"(r[0]), "=r"(r[1]), "=r"(r[2]), "=r"(r[3]) : "r"(addr) : "memory");
}
__device__ __forceinline__ void bulk_s2g(void* dst, uint32_t src, uint32_t bytes) {
    asm volatile("cp.async.bulk.global.shared::cta.bulk_group [%0], [%1], %2;\n" ::"l"(dst), "r"(src), "r"(bytes) : "memory");
}
__device__ __forceinline__ void cluster_sync_relaxed() {
    asm volatile("barrier.cluster.arrive.relaxed.aligned;\nbarrier.cluster.wait.aligned;\n" ::: "memory");
}
__device__ __forceinline__ uint32_t cluster_rank() {
    uint32_t r;
    asm volatile("mov.u32 %0, %%cluster_ctarank;\n" : "=r"(r));
    return r;
}
__device__ __forceinline__ bool elect_one() {
    uint32_t pred;
    asm volatile("{\n.reg .pred p;\nelect.sync _|p, 0xffffffff;\nselp.u32 %0, 1, 0, p;\n}\n" : "=r"(pred));
    return pred != 0;
}
__device__ __forceinline__ void wg_fence() { asm volatile("wgmma.fence.sync.aligned;\n" ::: "memory"); }
__device__ __forceinline__ void wg_commit() { asm volatile("wgmma.commit_group.sync.aligned;\n" ::: "memory"); }
template <int N> __device__ __forceinline__ void wg_wait() {
    asm volatile("wgmma.wait_group.sync.aligned %0;\n" ::"n"(N) : "memory");
}
template <int R> __device__ __forceinline__ void reg_inc() { asm volatile("setmaxnreg.inc.sync.aligned.u32 %0;\n" ::"n"(R)); }
template <int R> __device__ __forceinline__ void reg_dec() { asm volatile("setmaxnreg.dec.sync.aligned.u32 %0;\n" ::"n"(R)); }
__device__ __forceinline__ void bar_sync(int id, int n) { asm volatile("bar.sync %0, %1;\n" ::"r"(id), "r"(n) : "memory"); }
__device__ __forceinline__ void bar_arrive(int id, int n) { asm volatile("bar.arrive %0, %1;\n" ::"r"(id), "r"(n) : "memory"); }

__device__ __forceinline__ uint64_t make_desc(uint32_t saddr, uint32_t lbo, uint32_t sbo) {
    return (uint64_t)((saddr & 0x3FFFF) >> 4) | ((uint64_t)(lbo >> 4) << 16) | ((uint64_t)(sbo >> 4) << 32);
}

__device__ __forceinline__ void stg128_cs(void* p, uint32_t a, uint32_t b, uint32_t c, uint32_t d) {
    asm volatile("st.global.cs.v4.u32 [%0], {%1,%2,%3,%4};\n" ::"l"(p), "r"(a), "r"(b), "r"(c), "r"(d) : "memory");
}
__device__ __forceinline__ uint32_t pack_bf16(float lo, float hi) {
    uint32_t r;
    asm("cvt.rn.bf16x2.f32 %0, %1, %2;\n" : "=r"(r) : "f"(hi), "f"(lo));
    return r;
}
__device__ __forceinline__ float bf_lo(uint32_t v) { return __uint_as_float(v << 16); }
__device__ __forceinline__ float bf_hi(uint32_t v) { return __uint_as_float(v & 0xffff0000u); }
__device__ __forceinline__ uint32_t bf2_mul(uint32_t a, uint32_t b) {
    uint32_t r;
    asm("mul.rn.bf16x2 %0, %1, %2;\n" : "=r"(r) : "r"(a), "r"(b));
    return r;
}
__device__ __forceinline__ uint32_t bf2_fma(uint32_t a, uint32_t b, uint32_t c) {
    uint32_t r;
    asm("fma.rn.bf16x2 %0, %1, %2, %3;\n" : "=r"(r) : "r"(a), "r"(b), "r"(c));
    return r;
}
__device__ __forceinline__ uint32_t bf2_add(uint32_t a, uint32_t b) {
    uint32_t r;
    asm("add.rn.bf16x2 %0, %1, %2;\n" : "=r"(r) : "r"(a), "r"(b));
    return r;
}
__device__ __forceinline__ uint32_t h2_mul(uint32_t a, uint32_t b) {
    uint32_t r;
    asm("mul.rn.f16x2 %0, %1, %2;\n" : "=r"(r) : "r"(a), "r"(b));
    return r;
}
__device__ __forceinline__ uint32_t h2_fma(uint32_t a, uint32_t b, uint32_t c) {
    uint32_t r;
    asm("fma.rn.f16x2 %0, %1, %2, %3;\n" : "=r"(r) : "r"(a), "r"(b), "r"(c));
    return r;
}
__device__ __forceinline__ uint32_t h2_add(uint32_t a, uint32_t b) {
    uint32_t r;
    asm("add.rn.f16x2 %0, %1, %2;\n" : "=r"(r) : "r"(a), "r"(b));
    return r;
}
__device__ __forceinline__ uint32_t pack_f16(float lo, float hi) {
    uint32_t r;
    asm("cvt.rn.f16x2.f32 %0, %1, %2;\n" : "=r"(r) : "f"(hi), "f"(lo));
    return r;
}
__device__ __forceinline__ float h_lo(uint32_t v) { return __low2float(*reinterpret_cast<const __half2*>(&v)); }
__device__ __forceinline__ float h_hi(uint32_t v) { return __high2float(*reinterpret_cast<const __half2*>(&v)); }
__device__ __forceinline__ uint32_t bf2_to_h2(uint32_t v) { return (v & 0x7fff7fffu) * 7u + v; }
__device__ __forceinline__ uint32_t prmt(uint32_t a, uint32_t b, uint32_t sel) {
    uint32_t r;
    asm("prmt.b32 %0, %1, %2, %3;\n" : "=r"(r) : "r"(a), "r"(b), "r"(sel));
    return r;
}
__device__ __forceinline__ uint32_t bitsel(uint32_t a, uint32_t b, uint32_t m) {
    uint32_t r;
    asm("lop3.b32 %0, %1, %2, %3, 0xd8;\n" : "=r"(r) : "r"(a), "r"(b), "r"(m));
    return r;
}
constexpr float KAPPA = 0.3292034911525734f;
constexpr uint32_t GELU_C2 = 0x40d940d9u;
constexpr float HSCALE = 1.0f / (2.0f * KAPPA);
__device__ __forceinline__ float w2_scale(uint32_t m) { return __uint_as_float((257u - max(m >> 23, 16u)) << 23); }
__device__ __forceinline__ void sched_break(int zero) {
    asm volatile("{\n.reg .pred p;\nsetp.ne.s32 p, %0, 0;\nSB_LOOP:\n@p nanosleep.u32 1;\n@p bra SB_LOOP;\n}\n" ::"r"(zero));
}

#define ACC8(d, o) "+r"(d[o + 0]), "+r"(d[o + 1]), "+r"(d[o + 2]), "+r"(d[o + 3]), "+r"(d[o + 4]), "+r"(d[o + 5]), "+r"(d[o + 6]), "+r"(d[o + 7])

__device__ __forceinline__ void mma_rs_n128(uint32_t (&d)[32], const uint32_t (&a)[4], uint32_t desc, int scale_d) {
    asm volatile(
        "{\n.reg .pred p;\n.reg .b64 db;\nsetp.ne.b32 p, %37, 0;\nmov.b64 db, {%36, 0x40000040};\n"
        "wgmma.mma_async.sync.aligned.m64n128k16.f16.f16.f16 "
        "{%0,%1,%2,%3,%4,%5,%6,%7,%8,%9,%10,%11,%12,%13,%14,%15,"
        "%16,%17,%18,%19,%20,%21,%22,%23,%24,%25,%26,%27,%28,%29,%30,%31},"
        "{%32,%33,%34,%35}, db, p, 1, 1, 0;\n}\n"
        : ACC8(d, 0), ACC8(d, 8), ACC8(d, 16), ACC8(d, 24)
        : "r"(a[0]), "r"(a[1]), "r"(a[2]), "r"(a[3]), "r"(desc), "r"(scale_d));
}

__device__ __forceinline__ void mma_ss_n128(uint32_t (&d)[32], uint32_t da, uint32_t db, int scale_d) {
    asm volatile(
        "{\n.reg .pred p;\n.reg .b64 da, db;\nsetp.ne.b32 p, %34, 0;\nmov.b64 da, {%32, 0x40000040};\nmov.b64 db, {%33, 0x40000040};\n"
        "wgmma.mma_async.sync.aligned.m64n128k16.f16.f16.f16 "
        "{%0,%1,%2,%3,%4,%5,%6,%7,%8,%9,%10,%11,%12,%13,%14,%15,"
        "%16,%17,%18,%19,%20,%21,%22,%23,%24,%25,%26,%27,%28,%29,%30,%31},"
        "da, db, p, 1, 1, 1, 0;\n}\n"
        : ACC8(d, 0), ACC8(d, 8), ACC8(d, 16), ACC8(d, 24)
        : "r"(da), "r"(db), "r"(scale_d));
}

__device__ __forceinline__ void mma_rs_n192(uint32_t (&d)[48], const uint4& a, uint32_t db) {
    asm volatile(
        "{\n.reg .b64 db;\nmov.b64 db, {%52, 16};\n"
        "wgmma.mma_async.sync.aligned.m64n192k16.f16.f16.f16 "
        "{%0,%1,%2,%3,%4,%5,%6,%7,%8,%9,%10,%11,%12,%13,%14,%15,"
        "%16,%17,%18,%19,%20,%21,%22,%23,%24,%25,%26,%27,%28,%29,%30,%31,"
        "%32,%33,%34,%35,%36,%37,%38,%39,%40,%41,%42,%43,%44,%45,%46,%47},"
        "{%48,%49,%50,%51}, db, 1, 1, 1, 0;\n}\n"
        : ACC8(d, 0), ACC8(d, 8), ACC8(d, 16), ACC8(d, 24), ACC8(d, 32), ACC8(d, 40)
        : "r"(a.x), "r"(a.y), "r"(a.z), "r"(a.w), "r"(db));
}

constexpr int P1_SPLIT = 5;
constexpr int P1_SLOT = LN_TILE / 6, P1_NST = 6;
constexpr int P1_W = 64 * C_DIM * 2;
constexpr int P1_X = 32 * C_DIM * 2;
constexpr int P1_OFF_W = LN_TILE;
constexpr int P1_OFF_X = P1_OFF_W + 2 * P1_W;
constexpr int P1_OFF_BAR = 227328;
constexpr int P1_OFF_TILE = P1_OFF_BAR + (2 * P1_NST + 4 + 4 + 4) * 8;
constexpr int P1_OFF_EX = P1_OFF_TILE + 64;
constexpr int P1_OFF_DW = P1_OFF_EX + 256 * 4;
constexpr int OFF_PRE = P1_OFF_DW + C_DIM * 2;
constexpr int SMEM_BYTES = OFF_PRE + C_DIM * 4 + 16;

__device__ __forceinline__ float rsqrt_fast(float x) {
    float r;
    asm("rsqrt.approx.ftz.f32 %0, %1;\n" : "=f"(r) : "f"(x));
    return r;
}
__device__ __forceinline__ float row_sum(const uint32_t (&c)[4]) {
    const uint32_t u = bf2_add(bf2_add(c[0], c[1]), bf2_add(c[2], c[3]));
    float s = bf_lo(u) + bf_hi(u);
#pragma unroll
    for (int o = 1; o < 8; o <<= 1) s += __shfl_xor_sync(0xffffffffu, s, o);
    return s;
}
__device__ __forceinline__ uint32_t pace(uint32_t bar, uint32_t off, uint32_t val, int zero) {
    asm volatile(
        "{\n.reg .pred p, q;\n.reg .b32 par;\n"
        "lop3.b32 par, %0, %2, %3, 0xea;\n"
        "setp.eq.u32 q, par, 0;\n"
        "mov.pred p, 0;\n"
        "@q mbarrier.test_wait.parity.shared::cta.b64 p, [%1], par;\n"
        "selp.u32 par, 1, 0, p;\n"
        "@q mbarrier.try_wait.parity.shared::cta.b64 p, [%1], par, 1000;\n"
        "@p or.b32 %0, %0, %2;\n"
        "}\n" : "+r"(val) : "r"(bar), "r"(zero), "r"(off));
    return val;
}
__device__ __forceinline__ void ln_row(uint32_t (&v)[6][4], const uint32_t (&d)[6][4], uint32_t bar, uint32_t off, int zero, uint32_t bar_read) {
    const float inv = 1.0f / C_DIM;
    uint32_t c[4];
#pragma unroll
    for (int i = 0; i < 6; i++)
#pragma unroll
        for (int k = 0; k < 4; k++) c[k] = bf2_fma(v[i][k], d[i][k], i ? c[k] : 0);
    const float m = row_sum(c) * inv;
    uint32_t nm = pack_bf16(-m, -m);
    const float e = m + bf_lo(nm);
    if (bar_read) mbar_arrive(bar_read + (nm & zero));
    nm = pace(bar, off, nm, zero);
#pragma unroll
    for (int i = 0; i < 6; i++) {
#pragma unroll
        for (int k = 0; k < 4; k++) {
            v[i][k] = bf2_fma(v[i][k], d[i][k], nm);
            c[k] = i ? bf2_fma(v[i][k], v[i][k], c[k]) : bf2_mul(v[i][k], v[i][k]);
        }
    }
    float r = KAPPA * rsqrt_fast(fmaxf(fmaf(-e, e, row_sum(c) * inv), 0.f) + 1e-5f);
    const float er = -e * r * 0x1p-112f;
    if (__any_sync(0xffffffffu, r < 0x1p-8f)) {
        const uint32_t p2 = __float_as_uint(r) & 0x7f800000u;
        r = __uint_as_float((__float_as_uint(r) & 0x007fffffu) | 0x3f800000u);
#pragma unroll
        for (int i = 0; i < 6; i++)
#pragma unroll
            for (int k = 0; k < 4; k++) v[i][k] = bf2_mul(v[i][k], p2 | p2 >> 16);
    }
    const uint32_t rs = pack_bf16(r * 0x1p-112f, r * 0x1p-112f), sh = pack_bf16(er, er);
#pragma unroll
    for (int i = 0; i < 6; i++)
#pragma unroll
        for (int k = 0; k < 4; k++) v[i][k] = bf2_to_h2(bf2_fma(v[i][k], rs, sh));
}

template <int R>
__device__ __forceinline__ uint32_t gelu2(uint32_t a, uint32_t sc2) {
    uint32_t y, t;
    if (R) asm("{\n.reg .b16 l, h;\n.reg .b32 f;\nmov.b32 {l, h}, %2;\nmov.b32 f, {h, h};\nmul.rn.f16x2 %0, %1, f;\n}\n" : "=r"(y) : "r"(a), "r"(sc2));
    else asm("{\n.reg .b16 l, h;\n.reg .b32 f;\nmov.b32 {l, h}, %2;\nmov.b32 f, {l, l};\nmul.rn.f16x2 %0, %1, f;\n}\n" : "=r"(y) : "r"(a), "r"(sc2));
    asm("tanh.approx.f16x2 %0, %1;\n" : "=r"(t) : "r"(h2_mul(y, h2_fma(y, y, GELU_C2))));
    return h2_fma(a, t, a);
}
constexpr uint32_t SPARE = 0x40074007u;
constexpr float UNCHOP = 1.0023f;

__device__ __forceinline__ uint32_t p1_exponents(float (&t)[2], uint32_t (&ex)[2], uint32_t saddr, int lane) {
#pragma unroll
    for (int r = 0; r < 2; r++) {
        t[r] += __shfl_xor_sync(0xffffffffu, t[r], 1);
        t[r] += __shfl_xor_sync(0xffffffffu, t[r], 2);
        ex[r] = min(max(((__float_as_uint(193.3f * t[r]) >> 23) + 127u) >> 1, 72u), 198u);
        asm volatile("st.shared.u32 [%0], %1;\n" ::"r"(saddr + r * 32), "r"(ex[r] << 23) : "memory");
    }
    return pack_f16(__uint_as_float(min(ex[0], 142u) << 23), __uint_as_float(min(ex[1], 142u) << 23));
}
template <int N>
__device__ __forceinline__ void p1_convert(uint32_t (&o)[N][4], uint32_t (&v)[N][4], const uint32_t (&ex)[2]) {
    if (__any_sync(0xffffffffu, max(ex[0], ex[1]) > 141u)) {
#pragma unroll
        for (int k = 0; k < 4 * N; k++) v[k >> 2][k & 3] = bf2_mul(v[k >> 2][k & 3], ex[k & 1] > 141u ? 0x1f801f80u : 0x3f803f80u);
    }
#pragma unroll
    for (int k = 0; k < 4 * N; k++) {
        const uint32_t u = bf2_mul(v[k >> 2][k & 3], ((ex[k & 1] > 141u ? 206u : 142u) - ex[k & 1]) * 0x00800080u);
        asm volatile("mad.lo.u32 %0, %1, 7, %2;\n" : "=r"(o[k >> 2][k & 3]) : "r"(u & 0x7fff7fffu), "r"(u));
    }
}
template <int N>
__device__ __forceinline__ void p1_squares(const uint32_t (&v)[N][4], float (&t)[2]) {
#pragma unroll
    for (int j = 0; j < N / 2; j++) {
        const int r = j & 1, b = (j >> 1) * 4;
        uint32_t c = bf2_mul(v[b][r], v[b][r]);
#pragma unroll
        for (int k = 1; k < 8; k++) c = bf2_fma(v[b + k / 2][r + (k & 1) * 2], v[b + k / 2][r + (k & 1) * 2], c);
        t[r] += bf_lo(c) + bf_hi(c);
    }
}
__device__ __forceinline__ void p1_epilogue(const uint32_t (&acc)[2][32], const uint32_t (&sc2)[2], float (&ssq)[4], uint8_t* hp, int zero) {
    uint32_t sq[2], h[16][4];
#pragma unroll
    for (int i2 = 0; i2 < 9; i2++) {
#pragma unroll
        for (int c = 2 * i2 - 2; c < 2 * i2; c++) {
            if (c >= 0 && (c & 3)) {
                uint32_t o[4];
#pragma unroll
                for (int u = 0; u < 4; u++) {
                    const uint32_t v = h[c & 12][u];
                    o[u] = bitsel(h[c][u], (c & 3) == 2 ? prmt(v, v, 0xa381) : prmt(v >> 3, v, (c & 3) == 1 ? 0x6240 : 0xf3d1), SPARE);
                }
                stg128_cs(hp + (c >> 3) * 2 * H_STEP + ((c >> 2) & 1) * H_HALF + ((c & 3) - 1) * 512, o[0], o[1], o[2], o[3]);
            }
        }
        if (i2 < 8) {
#pragma unroll
            for (int u = 0; u < 4; u++) {
                h[2 * i2][u] = gelu2<0>(acc[i2 >> 2][8 * (i2 & 3) + 2 * u], sc2[i2 >> 2]);
                h[2 * i2 + 1][u] = gelu2<1>(acc[i2 >> 2][8 * (i2 & 3) + 2 * u + 1], sc2[i2 >> 2]);
#pragma unroll
                for (int r = 0; r < 2; r++) {
                    const uint32_t v = h[2 * i2 + r][u];
                    sq[r] = ((i2 & 3) | u) ? h2_fma(v, v, sq[r]) : h2_mul(v, v);
                }
            }
            if ((i2 & 3) == 3) {
#pragma unroll
                for (int r = 0; r < 2; r++) ssq[(i2 >> 2) * 2 + r] += h_lo(sq[r]) + h_hi(sq[r]);
            }
            sched_break(zero);
        }
    }
}
template <int WG>
__device__ __forceinline__ void p1_mma(uint32_t (&acc)[2][32], const uint32_t (&a)[24][4], uint32_t sbase, uint32_t empty_remote, int i, int lane, bool pass) {
    const uint32_t bar_full = sbase + P1_OFF_BAR;
    const uint32_t db = (uint32_t)make_desc(sbase, 16, 1024), da = db + (P1_OFF_W + WG * P1_W) / 16;
    if (WG == 0) mbar_wait(bar_full, i & 1);
    bar_sync(1 + WG, 256);
    TRACE(WG, i, 1);
    wg_fence();
#pragma unroll
    for (int k = 0; k < 24; k++) {
        if (WG == 0 && k && k % 4 == 0) mbar_wait(bar_full + (k >> 2) * 8, i & 1);
        mma_rs_n128(acc[0], a[k], db + (k >> 2) * 1024 + (k & 3) * 2, k != 0);
        mma_ss_n128(acc[1], da + k * 128, db + (k >> 2) * 1024 + (k & 3) * 2, k != 0);
        if (k == 23 && pass) bar_arrive(2 - WG, 256);
        if (k == 23 || (WG == 1 && k % 4 == 3)) wg_commit();
        if (WG == 1 && k % 4 == 3 && k > 3) {
            wg_wait<1>();
            if (lane < 2) mbar_arrive_cluster(empty_remote + ((k >> 2) - 1) * 8);
        }
    }
    TRACE(WG, i, 2);
    wg_wait<0>();
    if (WG == 1 && lane < 2) mbar_arrive_cluster(empty_remote + 5 * 8);
}
__device__ __forceinline__ bool p1_consumer(const uint32_t (&a)[24][4], const uint32_t (&sc2)[2], uint32_t sbase, int WG, int w, int lane, int zero) {
    const uint32_t bar_full = sbase + P1_OFF_BAR, bar_empty = bar_full + P1_NST * 8;
    const uint32_t empty_remote = mapa(bar_empty, lane & 1);
    const uint32_t bar_pace = bar_empty + P1_NST * 8 + 32 + w * 8;
    const int g = lane >> 2, q = lane & 3, half = WG ^ ((blockIdx.x / GRP_CTAS) & 1), cb = (blockIdx.x % GRP_CTAS) * 4 + half * 2;
    uint32_t acc[2][32];
    float ssq[4] = {0.f, 0.f, 0.f, 0.f};
    TSTAMP(0, 1);

    uint8_t* hp = reinterpret_cast<uint8_t*>(g_h) + ((cb * 2 + (w >> 1)) * H_STEP + (w & 1) * 1536) + g * 64 + (q ^ (g >> 1)) * 16;
    int i = 0;
    uint32_t more = 3, both;
#pragma unroll 1
    for (;; i++) {
        TRACE(WG, i, 0);
        both = more & 2;
        if (WG == 0) p1_mma<0>(acc, a, sbase, empty_remote, i, lane, both);
        else p1_mma<1>(acc, a, sbase, empty_remote, i, lane, true);
        TRACE(WG, i, 4);
        int step;
        asm volatile("ld.shared.v2.u32 {%0, %1}, [%2];\n" : "=r"(step), "=r"(more) : "r"(sbase + P1_OFF_TILE + (i & 3) * 16) : "memory");
        hp += step;
        if (!(more >> WG & 1) && lane == 0) asm volatile("red.relaxed.gpu.global.add.u32 [%0], 1;\n" ::"l"(g_prog[CNT_LAST]) : "memory");
        p1_epilogue(acc, sc2, ssq, hp, zero);
        if (lane == 0) mbar_arrive(bar_pace);
        if (more & 4) {
            asm volatile("fence.proxy.async.global;\n" ::: "memory");
            bar_arrive(8, 288);
            bar_arrive(9, 288);
        }
        if (!(more >> WG & 1)) break;
    }
    TSTAMP(0, 21);
    if (WG == 0 && both) bar_sync(1, 256);
#pragma unroll
    for (int r = 0; r < 4; r++) {
        ssq[r] += __shfl_xor_sync(0xffffffffu, ssq[r], 1);
        ssq[r] += __shfl_xor_sync(0xffffffffu, ssq[r], 2);
    }
    const float t = q == 0 ? ssq[0] : q == 1 ? ssq[1] : q == 2 ? ssq[2] : ssq[3];
    atomicAdd(&g_sq[cb * 64 + (q >> 1) * 64 + w * 16 + (q & 1) * 8 + g], (1ull << 56) + __float2ull_rn(fminf(t, 0x1p19f) * 0x1p32f));
    asm volatile("fence.proxy.async.global;\n" ::: "memory");
    bar_arrive(3, 288);
    asm volatile("barrier.cluster.arrive.relaxed.aligned;\n" ::: "memory");
    return WG ? more & 1 : both;
}

__device__ __forceinline__ void p2_init(uint32_t sbase);
template <int ROLE>
__device__ __forceinline__ bool pass1(const CUtensorMap& wmap, const __nv_bfloat16* __restrict__ x, const __nv_bfloat16* __restrict__ dw,
                                      const __nv_bfloat16* __restrict__ w2, const __nv_bfloat16* __restrict__ grn_b, uint32_t sbase,
                                      int warp, int lane, int zero) {
    const uint32_t bar_full = sbase + P1_OFF_BAR, bar_empty = bar_full + P1_NST * 8, bar_w = bar_empty + P1_NST * 8;
    const uint32_t rank = cluster_rank();
    const int cig = blockIdx.x % GRP_CTAS;
    uint8_t* const ring = reinterpret_cast<uint8_t*>(g_ln);

    TSTAMP(0, 0);
    TRACEW(110 + warp, 0);
    const uint32_t bar_pace = bar_w + 32, bar_xfull = bar_pace + 32, bar_xempty = bar_xfull + 8, bar_done = bar_xfull + 16;
    const int ln0 = blockIdx.x >> 2, first = blockIdx.x / GRP_CTAS;
    const uint8_t* xsrc = reinterpret_cast<const uint8_t*>(x) + (size_t)blockIdx.x * P1_X;

    if (ROLE == 2) {
        reg_dec<32>();
        asm volatile("barrier.cluster.arrive.relaxed.aligned;\n" ::: "memory");
        asm volatile("barrier.cluster.wait.aligned;\n" ::: "memory");
        if (warp == 12) {
            int prev = 0, t = first;
            const uint32_t rbase = mapa(sbase, lane & 1);
#pragma unroll 1
            for (int i = 0; t < NT128; i++) {
                const int round = t / LN_RING, slot = t - round * LN_RING;
                const uint8_t* src = ring + slot * LN_TILE + rank * (P1_SLOT / 2);
                int next = 0;
                if (rank == 0 && lane == 0) {
                    next = t < NT128 - P1_SPLIT ? NGRP + atomicAdd(&g_flag[LN_RING + (cig >> 1)][0][0], 1u) : 2 * NT128;
                    if (next >= NT128 - P1_SPLIT && next < 2 * NT128) next = NT128 - P1_SPLIT + atomicAdd(&g_flag[LN_RING + 3 + (cig >> 1)][first & 1][0], 1u);
                }
                flag_wait<true>(&g_flag[slot][0][0], 4 * round + 4);
                TRACEW(i, 2);
                asm volatile("fence.proxy.async.global;\n" ::: "memory");
                next = __shfl_sync(0xffffffffu, next, 0);
#pragma unroll 1
                for (int h = 0; h < P1_NST; h++) {
                    mbar_wait(bar_empty + h * 8, i & 1);
                    if (h == 0) TRACEW(i, 4);
                    if (h == 5) TRACEW(i, 5);
                    if (elect_one()) {
                        mbar_expect_tx(bar_full + h * 8, h ? P1_SLOT : P1_SLOT + 16);
                        bulk_g2s_mc(sbase + h * P1_SLOT + rank * (P1_SLOT / 2), src + h * P1_SLOT, P1_SLOT / 2, bar_full + h * 8, (uint16_t)3);
                    }
                    __syncwarp();
                    if (h == 0 && rank == 0 && lane < 2)
                        asm volatile("st.async.shared::cluster.mbarrier::complete_tx::bytes.v4.u32 [%0], {%1, %2, %3, %3}, [%4];\n"
                                     ::"r"(rbase + P1_OFF_TILE + (i & 3) * 16), "r"((t - prev) * (2 * H_TILE)), "r"((next < NT128 - P1_SPLIT ? 3 : next < NT128) + (t < NT_EARLY && next >= NT_EARLY ? 4 : 0)), "r"(next),
                                       "r"(rbase + P1_OFF_BAR) : "memory");
                }
                prev = t;
                t = next;
                if (rank != 0) {
                    mbar_wait(bar_full, i & 1);
                    asm volatile("ld.shared.u32 %0, [%1];\n" : "=r"(t) : "r"(sbase + P1_OFF_TILE + (i & 3) * 16 + 8) : "memory");
                }
            }
        } else if (warp == 13) {
            int ph = 0;
            unsigned target = 0;
#pragma unroll 1
            for (int i = ln0 + LN_STEP; i < NT128; i += LN_STEP, ph ^= 1) {
                target += ph * (GRP_CTAS / 2);
                xsrc += (size_t)NUM_CTAS * P1_X;
                mbar_wait(bar_xempty, ph);
                if (elect_one()) {
                    mbar_expect_tx(bar_xfull, P1_X);
                    bulk_g2s(sbase + P1_OFF_X, xsrc, P1_X, bar_xfull);
                }
                __syncwarp();
                const uint32_t off = flag_wait<false>(&g_flag[ln0 + (ph ^ 1) * LN_STEP][1][0], target);
                mbar_wait(bar_done, ph);
                if (elect_one()) {
                    asm volatile("st.shared.u32 [%0], %1;\n" ::"r"(bar_done + 8), "r"(off) : "memory");
                    mbar_arrive(bar_xfull);
                }
                __syncwarp();
            }
        } else if (warp == 15) {
            int t = first;
            if (rank == 1 && lane == 0) mbar_arrive(bar_empty);
#pragma unroll 1
            for (int i = 0; rank == 1 && t < NT128; i++) {
#pragma unroll 1
                for (int h = 0; h < P1_NST; h++) mbar_wait(bar_full + h * 8, i & 1);
                if (lane == 0) asm volatile("red.relaxed.gpu.global.add.u32 [%0], 1;\n" ::"l"(&g_flag[t % LN_RING][1][0]) : "memory");
                asm volatile("ld.shared.u32 %0, [%1];\n" : "=r"(t) : "r"(sbase + P1_OFF_TILE + (i & 3) * 16 + 8) : "memory");
                if (lane == 0) mbar_arrive(bar_empty);
                TRACEW(i, 3);
            }
            if (rank == 0) {
                mbar_wait(bar_full, 0);
                TRACEW(110 + warp, 3);
                mbar_wait(bar_full, 1);
                float* sums = g_sums;
                unsigned* flag = reinterpret_cast<unsigned*>(sums + C_DIM);
                if (blockIdx.x == 0) reinterpret_cast<uint2*>(g_half)[lane] = make_uint2(0, 0);
                if (blockIdx.x == 2 && lane < NUM_CNT) g_prog[lane][0] = 0;
                if (blockIdx.x < 96) g_redo[blockIdx.x * 16 + lane] = 0.f;
                float gs = 0.f;
#pragma unroll 1
                for (int pass = 0; pass < 2; pass++) {
                    float mx = 0.f;
#pragma unroll 1
                    for (int it = first; it < 96; it += NGRP) {
                        const int nb = it % 12, k0 = (cig * 4 + it / 12) * 64 + (lane >> 2);
                        const uint32_t sc = mapa(sbase + P1_OFF_EX + (k0 & 255) * 4, it / 48);
                        uint32_t* dst = reinterpret_cast<uint32_t*>(g_w2img[0]) + (k0 >> 4) * 3072 + nb * 256 + lane;
                        float bs[8] = {};
#pragma unroll 1
                        for (int c = 0; c < 8; c++) {
                            const uint4 u = __ldg(reinterpret_cast<const uint4*>(w2 + (size_t)(k0 + c * 8) * C_DIM + nb * 32) + (lane & 3));
                            const float b = __bfloat162float(grn_b[k0 + c * 8]);
                            float t;
                            asm volatile("ld.shared::cluster.f32 %0, [%1];\n" : "=f"(t) : "r"(sc + c * 32) : "memory");
                            if (nb == 0) g_scale[k0 + c * 8] = t;
#pragma unroll
                            for (int j = 0; j < 4; j++) {
                                const uint32_t v = j == 0 ? u.x : j == 1 ? u.y : j == 2 ? u.z : u.w;
                                mx = fmaxf(mx, fmaxf(fabsf(bf_lo(v)), fabsf(bf_hi(v))) * t);
                                if (pass) {
                                    bs[2 * j] = fmaf(b, bf_lo(v), bs[2 * j]);
                                    bs[2 * j + 1] = fmaf(b, bf_hi(v), bs[2 * j + 1]);
                                    uint32_t h = pack_f16(bf_lo(v) * t * gs, bf_hi(v) * t * gs);
                                    asm volatile("movmatrix.sync.aligned.m8n8.trans.b16 %0, %0;\n" : "+r"(h));
                                    dst[(c >> 1) * 3072 + (c & 1) * 32 + j * 64] = h;
                                }
                            }
                        }
                        if (pass) {
#pragma unroll
                            for (int j = 0; j < 8; j++) {
#pragma unroll
                                for (int o = 4; o < 32; o <<= 1) bs[j] += __shfl_xor_sync(0xffffffffu, bs[j], o);
                                if (lane >> 2 == j) atomicAdd(&sums[nb * 32 + (j >> 1) * 8 + (lane & 3) * 2 + (j & 1)], bs[j]);
                            }
                        }
                    }
                    if (!pass) {
                        const uint32_t m = __reduce_max_sync(0xffffffffu, __float_as_uint(mx));
                        __threadfence();
                        __syncwarp();
                        if (lane == 0) {
                            atomicMax(flag, m);
                            asm volatile("red.release.gpu.global.add.u32 [%0], 1;\n" ::"l"(flag + 32) : "memory");
                        }
                        flag_wait<true>(flag + 32, NUM_CTAS / 2);
                        gs = w2_scale(__ldcg(flag));
                    }
                }
                asm volatile("fence.proxy.async.global;\nfence.acq_rel.gpu;\n" ::: "memory");
                __syncwarp();
                if (lane == 0) asm volatile("red.relaxed.gpu.global.add.u32 [%0], 1;\n" ::"l"(g_prog[CNT_IMG0]) : "memory");
            }
        } else if (warp == 14) {
            int ph = 0;
#pragma unroll 1
            for (int i = ln0; i < NT128; i += LN_STEP, ph ^= 1) {
                mbar_wait(bar_done, ph);
                TRACEW(i / LN_STEP, 0);
                asm volatile("fence.proxy.async.global;\n" ::: "memory");
                if (elect_one()) asm volatile("red.release.gpu.global.add.u32 [%0], 1;\n" ::"l"(&g_flag[ln0 + ph * LN_STEP][0][0]) : "memory");
                __syncwarp();
                TRACEW(i / LN_STEP, 1);
            }
            if (lane == 0) p2_init(sbase);
#pragma unroll 1
            for (int i = CNT_EARLY; i >= CNT_H; i--) {
                bar_sync(i == CNT_EARLY ? 8 : 3, 288);
                asm volatile("fence.proxy.async.global;\n" ::: "memory");
                if (lane == 0) asm volatile("red.release.gpu.global.add.u32 [%0], 1;\n" ::"l"(&g_prog[i][0]) : "memory");
                __syncwarp();
            }
        }
        __syncwarp();
        asm volatile("barrier.cluster.arrive.relaxed.aligned;\n" ::: "memory");
        return false;
    } else if (ROLE == 1) {
        reg_dec<96>();
        asm volatile("barrier.cluster.arrive.relaxed.aligned;\n" ::: "memory");
        {
            const int l8 = lane & 7, row = (warp - 8) * 4 + (lane >> 3), px = (blockIdx.x & 3) * 32 + row;
            uint32_t d[6][4];
            const int n = (px & 64) + perm32(2 * row + ((px >> 5) & 1));
            uint8_t* const dst0 = ring + ln0 * LN_TILE + n * 128 + ((l8 ^ (n & 7)) << 4);
            const uint32_t src = sbase + P1_OFF_X + ((warp - 8) * 8 + (lane >> 3)) * (C_DIM * 2) + l8 * 16;
            int ph = 0;
#pragma unroll 1
            for (int i = ln0; i < NT128; i += LN_STEP, ph ^= 1) {
                TRACE(2, i / LN_STEP, 0);
                uint32_t off = 1;
#pragma unroll 1
                for (int ps = i == ln0 ? -2 : 0; ps < 2; ps += ps < 0 ? 2 : 1) {
                    if (ps == 0) {
                        if (i == ln0) asm volatile("barrier.cluster.wait.aligned;\n" ::: "memory");
                        mbar_wait(bar_xfull, ph);
                        asm volatile("ld.shared.u32 %0, [%1];\n" : "=r"(off) : "r"(bar_done + 8) : "memory");
                    }
                    if (ps == 0) TRACE(2, i / LN_STEP, 1);
                    if (i == ln0) {
#pragma unroll
                        for (int j = 0; j < 6; j++)
                            asm volatile("ld.shared.v4.u32 {%0,%1,%2,%3}, [%4];\n"
                                         : "=r"(d[j][0]), "=r"(d[j][1]), "=r"(d[j][2]), "=r"(d[j][3]) : "r"(sbase + P1_OFF_DW + j * 128 + l8 * 16) : "memory");
                    }
                    uint32_t v[6][4];
#pragma unroll
                    for (int j = 0; j < 6; j++)
                        asm volatile("ld.shared.v4.u32 {%0,%1,%2,%3}, [%4];\n"
                                     : "=r"(v[j][0]), "=r"(v[j][1]), "=r"(v[j][2]), "=r"(v[j][3]) : "r"(src + (ps & 1) * (4 * C_DIM * 2) + j * 128) : "memory");
                    ln_row(v, d, bar_pace + (warp - 8) * 8, off, zero, ps == 1 && lane == 0 ? bar_xempty : 0);
                    uint8_t* dst = dst0 + ph * (LN_STEP * LN_TILE) + (ps & 1) * 4096;
#pragma unroll
                    for (int j = 0; j < 6; j++) *reinterpret_cast<uint4*>(dst + j * 16384) = make_uint4(v[j][0], v[j][1], v[j][2], v[j][3]);
                    TRACE(2, i / LN_STEP, 3 + (ps & 1));
                }
                asm volatile("fence.proxy.async.global;\nfence.acq_rel.cta;\n" ::: "memory");
                __syncwarp();
                if (lane == 0) mbar_arrive(bar_done);
                TRACE(2, i / LN_STEP, 5);
                TRACE(2, i / LN_STEP, 2);
            }
        }
        __syncwarp();
        asm volatile("barrier.cluster.arrive.relaxed.aligned;\n" ::: "memory");
        return false;
    } else {
        const int wg = warp >> 2, w = warp & 3;
        auto load_w = [&](int i0, int i1) {
#pragma unroll 1
            for (int i = i0; i < i1; i++) {
                if (!(i & 1)) mbar_expect_tx(bar_w + (i >> 1) * 8, P1_W);
                tma2(sbase + (i & 2) * P1_W + (i >> 2) * P1_W + (i & 1) * (P1_W / 2), &wmap, cig * 256 + ((i >> 1) ^ (first & 1) * 2) * 64, (i & 1) * 192, bar_w + (i >> 1) * 8);
            }
        };
        if (warp == 4 && elect_one()) {
            mbar_init(bar_xfull, 2);
#pragma unroll
            for (int i = 0; i < 4; i++) mbar_init(bar_w + i * 8, 1);
            asm volatile("fence.mbarrier_init.release.cluster;\n" ::: "memory");
            mbar_expect_tx(bar_xfull, P1_X + C_DIM * 2);
            bulk_g2s(sbase + P1_OFF_X, xsrc, P1_X, bar_xfull);
            bulk_g2s(sbase + P1_OFF_DW, dw, C_DIM * 2, bar_xfull);
            load_w(0, 4);
            asm volatile("st.shared.u32 [%0], 1;\n" ::"r"(bar_done + 8) : "memory");
            mbar_arrive(bar_xfull);
        }
        if (warp == 5 && elect_one()) {
#pragma unroll
            for (int i = 0; i < P1_NST; i++) {
                mbar_init(bar_full + i * 8, 1);
                mbar_init(bar_empty + i * 8, i ? 8 : 8 + rank);
                if (i < 4) mbar_init(bar_pace + i * 8, 1);
            }
            mbar_init(bar_xempty, 4);
            mbar_init(bar_done, 4);
            asm volatile("fence.mbarrier_init.release.cluster;\n" ::: "memory");
        }
        __syncwarp();
        asm volatile("barrier.cluster.arrive.relaxed.aligned;\n" ::: "memory");
        reg_inc<192>();
        TRACEW(110 + warp, 1);
        uint32_t a[24][4];
        const uint32_t src = sbase + wg * P1_W + ((lane >> 4) * 8 + (lane & 7)) * 128 + (((2 * w + ((lane >> 3) & 1)) ^ (lane & 7)) << 4);
        const uint32_t s_ex = sbase + P1_OFF_EX + ((wg ^ (first & 1)) * 128 + w * 16 + (lane >> 2)) * 4;
        uint32_t sc2[2], ex[2];
        if (wg == 1) bar_arrive(1, 256);
#pragma unroll 1
        for (int it = 0; it < 2; it++) {
          if (it != wg) asm volatile("barrier.cluster.wait.aligned;\n" ::: "memory");
          if (it < wg) {
              mbar_wait(bar_xfull, 0);
              if (w == 0 && elect_one()) load_w(4, 8);
              __syncwarp();
          }
          if (it || wg == 0) {
            float t[2] = {0.f, 0.f};
            if (it) {
                TRACEW(110 + warp, 2);
                mbar_wait(bar_w + wg * 16, 0);
            }
            TRACEW(110 + warp, 5);
#pragma unroll
            for (int k = 0; k < 24; k++) ldsm4t(a[k], src + k * 2048);
            TRACEW(110 + warp, 6);
            p1_squares(a, t);
            sc2[0] = p1_exponents(t, ex, s_ex, lane);
            if (it && lane < 6) mbar_arrive_cluster(mapa(bar_empty, lane & 1) + (wg * 3 + (lane >> 1)) * 8 + (sc2[0] & zero));
            p1_convert<24>(a, a, ex);
          }
          if (it || wg == 1) {
            float t[2] = {0.f, 0.f};
            TRACEW(100 + warp, 0);
            if (it) mbar_wait(bar_w + wg * 16 + 8, 0);
            TRACEW(100 + warp, 1);
            uint32_t v[8][4], o[8][4];
#pragma unroll 1
            for (int j = 0; j <= 2 * it; j++) {
#pragma unroll
                for (int k = 0; k < 8; k++) ldsm4t(v[k], src + P1_OFF_W + (8 * j + k) * 2048);
                p1_squares(v, t);
            }
            sc2[1] = p1_exponents(t, ex, s_ex + 256, lane);
#pragma unroll 1
            for (int j = 2 * it; j >= 0; j--) {
                p1_convert<8>(o, v, ex);
#pragma unroll
                for (int k = 0; k < 8; k++) {
                    if (j) ldsm4t(v[k], src + P1_OFF_W + (8 * j - 8 + k) * 2048);
                    if (it) asm volatile("stmatrix.sync.aligned.m8n8.x4.trans.shared.b16 [%0], {%1,%2,%3,%4};\n"
                                         ::"r"(src + P1_OFF_W + (8 * j + k) * 2048), "r"(o[k][0]), "r"(o[k][1]), "r"(o[k][2]), "r"(o[k][3]) : "memory");
                }
            }
          }
        }
        asm volatile("fence.proxy.async.shared::cta;\n" ::: "memory");
        TRACEW(110 + warp, 7);
        bar_sync(6 + wg, 128);
        const bool early = p1_consumer(a, sc2, sbase, wg, w, lane, zero);
        TSTAMP(0, 30);
        return early;
    }
}

constexpr int P2_B = 24576, P2_NB = 4;
constexpr int P2_A = 3072, P2_NA = 8;
constexpr int P2_XROW = C_DIM * 2;
constexpr int P2_OFF_A = P2_B * P2_NB;
constexpr int P2_OFF_X = P2_OFF_A + 3 * P2_NA * P2_A + 128;
constexpr int P2_LHALF = 2 * P2_NA * P2_A + 64;
constexpr int P2_XHALF = 32 * P2_XROW + 64;
constexpr int P2_OFF_GRN = P2_OFF_X + 64 * P2_XROW + 128;
constexpr int P2_OFF_BIAS = P2_OFF_GRN + HID * 2;
constexpr int P2_OFF_RED = P2_OFF_BIAS + C_DIM * 4;
constexpr int P2_OFF_BAR = P2_OFF_RED + 192;
constexpr int P2_SMEM = P2_OFF_BAR + (2 * P2_NB + 6 * P2_NA + 7) * 8;
constexpr int P2_S1 = 16, P2_S2 = 32;
constexpr int P2_NCL = NUM_CTAS / 2, P2_ITEMS = NT128 / P2_NCL, P2_SHARED = NT128 - P2_ITEMS * P2_NCL;
constexpr int P2_NPOS = 6 * 48 + P2_S1;
constexpr int P2_RAW = 16;
constexpr int P2_XC = 8 * P2_XROW;
constexpr int P2_T0 = 5;
constexpr int P2_TL = 8;
constexpr int P2_XP0 = 30;
constexpr int P2_XPN = 13;
constexpr int P2_XPD = 3;
constexpr int P2_AH = 2;
__device__ __forceinline__ int p2_start(int n) { return n < 0 ? 0 : n / 3 * 48 + (n % 3 == 1 ? P2_S1 : n % 3 * (P2_S2 / 2)); }
__device__ __forceinline__ int p2_tile(int cl, int n) {
    return n == 0 ? NT_EARLY - 1 - cl : n < 0 ? NT_EARLY + (cl >> 1) : cl + P2_NCL * (n - 1);
}

constexpr int P2_EB = 2;
constexpr int P2_EX = 1;
__device__ __forceinline__ void p2_epilogue(uint32_t (&acc0)[48], uint32_t (&acc1)[48], uint32_t up, uint32_t sx, uint32_t sb, uint8_t* so, int zero) {
    uint32_t v[12][3][4];
    auto load = [&](int t, int j) {
        if (t >= 12) return;
        uint32_t (&w)[4] = v[t][j];
        asm volatile("ld.shared.v4.u32 {%0,%1,%2,%3}, [%4];\n" : "=r"(w[0]), "=r"(w[1]), "=r"(w[2]), "=r"(w[3])
                     : "r"((j ? sx + (j - 1) * 4 * P2_XROW : sb) + t * 64) : "memory");
    };
    auto store = [&](int t, int r) {
        const uint32_t* w = (t < 6 ? acc0 : acc1) + 8 * (t % 6) + 4 * r;
        asm volatile("st.v4.u32 [%4], {%0,%1,%2,%3};\n" ::"r"(w[0]), "r"(w[1]), "r"(w[2]), "r"(w[3]), "l"(so + t * 64 + r * 4 * P2_XROW) : "memory");
    };
#pragma unroll
    for (int t = 0; t < P2_EB; t++) load(t, 0);
#pragma unroll
    for (int t = 0; t < 2 * P2_EX; t++) load(t >> 1, 1 + (t & 1));
#pragma unroll
    for (int t = 0; t < 12; t++) {
        load(t + P2_EX, 1);
        load(t + P2_EX, 2);
        load(t + P2_EB, 0);
        uint32_t* acc = (t < 6 ? acc0 : acc1) + 8 * (t % 6);
        uint32_t y[8];
#pragma unroll
        for (int e = 0; e < 8; e++) {
            y[e] = h2_add(acc[e], v[t][0][e >> 1]);
            y[e] = pack_bf16(h_lo(y[e]), h_hi(y[e]));
        }
#pragma unroll
        for (int e = 0; e < 8; e++) acc[(e & 1) * 4 + (e >> 1)] = bf2_fma(y[e], up, v[t][1 + (e & 1)][e >> 1]);
        store(t, 0);
        store(t, 1);
        sched_break(zero);
    }
}

__device__ __forceinline__ void p2_unpack(uint32_t (&u)[4], uint32_t o1, uint32_t o2, uint32_t o3) {
    u[2] = o1 & ~SPARE;
    u[1] = o2 & ~SPARE;
    u[3] = o3 & ~SPARE;
    const uint32_t t = bitsel(prmt(o1, o2, 0x6341), prmt(o1, o3, 0x6240) << 3, 0x38383838u);
    u[0] = bitsel(t, prmt(o2, o3, 0x7351) << 1, 0x80808080u) & ~SPARE;
}

__device__ __forceinline__ void p2_redo_sums(int warp, int lane) {
    flag_wait<true>(g_prog[CNT_H], NUM_CTAS);
#pragma unroll 1
    for (int s = warp; s < 96; s += 12) {
        float t[2] = {0.f, 0.f};
#pragma unroll 1
        for (int tile = blockIdx.x; tile < 2 * NT128; tile += NUM_CTAS) {
            const uint32_t* p = reinterpret_cast<const uint32_t*>(reinterpret_cast<const uint8_t*>(g_h) + (size_t)(tile >> 1) * (2 * H_TILE) +
                                                                  (s >> 1) * H_STEP + (tile & 1) * H_HALF + (s & 1) * 1536) + lane * 4;
#pragma unroll
            for (int j = 0; j < 4; j++) {
                uint32_t u[4];
                p2_unpack(u, __ldcg(p + j), __ldcg(p + j + 128), __ldcg(p + j + 256));
#pragma unroll
                for (int c = 0; c < 4; c++) t[c >> 1] += h_lo(u[c]) * h_lo(u[c]) + h_hi(u[c]) * h_hi(u[c]);
            }
        }
#pragma unroll
        for (int r = 0; r < 2; r++) {
            const int ch = s * 16 + r * 8 + (lane >> 2);
            atomicAdd(&g_redo[ch], t[r] * (UNCHOP * UNCHOP));
        }
    }
    __threadfence();
    __syncwarp();
    if (lane == 0) asm volatile("red.release.gpu.global.add.u32 [%0], 1;\n" ::"l"(g_prog[CNT_REDO]) : "memory");
    flag_wait<true>(g_prog[CNT_REDO], 12 * NUM_CTAS);
}

static_assert(P2_OFF_GRN >= P1_OFF_X + P1_X && P1_OFF_BAR >= P2_SMEM, "barriers and tables keep their memory");
__device__ __forceinline__ void p2_init(uint32_t sbase) {
    const uint32_t bar = sbase + P2_OFF_BAR;
#pragma unroll 1
    for (int i = 0; i < 2 * P2_NB + 6 * P2_NA + 6; i++) {
        const int j = i - 2 * P2_NB;
        mbar_init(bar + i * 8, j < -P2_NB ? 1 : j < 0 ? 24 : j < 3 * P2_NA ? 1 : j >= 6 * P2_NA && j < 6 * P2_NA + 3 ? 2 : 4);
    }
    asm volatile("st.shared.v2.u32 [%0], {0, 0};\n" ::"r"(bar + (2 * P2_NB + 6 * P2_NA + 6) * 8) : "memory");
    asm volatile("fence.mbarrier_init.release.cluster;\nfence.acq_rel.cta;\n" ::: "memory");
}
template <int ROLE>
__device__ __forceinline__ void pass2(const __nv_bfloat16* __restrict__ x, const __nv_bfloat16* __restrict__ grn_g, __nv_bfloat16* __restrict__ out,
                                      uint8_t* smem, uint32_t sbase, bool early, int zero) {
    const uint32_t bar_bfull = sbase + P2_OFF_BAR, bar_bempty = bar_bfull + P2_NB * 8;
    const uint32_t bar_afull = bar_bempty + P2_NB * 8, bar_aempty = bar_afull + 3 * P2_NA * 8;
    const uint32_t bar_xfull = bar_aempty + 3 * P2_NA * 8, bar_oready = bar_xfull + 24, s_pos = bar_oready + 24;
    int tid;
    asm volatile("mov.u32 %0, %%tid.x;\n" : "=r"(tid));
    const int warp = __shfl_sync(0xffffffffu, tid >> 5, 0), lane = tid & 31;
    const uint32_t rank = cluster_rank();
    const int cl = blockIdx.x >> 1, pair = cl >> 1;
    const int half = pair < P2_SHARED, fin = half && (cl & 1);
    const int k0 = (pair + 3 * (cl & 1)) % 6 * 8;
    auto wait_pos = [&](int target) {
        int v;
        while (true) {
            asm volatile("ld.volatile.shared.u32 %0, [%1];\n" : "=r"(v) : "r"(s_pos) : "memory");
            if (v >= target) break;
            SAFE_BREAK;
            __nanosleep(100);
        }
    };

    TSTAMP(1, 0);
    if (ROLE == 2) {
        if (warp != 14) flag_wait<true>(g_prog[CNT_IMG0], P2_NCL);
        if (warp == 15) {
            float* pre = reinterpret_cast<float*>(smem + OFF_PRE);
            const float gs = w2_scale(__float_as_uint(__ldcg(&g_sums[C_DIM])));
            float mb = 0.f;
#pragma unroll 1
            for (int i = lane; i < C_DIM; i += 32) {
                pre[i] = __ldcg(&g_sums[i]) * gs;
                mb = fmaxf(mb, fabsf(pre[i]));
            }
            pre[C_DIM] = gs;
            pre[C_DIM + 1] = __uint_as_float(__reduce_max_sync(0xffffffffu, __float_as_uint(mb)));
            bar_sync(9, 288);
            flag_wait<false>(g_prog[CNT_LAST], NUM_CTAS * 8);
            bar_arrive(5, 416);
        }
        asm volatile("barrier.cluster.wait.aligned;\nfence.proxy.async;\n" ::: "memory");
        if (warp == 12) {
            const uint8_t* wsrc = reinterpret_cast<const uint8_t*>(g_w2img) + rank * (P2_B / 2);
            int kb = k0;
#pragma unroll 1
            for (int p = 0; p < P2_NPOS; p++) {
                const int st = p & 3;
                if (p == P2_RAW) {
                    flag_wait<true>(g_prog[CNT_IMG1], NUM_CTAS);
                    asm volatile("fence.proxy.async.global;\n" ::: "memory");
                    wsrc += sizeof(g_w2img[0]);
                }
                const int idle = (p < P2_S1 || p >= 6 * 48) + (p < P2_S2 ? !half || p >= 24 : p >= 5 * 48 + P2_S2);
                mbar_wait(bar_bempty + st * 8, (~p >> 2) & 1);
                TR2(3, p, 0);
                if (elect_one()) {
                    mbar_expect_tx(bar_bfull + st * 8, P2_B);
                    bulk_g2s_mc(sbase + st * P2_B + rank * (P2_B / 2), wsrc + kb * P2_B, P2_B / 2, bar_bfull + st * 8, (uint16_t)3);
                    asm volatile("st.volatile.shared.u32 [%0], %1;\n" ::"r"(s_pos), "r"(p) : "memory");
                    if (rank == 0) asm volatile("red.relaxed.gpu.global.add.u32 [%0], 1;\n" ::"l"(g_prog[CNT_POS]) : "memory");
                    if (idle) asm volatile("mbarrier.arrive.shared::cta.b64 _, [%0], %1;\n" ::"r"(bar_bempty + st * 8), "r"(8 * idle) : "memory");
                }
                __syncwarp();
                if (++kb == 48) kb = 0;
            }
            mbar_wait(bar_bempty, 1);
            if (lane == 0) mbar_arrive(bar_bfull);
        } else if (warp == 13) {
            const int w = lane % 3;
            const uint32_t dst0 = sbase + P2_OFF_A + w * P2_NA * P2_A;
            const uint32_t bf = bar_afull + w * P2_NA * 8, be = bar_aempty + w * P2_NA * 8;
            int n = (w == 2 && half ? -1 : w) - 3, left = 0, u = 0, c = 0;
            const uint8_t* src = nullptr;
            bool act = lane < 3;
            auto next = [&]() {
                n += 3;
                left = n >= P2_ITEMS ? -1 : n < 0 ? 24 : 48;
                u = (k0 + p2_start(n)) % 48;
                src = reinterpret_cast<const uint8_t*>(g_h) + (size_t)p2_tile(cl, n) * (2 * H_TILE) + rank * H_HALF + u * H_STEP;
            };
            next();
            flag_wait<true>(g_prog[CNT_EARLY], NUM_CTAS);
#pragma unroll 1
            for (int i = 3; i > 0; i--) {
                const int wi = i % 3;
                if (wi == 2) flag_wait<true>(g_prog[CNT_H], NUM_CTAS);
                asm volatile("fence.proxy.async.global;\n" ::: "memory");
                if (w == wi && lane < 24) {
                    mbar_expect_tx(bf + lane / 3 * 8, P2_A);
                    bulk_g2s(dst0 + lane / 3 * P2_A, src + lane / 3 * H_STEP, P2_A, bf + lane / 3 * 8);
                }
                __syncwarp();
            }
            c = 8;
            left -= 8;
            u += 8;
            src += 8 * H_STEP;
            if (u == 48) { u = 0; src -= 48 * H_STEP; }
            while (__any_sync(0xffffffffu, act)) {
                if (left == 0) next();
                const bool ok = act && mbar_test(be + ((c - 1) & 7) * 8, (~c >> 3) & 1);
                if (ok) {
                    const int st = c & 7;
                    if (left > 0) {
                        mbar_expect_tx(bf + st * 8, P2_A);
                        bulk_g2s(dst0 + st * P2_A, src, P2_A, bf + st * 8);
                    } else {
                        mbar_arrive(bf + st * 8);
                        act = false;
                    }
                    src += H_STEP;
                    if (++u == 48) { u = 0; src -= 48 * H_STEP; }
                    c++;
                    left--;
                }
                SAFE_BREAK;
                if (!__any_sync(0xffffffffu, ok)) __nanosleep(100);
            }
        } else if (warp == 14) {
            const uint32_t sx = sbase + P2_OFF_X;
            size_t o = 0;
            int wp = 0;
            uint32_t par = 0;
            if (fin) {
#pragma unroll 1
                for (int c = lane * 16; c < 64 * P2_XROW + 128; c += 512) asm volatile("st.shared.v4.u32 [%0], {0, 0, 0, 0};\n" ::"r"(sx + c) : "memory");
                __syncwarp();
            }
            wait_pos(6);
#pragma unroll 1
            for (int n = -half; n < P2_ITEMS; n++) {
                const int w = (n + 3) % 3, end = p2_start(n) + 48;
                const size_t on = (size_t)(2 * p2_tile(cl, n) + rank) * (64 * C_DIM * 2);
                const uint32_t xf = bar_xfull + w * 8;
                bool st = n + half > 0;
                const bool ld = n < P2_ITEMS - 1 && !(n < 0 && fin);
                if (n == P2_ITEMS - 1 && lane == 0) {
                    mbar_expect_tx(xf, 64 * C_DIM * 2);
#pragma unroll 1
                    for (int c = 4; c < 12; c++) {
                        if (c >= 8) {
                            mbar_wait(bar_aempty + ((2 * c - 1) & 7) * 8, 1);
                            mbar_wait(bar_aempty + ((2 * c) & 7) * 8, 1);
                        }
                        bulk_g2s(sbase + P2_OFF_A + (c & 3) * P2_XC + (c < 8 ? P2_LHALF : 0), reinterpret_cast<const uint8_t*>(x) + on + (c & 7) * P2_XC, P2_XC, xf);
                    }
                    mbar_arrive(xf);
                }
                if (st) {
                    mbar_wait(bar_oready + wp * 8, (par >> wp) & 1);
                    par ^= 1u << wp;
                }
                if (lane == 0) {
                    if (n < P2_ITEMS - 1) mbar_expect_tx(xf, ld ? 64 * C_DIM * 2 : 0);
                    const int t0 = (n ? p2_start(n - 1) + 48 : P2_S2) + (n == P2_ITEMS - 1 ? P2_TL : P2_T0), dt = end - t0;
                    int t = st ? 16 * t0 : -4096;
                    if ((n == 0 && half) || n == P2_ITEMS) {
                        if (fin && n == 0) {
                            flag_wait<true>(&g_half[pair][rank], 1);
                            asm volatile("fence.proxy.async.global;\n" ::: "memory");
                        }
#pragma unroll 1
                        for (int c = 0; c < 2; c++) {
                            uint8_t* dst = reinterpret_cast<uint8_t*>(out) + o + c * 32 * P2_XROW;
                            if (!fin || n) bulk_s2g(dst, n ? sbase + P2_OFF_A + c * P2_LHALF : sx + c * P2_XHALF, 32 * P2_XROW);
                            else asm volatile("cp.reduce.async.bulk.global.shared::cta.bulk_group.add.noftz.bf16 [%0], [%1], %2;\n"
                                              ::"l"(dst), "r"(sx + c * P2_XHALF), "r"(32 * P2_XROW) : "memory");
                        }
                        asm volatile("cp.async.bulk.commit_group;\n" ::: "memory");
                        if (!fin && n == 0) {
                            asm volatile("cp.async.bulk.wait_group 0;\nfence.proxy.async.global;\n" ::: "memory");
                            asm volatile("st.release.gpu.global.u32 [%0], 1;\n" ::"l"(&g_half[pair][rank]) : "memory");
                        }
                        st = false;
                    }
#pragma unroll 1
                    for (int c = 0; n < P2_ITEMS && c < 64 * P2_XROW; c += P2_XC, t += 2 * dt) {
                        const uint32_t sp = sx + c + (c >= 32 * P2_XROW ? 64 : 0);
                        wait_pos(t >> 4);
                        if (st) bulk_s2g(reinterpret_cast<uint8_t*>(out) + o + c, sp, P2_XC);
                        asm volatile("cp.async.bulk.commit_group;\n" ::: "memory");
                        if (ld) {
                            wait_pos((t + dt) >> 4);
                            asm volatile("cp.async.bulk.wait_group.read 0;\n" ::: "memory");
                            bulk_g2s(sp, reinterpret_cast<const uint8_t*>(x) + on + c, P2_XC, xf);
                        }
                    }
                    if (rank == 0 && n > 0 && n < P2_ITEMS - 2) flag_wait<false>(g_prog[CNT_POS], P2_NCL * (end - 1));
                    if (n < P2_ITEMS - 1) mbar_arrive(xf);
                }
                __syncwarp();
                o = on;
                wp = w;
            }
            asm volatile("cp.async.bulk.wait_group.read 0;\n" ::: "memory");
        } else {
            if (blockIdx.x == 120) {
                wait_pos(P2_RAW);
                for (int i = lane; i < (LN_RING + 6) * 2; i += 32) (&g_flag[0][0][0])[i * 8] = 0;
                for (int i = lane; i < HID; i += 32) g_sq[i] = 0;
                for (int i = lane; i < 512; i += 32) g_sums[i] = 0.f;
            }
            int t = 4 * P2_XP0;
#pragma unroll 1
            for (int n = 0; n < P2_ITEMS && lane == 0; n++) {
                const uint8_t* xn = reinterpret_cast<const uint8_t*>(x) + (size_t)(2 * p2_tile(cl, n) + rank) * (64 * C_DIM * 2);
#pragma unroll 1
                for (int c = 0; c < 16; c++, t += n < P2_XPN ? 4 : P2_XPD) {
                    wait_pos(t >> 2);
                    asm volatile("cp.async.bulk.prefetch.L2.global [%0], %1;\n" ::"l"(xn + c * (P2_XC / 2)), "r"(P2_XC / 2) : "memory");
                }
            }
        }
        __syncwarp();
        cluster_sync_relaxed();
    } else {
        const int wg = warp >> 2, w = warp & 3, g = lane >> 2, q = lane & 3;
        const uint32_t sx = sbase + P2_OFF_X + (g & 1) * P2_XHALF + (w * 8 + (g >> 1)) * P2_XROW + q * 16;
        const uint32_t af = bar_afull + wg * P2_NA * 8;
        const uint32_t s_a = sbase + P2_OFF_A + wg * P2_NA * P2_A + (lane >> 3) * 512 + (lane & 7) * 64 + ((w ^ ((lane & 7) >> 1)) << 4);
        uint32_t acc0[48], acc1[48], up;
        uint4 a[2][2];

        __nv_bfloat16 gg[4];
#pragma unroll
        for (int i = 0; i < 4; i++) gg[i] = grn_g[tid + 384 * i];
#pragma unroll 1
        for (int it = !early;; it++) {
            float* s_red = reinterpret_cast<float*>(smem + P2_OFF_RED);
            float gx[4], part = 0.f;
            if (it == 1) {
                TSTAMP(1, 27);
                bar_sync(5, 416);
            }
            unsigned long long v[4];
#pragma unroll
            for (int i = 0; i < 4; i++) gx[i] = __ldcg(&g_scale[tid + 384 * i]);
            while (true) {
#pragma unroll
                for (int i = 0; i < 4; i++) asm volatile("ld.relaxed.gpu.global.u64 %0, [%1];\n" : "=l"(v[i]) : "l"(&g_sq[tid + 384 * i]) : "memory");
                SAFE_BREAK;
                if (!it || !__any_sync(0xffffffffu, min(min(v[0], v[1]), min(v[2], v[3])) < (unsigned long long)NGRP << 56)) break;
            }
            TSTAMP(1, 1);
            const float bias = reinterpret_cast<const float*>(smem + OFF_PRE)[tid];
            const float2 pre = *reinterpret_cast<const float2*>(smem + OFF_PRE + C_DIM * 4);
            bool tiny = false;
#pragma unroll
            for (int i = 0; i < 4; i++) {
                const float t = it == 2 ? __ldcg(&g_redo[tid + 384 * i]) : __ull2float_rn(v[i] << 8) * 0x1p-40f;
                tiny |= t < M_TOTAL * 0x1p-19f;
                gx[i] *= gx[i] * t;
            }
            float mg = 0.f;
#pragma unroll
            for (int i = 0; i < 4; i++) {
                asm("sqrt.approx.f32 %0, %1;\n" : "=f"(gx[i]) : "f"(gx[i] * (HSCALE * HSCALE) + 1e-6f));
                part += gx[i];
                gx[i] *= __bfloat162float(gg[i]);
                mg = fmaxf(mg, fabsf(gx[i]));
            }
#pragma unroll
            for (int o = 16; o > 0; o >>= 1) part += __shfl_xor_sync(0xffffffffu, part, o);
            const uint32_t mgw = __reduce_max_sync(0xffffffffu, __float_as_uint(mg));
            TSTAMP(1, 26);
            if (lane == 0) *reinterpret_cast<float2*>(s_red + warp * 2) = make_float2(part, __uint_as_float(mgw));
            if (it) {
                uint32_t redo;
                asm volatile("{\n.reg .pred p;\nsetp.ne.u32 p, %1, 0;\nbar.red.or.pred p, 4, 384, p;\nselp.u32 %0, 1, 0, p;\n}\n"
                             : "=r"(redo) : "r"((uint32_t)(tiny && it == 1)) : "memory");
                if (__shfl_sync(0xffffffffu, redo, 0)) {
                    p2_redo_sums(warp, lane);
                    continue;
                }
            }
            float tot = 0.f;
#pragma unroll
            for (int i = 0; i < 6; i++) {
                const float4 t = *reinterpret_cast<const float4*>(s_red + i * 4);
                tot += t.x + t.z;
                mg = fmaxf(mg, fmaxf(t.y, t.w));
            }
            const float inv = __fdividef(1.0f, tot * (1.0f / HID) + 1e-6f);
            const uint32_t ej = min((__float_as_uint(fmaxf(fmaf(mg, inv, 1.0f) * (HSCALE * UNCHOP), pre.y * 0x1p-13f)) >> 23) + 1, 250u);
            const float dn = __uint_as_float((254u - ej) << 23);
            up = min(ej + 127u - (__float_as_uint(pre.x) >> 23), 254u) * 0x00800080u;
            reinterpret_cast<uint16_t*>(smem + P2_OFF_BIAS + C_DIM * 2)[tid] = 0;
            *reinterpret_cast<__half*>(smem + P2_OFF_BIAS + (tid >> 5) * 64 + (tid & 6) * 8 + (tid & 24) / 2 + (tid & 1) * 2) = __float2half_rn(bias * dn);
#pragma unroll
            for (int i = 0; i < 4; i++) {
                const int k = tid + 384 * i;
                *reinterpret_cast<__half*>(smem + P2_OFF_GRN + (k >> 4) * 32 + (k & 6) * 4 + (k & 8) / 2 + (k & 1) * 2) =
                    __float2half_rn(fmaf(gx[i], inv, 1.0f) * (HSCALE * UNCHOP * dn));
            }
            TSTAMP(1, 25);
            if (it) break;
        }
        bar_sync(4, 384);
        asm volatile("barrier.cluster.wait.aligned;\n" ::: "memory");
        TSTAMP(1, 28);
        if (wg == 1) {
            constexpr int N = sizeof(g_w2img[0]) / 16, PER = (N + NUM_CTAS - 1) / NUM_CTAS;
            uint4 v[5];
#pragma unroll
            for (int i = 0; i < 5; i++) v[i] = __ldcg(&g_w2img[0][min(blockIdx.x * PER + (tid & 127) + 128 * i, N - 1)]);
#pragma unroll
            for (int i = 0; i < 5; i++) {
                const int j = min(blockIdx.x * PER + (tid & 127) + 128 * i, N - 1);
                const uint32_t* t = reinterpret_cast<const uint32_t*>(smem + P2_OFF_GRN + (j / 768) * 32 + (j & 8) / 2);
                auto sc = [&](uint32_t u, int e) { return (h2_mul(u, t[2 * e]) + 0x00040004u) & 0xfff8fff8u; };
                g_w2img[1][j] = make_uint4(sc(v[i].x, 0), sc(v[i].y, 1), sc(v[i].z, 2), sc(v[i].w, 3));
            }
            asm volatile("fence.proxy.async.global;\n" ::: "memory");
            bar_sync(2, 128);
            if (tid == 128) asm volatile("fence.acq_rel.gpu;\nred.release.gpu.global.add.u32 [%0], 1;\n" ::"l"(g_prog[CNT_IMG1]) : "memory");
        }

        const int who = __shfl_sync(0xffffffffu, lane == 2 ? 0 : lane < 2 ? 1 : 2, lane);
        const uint32_t rel0 = who ? mapa(bar_bempty, lane & 1) : mapa(bar_aempty + wg * P2_NA * 8, rank), rel1 = rel0 + (who ? 0 : 32);
        auto publish = [&]() {
            asm volatile("fence.proxy.async.shared::cta;\n" ::: "memory");
            __syncwarp();
            if (who == 0) mbar_arrive(bar_oready + wg * 8);
        };
        bool ok_a, pend = false;
        uint32_t pa = 0, s_t;
        auto fetch = [&](int j, bool raw) {
            uint32_t o[6], u0[4], u1[4];
            uint2 t0 = make_uint2(0, 0), t1 = t0;
            if (raw) {
                asm volatile("ld.shared.v2.u32 {%0,%1}, [%2];\n" : "=r"(t0.x), "=r"(t0.y) : "r"(s_t + j * 64) : "memory");
                asm volatile("ld.shared.v2.u32 {%0,%1}, [%2];\n" : "=r"(t1.x), "=r"(t1.y) : "r"(s_t + j * 64 + 32) : "memory");
            }
            const bool ok_b = mbar_test(bar_bfull + (j & 3) * 8, j >> 2);
            if (j == 7) pa ^= 1;
            ok_a = mbar_test(af + ((j + 1) & 7) * 8, pa);
            asm volatile("ldmatrix.sync.aligned.m8n8.x4.trans.shared.b16 {%0,%1,%2,%3}, [%4];\n"
                         : "=r"(o[0]), "=r"(o[1]), "=r"(o[2]), "=r"(o[3]) : "r"(s_a + j * P2_A) : "memory");
            asm volatile("ldmatrix.sync.aligned.m8n8.x2.trans.shared.b16 {%0,%1}, [%2];\n"
                         : "=r"(o[4]), "=r"(o[5]) : "r"(s_a + j * P2_A + 2048) : "memory");
            p2_unpack(u0, o[0], o[1], o[2]);
            p2_unpack(u1, o[3], o[4], o[5]);
            if (raw) {
                u0[0] = h2_mul(u0[0], t0.x); u0[1] = h2_mul(u0[1], t0.x); u0[2] = h2_mul(u0[2], t0.y); u0[3] = h2_mul(u0[3], t0.y);
                u1[0] = h2_mul(u1[0], t1.x); u1[1] = h2_mul(u1[1], t1.x); u1[2] = h2_mul(u1[2], t1.y); u1[3] = h2_mul(u1[3], t1.y);
            }
            a[j & 1][0] = make_uint4(u0[0], u0[1], u0[2], u0[3]);
            a[j & 1][1] = make_uint4(u1[0], u1[1], u1[2], u1[3]);
            if (!ok_b) mbar_wait(bar_bfull + (j & 3) * 8, j >> 2);
        };
        auto table = [&](int pos) { s_t = sbase + P2_OFF_GRN + q * 8 + (k0 + pos) % 48 * 64; };
        const uint32_t db0 = (uint32_t)make_desc(sbase, 128, 256);
        auto block8 = [&](bool raw, int pos, int thr0, int mode) {
#pragma unroll
            for (int j = 0; j < 8; j++) {
                const uint32_t db = db0 + (j & 3) * (P2_B / 16);
                if (j == 8 - P2_AH && mode == 1) bar_sync(4, 384);
                TR2(wg, pos + j, 0);
                wg_fence();
                mma_rs_n192(acc0, a[j & 1][0], db);
                mma_rs_n192(acc1, a[j & 1][0], db + 384);
                mma_rs_n192(acc0, a[j & 1][1], db + 768);
                mma_rs_n192(acc1, a[j & 1][1], db + 768 + 384);
                wg_commit();
                if (j == 7 && mode == 2) bar_arrive(4, 384);
                const uint32_t rel = ((j - 1) & 4 ? rel1 : rel0) + ((j - 1) & 3) * 8;
                TR2(wg, pos + j, 1);
                wg_wait<1>();
                TR2(wg, pos + j, 2);
                if (who < (j ? 2 : thr0)) mbar_arrive_cluster(rel);
                if (!ok_a) {
                    if (j == 0 && pend) { publish(); pend = false; }
                    mbar_wait(af + ((j + 1) & 7) * 8, pa);
                }
                TR2(wg, pos + j, 3);
                if (raw && j == 7) table(pos + 8);
                fetch((j + 1) & 7, raw && (j < 7 || pos + 8 < P2_RAW));
            }
        };
        int n = wg == 2 && half ? -1 : wg, pos = p2_start(n);
        uint32_t px = 0;
        wait_pos(pos);
        mbar_wait(af, 0);
        table(pos);
        fetch(0, pos < P2_RAW);
#pragma unroll 1
        for (;; n += 3) {
            TSTAMP(1, 2 + n);
            const int end = pos + (n < 0 ? 24 : 48);
#pragma unroll
            for (int i = 0; i < 48; i += 2) {
                asm volatile("mov.b64 {%0, %1}, 0;\n" : "=r"(acc0[i]), "=r"(acc0[i + 1]));
                asm volatile("mov.b64 {%0, %1}, 0;\n" : "=r"(acc1[i]), "=r"(acc1[i + 1]));
            }
            int thr = 1;
#pragma unroll 1
            for (; pos < P2_RAW; pos += 8, thr = 2) block8(true, pos, thr, 0);
#pragma unroll 1
            for (; pos < end; pos += 8, thr = 2) {
                const int e = pos + 8, r = e % 48;
                block8(false, pos, thr, e < 48 || e > 256 || (r != 0 && r != P2_S1 && r != P2_S2) ? 0 : e == end ? 2 : 1);
            }
            TR2(wg, pos - 1, 4);
            wg_wait<0>();
            TR2(wg, pos - 1, 5);
            if (who == 1) mbar_arrive_cluster(rel0 + 24);
            mbar_wait(bar_xfull + wg * 8, px);
            TR2(wg, pos - 1, 6);
            px ^= 1;
            __syncwarp();
            const bool last = n == P2_ITEMS - 1;
            uint8_t* so = last ? reinterpret_cast<uint8_t*>(out) + (size_t)(2 * p2_tile(cl, n) + rank) * (64 * P2_XROW) - (g & 1) * 64 : smem + P2_OFF_X;
            p2_epilogue(acc0, acc1, up, last ? sx - (P2_OFF_X - P2_OFF_A) + (g & 1) * (P2_LHALF - P2_XHALF) : sx,
                        sbase + P2_OFF_BIAS + q * 16 + (n < 0 && fin ? C_DIM * 2 : 0), so + (sx - sbase - P2_OFF_X), zero);
            if (last) break;
            TR2(wg, pos - 1, 7);
            if (n + 3 >= P2_ITEMS) { publish(); break; }
            if (n < 0) {
                publish();
                pos = P2_S2;
                wait_pos(pos);
                mbar_wait(bar_bfull, 0);
            } else {
                pend = true;
                ok_a = false;
            }
        }
        TSTAMP(1, 29);
        cluster_sync_relaxed();
        TSTAMP(1, 30);
    }
}

__global__ void __cluster_dims__(2, 1, 1) __launch_bounds__(512, 1)
block_kernel(const __grid_constant__ CUtensorMap wmap, const __nv_bfloat16* __restrict__ x, const __nv_bfloat16* __restrict__ dw,
             const __nv_bfloat16* __restrict__ w2, const __nv_bfloat16* __restrict__ grn_g, const __nv_bfloat16* __restrict__ grn_b,
             __nv_bfloat16* __restrict__ out, int zero) {
    extern __shared__ __align__(1024) uint8_t smem[];
    const uint32_t sbase = smem_u32(smem);
    const int warp = __shfl_sync(0xffffffffu, threadIdx.x >> 5, 0), lane = threadIdx.x & 31;
    if (warp >= 12) {
        pass1<2>(wmap, x, dw, w2, grn_b, sbase, warp, lane, zero);
        pass2<2>(x, grn_g, out, smem, sbase, false, zero);
    } else {
        bool early = false;
        if (warp >= 8) {
            pass1<1>(wmap, x, dw, w2, grn_b, sbase, warp, lane, zero);
            reg_inc<160>();
        } else {
            early = pass1<0>(wmap, x, dw, w2, grn_b, sbase, warp, lane, zero);
            reg_dec<160>();
        }
        pass2<0>(x, grn_g, out, smem, sbase, early, zero);
    }
}

}

extern "C" void kernel_launch(void* const* d_in, const int* in_sizes, int n_in, void* d_out, int out_size) {
    const __nv_bfloat16* x = (const __nv_bfloat16*)d_in[0];
    const __nv_bfloat16* dw = (const __nv_bfloat16*)d_in[1];
    const __nv_bfloat16* w1 = (const __nv_bfloat16*)d_in[2];
    const __nv_bfloat16* w2 = (const __nv_bfloat16*)d_in[3];
    const __nv_bfloat16* grn_g = (const __nv_bfloat16*)d_in[4];
    const __nv_bfloat16* grn_b = (const __nv_bfloat16*)d_in[5];
    __nv_bfloat16* out = (__nv_bfloat16*)d_out;

    cudaFuncSetAttribute(block_kernel, cudaFuncAttributeMaxDynamicSharedMemorySize, SMEM_BYTES);

    typedef CUresult (*EncodeFn)(CUtensorMap*, CUtensorMapDataType, cuuint32_t, void*, const cuuint64_t*, const cuuint64_t*,
                                 const cuuint32_t*, const cuuint32_t*, CUtensorMapInterleave, CUtensorMapSwizzle,
                                 CUtensorMapL2promotion, CUtensorMapFloatOOBfill);
    static EncodeFn encode = nullptr;
    if (!encode) {
        cudaDriverEntryPointQueryResult qres;
        cudaGetDriverEntryPoint("cuTensorMapEncodeTiled", (void**)&encode, cudaEnableDefault, &qres);
    }
    CUtensorMap wmap;
    const cuuint64_t gdim[2] = {HID, C_DIM};
    const cuuint64_t gstr[1] = {HID * 2};
    const cuuint32_t box[2] = {64, 192}, estr[2] = {1, 1};
    CUresult er = encode(&wmap, CU_TENSOR_MAP_DATA_TYPE_BFLOAT16, 2, (void*)w1, gdim, gstr, box, estr, CU_TENSOR_MAP_INTERLEAVE_NONE,
           CU_TENSOR_MAP_SWIZZLE_128B, CU_TENSOR_MAP_L2_PROMOTION_L2_128B, CU_TENSOR_MAP_FLOAT_OOB_FILL_NONE);
    if (er != CUDA_SUCCESS) printf("tensor map encode failed %d\n", (int)er);

    block_kernel<<<NUM_CTAS, 512, SMEM_BYTES>>>(wmap, x, dw, w2, grn_g, grn_b, out, 0);
}
```

```cpp
#include <cuda.h>
#include <cuda_runtime.h>
#include <cuda_bf16.h>
#include <cuda_fp16.h>
#include <stdint.h>
#include <stdio.h>

namespace {

constexpr int M_TOTAL = 384 * 384;
constexpr int C_DIM   = 384;
constexpr int HID     = 1536;
constexpr int NT128   = M_TOTAL / 128;
constexpr int NUM_CTAS = 132;

constexpr int NGRP = 22, GRP_CTAS = 6;
constexpr int NT_EARLY = NT128 - 30;
constexpr int LN_STEP = NUM_CTAS / 4, LN_RING = 2 * LN_STEP;
constexpr int LN_TILE = 128 * C_DIM * 2;
constexpr int H_TILE = 64 * HID * 3 / 2;
constexpr int H_HALF = 3072, H_STEP = 6144;

__device__ __align__(1024) uint4 g_h[(size_t)M_TOTAL * HID * 3 / 32];
__device__ __align__(1024) uint4 g_ln[LN_RING * LN_TILE / 16];
__device__ __align__(1024) uint4 g_w2img[2][HID * C_DIM * 2 / 16];
__device__ __align__(16) unsigned long long g_sq[HID];
__device__ __align__(16) float g_sums[512];
__device__ float g_scale[HID];
__device__ float g_redo[HID];
enum { CNT_POS, CNT_IMG1, CNT_REDO, CNT_IMG0, CNT_LAST, CNT_H, CNT_EARLY, NUM_CNT };
__device__ __align__(128) unsigned g_prog[NUM_CNT][32];
__device__ __align__(128) unsigned g_half[32][2];
__device__ unsigned g_flag[LN_RING + 6][2][8];
#define TSTAMP(k, i)
#define TRACE(wg, pos, i)
#define TRACEW(pos, i)

#define TR2(wg, pos, i)
__host__ __device__ __forceinline__ int perm32(int n) {
    return (n & ~31) | (((n >> 1) & 3) << 3) | (((n >> 3) & 3) << 1) | (n & 1);
}

__device__ __forceinline__ uint32_t smem_u32(const void* p) { return (uint32_t)__cvta_generic_to_shared(p); }

__device__ __forceinline__ void mbar_init(uint32_t bar, uint32_t count) {
    asm volatile("mbarrier.init.shared::cta.b64 [%0], %1;\n" ::"r"(bar), "r"(count) : "memory");
}
__device__ __forceinline__ void mbar_expect_tx(uint32_t bar, uint32_t bytes) {
    asm volatile("mbarrier.arrive.expect_tx.shared::cta.b64 _, [%0], %1;\n" ::"r"(bar), "r"(bytes) : "memory");
}
__device__ __forceinline__ void mbar_arrive(uint32_t bar) {
    asm volatile("mbarrier.arrive.shared::cta.b64 _, [%0];\n" ::"r"(bar) : "memory");
}
__device__ __forceinline__ void mbar_arrive_cluster(uint32_t bar_cluster_addr) {
    asm volatile("mbarrier.arrive.shared::cluster.b64 _, [%0];\n" ::"r"(bar_cluster_addr) : "memory");
}
#define SAFE_BREAK
__device__ __forceinline__ void mbar_wait(uint32_t bar, uint32_t parity) {
    asm volatile(
        "{\n"
        ".reg .pred p;\n"
        "LAB_WAIT:\n"
        "mbarrier.try_wait.parity.shared::cta.b64 p, [%0], %1;\n"
        "@!p bra LAB_WAIT;\n"
        "}\n" ::"r"(bar), "r"(parity) : "memory");
}
__device__ __forceinline__ bool mbar_test(uint32_t bar, uint32_t parity) {
    uint32_t ok;
    asm volatile("{\n.reg .pred p;\n"
                 "mbarrier.test_wait.parity.shared::cta.b64 p, [%1], %2;\n"
                 "selp.u32 %0, 1, 0, p;\n}\n" : "=r"(ok) : "r"(bar), "r"(parity) : "memory");
    return ok != 0;
}
__device__ __forceinline__ uint32_t mapa(uint32_t addr, uint32_t rank) {
    uint32_t r;
    asm volatile("mapa.shared::cluster.u32 %0, %1, %2;\n" : "=r"(r) : "r"(addr), "r"(rank));
    return r;
}
__device__ __forceinline__ void bulk_g2s(uint32_t dst, const void* src, uint32_t bytes, uint32_t bar) {
    asm volatile("cp.async.bulk.shared::cluster.global.mbarrier::complete_tx::bytes [%0], [%1], %2, [%3];\n"
                 ::"r"(dst), "l"(src), "r"(bytes), "r"(bar) : "memory");
}
__device__ __forceinline__ void bulk_g2s_mc(uint32_t dst, const void* src, uint32_t bytes, uint32_t bar, uint16_t mask) {
    asm volatile("cp.async.bulk.shared::cluster.global.mbarrier::complete_tx::bytes.multicast::cluster [%0], [%1], %2, [%3], %4;\n"
                 ::"r"(dst), "l"(src), "r"(bytes), "r"(bar), "h"(mask) : "memory");
}
__device__ __forceinline__ void tma2(uint32_t dst, const CUtensorMap* map, int c0, int c1, uint32_t bar) {
    asm volatile("cp.async.bulk.tensor.2d.shared::cluster.global.tile.mbarrier::complete_tx::bytes [%0], [%1, {%2, %3}], [%4];\n"
                 ::"r"(dst), "l"(map), "r"(c0), "r"(c1), "r"(bar) : "memory");
}
template <bool ACQ>
__device__ __forceinline__ uint32_t flag_wait(const unsigned* p, unsigned target) {
    unsigned v, n = 0;
    do {
        if (ACQ) asm volatile("ld.acquire.gpu.global.u32 %0, [%1];\n" : "=r"(v) : "l"(p) : "memory");
        else asm volatile("ld.relaxed.gpu.global.u32 %0, [%1];\n" : "=r"(v) : "l"(p) : "memory");
        n++;
    } while (v < target);
    return n == 1;
}
__device__ __forceinline__ void ldsm4t(uint32_t (&r)[4], uint32_t addr) {
    asm volatile("ldmatrix.sync.aligned.m8n8.x4.trans.shared.b16 {%0,%1,%2,%3}, [%4];\n"
                 : "=r"(r[0]), "=r"(r[1]), "=r"(r[2]), "=r"(r[3]) : "r"(addr) : "memory");
}
__device__ __forceinline__ void bulk_s2g(void* dst, uint32_t src, uint32_t bytes) {
    asm volatile("cp.async.bulk.global.shared::cta.bulk_group [%0], [%1], %2;\n" ::"l"(dst), "r"(src), "r"(bytes) : "memory");
}
__device__ __forceinline__ void cluster_sync_relaxed() {
    asm volatile("barrier.cluster.arrive.relaxed.aligned;\nbarrier.cluster.wait.aligned;\n" ::: "memory");
}
__device__ __forceinline__ uint32_t cluster_rank() {
    uint32_t r;
    asm volatile("mov.u32 %0, %%cluster_ctarank;\n" : "=r"(r));
    return r;
}
__device__ __forceinline__ bool elect_one() {
    uint32_t pred;
    asm volatile("{\n.reg .pred p;\nelect.sync _|p, 0xffffffff;\nselp.u32 %0, 1, 0, p;\n}\n" : "=r"(pred));
    return pred != 0;
}
__device__ __forceinline__ void wg_fence() { asm volatile("wgmma.fence.sync.aligned;\n" ::: "memory"); }
__device__ __forceinline__ void wg_commit() { asm volatile("wgmma.commit_group.sync.aligned;\n" ::: "memory"); }
template <int N> __device__ __forceinline__ void wg_wait() {
    asm volatile("wgmma.wait_group.sync.aligned %0;\n" ::"n"(N) : "memory");
}
template <int R> __device__ __forceinline__ void reg_inc() { asm volatile("setmaxnreg.inc.sync.aligned.u32 %0;\n" ::"n"(R)); }
template <int R> __device__ __forceinline__ void reg_dec() { asm volatile("setmaxnreg.dec.sync.aligned.u32 %0;\n" ::"n"(R)); }
__device__ __forceinline__ void bar_sync(int id, int n) { asm volatile("bar.sync %0, %1;\n" ::"r"(id), "r"(n) : "memory"); }
__device__ __forceinline__ void bar_arrive(int id, int n) { asm volatile("bar.arrive %0, %1;\n" ::"r"(id), "r"(n) : "memory"); }

__device__ __forceinline__ uint64_t make_desc(uint32_t saddr, uint32_t lbo, uint32_t sbo) {
    return (uint64_t)((saddr & 0x3FFFF) >> 4) | ((uint64_t)(lbo >> 4) << 16) | ((uint64_t)(sbo >> 4) << 32);
}

__device__ __forceinline__ void stg128_cs(void* p, uint32_t a, uint32_t b, uint32_t c, uint32_t d) {
    asm volatile("st.global.cs.v4.u32 [%0], {%1,%2,%3,%4};\n" ::"l"(p), "r"(a), "r"(b), "r"(c), "r"(d) : "memory");
}
__device__ __forceinline__ uint32_t pack_bf16(float lo, float hi) {
    uint32_t r;
    asm("cvt.rn.bf16x2.f32 %0, %1, %2;\n" : "=r"(r) : "f"(hi), "f"(lo));
    return r;
}
__device__ __forceinline__ float bf_lo(uint32_t v) { return __uint_as_float(v << 16); }
__device__ __forceinline__ float bf_hi(uint32_t v) { return __uint_as_float(v & 0xffff0000u); }
__device__ __forceinline__ uint32_t bf2_mul(uint32_t a, uint32_t b) {
    uint32_t r;
    asm("mul.rn.bf16x2 %0, %1, %2;\n" : "=r"(r) : "r"(a), "r"(b));
    return r;
}
__device__ __forceinline__ uint32_t bf2_fma(uint32_t a, uint32_t b, uint32_t c) {
    uint32_t r;
    asm("fma.rn.bf16x2 %0, %1, %2, %3;\n" : "=r"(r) : "r"(a), "r"(b), "r"(c));
    return r;
}
__device__ __forceinline__ uint32_t bf2_add(uint32_t a, uint32_t b) {
    uint32_t r;
    asm("add.rn.bf16x2 %0, %1, %2;\n" : "=r"(r) : "r"(a), "r"(b));
    return r;
}
__device__ __forceinline__ uint32_t h2_mul(uint32_t a, uint32_t b) {
    uint32_t r;
    asm("mul.rn.f16x2 %0, %1, %2;\n" : "=r"(r) : "r"(a), "r"(b));
    return r;
}
__device__ __forceinline__ uint32_t h2_fma(uint32_t a, uint32_t b, uint32_t c) {
    uint32_t r;
    asm("fma.rn.f16x2 %0, %1, %2, %3;\n" : "=r"(r) : "r"(a), "r"(b), "r"(c));
    return r;
}
__device__ __forceinline__ uint32_t h2_add(uint32_t a, uint32_t b) {
    uint32_t r;
    asm("add.rn.f16x2 %0, %1, %2;\n" : "=r"(r) : "r"(a), "r"(b));
    return r;
}
__device__ __forceinline__ uint32_t pack_f16(float lo, float hi) {
    uint32_t r;
    asm("cvt.rn.f16x2.f32 %0, %1, %2;\n" : "=r"(r) : "f"(hi), "f"(lo));
    return r;
}
__device__ __forceinline__ float h_lo(uint32_t v) { return __low2float(*reinterpret_cast<const __half2*>(&v)); }
__device__ __forceinline__ float h_hi(uint32_t v) { return __high2float(*reinterpret_cast<const __half2*>(&v)); }
__device__ __forceinline__ uint32_t bf2_to_h2(uint32_t v) { return (v & 0x7fff7fffu) * 7u + v; }
__device__ __forceinline__ uint32_t prmt(uint32_t a, uint32_t b, uint32_t sel) {
    uint32_t r;
    asm("prmt.b32 %0, %1, %2, %3;\n" : "=r"(r) : "r"(a), "r"(b), "r"(sel));
    return r;
}
__device__ __forceinline__ uint32_t bitsel(uint32_t a, uint32_t b, uint32_t m) {
    uint32_t r;
    asm("lop3.b32 %0, %1, %2, %3, 0xd8;\n" : "=r"(r) : "r"(a), "r"(b), "r"(m));
    return r;
}
constexpr float KAPPA = 0.3292034911525734f;
constexpr uint32_t GELU_C2 = 0x40d940d9u;
constexpr float HSCALE = 1.0f / (2.0f * KAPPA);
__device__ __forceinline__ float w2_scale(uint32_t m) { return __uint_as_float((257u - max(m >> 23, 16u)) << 23); }
__device__ __forceinline__ void sched_break(int zero) {
    asm volatile("{\n.reg .pred p;\nsetp.ne.s32 p, %0, 0;\nSB_LOOP:\n@p nanosleep.u32 1;\n@p bra SB_LOOP;\n}\n" ::"r"(zero));
}

#define ACC8(d, o) "+r"(d[o + 0]), "+r"(d[o + 1]), "+r"(d[o + 2]), "+r"(d[o + 3]), "+r"(d[o + 4]), "+r"(d[o + 5]), "+r"(d[o + 6]), "+r"(d[o + 7])

__device__ __forceinline__ void mma_rs_n128(uint32_t (&d)[32], const uint32_t (&a)[4], uint32_t desc, int scale_d) {
    asm volatile(
        "{\n.reg .pred p;\n.reg .b64 db;\nsetp.ne.b32 p, %37, 0;\nmov.b64 db, {%36, 0x40000040};\n"
        "wgmma.mma_async.sync.aligned.m64n128k16.f16.f16.f16 "
        "{%0,%1,%2,%3,%4,%5,%6,%7,%8,%9,%10,%11,%12,%13,%14,%15,"
        "%16,%17,%18,%19,%20,%21,%22,%23,%24,%25,%26,%27,%28,%29,%30,%31},"
        "{%32,%33,%34,%35}, db, p, 1, 1, 0;\n}\n"
        : ACC8(d, 0), ACC8(d, 8), ACC8(d, 16), ACC8(d, 24)
        : "r"(a[0]), "r"(a[1]), "r"(a[2]), "r"(a[3]), "r"(desc), "r"(scale_d));
}

__device__ __forceinline__ void mma_ss_n128(uint32_t (&d)[32], uint32_t da, uint32_t db, int scale_d) {
    asm volatile(
        "{\n.reg .pred p;\n.reg .b64 da, db;\nsetp.ne.b32 p, %34, 0;\nmov.b64 da, {%32, 0x40000040};\nmov.b64 db, {%33, 0x40000040};\n"
        "wgmma.mma_async.sync.aligned.m64n128k16.f16.f16.f16 "
        "{%0,%1,%2,%3,%4,%5,%6,%7,%8,%9,%10,%11,%12,%13,%14,%15,"
        "%16,%17,%18,%19,%20,%21,%22,%23,%24,%25,%26,%27,%28,%29,%30,%31},"
        "da, db, p, 1, 1, 1, 0;\n}\n"
        : ACC8(d, 0), ACC8(d, 8), ACC8(d, 16), ACC8(d, 24)
        : "r"(da), "r"(db), "r"(scale_d));
}

__device__ __forceinline__ void mma_rs_n192(uint32_t (&d)[48], const uint4& a, uint32_t db) {
    asm volatile(
        "{\n.reg .b64 db;\nmov.b64 db, {%52, 16};\n"
        "wgmma.mma_async.sync.aligned.m64n192k16.f16.f16.f16 "
        "{%0,%1,%2,%3,%4,%5,%6,%7,%8,%9,%10,%11,%12,%13,%14,%15,"
        "%16,%17,%18,%19,%20,%21,%22,%23,%24,%25,%26,%27,%28,%29,%30,%31,"
        "%32,%33,%34,%35,%36,%37,%38,%39,%40,%41,%42,%43,%44,%45,%46,%47},"
        "{%48,%49,%50,%51}, db, 1, 1, 1, 0;\n}\n"
        : ACC8(d, 0), ACC8(d, 8), ACC8(d, 16), ACC8(d, 24), ACC8(d, 32), ACC8(d, 40)
        : "r"(a.x), "r"(a.y), "r"(a.z), "r"(a.w), "r"(db));
}

constexpr int P1_SPLIT = 5;
constexpr int P1_SLOT = LN_TILE / 6, P1_NST = 6;
constexpr int P1_W = 64 * C_DIM * 2;
constexpr int P1_X = 32 * C_DIM * 2;
constexpr int P1_OFF_W = LN_TILE;
constexpr int P1_OFF_X = P1_OFF_W + 2 * P1_W;
constexpr int P1_OFF_BAR = 227328;
constexpr int P1_OFF_TILE = P1_OFF_BAR + (2 * P1_NST + 4 + 4 + 4) * 8;
constexpr int P1_OFF_EX = P1_OFF_TILE + 64;
constexpr int P1_OFF_DW = P1_OFF_EX + 256 * 4;
constexpr int OFF_PRE = P1_OFF_DW + C_DIM * 2;
constexpr int SMEM_BYTES = OFF_PRE + C_DIM * 4 + 16;

__device__ __forceinline__ float rsqrt_fast(float x) {
    float r;
    asm("rsqrt.approx.ftz.f32 %0, %1;\n" : "=f"(r) : "f"(x));
    return r;
}
__device__ __forceinline__ float row_sum(const uint32_t (&c)[4]) {
    const uint32_t u = bf2_add(bf2_add(c[0], c[1]), bf2_add(c[2], c[3]));
    float s = bf_lo(u) + bf_hi(u);
#pragma unroll
    for (int o = 1; o < 8; o <<= 1) s += __shfl_xor_sync(0xffffffffu, s, o);
    return s;
}
__device__ __forceinline__ uint32_t pace(uint32_t bar, uint32_t off, uint32_t val, int zero) {
    asm volatile(
        "{\n.reg .pred p, q;\n.reg .b32 par;\n"
        "lop3.b32 par, %0, %2, %3, 0xea;\n"
        "setp.eq.u32 q, par, 0;\n"
        "mov.pred p, 0;\n"
        "@q mbarrier.test_wait.parity.shared::cta.b64 p, [%1], par;\n"
        "selp.u32 par, 1, 0, p;\n"
        "@q mbarrier.try_wait.parity.shared::cta.b64 p, [%1], par, 1000;\n"
        "@p or.b32 %0, %0, %2;\n"
        "}\n" : "+r"(val) : "r"(bar), "r"(zero), "r"(off));
    return val;
}
__device__ __forceinline__ void ln_row(uint32_t (&v)[6][4], const uint32_t (&d)[6][4], uint32_t bar, uint32_t off, int zero, uint32_t bar_read) {
    const float inv = 1.0f / C_DIM;
    uint32_t c[4];
#pragma unroll
    for (int i = 0; i < 6; i++)
#pragma unroll
        for (int k = 0; k < 4; k++) c[k] = bf2_fma(v[i][k], d[i][k], i ? c[k] : 0);
    const float m = row_sum(c) * inv;
    uint32_t nm = pack_bf16(-m, -m);
    const float e = m + bf_lo(nm);
    if (bar_read) mbar_arrive(bar_read + (nm & zero));
    nm = pace(bar, off, nm, zero);
#pragma unroll
    for (int i = 0; i < 6; i++) {
#pragma unroll
        for (int k = 0; k < 4; k++) {
            v[i][k] = bf2_fma(v[i][k], d[i][k], nm);
            c[k] = i ? bf2_fma(v[i][k], v[i][k], c[k]) : bf2_mul(v[i][k], v[i][k]);
        }
    }
    float r = KAPPA * rsqrt_fast(fmaxf(fmaf(-e, e, row_sum(c) * inv), 0.f) + 1e-5f);
    const float er = -e * r * 0x1p-112f;
    if (__any_sync(0xffffffffu, r < 0x1p-8f)) {
        const uint32_t p2 = __float_as_uint(r) & 0x7f800000u;
        r = __uint_as_float((__float_as_uint(r) & 0x007fffffu) | 0x3f800000u);
#pragma unroll
        for (int i = 0; i < 6; i++)
#pragma unroll
            for (int k = 0; k < 4; k++) v[i][k] = bf2_mul(v[i][k], p2 | p2 >> 16);
    }
    const uint32_t rs = pack_bf16(r * 0x1p-112f, r * 0x1p-112f), sh = pack_bf16(er, er);
#pragma unroll
    for (int i = 0; i < 6; i++)
#pragma unroll
        for (int k = 0; k < 4; k++) v[i][k] = bf2_to_h2(bf2_fma(v[i][k], rs, sh));
}

template <int R>
__device__ __forceinline__ uint32_t gelu2(uint32_t a, uint32_t sc2) {
    uint32_t y, t;
    if (R) asm("{\n.reg .b16 l, h;\n.reg .b32 f;\nmov.b32 {l, h}, %2;\nmov.b32 f, {h, h};\nmul.rn.f16x2 %0, %1, f;\n}\n" : "=r"(y) : "r"(a), "r"(sc2));
    else asm("{\n.reg .b16 l, h;\n.reg .b32 f;\nmov.b32 {l, h}, %2;\nmov.b32 f, {l, l};\nmul.rn.f16x2 %0, %1, f;\n}\n" : "=r"(y) : "r"(a), "r"(sc2));
    asm("tanh.approx.f16x2 %0, %1;\n" : "=r"(t) : "r"(h2_mul(y, h2_fma(y, y, GELU_C2))));
    return h2_fma(a, t, a);
}
constexpr uint32_t SPARE = 0x40074007u;
constexpr float UNCHOP = 1.0023f;

__device__ __forceinline__ uint32_t p1_exponents(float (&t)[2], uint32_t (&ex)[2], uint32_t saddr, int lane) {
#pragma unroll
    for (int r = 0; r < 2; r++) {
        t[r] += __shfl_xor_sync(0xffffffffu, t[r], 1);
        t[r] += __shfl_xor_sync(0xffffffffu, t[r], 2);
        ex[r] = min(max(((__float_as_uint(193.3f * t[r]) >> 23) + 127u) >> 1, 72u), 198u);
        asm volatile("st.shared.u32 [%0], %1;\n" ::"r"(saddr + r * 32), "r"(ex[r] << 23) : "memory");
    }
    return pack_f16(__uint_as_float(min(ex[0], 142u) << 23), __uint_as_float(min(ex[1], 142u) << 23));
}
template <int N>
__device__ __forceinline__ void p1_convert(uint32_t (&o)[N][4], uint32_t (&v)[N][4], const uint32_t (&ex)[2]) {
    if (__any_sync(0xffffffffu, max(ex[0], ex[1]) > 141u)) {
#pragma unroll
        for (int k = 0; k < 4 * N; k++) v[k >> 2][k & 3] = bf2_mul(v[k >> 2][k & 3], ex[k & 1] > 141u ? 0x1f801f80u : 0x3f803f80u);
    }
#pragma unroll
    for (int k = 0; k < 4 * N; k++) {
        const uint32_t u = bf2_mul(v[k >> 2][k & 3], ((ex[k & 1] > 141u ? 206u : 142u) - ex[k & 1]) * 0x00800080u);
        asm volatile("mad.lo.u32 %0, %1, 7, %2;\n" : "=r"(o[k >> 2][k & 3]) : "r"(u & 0x7fff7fffu), "r"(u));
    }
}
template <int N>
__device__ __forceinline__ void p1_squares(const uint32_t (&v)[N][4], float (&t)[2]) {
#pragma unroll
    for (int j = 0; j < N / 2; j++) {
        const int r = j & 1, b = (j >> 1) * 4;
        uint32_t c = bf2_mul(v[b][r], v[b][r]);
#pragma unroll
        for (int k = 1; k < 8; k++) c = bf2_fma(v[b + k / 2][r + (k & 1) * 2], v[b + k / 2][r + (k & 1) * 2], c);
        t[r] += bf_lo(c) + bf_hi(c);
    }
}
__device__ __forceinline__ void p1_epilogue(const uint32_t (&acc)[2][32], const uint32_t (&sc2)[2], float (&ssq)[4], uint8_t* hp, int zero) {
    uint32_t sq[2], h[16][4];
#pragma unroll
    for (int i2 = 0; i2 < 9; i2++) {
#pragma unroll
        for (int c = 2 * i2 - 2; c < 2 * i2; c++) {
            if (c >= 0 && (c & 3)) {
                uint32_t o[4];
#pragma unroll
                for (int u = 0; u < 4; u++) {
                    const uint32_t v = h[c & 12][u];
                    o[u] = bitsel(h[c][u], (c & 3) == 2 ? prmt(v, v, 0xa381) : prmt(v >> 3, v, (c & 3) == 1 ? 0x6240 : 0xf3d1), SPARE);
                }
                stg128_cs(hp + (c >> 3) * 2 * H_STEP + ((c >> 2) & 1) * H_HALF + ((c & 3) - 1) * 512, o[0], o[1], o[2], o[3]);
            }
        }
        if (i2 < 8) {
#pragma unroll
            for (int u = 0; u < 4; u++) {
                h[2 * i2][u] = gelu2<0>(acc[i2 >> 2][8 * (i2 & 3) + 2 * u], sc2[i2 >> 2]);
                h[2 * i2 + 1][u] = gelu2<1>(acc[i2 >> 2][8 * (i2 & 3) + 2 * u + 1], sc2[i2 >> 2]);
#pragma unroll
                for (int r = 0; r < 2; r++) {
                    const uint32_t v = h[2 * i2 + r][u];
                    sq[r] = ((i2 & 3) | u) ? h2_fma(v, v, sq[r]) : h2_mul(v, v);
                }
            }
            if ((i2 & 3) == 3) {
#pragma unroll
                for (int r = 0; r < 2; r++) ssq[(i2 >> 2) * 2 + r] += h_lo(sq[r]) + h_hi(sq[r]);
            }
            sched_break(zero);
        }
    }
}
template <int WG>
__device__ __forceinline__ void p1_mma(uint32_t (&acc)[2][32], const uint32_t (&a)[24][4], uint32_t sbase, uint32_t empty_remote, int i, int lane, bool pass) {
    const uint32_t bar_full = sbase + P1_OFF_BAR;
    const uint32_t db = (uint32_t)make_desc(sbase, 16, 1024), da = db + (P1_OFF_W + WG * P1_W) / 16;
    if (WG == 0) mbar_wait(bar_full, i & 1);
    bar_sync(1 + WG, 256);
    TRACE(WG, i, 1);
    wg_fence();
#pragma unroll
    for (int k = 0; k < 24; k++) {
        if (WG == 0 && k && k % 4 == 0) mbar_wait(bar_full + (k >> 2) * 8, i & 1);
        mma_rs_n128(acc[0], a[k], db + (k >> 2) * 1024 + (k & 3) * 2, k != 0);
        mma_ss_n128(acc[1], da + k * 128, db + (k >> 2) * 1024 + (k & 3) * 2, k != 0);
        if (k == 23 && pass) bar_arrive(2 - WG, 256);
        if (k == 23 || (WG == 1 && k % 4 == 3)) wg_commit();
        if (WG == 1 && k % 4 == 3 && k > 3) {
            wg_wait<1>();
            if (lane < 2) mbar_arrive_cluster(empty_remote + ((k >> 2) - 1) * 8);
        }
    }
    TRACE(WG, i, 2);
    wg_wait<0>();
    if (WG == 1 && lane < 2) mbar_arrive_cluster(empty_remote + 5 * 8);
}
__device__ __forceinline__ bool p1_consumer(const uint32_t (&a)[24][4], const uint32_t (&sc2)[2], uint32_t sbase, int WG, int w, int lane, int zero) {
    const uint32_t bar_full = sbase + P1_OFF_BAR, bar_empty = bar_full + P1_NST * 8;
    const uint32_t empty_remote = mapa(bar_empty, lane & 1);
    const uint32_t bar_pace = bar_empty + P1_NST * 8 + 32 + w * 8;
    const int g = lane >> 2, q = lane & 3, half = WG ^ ((blockIdx.x / GRP_CTAS) & 1), cb = (blockIdx.x % GRP_CTAS) * 4 + half * 2;
    uint32_t acc[2][32];
    float ssq[4] = {0.f, 0.f, 0.f, 0.f};
    TSTAMP(0, 1);

    uint8_t* hp = reinterpret_cast<uint8_t*>(g_h) + ((cb * 2 + (w >> 1)) * H_STEP + (w & 1) * 1536) + g * 64 + (q ^ (g >> 1)) * 16;
    int i = 0;
    uint32_t more = 3, both;
#pragma unroll 1
    for (;; i++) {
        TRACE(WG, i, 0);
        both = more & 2;
        if (WG == 0) p1_mma<0>(acc, a, sbase, empty_remote, i, lane, both);
        else p1_mma<1>(acc, a, sbase, empty_remote, i, lane, true);
        TRACE(WG, i, 4);
        int step;
        asm volatile("ld.shared.v2.u32 {%0, %1}, [%2];\n" : "=r"(step), "=r"(more) : "r"(sbase + P1_OFF_TILE + (i & 3) * 16) : "memory");
        hp += step;
        if (!(more >> WG & 1) && lane == 0) asm volatile("red.relaxed.gpu.global.add.u32 [%0], 1;\n" ::"l"(g_prog[CNT_LAST]) : "memory");
        p1_epilogue(acc, sc2, ssq, hp, zero);
        if (lane == 0) mbar_arrive(bar_pace);
        if (more & 4) {
            asm volatile("fence.proxy.async.global;\n" ::: "memory");
            bar_arrive(8, 288);
            bar_arrive(9, 288);
        }
        if (!(more >> WG & 1)) break;
    }
    TSTAMP(0, 21);
    if (WG == 0 && both) bar_sync(1, 256);
#pragma unroll
    for (int r = 0; r < 4; r++) {
        ssq[r] += __shfl_xor_sync(0xffffffffu, ssq[r], 1);
        ssq[r] += __shfl_xor_sync(0xffffffffu, ssq[r], 2);
    }
    const float t = q == 0 ? ssq[0] : q == 1 ? ssq[1] : q == 2 ? ssq[2] : ssq[3];
    atomicAdd(&g_sq[cb * 64 + (q >> 1) * 64 + w * 16 + (q & 1) * 8 + g], (1ull << 56) + __float2ull_rn(fminf(t, 0x1p19f) * 0x1p32f));
    asm volatile("fence.proxy.async.global;\n" ::: "memory");
    bar_arrive(3, 288);
    asm volatile("barrier.cluster.arrive.relaxed.aligned;\n" ::: "memory");
    return WG ? more & 1 : both;
}

__device__ __forceinline__ void p2_init(uint32_t sbase);
template <int ROLE>
__device__ __forceinline__ bool pass1(const CUtensorMap& wmap, const __nv_bfloat16* __restrict__ x, const __nv_bfloat16* __restrict__ dw,
                                      const __nv_bfloat16* __restrict__ w2, const __nv_bfloat16* __restrict__ grn_b, uint32_t sbase,
                                      int warp, int lane, int zero) {
    const uint32_t bar_full = sbase + P1_OFF_BAR, bar_empty = bar_full + P1_NST * 8, bar_w = bar_empty + P1_NST * 8;
    const uint32_t rank = cluster_rank();
    const int cig = blockIdx.x % GRP_CTAS;
    uint8_t* const ring = reinterpret_cast<uint8_t*>(g_ln);

    TSTAMP(0, 0);
    TRACEW(110 + warp, 0);
    const uint32_t bar_pace = bar_w + 32, bar_xfull = bar_pace + 32, bar_xempty = bar_xfull + 8, bar_done = bar_xfull + 16;
    const int ln0 = blockIdx.x >> 2, first = blockIdx.x / GRP_CTAS;
    const uint8_t* xsrc = reinterpret_cast<const uint8_t*>(x) + (size_t)blockIdx.x * P1_X;

    if (ROLE == 2) {
        reg_dec<32>();
        asm volatile("barrier.cluster.arrive.relaxed.aligned;\n" ::: "memory");
        asm volatile("barrier.cluster.wait.aligned;\n" ::: "memory");
        if (warp == 12) {
            int prev = 0, t = first;
            const uint32_t rbase = mapa(sbase, lane & 1);
#pragma unroll 1
            for (int i = 0; t < NT128; i++) {
                const int round = t / LN_RING, slot = t - round * LN_RING;
                const uint8_t* src = ring + slot * LN_TILE + rank * (P1_SLOT / 2);
                int next = 0;
                if (rank == 0 && lane == 0) {
                    next = t < NT128 - P1_SPLIT ? NGRP + atomicAdd(&g_flag[LN_RING + (cig >> 1)][0][0], 1u) : 2 * NT128;
                    if (next >= NT128 - P1_SPLIT && next < 2 * NT128) next = NT128 - P1_SPLIT + atomicAdd(&g_flag[LN_RING + 3 + (cig >> 1)][first & 1][0], 1u);
                }
                flag_wait<true>(&g_flag[slot][0][0], 4 * round + 4);
                TRACEW(i, 2);
                asm volatile("fence.proxy.async.global;\n" ::: "memory");
                next = __shfl_sync(0xffffffffu, next, 0);
#pragma unroll 1
                for (int h = 0; h < P1_NST; h++) {
                    mbar_wait(bar_empty + h * 8, i & 1);
                    if (h == 0) TRACEW(i, 4);
                    if (h == 5) TRACEW(i, 5);
                    if (elect_one()) {
                        mbar_expect_tx(bar_full + h * 8, h ? P1_SLOT : P1_SLOT + 16);
                        bulk_g2s_mc(sbase + h * P1_SLOT + rank * (P1_SLOT / 2), src + h * P1_SLOT, P1_SLOT / 2, bar_full + h * 8, (uint16_t)3);
                    }
                    __syncwarp();
                    if (h == 0 && rank == 0 && lane < 2)
                        asm volatile("st.async.shared::cluster.mbarrier::complete_tx::bytes.v4.u32 [%0], {%1, %2, %3, %3}, [%4];\n"
                                     ::"r"(rbase + P1_OFF_TILE + (i & 3) * 16), "r"((t - prev) * (2 * H_TILE)), "r"((next < NT128 - P1_SPLIT ? 3 : next < NT128) + (t < NT_EARLY && next >= NT_EARLY ? 4 : 0)), "r"(next),
                                       "r"(rbase + P1_OFF_BAR) : "memory");
                }
                prev = t;
                t = next;
                if (rank != 0) {
                    mbar_wait(bar_full, i & 1);
                    asm volatile("ld.shared.u32 %0, [%1];\n" : "=r"(t) : "r"(sbase + P1_OFF_TILE + (i & 3) * 16 + 8) : "memory");
                }
            }
        } else if (warp == 13) {
            int ph = 0;
            unsigned target = 0;
#pragma unroll 1
            for (int i = ln0 + LN_STEP; i < NT128; i += LN_STEP, ph ^= 1) {
                target += ph * (GRP_CTAS / 2);
                xsrc += (size_t)NUM_CTAS * P1_X;
                mbar_wait(bar_xempty, ph);
                if (elect_one()) {
                    mbar_expect_tx(bar_xfull, P1_X);
                    bulk_g2s(sbase + P1_OFF_X, xsrc, P1_X, bar_xfull);
                }
                __syncwarp();
                const uint32_t off = flag_wait<false>(&g_flag[ln0 + (ph ^ 1) * LN_STEP][1][0], target);
                mbar_wait(bar_done, ph);
                if (elect_one()) {
                    asm volatile("st.shared.u32 [%0], %1;\n" ::"r"(bar_done + 8), "r"(off) : "memory");
                    mbar_arrive(bar_xfull);
                }
                __syncwarp();
            }
        } else if (warp == 15) {
            int t = first;
            if (rank == 1 && lane == 0) mbar_arrive(bar_empty);
#pragma unroll 1
            for (int i = 0; rank == 1 && t < NT128; i++) {
#pragma unroll 1
                for (int h = 0; h < P1_NST; h++) mbar_wait(bar_full + h * 8, i & 1);
                if (lane == 0) asm volatile("red.relaxed.gpu.global.add.u32 [%0], 1;\n" ::"l"(&g_flag[t % LN_RING][1][0]) : "memory");
                asm volatile("ld.shared.u32 %0, [%1];\n" : "=r"(t) : "r"(sbase + P1_OFF_TILE + (i & 3) * 16 + 8) : "memory");
                if (lane == 0) mbar_arrive(bar_empty);
                TRACEW(i, 3);
            }
            if (rank == 0) {
                mbar_wait(bar_full, 0);
                TRACEW(110 + warp, 3);
                mbar_wait(bar_full, 1);
                float* sums = g_sums;
                unsigned* flag = reinterpret_cast<unsigned*>(sums + C_DIM);
                if (blockIdx.x == 0) reinterpret_cast<uint2*>(g_half)[lane] = make_uint2(0, 0);
                if (blockIdx.x == 2 && lane < NUM_CNT) g_prog[lane][0] = 0;
                if (blockIdx.x < 96) g_redo[blockIdx.x * 16 + lane] = 0.f;
                float gs = 0.f;
#pragma unroll 1
                for (int pass = 0; pass < 2; pass++) {
                    float mx = 0.f;
#pragma unroll 1
                    for (int it = first; it < 96; it += NGRP) {
                        const int nb = it % 12, k0 = (cig * 4 + it / 12) * 64 + (lane >> 2);
                        const uint32_t sc = mapa(sbase + P1_OFF_EX + (k0 & 255) * 4, it / 48);
                        uint32_t* dst = reinterpret_cast<uint32_t*>(g_w2img[0]) + (k0 >> 4) * 3072 + nb * 256 + lane;
                        float bs[8] = {};
#pragma unroll 1
                        for (int c = 0; c < 8; c++) {
                            const uint4 u = __ldg(reinterpret_cast<const uint4*>(w2 + (size_t)(k0 + c * 8) * C_DIM + nb * 32) + (lane & 3));
                            const float b = __bfloat162float(grn_b[k0 + c * 8]);
                            float t;
                            asm volatile("ld.shared::cluster.f32 %0, [%1];\n" : "=f"(t) : "r"(sc + c * 32) : "memory");
                            if (nb == 0) g_scale[k0 + c * 8] = t;
#pragma unroll
                            for (int j = 0; j < 4; j++) {
                                const uint32_t v = j == 0 ? u.x : j == 1 ? u.y : j == 2 ? u.z : u.w;
                                mx = fmaxf(mx, fmaxf(fabsf(bf_lo(v)), fabsf(bf_hi(v))) * t);
                                if (pass) {
                                    bs[2 * j] = fmaf(b, bf_lo(v), bs[2 * j]);
                                    bs[2 * j + 1] = fmaf(b, bf_hi(v), bs[2 * j + 1]);
                                    uint32_t h = pack_f16(bf_lo(v) * t * gs, bf_hi(v) * t * gs);
                                    asm volatile("movmatrix.sync.aligned.m8n8.trans.b16 %0, %0;\n" : "+r"(h));
                                    dst[(c >> 1) * 3072 + (c & 1) * 32 + j * 64] = h;
                                }
                            }
                        }
                        if (pass) {
#pragma unroll
                            for (int j = 0; j < 8; j++) {
#pragma unroll
                                for (int o = 4; o < 32; o <<= 1) bs[j] += __shfl_xor_sync(0xffffffffu, bs[j], o);
                                if (lane >> 2 == j) atomicAdd(&sums[nb * 32 + (j >> 1) * 8 + (lane & 3) * 2 + (j & 1)], bs[j]);
                            }
                        }
                    }
                    if (!pass) {
                        const uint32_t m = __reduce_max_sync(0xffffffffu, __float_as_uint(mx));
                        __threadfence();
                        __syncwarp();
                        if (lane == 0) {
                            atomicMax(flag, m);
                            asm volatile("red.release.gpu.global.add.u32 [%0], 1;\n" ::"l"(flag + 32) : "memory");
                        }
                        flag_wait<true>(flag + 32, NUM_CTAS / 2);
                        gs = w2_scale(__ldcg(flag));
                    }
                }
                asm volatile("fence.proxy.async.global;\nfence.acq_rel.gpu;\n" ::: "memory");
                __syncwarp();
                if (lane == 0) asm volatile("red.relaxed.gpu.global.add.u32 [%0], 1;\n" ::"l"(g_prog[CNT_IMG0]) : "memory");
            }
        } else if (warp == 14) {
            int ph = 0;
#pragma unroll 1
            for (int i = ln0; i < NT128; i += LN_STEP, ph ^= 1) {
                mbar_wait(bar_done, ph);
                TRACEW(i / LN_STEP, 0);
                asm volatile("fence.proxy.async.global;\n" ::: "memory");
                if (elect_one()) asm volatile("red.release.gpu.global.add.u32 [%0], 1;\n" ::"l"(&g_flag[ln0 + ph * LN_STEP][0][0]) : "memory");
                __syncwarp();
                TRACEW(i / LN_STEP, 1);
            }
            if (lane == 0) p2_init(sbase);
#pragma unroll 1
            for (int i = CNT_EARLY; i >= CNT_H; i--) {
                bar_sync(i == CNT_EARLY ? 8 : 3, 288);
                asm volatile("fence.proxy.async.global;\n" ::: "memory");
                if (lane == 0) asm volatile("red.release.gpu.global.add.u32 [%0], 1;\n" ::"l"(&g_prog[i][0]) : "memory");
                __syncwarp();
            }
        }
        __syncwarp();
        asm volatile("barrier.cluster.arrive.relaxed.aligned;\n" ::: "memory");
        return false;
    } else if (ROLE == 1) {
        reg_dec<96>();
        asm volatile("barrier.cluster.arrive.relaxed.aligned;\n" ::: "memory");
        {
            const int l8 = lane & 7, row = (warp - 8) * 4 + (lane >> 3), px = (blockIdx.x & 3) * 32 + row;
            uint32_t d[6][4];
            const int n = (px & 64) + perm32(2 * row + ((px >> 5) & 1));
            uint8_t* const dst0 = ring + ln0 * LN_TILE + n * 128 + ((l8 ^ (n & 7)) << 4);
            const uint32_t src = sbase + P1_OFF_X + ((warp - 8) * 8 + (lane >> 3)) * (C_DIM * 2) + l8 * 16;
            int ph = 0;
#pragma unroll 1
            for (int i = ln0; i < NT128; i += LN_STEP, ph ^= 1) {
                TRACE(2, i / LN_STEP, 0);
                uint32_t off = 1;
#pragma unroll 1
                for (int ps = i == ln0 ? -2 : 0; ps < 2; ps += ps < 0 ? 2 : 1) {
                    if (ps == 0) {
                        if (i == ln0) asm volatile("barrier.cluster.wait.aligned;\n" ::: "memory");
                        mbar_wait(bar_xfull, ph);
                        asm volatile("ld.shared.u32 %0, [%1];\n" : "=r"(off) : "r"(bar_done + 8) : "memory");
                    }
                    if (ps == 0) TRACE(2, i / LN_STEP, 1);
                    if (i == ln0) {
#pragma unroll
                        for (int j = 0; j < 6; j++)
                            asm volatile("ld.shared.v4.u32 {%0,%1,%2,%3}, [%4];\n"
                                         : "=r"(d[j][0]), "=r"(d[j][1]), "=r"(d[j][2]), "=r"(d[j][3]) : "r"(sbase + P1_OFF_DW + j * 128 + l8 * 16) : "memory");
                    }
                    uint32_t v[6][4];
#pragma unroll
                    for (int j = 0; j < 6; j++)
                        asm volatile("ld.shared.v4.u32 {%0,%1,%2,%3}, [%4];\n"
                                     : "=r"(v[j][0]), "=r"(v[j][1]), "=r"(v[j][2]), "=r"(v[j][3]) : "r"(src + (ps & 1) * (4 * C_DIM * 2) + j * 128) : "memory");
                    ln_row(v, d, bar_pace + (warp - 8) * 8, off, zero, ps == 1 && lane == 0 ? bar_xempty : 0);
                    uint8_t* dst = dst0 + ph * (LN_STEP * LN_TILE) + (ps & 1) * 4096;
#pragma unroll
                    for (int j = 0; j < 6; j++) *reinterpret_cast<uint4*>(dst + j * 16384) = make_uint4(v[j][0], v[j][1], v[j][2], v[j][3]);
                    TRACE(2, i / LN_STEP, 3 + (ps & 1));
                }
                asm volatile("fence.proxy.async.global;\nfence.acq_rel.cta;\n" ::: "memory");
                __syncwarp();
                if (lane == 0) mbar_arrive(bar_done);
                TRACE(2, i / LN_STEP, 5);
                TRACE(2, i / LN_STEP, 2);
            }
        }
        __syncwarp();
        asm volatile("barrier.cluster.arrive.relaxed.aligned;\n" ::: "memory");
        return false;
    } else {
        const int wg = warp >> 2, w = warp & 3;
        auto load_w = [&](int i0, int i1) {
#pragma unroll 1
            for (int i = i0; i < i1; i++) {
                if (!(i & 1)) mbar_expect_tx(bar_w + (i >> 1) * 8, P1_W);
                tma2(sbase + (i & 2) * P1_W + (i >> 2) * P1_W + (i & 1) * (P1_W / 2), &wmap, cig * 256 + ((i >> 1) ^ (first & 1) * 2) * 64, (i & 1) * 192, bar_w + (i >> 1) * 8);
            }
        };
        if (warp == 4 && elect_one()) {
            mbar_init(bar_xfull, 2);
#pragma unroll
            for (int i = 0; i < 4; i++) mbar_init(bar_w + i * 8, 1);
            asm volatile("fence.mbarrier_init.release.cluster;\n" ::: "memory");
            mbar_expect_tx(bar_xfull, P1_X + C_DIM * 2);
            bulk_g2s(sbase + P1_OFF_X, xsrc, P1_X, bar_xfull);
            bulk_g2s(sbase + P1_OFF_DW, dw, C_DIM * 2, bar_xfull);
            load_w(0, 4);
            asm volatile("st.shared.u32 [%0], 1;\n" ::"r"(bar_done + 8) : "memory");
            mbar_arrive(bar_xfull);
        }
        if (warp == 5 && elect_one()) {
#pragma unroll
            for (int i = 0; i < P1_NST; i++) {
                mbar_init(bar_full + i * 8, 1);
                mbar_init(bar_empty + i * 8, i ? 8 : 8 + rank);
                if (i < 4) mbar_init(bar_pace + i * 8, 1);
            }
            mbar_init(bar_xempty, 4);
            mbar_init(bar_done, 4);
            asm volatile("fence.mbarrier_init.release.cluster;\n" ::: "memory");
        }
        __syncwarp();
        asm volatile("barrier.cluster.arrive.relaxed.aligned;\n" ::: "memory");
        reg_inc<192>();
        TRACEW(110 + warp, 1);
        uint32_t a[24][4];
        const uint32_t src = sbase + wg * P1_W + ((lane >> 4) * 8 + (lane & 7)) * 128 + (((2 * w + ((lane >> 3) & 1)) ^ (lane & 7)) << 4);
        const uint32_t s_ex = sbase + P1_OFF_EX + ((wg ^ (first & 1)) * 128 + w * 16 + (lane >> 2)) * 4;
        uint32_t sc2[2], ex[2];
        if (wg == 1) bar_arrive(1, 256);
#pragma unroll 1
        for (int it = 0; it < 2; it++) {
          if (it != wg) asm volatile("barrier.cluster.wait.aligned;\n" ::: "memory");
          if (it < wg) {
              for (int n = 0; n < 64 && !mbar_test(bar_xfull, 0); n++) __nanosleep(40);
              if (w == 0 && elect_one()) load_w(4, 8);
              __syncwarp();
          }
          if (it || wg == 0) {
            float t[2] = {0.f, 0.f};
            if (it) {
                TRACEW(110 + warp, 2);
                mbar_wait(bar_w + wg * 16, 0);
            }
            TRACEW(110 + warp, 5);
#pragma unroll
            for (int k = 0; k < 24; k++) ldsm4t(a[k], src + k * 2048);
            TRACEW(110 + warp, 6);
            p1_squares(a, t);
            sc2[0] = p1_exponents(t, ex, s_ex, lane);
            if (it && lane < 6) mbar_arrive_cluster(mapa(bar_empty, lane & 1) + (wg * 3 + (lane >> 1)) * 8 + (sc2[0] & zero));
            p1_convert<24>(a, a, ex);
          }
          if (it || wg == 1) {
            float t[2] = {0.f, 0.f};
            TRACEW(100 + warp, 0);
            if (it) mbar_wait(bar_w + wg * 16 + 8, 0);
            TRACEW(100 + warp, 1);
            uint32_t v[8][4], o[8][4];
#pragma unroll 1
            for (int j = 0; j <= 2 * it; j++) {
#pragma unroll
                for (int k = 0; k < 8; k++) ldsm4t(v[k], src + P1_OFF_W + (8 * j + k) * 2048);
                p1_squares(v, t);
            }
            sc2[1] = p1_exponents(t, ex, s_ex + 256, lane);
#pragma unroll 1
            for (int j = 2 * it; j >= 0; j--) {
                p1_convert<8>(o, v, ex);
#pragma unroll
                for (int k = 0; k < 8; k++) {
                    if (j) ldsm4t(v[k], src + P1_OFF_W + (8 * j - 8 + k) * 2048);
                    if (it) asm volatile("stmatrix.sync.aligned.m8n8.x4.trans.shared.b16 [%0], {%1,%2,%3,%4};\n"
                                         ::"r"(src + P1_OFF_W + (8 * j + k) * 2048), "r"(o[k][0]), "r"(o[k][1]), "r"(o[k][2]), "r"(o[k][3]) : "memory");
                }
            }
          }
        }
        asm volatile("fence.proxy.async.shared::cta;\n" ::: "memory");
        TRACEW(110 + warp, 7);
        bar_sync(6 + wg, 128);
        const bool early = p1_consumer(a, sc2, sbase, wg, w, lane, zero);
        TSTAMP(0, 30);
        return early;
    }
}

constexpr int P2_B = 24576, P2_NB = 4;
constexpr int P2_A = 3072, P2_NA = 8;
constexpr int P2_XROW = C_DIM * 2;
constexpr int P2_OFF_A = P2_B * P2_NB;
constexpr int P2_OFF_X = P2_OFF_A + 3 * P2_NA * P2_A + 128;
constexpr int P2_LHALF = 2 * P2_NA * P2_A + 64;
constexpr int P2_XHALF = 32 * P2_XROW + 64;
constexpr int P2_OFF_GRN = P2_OFF_X + 64 * P2_XROW + 128;
constexpr int P2_OFF_BIAS = P2_OFF_GRN + HID * 2;
constexpr int P2_OFF_RED = P2_OFF_BIAS + C_DIM * 4;
constexpr int P2_OFF_BAR = P2_OFF_RED + 192;
constexpr int P2_SMEM = P2_OFF_BAR + (2 * P2_NB + 6 * P2_NA + 7) * 8;
constexpr int P2_S1 = 16, P2_S2 = 32;
constexpr int P2_NCL = NUM_CTAS / 2, P2_ITEMS = NT128 / P2_NCL, P2_SHARED = NT128 - P2_ITEMS * P2_NCL;
constexpr int P2_NPOS = 6 * 48 + P2_S1;
constexpr int P2_RAW = 16;
constexpr int P2_XC = 8 * P2_XROW;
constexpr int P2_T0 = 5;
constexpr int P2_TL = 8;
constexpr int P2_XP0 = 30;
constexpr int P2_XPN = 13;
constexpr int P2_XPD = 3;
constexpr int P2_AH = 2;
__device__ __forceinline__ int p2_start(int n) { return n < 0 ? 0 : n / 3 * 48 + (n % 3 == 1 ? P2_S1 : n % 3 * (P2_S2 / 2)); }
__device__ __forceinline__ int p2_tile(int cl, int n) {
    return n == 0 ? NT_EARLY - 1 - cl : n < 0 ? NT_EARLY + (cl >> 1) : cl + P2_NCL * (n - 1);
}

__device__ __forceinline__ void p2_epilogue(uint32_t (&acc0)[48], uint32_t (&acc1)[48], uint32_t up, uint32_t sx, uint32_t sb, uint8_t* so, int zero) {
    uint32_t v[12][3][4];
    auto load = [&](int t, int j) {
        if (t >= 12) return;
        uint32_t (&w)[4] = v[t][j];
        asm volatile("ld.shared.v4.u32 {%0,%1,%2,%3}, [%4];\n" : "=r"(w[0]), "=r"(w[1]), "=r"(w[2]), "=r"(w[3])
                     : "r"((j ? sx + (j - 1) * 4 * P2_XROW : sb) + t * 64) : "memory");
    };
    auto store = [&](int t, int r) {
        const uint32_t* w = (t < 6 ? acc0 : acc1) + 8 * (t % 6) + 4 * r;
        asm volatile("st.v4.u32 [%4], {%0,%1,%2,%3};\n" ::"r"(w[0]), "r"(w[1]), "r"(w[2]), "r"(w[3]), "l"(so + t * 64 + r * 4 * P2_XROW) : "memory");
    };
#pragma unroll
    for (int j = 0; j < 3; j++) load(0, j);
#pragma unroll
    for (int t = 0; t < 12; t++) {
        load(t + 1, 1);
        load(t + 1, 2);
        load(t + 1, 0);
        uint32_t* acc = (t < 6 ? acc0 : acc1) + 8 * (t % 6);
        uint32_t y[8];
#pragma unroll
        for (int e = 0; e < 8; e++) {
            y[e] = h2_add(acc[e], v[t][0][e >> 1]);
            y[e] = pack_bf16(h_lo(y[e]), h_hi(y[e]));
        }
#pragma unroll
        for (int e = 0; e < 8; e++) acc[(e & 1) * 4 + (e >> 1)] = bf2_fma(y[e], up, v[t][1 + (e & 1)][e >> 1]);
        store(t, 0);
        store(t, 1);
        if (t & 1) sched_break(zero);
    }
}

__device__ __forceinline__ void p2_unpack(uint32_t (&u)[4], uint32_t o1, uint32_t o2, uint32_t o3) {
    u[2] = o1 & ~SPARE;
    u[1] = o2 & ~SPARE;
    u[3] = o3 & ~SPARE;
    const uint32_t t = bitsel(prmt(o1, o2, 0x6341), prmt(o1, o3, 0x6240) << 3, 0x38383838u);
    u[0] = bitsel(t, prmt(o2, o3, 0x7351) << 1, 0x80808080u) & ~SPARE;
}

__device__ __forceinline__ void p2_redo_sums(int warp, int lane) {
    flag_wait<true>(g_prog[CNT_H], NUM_CTAS);
#pragma unroll 1
    for (int s = warp; s < 96; s += 12) {
        float t[2] = {0.f, 0.f};
#pragma unroll 1
        for (int tile = blockIdx.x; tile < 2 * NT128; tile += NUM_CTAS) {
            const uint32_t* p = reinterpret_cast<const uint32_t*>(reinterpret_cast<const uint8_t*>(g_h) + (size_t)(tile >> 1) * (2 * H_TILE) +
                                                                  (s >> 1) * H_STEP + (tile & 1) * H_HALF + (s & 1) * 1536) + lane * 4;
#pragma unroll
            for (int j = 0; j < 4; j++) {
                uint32_t u[4];
                p2_unpack(u, __ldcg(p + j), __ldcg(p + j + 128), __ldcg(p + j + 256));
#pragma unroll
                for (int c = 0; c < 4; c++) t[c >> 1] += h_lo(u[c]) * h_lo(u[c]) + h_hi(u[c]) * h_hi(u[c]);
            }
        }
#pragma unroll
        for (int r = 0; r < 2; r++) {
            const int ch = s * 16 + r * 8 + (lane >> 2);
            atomicAdd(&g_redo[ch], t[r] * (UNCHOP * UNCHOP));
        }
    }
    __threadfence();
    __syncwarp();
    if (lane == 0) asm volatile("red.release.gpu.global.add.u32 [%0], 1;\n" ::"l"(g_prog[CNT_REDO]) : "memory");
    flag_wait<true>(g_prog[CNT_REDO], 12 * NUM_CTAS);
}

static_assert(P2_OFF_GRN >= P1_OFF_X + P1_X && P1_OFF_BAR >= P2_SMEM, "barriers and tables keep their memory");
__device__ __forceinline__ void p2_init(uint32_t sbase) {
    const uint32_t bar = sbase + P2_OFF_BAR;
#pragma unroll 1
    for (int i = 0; i < 2 * P2_NB + 6 * P2_NA + 6; i++) {
        const int j = i - 2 * P2_NB;
        mbar_init(bar + i * 8, j < -P2_NB ? 1 : j < 0 ? 24 : j < 3 * P2_NA ? 1 : j >= 6 * P2_NA && j < 6 * P2_NA + 3 ? 2 : 4);
    }
    asm volatile("st.shared.v2.u32 [%0], {0, 0};\n" ::"r"(bar + (2 * P2_NB + 6 * P2_NA + 6) * 8) : "memory");
    asm volatile("fence.mbarrier_init.release.cluster;\nfence.acq_rel.cta;\n" ::: "memory");
}
template <int ROLE>
__device__ __forceinline__ void pass2(const __nv_bfloat16* __restrict__ x, const __nv_bfloat16* __restrict__ grn_g, __nv_bfloat16* __restrict__ out,
                                      uint8_t* smem, uint32_t sbase, bool early, int zero) {
    const uint32_t bar_bfull = sbase + P2_OFF_BAR, bar_bempty = bar_bfull + P2_NB * 8;
    const uint32_t bar_afull = bar_bempty + P2_NB * 8, bar_aempty = bar_afull + 3 * P2_NA * 8;
    const uint32_t bar_xfull = bar_aempty + 3 * P2_NA * 8, bar_oready = bar_xfull + 24, s_pos = bar_oready + 24;
    int tid;
    asm volatile("mov.u32 %0, %%tid.x;\n" : "=r"(tid));
    const int warp = __shfl_sync(0xffffffffu, tid >> 5, 0), lane = tid & 31;
    const uint32_t rank = cluster_rank();
    const int cl = blockIdx.x >> 1, pair = cl >> 1;
    const int half = pair < P2_SHARED, fin = half && (cl & 1);
    const int k0 = (pair + 3 * (cl & 1)) % 6 * 8;
    auto wait_pos = [&](int target) {
        int v;
        while (true) {
            asm volatile("ld.volatile.shared.u32 %0, [%1];\n" : "=r"(v) : "r"(s_pos) : "memory");
            if (v >= target) break;
            SAFE_BREAK;
            __nanosleep(100);
        }
    };

    TSTAMP(1, 0);
    if (ROLE == 2) {
        if (warp != 14) flag_wait<true>(g_prog[CNT_IMG0], P2_NCL);
        if (warp == 15) {
            float* pre = reinterpret_cast<float*>(smem + OFF_PRE);
            const float gs = w2_scale(__float_as_uint(__ldcg(&g_sums[C_DIM])));
            float mb = 0.f;
#pragma unroll 1
            for (int i = lane; i < C_DIM; i += 32) {
                pre[i] = __ldcg(&g_sums[i]) * gs;
                mb = fmaxf(mb, fabsf(pre[i]));
            }
            pre[C_DIM] = gs;
            pre[C_DIM + 1] = __uint_as_float(__reduce_max_sync(0xffffffffu, __float_as_uint(mb)));
            bar_sync(9, 288);
            flag_wait<false>(g_prog[CNT_LAST], NUM_CTAS * 8);
            bar_arrive(5, 416);
        }
        asm volatile("barrier.cluster.wait.aligned;\nfence.proxy.async;\n" ::: "memory");
        if (warp == 12) {
            const uint8_t* wsrc = reinterpret_cast<const uint8_t*>(g_w2img) + rank * (P2_B / 2);
            int kb = k0;
#pragma unroll 1
            for (int p = 0; p < P2_NPOS; p++) {
                const int st = p & 3;
                if (p == P2_RAW) {
                    flag_wait<true>(g_prog[CNT_IMG1], NUM_CTAS);
                    asm volatile("fence.proxy.async.global;\n" ::: "memory");
                    wsrc += sizeof(g_w2img[0]);
                }
                const int idle = (p < P2_S1 || p >= 6 * 48) + (p < P2_S2 ? !half || p >= 24 : p >= 5 * 48 + P2_S2);
                mbar_wait(bar_bempty + st * 8, (~p >> 2) & 1);
                TR2(3, p, 0);
                if (elect_one()) {
                    mbar_expect_tx(bar_bfull + st * 8, P2_B);
                    bulk_g2s_mc(sbase + st * P2_B + rank * (P2_B / 2), wsrc + kb * P2_B, P2_B / 2, bar_bfull + st * 8, (uint16_t)3);
                    asm volatile("st.volatile.shared.u32 [%0], %1;\n" ::"r"(s_pos), "r"(p) : "memory");
                    if (rank == 0) asm volatile("red.relaxed.gpu.global.add.u32 [%0], 1;\n" ::"l"(g_prog[CNT_POS]) : "memory");
                    if (idle) asm volatile("mbarrier.arrive.shared::cta.b64 _, [%0], %1;\n" ::"r"(bar_bempty + st * 8), "r"(8 * idle) : "memory");
                }
                __syncwarp();
                if (++kb == 48) kb = 0;
            }
            mbar_wait(bar_bempty, 1);
            if (lane == 0) mbar_arrive(bar_bfull);
        } else if (warp == 13) {
            const int w = lane % 3;
            const uint32_t dst0 = sbase + P2_OFF_A + w * P2_NA * P2_A;
            const uint32_t bf = bar_afull + w * P2_NA * 8, be = bar_aempty + w * P2_NA * 8;
            int n = (w == 2 && half ? -1 : w) - 3, left = 0, u = 0, c = 0;
            const uint8_t* src = nullptr;
            bool act = lane < 3;
            auto next = [&]() {
                n += 3;
                left = n >= P2_ITEMS ? -1 : n < 0 ? 24 : 48;
                u = (k0 + p2_start(n)) % 48;
                src = reinterpret_cast<const uint8_t*>(g_h) + (size_t)p2_tile(cl, n) * (2 * H_TILE) + rank * H_HALF + u * H_STEP;
            };
            next();
            flag_wait<true>(g_prog[CNT_EARLY], NUM_CTAS);
#pragma unroll 1
            for (int i = 3; i > 0; i--) {
                const int wi = i % 3;
                if (wi == 2) flag_wait<true>(g_prog[CNT_H], NUM_CTAS);
                asm volatile("fence.proxy.async.global;\n" ::: "memory");
                if (w == wi && lane < 24) {
                    mbar_expect_tx(bf + lane / 3 * 8, P2_A);
                    bulk_g2s(dst0 + lane / 3 * P2_A, src + lane / 3 * H_STEP, P2_A, bf + lane / 3 * 8);
                }
                __syncwarp();
            }
            c = 8;
            left -= 8;
            u += 8;
            src += 8 * H_STEP;
            if (u == 48) { u = 0; src -= 48 * H_STEP; }
            while (__any_sync(0xffffffffu, act)) {
                if (left == 0) next();
                const bool ok = act && mbar_test(be + ((c - 1) & 7) * 8, (~c >> 3) & 1);
                if (ok) {
                    const int st = c & 7;
                    if (left > 0) {
                        mbar_expect_tx(bf + st * 8, P2_A);
                        bulk_g2s(dst0 + st * P2_A, src, P2_A, bf + st * 8);
                    } else {
                        mbar_arrive(bf + st * 8);
                        act = false;
                    }
                    src += H_STEP;
                    if (++u == 48) { u = 0; src -= 48 * H_STEP; }
                    c++;
                    left--;
                }
                SAFE_BREAK;
                if (!__any_sync(0xffffffffu, ok)) __nanosleep(100);
            }
        } else if (warp == 14) {
            const uint32_t sx = sbase + P2_OFF_X;
            size_t o = 0;
            int wp = 0;
            uint32_t par = 0;
            if (fin) {
#pragma unroll 1
                for (int c = lane * 16; c < 64 * P2_XROW + 128; c += 512) asm volatile("st.shared.v4.u32 [%0], {0, 0, 0, 0};\n" ::"r"(sx + c) : "memory");
                __syncwarp();
            }
            wait_pos(6);
#pragma unroll 1
            for (int n = -half; n < P2_ITEMS; n++) {
                const int w = (n + 3) % 3, end = p2_start(n) + 48;
                const size_t on = (size_t)(2 * p2_tile(cl, n) + rank) * (64 * C_DIM * 2);
                const uint32_t xf = bar_xfull + w * 8;
                bool st = n + half > 0;
                const bool ld = n < P2_ITEMS - 1 && !(n < 0 && fin);
                if (n == P2_ITEMS - 1 && lane == 0) {
                    mbar_expect_tx(xf, 64 * C_DIM * 2);
#pragma unroll 1
                    for (int c = 4; c < 12; c++) {
                        if (c >= 8) {
                            mbar_wait(bar_aempty + ((2 * c - 1) & 7) * 8, 1);
                            mbar_wait(bar_aempty + ((2 * c) & 7) * 8, 1);
                        }
                        bulk_g2s(sbase + P2_OFF_A + (c & 3) * P2_XC + (c < 8 ? P2_LHALF : 0), reinterpret_cast<const uint8_t*>(x) + on + (c & 7) * P2_XC, P2_XC, xf);
                    }
                    mbar_arrive(xf);
                }
                if (st) {
                    mbar_wait(bar_oready + wp * 8, (par >> wp) & 1);
                    par ^= 1u << wp;
                }
                if (lane == 0) {
                    if (n < P2_ITEMS - 1) mbar_expect_tx(xf, ld ? 64 * C_DIM * 2 : 0);
                    const int t0 = (n ? p2_start(n - 1) + 48 : P2_S2) + (n == P2_ITEMS - 1 ? P2_TL : P2_T0), dt = end - t0;
                    int t = st ? 16 * t0 : -4096;
                    if (n == 0 && half) {
                        if (fin) {
                            flag_wait<true>(&g_half[pair][rank], 1);
                            asm volatile("fence.proxy.async.global;\n" ::: "memory");
                        }
#pragma unroll 1
                        for (int c = 0; c < 2; c++) {
                            uint8_t* dst = reinterpret_cast<uint8_t*>(out) + o + c * 32 * P2_XROW;
                            if (!fin) bulk_s2g(dst, sx + c * P2_XHALF, 32 * P2_XROW);
                            else asm volatile("cp.reduce.async.bulk.global.shared::cta.bulk_group.add.noftz.bf16 [%0], [%1], %2;\n"
                                              ::"l"(dst), "r"(sx + c * P2_XHALF), "r"(32 * P2_XROW) : "memory");
                        }
                        asm volatile("cp.async.bulk.commit_group;\n" ::: "memory");
                        if (!fin) {
                            asm volatile("cp.async.bulk.wait_group 0;\nfence.proxy.async.global;\n" ::: "memory");
                            asm volatile("st.release.gpu.global.u32 [%0], 1;\n" ::"l"(&g_half[pair][rank]) : "memory");
                        }
                        st = false;
                    }
#pragma unroll 1
                    for (int c = 0; c < 64 * P2_XROW; c += P2_XC, t += 2 * dt) {
                        const uint32_t sp = sx + c + (c >= 32 * P2_XROW ? 64 : 0);
                        wait_pos(t >> 4);
                        if (st) bulk_s2g(reinterpret_cast<uint8_t*>(out) + o + c, sp, P2_XC);
                        asm volatile("cp.async.bulk.commit_group;\n" ::: "memory");
                        if (ld) {
                            wait_pos((t + dt) >> 4);
                            asm volatile("cp.async.bulk.wait_group.read 0;\n" ::: "memory");
                            bulk_g2s(sp, reinterpret_cast<const uint8_t*>(x) + on + c, P2_XC, xf);
                        }
                    }
                    if (rank == 0 && n > 0 && n < P2_ITEMS - 2) flag_wait<false>(g_prog[CNT_POS], P2_NCL * (end - 1));
                    if (n < P2_ITEMS - 1) mbar_arrive(xf);
                }
                __syncwarp();
                o = on;
                wp = w;
            }
            asm volatile("cp.async.bulk.wait_group.read 0;\n" ::: "memory");
        } else {
            if (blockIdx.x == 120) {
                wait_pos(P2_RAW);
                for (int i = lane; i < (LN_RING + 6) * 2; i += 32) (&g_flag[0][0][0])[i * 8] = 0;
                for (int i = lane; i < HID; i += 32) g_sq[i] = 0;
                for (int i = lane; i < 512; i += 32) g_sums[i] = 0.f;
            }
            int t = 4 * P2_XP0;
#pragma unroll 1
            for (int n = 0; n < P2_ITEMS && lane == 0; n++) {
                const uint8_t* xn = reinterpret_cast<const uint8_t*>(x) + (size_t)(2 * p2_tile(cl, n) + rank) * (64 * C_DIM * 2);
#pragma unroll 1
                for (int c = 0; c < 16; c++, t += n < P2_XPN ? 4 : P2_XPD) {
                    wait_pos(t >> 2);
                    asm volatile("cp.async.bulk.prefetch.L2.global [%0], %1;\n" ::"l"(xn + c * (P2_XC / 2)), "r"(P2_XC / 2) : "memory");
                }
            }
        }
        __syncwarp();
        cluster_sync_relaxed();
    } else {
        const int wg = warp >> 2, w = warp & 3, q = lane & 3;
        const uint32_t af = bar_afull + wg * P2_NA * 8;
        const uint32_t s_a = sbase + P2_OFF_A + wg * P2_NA * P2_A + (lane >> 3) * 512 + (lane & 7) * 64 + ((w ^ ((lane & 7) >> 1)) << 4);
        uint32_t acc0[48], acc1[48], up;
        uint4 a[2][2];

        __nv_bfloat16 gg[4];
#pragma unroll
        for (int i = 0; i < 4; i++) gg[i] = grn_g[tid + 384 * i];
#pragma unroll 1
        for (int it = !early;; it++) {
            float* s_red = reinterpret_cast<float*>(smem + P2_OFF_RED);
            float gx[4], part = 0.f;
            if (it == 1) {
                TSTAMP(1, 27);
                bar_sync(5, 416);
            }
            unsigned long long v[4];
#pragma unroll
            for (int i = 0; i < 4; i++) gx[i] = __ldcg(&g_scale[tid + 384 * i]);
            while (true) {
#pragma unroll
                for (int i = 0; i < 4; i++) asm volatile("ld.relaxed.gpu.global.u64 %0, [%1];\n" : "=l"(v[i]) : "l"(&g_sq[tid + 384 * i]) : "memory");
                SAFE_BREAK;
                if (!it || !__any_sync(0xffffffffu, min(min(v[0], v[1]), min(v[2], v[3])) < (unsigned long long)NGRP << 56)) break;
            }
            TSTAMP(1, 1);
            const float bias = reinterpret_cast<const float*>(smem + OFF_PRE)[tid];
            const float2 pre = *reinterpret_cast<const float2*>(smem + OFF_PRE + C_DIM * 4);
            bool tiny = false;
#pragma unroll
            for (int i = 0; i < 4; i++) {
                const float t = it == 2 ? __ldcg(&g_redo[tid + 384 * i]) : __ull2float_rn(v[i] << 8) * 0x1p-40f;
                tiny |= t < M_TOTAL * 0x1p-19f;
                gx[i] *= gx[i] * t;
            }
            float mg = 0.f;
#pragma unroll
            for (int i = 0; i < 4; i++) {
                asm("sqrt.approx.f32 %0, %1;\n" : "=f"(gx[i]) : "f"(gx[i] * (HSCALE * HSCALE) + 1e-6f));
                part += gx[i];
                gx[i] *= __bfloat162float(gg[i]);
                mg = fmaxf(mg, fabsf(gx[i]));
            }
#pragma unroll
            for (int o = 16; o > 0; o >>= 1) part += __shfl_xor_sync(0xffffffffu, part, o);
            const uint32_t mgw = __reduce_max_sync(0xffffffffu, __float_as_uint(mg));
            TSTAMP(1, 26);
            if (lane == 0) *reinterpret_cast<float2*>(s_red + warp * 2) = make_float2(part, __uint_as_float(mgw));
            if (it) {
                uint32_t redo;
                asm volatile("{\n.reg .pred p;\nsetp.ne.u32 p, %1, 0;\nbar.red.or.pred p, 4, 384, p;\nselp.u32 %0, 1, 0, p;\n}\n"
                             : "=r"(redo) : "r"((uint32_t)(tiny && it == 1)) : "memory");
                if (__shfl_sync(0xffffffffu, redo, 0)) {
                    p2_redo_sums(warp, lane);
                    continue;
                }
            }
            float tot = 0.f;
#pragma unroll
            for (int i = 0; i < 6; i++) {
                const float4 t = *reinterpret_cast<const float4*>(s_red + i * 4);
                tot += t.x + t.z;
                mg = fmaxf(mg, fmaxf(t.y, t.w));
            }
            const float inv = __fdividef(1.0f, tot * (1.0f / HID) + 1e-6f);
            const uint32_t ej = min((__float_as_uint(fmaxf(fmaf(mg, inv, 1.0f) * (HSCALE * UNCHOP), pre.y * 0x1p-13f)) >> 23) + 1, 250u);
            const float dn = __uint_as_float((254u - ej) << 23);
            up = min(ej + 127u - (__float_as_uint(pre.x) >> 23), 254u) * 0x00800080u;
            reinterpret_cast<uint16_t*>(smem + P2_OFF_BIAS + C_DIM * 2)[tid] = 0;
            *reinterpret_cast<__half*>(smem + P2_OFF_BIAS + (tid >> 5) * 64 + (tid & 6) * 8 + (tid & 24) / 2 + (tid & 1) * 2) = __float2half_rn(bias * dn);
#pragma unroll
            for (int i = 0; i < 4; i++) {
                const int k = tid + 384 * i;
                *reinterpret_cast<__half*>(smem + P2_OFF_GRN + (k >> 4) * 32 + (k & 6) * 4 + (k & 8) / 2 + (k & 1) * 2) =
                    __float2half_rn(fmaf(gx[i], inv, 1.0f) * (HSCALE * UNCHOP * dn));
            }
            TSTAMP(1, 25);
            if (it) break;
        }
        bar_sync(4, 384);
        asm volatile("barrier.cluster.wait.aligned;\n" ::: "memory");
        TSTAMP(1, 28);
        if (wg == 1) {
            constexpr int N = sizeof(g_w2img[0]) / 16, PER = (N + NUM_CTAS - 1) / NUM_CTAS;
            uint4 v[5];
#pragma unroll
            for (int i = 0; i < 5; i++) v[i] = __ldcg(&g_w2img[0][min(blockIdx.x * PER + (tid & 127) + 128 * i, N - 1)]);
#pragma unroll
            for (int i = 0; i < 5; i++) {
                const int j = min(blockIdx.x * PER + (tid & 127) + 128 * i, N - 1);
                const uint32_t* t = reinterpret_cast<const uint32_t*>(smem + P2_OFF_GRN + (j / 768) * 32 + (j & 8) / 2);
                auto sc = [&](uint32_t u, int e) { return (h2_mul(u, t[2 * e]) + 0x00040004u) & 0xfff8fff8u; };
                g_w2img[1][j] = make_uint4(sc(v[i].x, 0), sc(v[i].y, 1), sc(v[i].z, 2), sc(v[i].w, 3));
            }
            asm volatile("fence.proxy.async.global;\n" ::: "memory");
            bar_sync(2, 128);
            if (tid == 128) asm volatile("fence.acq_rel.gpu;\nred.release.gpu.global.add.u32 [%0], 1;\n" ::"l"(g_prog[CNT_IMG1]) : "memory");
        }

        const int who = __shfl_sync(0xffffffffu, lane == 2 ? 0 : lane < 2 ? 1 : 2, lane);
        const uint32_t rel0 = who ? mapa(bar_bempty, lane & 1) : mapa(bar_aempty + wg * P2_NA * 8, rank), rel1 = rel0 + (who ? 0 : 32);
        auto publish = [&]() {
            asm volatile("fence.proxy.async.shared::cta;\n" ::: "memory");
            __syncwarp();
            if (who == 0) mbar_arrive(bar_oready + wg * 8);
        };
        bool ok_a, pend = false;
        uint32_t pa = 0, s_t;
        auto fetch = [&](int j, bool raw) {
            uint32_t o[6], u0[4], u1[4];
            uint2 t0 = make_uint2(0, 0), t1 = t0;
            if (raw) {
                asm volatile("ld.shared.v2.u32 {%0,%1}, [%2];\n" : "=r"(t0.x), "=r"(t0.y) : "r"(s_t + j * 64) : "memory");
                asm volatile("ld.shared.v2.u32 {%0,%1}, [%2];\n" : "=r"(t1.x), "=r"(t1.y) : "r"(s_t + j * 64 + 32) : "memory");
            }
            const bool ok_b = mbar_test(bar_bfull + (j & 3) * 8, j >> 2);
            if (j == 7) pa ^= 1;
            ok_a = mbar_test(af + ((j + 1) & 7) * 8, pa);
            asm volatile("ldmatrix.sync.aligned.m8n8.x4.trans.shared.b16 {%0,%1,%2,%3}, [%4];\n"
                         : "=r"(o[0]), "=r"(o[1]), "=r"(o[2]), "=r"(o[3]) : "r"(s_a + j * P2_A) : "memory");
            asm volatile("ldmatrix.sync.aligned.m8n8.x2.trans.shared.b16 {%0,%1}, [%2];\n"
                         : "=r"(o[4]), "=r"(o[5]) : "r"(s_a + j * P2_A + 2048) : "memory");
            p2_unpack(u0, o[0], o[1], o[2]);
            p2_unpack(u1, o[3], o[4], o[5]);
            if (raw) {
                u0[0] = h2_mul(u0[0], t0.x); u0[1] = h2_mul(u0[1], t0.x); u0[2] = h2_mul(u0[2], t0.y); u0[3] = h2_mul(u0[3], t0.y);
                u1[0] = h2_mul(u1[0], t1.x); u1[1] = h2_mul(u1[1], t1.x); u1[2] = h2_mul(u1[2], t1.y); u1[3] = h2_mul(u1[3], t1.y);
            }
            a[j & 1][0] = make_uint4(u0[0], u0[1], u0[2], u0[3]);
            a[j & 1][1] = make_uint4(u1[0], u1[1], u1[2], u1[3]);
            if (!ok_b) mbar_wait(bar_bfull + (j & 3) * 8, j >> 2);
        };
        auto table = [&](int pos) { s_t = sbase + P2_OFF_GRN + q * 8 + (k0 + pos) % 48 * 64; };
        const uint32_t db0 = (uint32_t)make_desc(sbase, 128, 256);
        auto block8 = [&](bool raw, int pos, int thr0, int mode) {
#pragma unroll
            for (int j = 0; j < 8; j++) {
                const uint32_t db = db0 + (j & 3) * (P2_B / 16);
                if (j == 8 - P2_AH && mode == 1) bar_sync(4, 384);
                TR2(wg, pos + j, 0);
                wg_fence();
                mma_rs_n192(acc0, a[j & 1][0], db);
                mma_rs_n192(acc1, a[j & 1][0], db + 384);
                mma_rs_n192(acc0, a[j & 1][1], db + 768);
                mma_rs_n192(acc1, a[j & 1][1], db + 768 + 384);
                wg_commit();
                if (j == 7 && mode == 2) bar_arrive(4, 384);
                const uint32_t rel = ((j - 1) & 4 ? rel1 : rel0) + ((j - 1) & 3) * 8;
                TR2(wg, pos + j, 1);
                wg_wait<1>();
                TR2(wg, pos + j, 2);
                if (who < (j ? 2 : thr0)) mbar_arrive_cluster(rel);
                if (!ok_a) {
                    if (j == 0 && pend) { publish(); pend = false; }
                    mbar_wait(af + ((j + 1) & 7) * 8, pa);
                }
                TR2(wg, pos + j, 3);
                if (raw && j == 7) table(pos + 8);
                fetch((j + 1) & 7, raw && (j < 7 || pos + 8 < P2_RAW));
            }
        };
        int n = wg == 2 && half ? -1 : wg, pos = p2_start(n);
        uint32_t px = 0;
        wait_pos(pos);
        mbar_wait(af, 0);
        table(pos);
        fetch(0, pos < P2_RAW);
#pragma unroll 1
        for (;; n += 3) {
            TSTAMP(1, 2 + n);
            const int end = pos + (n < 0 ? 24 : 48);
#pragma unroll
            for (int i = 0; i < 48; i += 2) {
                asm volatile("mov.b64 {%0, %1}, 0;\n" : "=r"(acc0[i]), "=r"(acc0[i + 1]));
                asm volatile("mov.b64 {%0, %1}, 0;\n" : "=r"(acc1[i]), "=r"(acc1[i + 1]));
            }
            int thr = 1;
#pragma unroll 1
            for (; pos < P2_RAW; pos += 8, thr = 2) block8(true, pos, thr, 0);
#pragma unroll 1
            for (; pos < end; pos += 8, thr = 2) {
                const int e = pos + 8, r = e % 48;
                block8(false, pos, thr, e < 48 || e > 256 || (r != 0 && r != P2_S1 && r != P2_S2) ? 0 : e == end ? 2 : 1);
            }
            TR2(wg, pos - 1, 4);
            wg_wait<0>();
            TR2(wg, pos - 1, 5);
            if (who == 1) mbar_arrive_cluster(rel0 + 24);
            mbar_wait(bar_xfull + wg * 8, px);
            TR2(wg, pos - 1, 6);
            px ^= 1;
            __syncwarp();
            const bool last = n == P2_ITEMS - 1;
            uint32_t l;
            asm volatile("mov.u32 %0, %%laneid;\n" : "=r"(l));
            const uint32_t q16 = (l & 3) * 16, odd = (l >> 2) & 1, row = (w * 8 + (l >> 3)) * P2_XROW + q16;
            uint8_t* so = last ? reinterpret_cast<uint8_t*>(out) + (size_t)(2 * p2_tile(cl, n) + rank) * (64 * P2_XROW) : smem + P2_OFF_X;
            p2_epilogue(acc0, acc1, up, sbase + row + (last ? P2_OFF_A + odd * P2_LHALF : P2_OFF_X + odd * P2_XHALF),
                        sbase + P2_OFF_BIAS + q16 + (n < 0 && fin ? C_DIM * 2 : 0), so + (row + odd * (last ? 32 * P2_XROW : P2_XHALF)), zero);
            if (last) break;
            TR2(wg, pos - 1, 7);
            if (n + 3 >= P2_ITEMS) { publish(); break; }
            if (n < 0) {
                publish();
                pos = P2_S2;
                wait_pos(pos);
                mbar_wait(bar_bfull, 0);
            } else {
                pend = true;
                ok_a = false;
            }
        }
        TSTAMP(1, 29);
        cluster_sync_relaxed();
        TSTAMP(1, 30);
    }
}

__global__ void __cluster_dims__(2, 1, 1) __launch_bounds__(512, 1)
block_kernel(const __grid_constant__ CUtensorMap wmap, const __nv_bfloat16* __restrict__ x, const __nv_bfloat16* __restrict__ dw,
             const __nv_bfloat16* __restrict__ w2, const __nv_bfloat16* __restrict__ grn_g, const __nv_bfloat16* __restrict__ grn_b,
             __nv_bfloat16* __restrict__ out, int zero) {
    extern __shared__ __align__(1024) uint8_t smem[];
    const uint32_t sbase = smem_u32(smem);
    const int warp = __shfl_sync(0xffffffffu, threadIdx.x >> 5, 0), lane = threadIdx.x & 31;
    if (warp >= 12) {
        pass1<2>(wmap, x, dw, w2, grn_b, sbase, warp, lane, zero);
        pass2<2>(x, grn_g, out, smem, sbase, false, zero);
    } else {
        bool early = false;
        if (warp >= 8) {
            pass1<1>(wmap, x, dw, w2, grn_b, sbase, warp, lane, zero);
            reg_inc<160>();
        } else {
            early = pass1<0>(wmap, x, dw, w2, grn_b, sbase, warp, lane, zero);
            reg_dec<160>();
        }
        pass2<0>(x, grn_g, out, smem, sbase, early, zero);
    }
}

}

extern "C" void kernel_launch(void* const* d_in, const int* in_sizes, int n_in, void* d_out, int out_size) {
    const __nv_bfloat16* x = (const __nv_bfloat16*)d_in[0];
    const __nv_bfloat16* dw = (const __nv_bfloat16*)d_in[1];
    const __nv_bfloat16* w1 = (const __nv_bfloat16*)d_in[2];
    const __nv_bfloat16* w2 = (const __nv_bfloat16*)d_in[3];
    const __nv_bfloat16* grn_g = (const __nv_bfloat16*)d_in[4];
    const __nv_bfloat16* grn_b = (const __nv_bfloat16*)d_in[5];
    __nv_bfloat16* out = (__nv_bfloat16*)d_out;

    cudaFuncSetAttribute(block_kernel, cudaFuncAttributeMaxDynamicSharedMemorySize, SMEM_BYTES);

    typedef CUresult (*EncodeFn)(CUtensorMap*, CUtensorMapDataType, cuuint32_t, void*, const cuuint64_t*, const cuuint64_t*,
                                 const cuuint32_t*, const cuuint32_t*, CUtensorMapInterleave, CUtensorMapSwizzle,
                                 CUtensorMapL2promotion, CUtensorMapFloatOOBfill);
    static EncodeFn encode = nullptr;
    if (!encode) {
        cudaDriverEntryPointQueryResult qres;
        cudaGetDriverEntryPoint("cuTensorMapEncodeTiled", (void**)&encode, cudaEnableDefault, &qres);
    }
    CUtensorMap wmap;
    const cuuint64_t gdim[2] = {HID, C_DIM};
    const cuuint64_t gstr[1] = {HID * 2};
    const cuuint32_t box[2] = {64, 192}, estr[2] = {1, 1};
    CUresult er = encode(&wmap, CU_TENSOR_MAP_DATA_TYPE_BFLOAT16, 2, (void*)w1, gdim, gstr, box, estr, CU_TENSOR_MAP_INTERLEAVE_NONE,
           CU_TENSOR_MAP_SWIZZLE_128B, CU_TENSOR_MAP_L2_PROMOTION_L2_128B, CU_TENSOR_MAP_FLOAT_OOB_FILL_NONE);
    if (er != CUDA_SUCCESS) printf("tensor map encode failed %d\n", (int)er);

    block_kernel<<<NUM_CTAS, 512, SMEM_BYTES>>>(wmap, x, dw, w2, grn_g, grn_b, out, 0);
}
```

```cpp
#include <cuda.h>
#include <cuda_runtime.h>
#include <cuda_bf16.h>
#include <cuda_fp16.h>
#include <stdint.h>
#include <stdio.h>

namespace {

constexpr int M_TOTAL = 384 * 384;
constexpr int C_DIM   = 384;
constexpr int HID     = 1536;
constexpr int NT128   = M_TOTAL / 128;
constexpr int NUM_CTAS = 132;

constexpr int NGRP = 22, GRP_CTAS = 6;
constexpr int NT_EARLY = NT128 - 30;
constexpr int LN_STEP = NUM_CTAS / 4, LN_RING = 2 * LN_STEP;
constexpr int LN_TILE = 128 * C_DIM * 2;
constexpr int H_TILE = 64 * HID * 3 / 2;
constexpr int H_HALF = 3072, H_STEP = 6144;

__device__ __align__(1024) uint4 g_h[(size_t)M_TOTAL * HID * 3 / 32];
__device__ __align__(1024) uint4 g_ln[LN_RING * LN_TILE / 16];
__device__ __align__(1024) uint4 g_w2img[2][HID * C_DIM * 2 / 16];
__device__ __align__(16) unsigned long long g_sq[HID];
__device__ __align__(16) float g_sums[512];
__device__ float g_scale[HID];
__device__ float g_redo[HID];
enum { CNT_POS, CNT_IMG1, CNT_REDO, CNT_IMG0, CNT_LAST, CNT_H, CNT_EARLY, NUM_CNT };
__device__ __align__(128) unsigned g_prog[NUM_CNT][32];
__device__ __align__(128) unsigned g_half[32][2];
__device__ unsigned g_flag[LN_RING + 6][2][8];
#define TSTAMP(k, i)
#define TRACE(wg, pos, i)
#define TRACEW(pos, i)

#define TR2(wg, pos, i)
__host__ __device__ __forceinline__ int perm32(int n) {
    return (n & ~31) | (((n >> 1) & 3) << 3) | (((n >> 3) & 3) << 1) | (n & 1);
}

__device__ __forceinline__ uint32_t smem_u32(const void* p) { return (uint32_t)__cvta_generic_to_shared(p); }

__device__ __forceinline__ void mbar_init(uint32_t bar, uint32_t count) {
    asm volatile("mbarrier.init.shared::cta.b64 [%0], %1;\n" ::"r"(bar), "r"(count) : "memory");
}
__device__ __forceinline__ void mbar_expect_tx(uint32_t bar, uint32_t bytes) {
    asm volatile("mbarrier.arrive.expect_tx.shared::cta.b64 _, [%0], %1;\n" ::"r"(bar), "r"(bytes) : "memory");
}
__device__ __forceinline__ void mbar_arrive(uint32_t bar) {
    asm volatile("mbarrier.arrive.shared::cta.b64 _, [%0];\n" ::"r"(bar) : "memory");
}
__device__ __forceinline__ void mbar_arrive_cluster(uint32_t bar_cluster_addr) {
    asm volatile("mbarrier.arrive.shared::cluster.b64 _, [%0];\n" ::"r"(bar_cluster_addr) : "memory");
}
#define LAG_HERE(k)
#define SAFE_BREAK
__device__ __forceinline__ void mbar_wait(uint32_t bar, uint32_t parity) {
    asm volatile(
        "{\n"
        ".reg .pred p;\n"
        "LAB_WAIT:\n"
        "mbarrier.try_wait.parity.shared::cta.b64 p, [%0], %1;\n"
        "@!p bra LAB_WAIT;\n"
        "}\n" ::"r"(bar), "r"(parity) : "memory");
}
__device__ __forceinline__ bool mbar_test(uint32_t bar, uint32_t parity) {
    uint32_t ok;
    asm volatile("{\n.reg .pred p;\n"
                 "mbarrier.test_wait.parity.shared::cta.b64 p, [%1], %2;\n"
                 "selp.u32 %0, 1, 0, p;\n}\n" : "=r"(ok) : "r"(bar), "r"(parity) : "memory");
    return ok != 0;
}
__device__ __forceinline__ uint32_t mapa(uint32_t addr, uint32_t rank) {
    uint32_t r;
    asm volatile("mapa.shared::cluster.u32 %0, %1, %2;\n" : "=r"(r) : "r"(addr), "r"(rank));
    return r;
}
__device__ __forceinline__ void bulk_g2s(uint32_t dst, const void* src, uint32_t bytes, uint32_t bar) {
    asm volatile("cp.async.bulk.shared::cluster.global.mbarrier::complete_tx::bytes [%0], [%1], %2, [%3];\n"
                 ::"r"(dst), "l"(src), "r"(bytes), "r"(bar) : "memory");
}
__device__ __forceinline__ void bulk_g2s_mc(uint32_t dst, const void* src, uint32_t bytes, uint32_t bar, uint16_t mask) {
    asm volatile("cp.async.bulk.shared::cluster.global.mbarrier::complete_tx::bytes.multicast::cluster [%0], [%1], %2, [%3], %4;\n"
                 ::"r"(dst), "l"(src), "r"(bytes), "r"(bar), "h"(mask) : "memory");
}
__device__ __forceinline__ void tma2(uint32_t dst, const CUtensorMap* map, int c0, int c1, uint32_t bar) {
    asm volatile("cp.async.bulk.tensor.2d.shared::cluster.global.tile.mbarrier::complete_tx::bytes [%0], [%1, {%2, %3}], [%4];\n"
                 ::"r"(dst), "l"(map), "r"(c0), "r"(c1), "r"(bar) : "memory");
}
template <bool ACQ>
__device__ __forceinline__ uint32_t flag_wait(const unsigned* p, unsigned target) {
    unsigned v, n = 0;
    do {
        if (ACQ) asm volatile("ld.acquire.gpu.global.u32 %0, [%1];\n" : "=r"(v) : "l"(p) : "memory");
        else asm volatile("ld.relaxed.gpu.global.u32 %0, [%1];\n" : "=r"(v) : "l"(p) : "memory");
        n++;
    } while (v < target);
    return n == 1;
}
__device__ __forceinline__ void ldsm4t(uint32_t (&r)[4], uint32_t addr) {
    asm volatile("ldmatrix.sync.aligned.m8n8.x4.trans.shared.b16 {%0,%1,%2,%3}, [%4];\n"
                 : "=r"(r[0]), "=r"(r[1]), "=r"(r[2]), "=r"(r[3]) : "r"(addr) : "memory");
}
__device__ __forceinline__ void bulk_s2g(void* dst, uint32_t src, uint32_t bytes) {
    asm volatile("cp.async.bulk.global.shared::cta.bulk_group [%0], [%1], %2;\n" ::"l"(dst), "r"(src), "r"(bytes) : "memory");
}
__device__ __forceinline__ void cluster_sync_relaxed() {
    asm volatile("barrier.cluster.arrive.relaxed.aligned;\nbarrier.cluster.wait.aligned;\n" ::: "memory");
}
__device__ __forceinline__ uint32_t cluster_rank() {
    uint32_t r;
    asm volatile("mov.u32 %0, %%cluster_ctarank;\n" : "=r"(r));
    return r;
}
__device__ __forceinline__ bool elect_one() {
    uint32_t pred;
    asm volatile("{\n.reg .pred p;\nelect.sync _|p, 0xffffffff;\nselp.u32 %0, 1, 0, p;\n}\n" : "=r"(pred));
    return pred != 0;
}
__device__ __forceinline__ void wg_fence() { asm volatile("wgmma.fence.sync.aligned;\n" ::: "memory"); }
__device__ __forceinline__ void wg_commit() { asm volatile("wgmma.commit_group.sync.aligned;\n" ::: "memory"); }
template <int N> __device__ __forceinline__ void wg_wait() {
    asm volatile("wgmma.wait_group.sync.aligned %0;\n" ::"n"(N) : "memory");
}
template <int R> __device__ __forceinline__ void reg_inc() { asm volatile("setmaxnreg.inc.sync.aligned.u32 %0;\n" ::"n"(R)); }
template <int R> __device__ __forceinline__ void reg_dec() { asm volatile("setmaxnreg.dec.sync.aligned.u32 %0;\n" ::"n"(R)); }
__device__ __forceinline__ void bar_sync(int id, int n) { asm volatile("bar.sync %0, %1;\n" ::"r"(id), "r"(n) : "memory"); }
__device__ __forceinline__ void bar_arrive(int id, int n) { asm volatile("bar.arrive %0, %1;\n" ::"r"(id), "r"(n) : "memory"); }

__device__ __forceinline__ uint64_t make_desc(uint32_t saddr, uint32_t lbo, uint32_t sbo) {
    return (uint64_t)((saddr & 0x3FFFF) >> 4) | ((uint64_t)(lbo >> 4) << 16) | ((uint64_t)(sbo >> 4) << 32);
}

__device__ __forceinline__ void stg128_cs(void* p, uint32_t a, uint32_t b, uint32_t c, uint32_t d) {
    asm volatile("st.global.cs.v4.u32 [%0], {%1,%2,%3,%4};\n" ::"l"(p), "r"(a), "r"(b), "r"(c), "r"(d) : "memory");
}
__device__ __forceinline__ uint32_t pack_bf16(float lo, float hi) {
    uint32_t r;
    asm("cvt.rn.bf16x2.f32 %0, %1, %2;\n" : "=r"(r) : "f"(hi), "f"(lo));
    return r;
}
__device__ __forceinline__ float bf_lo(uint32_t v) { return __uint_as_float(v << 16); }
__device__ __forceinline__ float bf_hi(uint32_t v) { return __uint_as_float(v & 0xffff0000u); }
__device__ __forceinline__ uint32_t bf2_mul(uint32_t a, uint32_t b) {
    uint32_t r;
    asm("mul.rn.bf16x2 %0, %1, %2;\n" : "=r"(r) : "r"(a), "r"(b));
    return r;
}
__device__ __forceinline__ uint32_t bf2_fma(uint32_t a, uint32_t b, uint32_t c) {
    uint32_t r;
    asm("fma.rn.bf16x2 %0, %1, %2, %3;\n" : "=r"(r) : "r"(a), "r"(b), "r"(c));
    return r;
}
__device__ __forceinline__ uint32_t bf2_add(uint32_t a, uint32_t b) {
    uint32_t r;
    asm("add.rn.bf16x2 %0, %1, %2;\n" : "=r"(r) : "r"(a), "r"(b));
    return r;
}
__device__ __forceinline__ uint32_t h2_mul(uint32_t a, uint32_t b) {
    uint32_t r;
    asm("mul.rn.f16x2 %0, %1, %2;\n" : "=r"(r) : "r"(a), "r"(b));
    return r;
}
__device__ __forceinline__ uint32_t h2_fma(uint32_t a, uint32_t b, uint32_t c) {
    uint32_t r;
    asm("fma.rn.f16x2 %0, %1, %2, %3;\n" : "=r"(r) : "r"(a), "r"(b), "r"(c));
    return r;
}
__device__ __forceinline__ uint32_t h2_add(uint32_t a, uint32_t b) {
    uint32_t r;
    asm("add.rn.f16x2 %0, %1, %2;\n" : "=r"(r) : "r"(a), "r"(b));
    return r;
}
__device__ __forceinline__ uint32_t pack_f16(float lo, float hi) {
    uint32_t r;
    asm("cvt.rn.f16x2.f32 %0, %1, %2;\n" : "=r"(r) : "f"(hi), "f"(lo));
    return r;
}
__device__ __forceinline__ float h_lo(uint32_t v) { return __low2float(*reinterpret_cast<const __half2*>(&v)); }
__device__ __forceinline__ float h_hi(uint32_t v) { return __high2float(*reinterpret_cast<const __half2*>(&v)); }
__device__ __forceinline__ uint32_t bf2_to_h2(uint32_t v) { return (v & 0x7fff7fffu) * 7u + v; }
__device__ __forceinline__ uint32_t prmt(uint32_t a, uint32_t b, uint32_t sel) {
    uint32_t r;
    asm("prmt.b32 %0, %1, %2, %3;\n" : "=r"(r) : "r"(a), "r"(b), "r"(sel));
    return r;
}
__device__ __forceinline__ uint32_t bitsel(uint32_t a, uint32_t b, uint32_t m) {
    uint32_t r;
    asm("lop3.b32 %0, %1, %2, %3, 0xd8;\n" : "=r"(r) : "r"(a), "r"(b), "r"(m));
    return r;
}
constexpr float KAPPA = 0.3292034911525734f;
constexpr uint32_t GELU_C2 = 0x40d940d9u;
constexpr float HSCALE = 1.0f / (2.0f * KAPPA);
__device__ __forceinline__ float w2_scale(uint32_t m) { return __uint_as_float((257u - max(m >> 23, 16u)) << 23); }
__device__ __forceinline__ void sched_break(int zero) {
    asm volatile("{\n.reg .pred p;\nsetp.ne.s32 p, %0, 0;\nSB_LOOP:\n@p nanosleep.u32 1;\n@p bra SB_LOOP;\n}\n" ::"r"(zero));
}

#define ACC8(d, o) "+r"(d[o + 0]), "+r"(d[o + 1]), "+r"(d[o + 2]), "+r"(d[o + 3]), "+r"(d[o + 4]), "+r"(d[o + 5]), "+r"(d[o + 6]), "+r"(d[o + 7])

__device__ __forceinline__ void mma_rs_n128(uint32_t (&d)[32], const uint32_t (&a)[4], uint32_t desc, int scale_d) {
    asm volatile(
        "{\n.reg .pred p;\n.reg .b64 db;\nsetp.ne.b32 p, %37, 0;\nmov.b64 db, {%36, 0x40000040};\n"
        "wgmma.mma_async.sync.aligned.m64n128k16.f16.f16.f16 "
        "{%0,%1,%2,%3,%4,%5,%6,%7,%8,%9,%10,%11,%12,%13,%14,%15,"
        "%16,%17,%18,%19,%20,%21,%22,%23,%24,%25,%26,%27,%28,%29,%30,%31},"
        "{%32,%33,%34,%35}, db, p, 1, 1, 0;\n}\n"
        : ACC8(d, 0), ACC8(d, 8), ACC8(d, 16), ACC8(d, 24)
        : "r"(a[0]), "r"(a[1]), "r"(a[2]), "r"(a[3]), "r"(desc), "r"(scale_d));
}

__device__ __forceinline__ void mma_ss_n128(uint32_t (&d)[32], uint32_t da, uint32_t db, int scale_d) {
    asm volatile(
        "{\n.reg .pred p;\n.reg .b64 da, db;\nsetp.ne.b32 p, %34, 0;\nmov.b64 da, {%32, 0x40000040};\nmov.b64 db, {%33, 0x40000040};\n"
        "wgmma.mma_async.sync.aligned.m64n128k16.f16.f16.f16 "
        "{%0,%1,%2,%3,%4,%5,%6,%7,%8,%9,%10,%11,%12,%13,%14,%15,"
        "%16,%17,%18,%19,%20,%21,%22,%23,%24,%25,%26,%27,%28,%29,%30,%31},"
        "da, db, p, 1, 1, 1, 0;\n}\n"
        : ACC8(d, 0), ACC8(d, 8), ACC8(d, 16), ACC8(d, 24)
        : "r"(da), "r"(db), "r"(scale_d));
}

__device__ __forceinline__ void mma_rs_n192(uint32_t (&d)[48], const uint4& a, uint32_t db) {
    asm volatile(
        "{\n.reg .b64 db;\nmov.b64 db, {%52, 16};\n"
        "wgmma.mma_async.sync.aligned.m64n192k16.f16.f16.f16 "
        "{%0,%1,%2,%3,%4,%5,%6,%7,%8,%9,%10,%11,%12,%13,%14,%15,"
        "%16,%17,%18,%19,%20,%21,%22,%23,%24,%25,%26,%27,%28,%29,%30,%31,"
        "%32,%33,%34,%35,%36,%37,%38,%39,%40,%41,%42,%43,%44,%45,%46,%47},"
        "{%48,%49,%50,%51}, db, 1, 1, 1, 0;\n}\n"
        : ACC8(d, 0), ACC8(d, 8), ACC8(d, 16), ACC8(d, 24), ACC8(d, 32), ACC8(d, 40)
        : "r"(a.x), "r"(a.y), "r"(a.z), "r"(a.w), "r"(db));
}

constexpr int P1_SPLIT = 5;
constexpr int P1_SLOT = LN_TILE / 6, P1_NST = 6;
constexpr int P1_W = 64 * C_DIM * 2;
constexpr int P1_X = 32 * C_DIM * 2;
constexpr int P1_OFF_W = LN_TILE;
constexpr int P1_OFF_X = P1_OFF_W + 2 * P1_W;
constexpr int P1_OFF_BAR = 227328;
constexpr int P1_OFF_TILE = P1_OFF_BAR + (2 * P1_NST + 4 + 4 + 4) * 8;
constexpr int P1_OFF_EX = P1_OFF_TILE + 64;
constexpr int P1_OFF_DW = P1_OFF_EX + 256 * 4;
constexpr int OFF_PRE = P1_OFF_DW + C_DIM * 2;
constexpr int SMEM_BYTES = OFF_PRE + C_DIM * 4 + 16;

__device__ __forceinline__ float rsqrt_fast(float x) {
    float r;
    asm("rsqrt.approx.ftz.f32 %0, %1;\n" : "=f"(r) : "f"(x));
    return r;
}
__device__ __forceinline__ float row_sum(const uint32_t (&c)[4]) {
    const uint32_t u = bf2_add(bf2_add(c[0], c[1]), bf2_add(c[2], c[3]));
    float s = bf_lo(u) + bf_hi(u);
#pragma unroll
    for (int o = 1; o < 8; o <<= 1) s += __shfl_xor_sync(0xffffffffu, s, o);
    return s;
}
__device__ __forceinline__ uint32_t pace(uint32_t bar, uint32_t off, uint32_t val, int zero) {
    asm volatile(
        "{\n.reg .pred p, q;\n.reg .b32 par;\n"
        "lop3.b32 par, %0, %2, %3, 0xea;\n"
        "setp.eq.u32 q, par, 0;\n"
        "mov.pred p, 0;\n"
        "@q mbarrier.test_wait.parity.shared::cta.b64 p, [%1], par;\n"
        "selp.u32 par, 1, 0, p;\n"
        "@q mbarrier.try_wait.parity.shared::cta.b64 p, [%1], par, 1000;\n"
        "@p or.b32 %0, %0, %2;\n"
        "}\n" : "+r"(val) : "r"(bar), "r"(zero), "r"(off));
    return val;
}
__device__ __forceinline__ void ln_row(uint32_t (&v)[6][4], const uint32_t (&d)[6][4], uint32_t bar, uint32_t off, int zero, uint32_t bar_read) {
    const float inv = 1.0f / C_DIM;
    uint32_t c[4];
#pragma unroll
    for (int i = 0; i < 6; i++)
#pragma unroll
        for (int k = 0; k < 4; k++) c[k] = bf2_fma(v[i][k], d[i][k], i ? c[k] : 0);
    const float m = row_sum(c) * inv;
    uint32_t nm = pack_bf16(-m, -m);
    const float e = m + bf_lo(nm);
    if (bar_read) mbar_arrive(bar_read + (nm & zero));
    nm = pace(bar, off, nm, zero);
#pragma unroll
    for (int i = 0; i < 6; i++) {
#pragma unroll
        for (int k = 0; k < 4; k++) {
            v[i][k] = bf2_fma(v[i][k], d[i][k], nm);
            c[k] = i ? bf2_fma(v[i][k], v[i][k], c[k]) : bf2_mul(v[i][k], v[i][k]);
        }
    }
    float r = KAPPA * rsqrt_fast(fmaxf(fmaf(-e, e, row_sum(c) * inv), 0.f) + 1e-5f);
    const float er = -e * r * 0x1p-112f;
    if (__any_sync(0xffffffffu, r < 0x1p-8f)) {
        const uint32_t p2 = __float_as_uint(r) & 0x7f800000u;
        r = __uint_as_float((__float_as_uint(r) & 0x007fffffu) | 0x3f800000u);
#pragma unroll
        for (int i = 0; i < 6; i++)
#pragma unroll
            for (int k = 0; k < 4; k++) v[i][k] = bf2_mul(v[i][k], p2 | p2 >> 16);
    }
    const uint32_t rs = pack_bf16(r * 0x1p-112f, r * 0x1p-112f), sh = pack_bf16(er, er);
#pragma unroll
    for (int i = 0; i < 6; i++)
#pragma unroll
        for (int k = 0; k < 4; k++) v[i][k] = bf2_to_h2(bf2_fma(v[i][k], rs, sh));
}

template <int R>
__device__ __forceinline__ uint32_t gelu2(uint32_t a, uint32_t sc2) {
    uint32_t y, t;
    if (R) asm("{\n.reg .b16 l, h;\n.reg .b32 f;\nmov.b32 {l, h}, %2;\nmov.b32 f, {h, h};\nmul.rn.f16x2 %0, %1, f;\n}\n" : "=r"(y) : "r"(a), "r"(sc2));
    else asm("{\n.reg .b16 l, h;\n.reg .b32 f;\nmov.b32 {l, h}, %2;\nmov.b32 f, {l, l};\nmul.rn.f16x2 %0, %1, f;\n}\n" : "=r"(y) : "r"(a), "r"(sc2));
    asm("tanh.approx.f16x2 %0, %1;\n" : "=r"(t) : "r"(h2_mul(y, h2_fma(y, y, GELU_C2))));
    return h2_fma(a, t, a);
}
constexpr uint32_t SPARE = 0x40074007u;
constexpr float UNCHOP = 1.0023f;

__device__ __forceinline__ uint32_t p1_exponents(float (&t)[2], uint32_t (&ex)[2], uint32_t saddr, int lane) {
#pragma unroll
    for (int r = 0; r < 2; r++) {
        t[r] += __shfl_xor_sync(0xffffffffu, t[r], 1);
        t[r] += __shfl_xor_sync(0xffffffffu, t[r], 2);
        ex[r] = min(max(((__float_as_uint(193.3f * t[r]) >> 23) + 127u) >> 1, 72u), 198u);
        asm volatile("st.shared.u32 [%0], %1;\n" ::"r"(saddr + r * 32), "r"(ex[r] << 23) : "memory");
    }
    return pack_f16(__uint_as_float(min(ex[0], 142u) << 23), __uint_as_float(min(ex[1], 142u) << 23));
}
template <int N>
__device__ __forceinline__ void p1_convert(uint32_t (&o)[N][4], uint32_t (&v)[N][4], const uint32_t (&ex)[2]) {
    if (__any_sync(0xffffffffu, max(ex[0], ex[1]) > 141u)) {
#pragma unroll
        for (int k = 0; k < 4 * N; k++) v[k >> 2][k & 3] = bf2_mul(v[k >> 2][k & 3], ex[k & 1] > 141u ? 0x1f801f80u : 0x3f803f80u);
    }
#pragma unroll
    for (int k = 0; k < 4 * N; k++) {
        const uint32_t u = bf2_mul(v[k >> 2][k & 3], ((ex[k & 1] > 141u ? 206u : 142u) - ex[k & 1]) * 0x00800080u);
        asm volatile("mad.lo.u32 %0, %1, 7, %2;\n" : "=r"(o[k >> 2][k & 3]) : "r"(u & 0x7fff7fffu), "r"(u));
    }
}
template <int N>
__device__ __forceinline__ void p1_squares(const uint32_t (&v)[N][4], float (&t)[2]) {
#pragma unroll
    for (int j = 0; j < N / 2; j++) {
        const int r = j & 1, b = (j >> 1) * 4;
        uint32_t c = bf2_mul(v[b][r], v[b][r]);
#pragma unroll
        for (int k = 1; k < 8; k++) c = bf2_fma(v[b + k / 2][r + (k & 1) * 2], v[b + k / 2][r + (k & 1) * 2], c);
        t[r] += bf_lo(c) + bf_hi(c);
    }
}
__device__ __forceinline__ void p1_epilogue(const uint32_t (&acc)[2][32], const uint32_t (&sc2)[2], float (&ssq)[4], uint8_t* hp, int zero) {
    uint32_t sq[2], h[16][4];
#pragma unroll
    for (int i2 = 0; i2 < 9; i2++) {
#pragma unroll
        for (int c = 2 * i2 - 2; c < 2 * i2; c++) {
            if (c >= 0 && (c & 3)) {
                uint32_t o[4];
#pragma unroll
                for (int u = 0; u < 4; u++) {
                    const uint32_t v = h[c & 12][u];
                    o[u] = bitsel(h[c][u], (c & 3) == 2 ? prmt(v, v, 0xa381) : prmt(v >> 3, v, (c & 3) == 1 ? 0x6240 : 0xf3d1), SPARE);
                }
                stg128_cs(hp + (c >> 3) * 2 * H_STEP + ((c >> 2) & 1) * H_HALF + ((c & 3) - 1) * 512, o[0], o[1], o[2], o[3]);
            }
        }
        if (i2 < 8) {
#pragma unroll
            for (int u = 0; u < 4; u++) {
                h[2 * i2][u] = gelu2<0>(acc[i2 >> 2][8 * (i2 & 3) + 2 * u], sc2[i2 >> 2]);
                h[2 * i2 + 1][u] = gelu2<1>(acc[i2 >> 2][8 * (i2 & 3) + 2 * u + 1], sc2[i2 >> 2]);
#pragma unroll
                for (int r = 0; r < 2; r++) {
                    const uint32_t v = h[2 * i2 + r][u];
                    sq[r] = ((i2 & 3) | u) ? h2_fma(v, v, sq[r]) : h2_mul(v, v);
                }
            }
            if ((i2 & 3) == 3) {
#pragma unroll
                for (int r = 0; r < 2; r++) ssq[(i2 >> 2) * 2 + r] += h_lo(sq[r]) + h_hi(sq[r]);
            }
            sched_break(zero);
        }
    }
}
template <int WG>
__device__ __forceinline__ void p1_mma(uint32_t (&acc)[2][32], const uint32_t (&a)[24][4], uint32_t sbase, uint32_t empty_remote, int i, int lane, bool pass) {
    const uint32_t bar_full = sbase + P1_OFF_BAR;
    const uint32_t db = (uint32_t)make_desc(sbase, 16, 1024), da = db + (P1_OFF_W + WG * P1_W) / 16;
    if (WG == 0) mbar_wait(bar_full, i & 1);
    bar_sync(1 + WG, 256);
    TRACE(WG, i, 1);
    wg_fence();
#pragma unroll
    for (int k = 0; k < 24; k++) {
        if (WG == 0 && k && k % 4 == 0) mbar_wait(bar_full + (k >> 2) * 8, i & 1);
        mma_rs_n128(acc[0], a[k], db + (k >> 2) * 1024 + (k & 3) * 2, k != 0);
        mma_ss_n128(acc[1], da + k * 128, db + (k >> 2) * 1024 + (k & 3) * 2, k != 0);
        if (k == 23 && pass) bar_arrive(2 - WG, 256);
        if (k == 23 || (WG == 1 && k % 4 == 3)) wg_commit();
        if (WG == 1 && k % 4 == 3 && k > 3) {
            wg_wait<1>();
            if (lane < 2) mbar_arrive_cluster(empty_remote + ((k >> 2) - 1) * 8);
        }
    }
    TRACE(WG, i, 2);
    wg_wait<0>();
    if (WG == 1 && lane < 2) mbar_arrive_cluster(empty_remote + 5 * 8);
}
__device__ __forceinline__ bool p1_consumer(const uint32_t (&a)[24][4], const uint32_t (&sc2)[2], uint32_t sbase, int WG, int w, int lane, int zero) {
    const uint32_t bar_full = sbase + P1_OFF_BAR, bar_empty = bar_full + P1_NST * 8;
    const uint32_t empty_remote = mapa(bar_empty, lane & 1);
    const uint32_t bar_pace = bar_empty + P1_NST * 8 + 32 + w * 8;
    const int g = lane >> 2, q = lane & 3, half = WG ^ ((blockIdx.x / GRP_CTAS) & 1), cb = (blockIdx.x % GRP_CTAS) * 4 + half * 2;
    uint32_t acc[2][32];
    float ssq[4] = {0.f, 0.f, 0.f, 0.f};
    TSTAMP(0, 1);

    uint8_t* hp = reinterpret_cast<uint8_t*>(g_h) + ((cb * 2 + (w >> 1)) * H_STEP + (w & 1) * 1536) + g * 64 + (q ^ (g >> 1)) * 16;
    int i = 0;
    uint32_t more = 3, both;
#pragma unroll 1
    for (;; i++) {
        TRACE(WG, i, 0);
        both = more & 2;
        if (WG == 0) p1_mma<0>(acc, a, sbase, empty_remote, i, lane, both);
        else p1_mma<1>(acc, a, sbase, empty_remote, i, lane, true);
        TRACE(WG, i, 4);
        int step;
        asm volatile("ld.shared.v2.u32 {%0, %1}, [%2];\n" : "=r"(step), "=r"(more) : "r"(sbase + P1_OFF_TILE + (i & 3) * 16) : "memory");
        hp += step;
        if (i < 2 || more != 3) { LAG_HERE(4); }
        if (!(more >> WG & 1) && lane == 0) asm volatile("red.relaxed.gpu.global.add.u32 [%0], 1;\n" ::"l"(g_prog[CNT_LAST]) : "memory");
        p1_epilogue(acc, sc2, ssq, hp, zero);
        if (lane == 0) mbar_arrive(bar_pace);
        if (more & 4) {
            asm volatile("fence.proxy.async.global;\n" ::: "memory");
            bar_arrive(8, 288);
            bar_arrive(9, 288);
        }
        if (!(more >> WG & 1)) break;
    }
    TSTAMP(0, 21);
    if (WG == 0 && both) bar_sync(1, 256);
#pragma unroll
    for (int r = 0; r < 4; r++) {
        ssq[r] += __shfl_xor_sync(0xffffffffu, ssq[r], 1);
        ssq[r] += __shfl_xor_sync(0xffffffffu, ssq[r], 2);
    }
    const float t = q == 0 ? ssq[0] : q == 1 ? ssq[1] : q == 2 ? ssq[2] : ssq[3];
    atomicAdd(&g_sq[cb * 64 + (q >> 1) * 64 + w * 16 + (q & 1) * 8 + g], (1ull << 56) + __float2ull_rn(fminf(t, 0x1p19f) * 0x1p32f));
    asm volatile("fence.proxy.async.global;\n" ::: "memory");
    bar_arrive(3, 288);
    asm volatile("barrier.cluster.arrive.relaxed.aligned;\n" ::: "memory");
    return WG ? more & 1 : both;
}

__device__ __forceinline__ void p2_init(uint32_t sbase);
template <int ROLE>
__device__ __forceinline__ bool pass1(const CUtensorMap& wmap, const __nv_bfloat16* __restrict__ x, const __nv_bfloat16* __restrict__ dw,
                                      const __nv_bfloat16* __restrict__ w2, const __nv_bfloat16* __restrict__ grn_b, uint32_t sbase,
                                      int warp, int lane, int zero) {
    const uint32_t bar_full = sbase + P1_OFF_BAR, bar_empty = bar_full + P1_NST * 8, bar_w = bar_empty + P1_NST * 8;
    const uint32_t rank = cluster_rank();
    const int cig = blockIdx.x % GRP_CTAS;
    uint8_t* const ring = reinterpret_cast<uint8_t*>(g_ln);

    TSTAMP(0, 0);
    TRACEW(110 + warp, 0);
    const uint32_t bar_pace = bar_w + 32, bar_xfull = bar_pace + 32, bar_xempty = bar_xfull + 8, bar_done = bar_xfull + 16;
    const int ln0 = blockIdx.x >> 2, first = blockIdx.x / GRP_CTAS;
    const uint8_t* xsrc = reinterpret_cast<const uint8_t*>(x) + (size_t)blockIdx.x * P1_X;

    if (ROLE == 2) {
        reg_dec<32>();
        asm volatile("barrier.cluster.arrive.relaxed.aligned;\n" ::: "memory");
        asm volatile("barrier.cluster.wait.aligned;\n" ::: "memory");
        LAG_HERE(0);
        if (warp == 12) {
            int prev = 0, t = first;
            const uint32_t rbase = mapa(sbase, lane & 1);
#pragma unroll 1
            for (int i = 0; t < NT128; i++) {
                const int round = t / LN_RING, slot = t - round * LN_RING;
                const uint8_t* src = ring + slot * LN_TILE + rank * (P1_SLOT / 2);
                int next = 0;
                if (rank == 0 && lane == 0) {
                    next = t < NT128 - P1_SPLIT ? NGRP + atomicAdd(&g_flag[LN_RING + (cig >> 1)][0][0], 1u) : 2 * NT128;
                    if (next >= NT128 - P1_SPLIT && next < 2 * NT128) next = NT128 - P1_SPLIT + atomicAdd(&g_flag[LN_RING + 3 + (cig >> 1)][first & 1][0], 1u);
                }
                flag_wait<true>(&g_flag[slot][0][0], 4 * round + 4);
                TRACEW(i, 2);
                asm volatile("fence.proxy.async.global;\n" ::: "memory");
                next = __shfl_sync(0xffffffffu, next, 0);
#pragma unroll 1
                for (int h = 0; h < P1_NST; h++) {
                    mbar_wait(bar_empty + h * 8, i & 1);
                    if (h == 0) TRACEW(i, 4);
                    if (h == 5) TRACEW(i, 5);
                    if (elect_one()) {
                        mbar_expect_tx(bar_full + h * 8, h ? P1_SLOT : P1_SLOT + 16);
                        bulk_g2s_mc(sbase + h * P1_SLOT + rank * (P1_SLOT / 2), src + h * P1_SLOT, P1_SLOT / 2, bar_full + h * 8, (uint16_t)3);
                    }
                    __syncwarp();
                    if (h == 0 && rank == 0 && lane < 2)
                        asm volatile("st.async.shared::cluster.mbarrier::complete_tx::bytes.v4.u32 [%0], {%1, %2, %3, %3}, [%4];\n"
                                     ::"r"(rbase + P1_OFF_TILE + (i & 3) * 16), "r"((t - prev) * (2 * H_TILE)), "r"((next < NT128 - P1_SPLIT ? 3 : next < NT128) + (t < NT_EARLY && next >= NT_EARLY ? 4 : 0)), "r"(next),
                                       "r"(rbase + P1_OFF_BAR) : "memory");
                }
                prev = t;
                t = next;
                if (rank != 0) {
                    mbar_wait(bar_full, i & 1);
                    asm volatile("ld.shared.u32 %0, [%1];\n" : "=r"(t) : "r"(sbase + P1_OFF_TILE + (i & 3) * 16 + 8) : "memory");
                }
            }
        } else if (warp == 13) {
            int ph = 0;
            unsigned target = 0;
#pragma unroll 1
            for (int i = ln0 + LN_STEP; i < NT128; i += LN_STEP, ph ^= 1) {
                target += ph * (GRP_CTAS / 2);
                xsrc += (size_t)NUM_CTAS * P1_X;
                mbar_wait(bar_xempty, ph);
                if (elect_one()) {
                    mbar_expect_tx(bar_xfull, P1_X);
                    bulk_g2s(sbase + P1_OFF_X, xsrc, P1_X, bar_xfull);
                }
                __syncwarp();
                const uint32_t off = flag_wait<false>(&g_flag[ln0 + (ph ^ 1) * LN_STEP][1][0], target);
                if (elect_one()) {
                    asm volatile("st.shared.u32 [%0], %1;\n" ::"r"(bar_done + 8), "r"(off) : "memory");
                    mbar_arrive(bar_xfull);
                }
                __syncwarp();
            }
        } else if (warp == 15) {
            int t = first;
            if (rank == 1 && lane == 0) mbar_arrive(bar_empty);
#pragma unroll 1
            for (int i = 0; rank == 1 && t < NT128; i++) {
#pragma unroll 1
                for (int h = 0; h < P1_NST; h++) mbar_wait(bar_full + h * 8, i & 1);
                if (lane == 0) asm volatile("red.relaxed.gpu.global.add.u32 [%0], 1;\n" ::"l"(&g_flag[t % LN_RING][1][0]) : "memory");
                asm volatile("ld.shared.u32 %0, [%1];\n" : "=r"(t) : "r"(sbase + P1_OFF_TILE + (i & 3) * 16 + 8) : "memory");
                if (lane == 0) mbar_arrive(bar_empty);
                TRACEW(i, 3);
            }
            if (rank == 0) {
                mbar_wait(bar_full, 0);
                TRACEW(110 + warp, 3);
                mbar_wait(bar_full, 1);
                float* sums = g_sums;
                unsigned* flag = reinterpret_cast<unsigned*>(sums + C_DIM);
                if (blockIdx.x == 0) reinterpret_cast<uint2*>(g_half)[lane] = make_uint2(0, 0);
                if (blockIdx.x == 2 && lane < NUM_CNT) g_prog[lane][0] = 0;
                if (blockIdx.x < 96) g_redo[blockIdx.x * 16 + lane] = 0.f;
                float gs = 0.f;
#pragma unroll 1
                for (int pass = 0; pass < 2; pass++) {
                    float mx = 0.f;
#pragma unroll 1
                    for (int it = first; it < 96; it += NGRP) {
                        const int nb = it % 12, k0 = (cig * 4 + it / 12) * 64 + (lane >> 2);
                        const uint32_t sc = mapa(sbase + P1_OFF_EX + (k0 & 255) * 4, it / 48);
                        uint32_t* dst = reinterpret_cast<uint32_t*>(g_w2img[0]) + (k0 >> 4) * 3072 + nb * 256 + lane;
                        float bs[8] = {};
#pragma unroll 1
                        for (int c = 0; c < 8; c++) {
                            const uint4 u = __ldg(reinterpret_cast<const uint4*>(w2 + (size_t)(k0 + c * 8) * C_DIM + nb * 32) + (lane & 3));
                            const float b = __bfloat162float(grn_b[k0 + c * 8]);
                            float t;
                            asm volatile("ld.shared::cluster.f32 %0, [%1];\n" : "=f"(t) : "r"(sc + c * 32) : "memory");
                            if (nb == 0) g_scale[k0 + c * 8] = t;
#pragma unroll
                            for (int j = 0; j < 4; j++) {
                                const uint32_t v = j == 0 ? u.x : j == 1 ? u.y : j == 2 ? u.z : u.w;
                                mx = fmaxf(mx, fmaxf(fabsf(bf_lo(v)), fabsf(bf_hi(v))) * t);
                                if (pass) {
                                    bs[2 * j] = fmaf(b, bf_lo(v), bs[2 * j]);
                                    bs[2 * j + 1] = fmaf(b, bf_hi(v), bs[2 * j + 1]);
                                    uint32_t h = pack_f16(bf_lo(v) * t * gs, bf_hi(v) * t * gs);
                                    asm volatile("movmatrix.sync.aligned.m8n8.trans.b16 %0, %0;\n" : "+r"(h));
                                    dst[(c >> 1) * 3072 + (c & 1) * 32 + j * 64] = h;
                                }
                            }
                        }
                        if (pass) {
#pragma unroll
                            for (int j = 0; j < 8; j++) {
#pragma unroll
                                for (int o = 4; o < 32; o <<= 1) bs[j] += __shfl_xor_sync(0xffffffffu, bs[j], o);
                                if (lane >> 2 == j) atomicAdd(&sums[nb * 32 + (j >> 1) * 8 + (lane & 3) * 2 + (j & 1)], bs[j]);
                            }
                        }
                    }
                    if (!pass) {
                        const uint32_t m = __reduce_max_sync(0xffffffffu, __float_as_uint(mx));
                        __threadfence();
                        __syncwarp();
                        if (lane == 0) {
                            atomicMax(flag, m);
                            asm volatile("red.release.gpu.global.add.u32 [%0], 1;\n" ::"l"(flag + 32) : "memory");
                        }
                        flag_wait<true>(flag + 32, NUM_CTAS / 2);
                        gs = w2_scale(__ldcg(flag));
                    }
                }
                asm volatile("fence.proxy.async.global;\nfence.acq_rel.gpu;\n" ::: "memory");
                __syncwarp();
                if (lane == 0) asm volatile("red.relaxed.gpu.global.add.u32 [%0], 1;\n" ::"l"(g_prog[CNT_IMG0]) : "memory");
            }
        } else if (warp == 14) {
            int ph = 0;
#pragma unroll 1
            for (int i = ln0; i < NT128; i += LN_STEP, ph ^= 1) {
                mbar_wait(bar_done, ph);
                if (lane == 0) mbar_arrive(bar_xfull);
                TRACEW(i / LN_STEP, 0);
                asm volatile("fence.proxy.async.global;\n" ::: "memory");
                if (elect_one()) asm volatile("red.release.gpu.global.add.u32 [%0], 1;\n" ::"l"(&g_flag[ln0 + ph * LN_STEP][0][0]) : "memory");
                __syncwarp();
                TRACEW(i / LN_STEP, 1);
            }
            if (lane == 0) p2_init(sbase);
#pragma unroll 1
            for (int i = CNT_EARLY; i >= CNT_H; i--) {
                bar_sync(i == CNT_EARLY ? 8 : 3, 288);
                asm volatile("fence.proxy.async.global;\n" ::: "memory");
                if (lane == 0) asm volatile("red.release.gpu.global.add.u32 [%0], 1;\n" ::"l"(&g_prog[i][0]) : "memory");
                __syncwarp();
            }
        }
        __syncwarp();
        asm volatile("barrier.cluster.arrive.relaxed.aligned;\n" ::: "memory");
        return false;
    } else if (ROLE == 1) {
        reg_dec<96>();
        asm volatile("barrier.cluster.arrive.relaxed.aligned;\n" ::: "memory");
        {
            const int l8 = lane & 7, row = (warp - 8) * 4 + (lane >> 3), px = (blockIdx.x & 3) * 32 + row;
            uint32_t d[6][4];
            const int n = (px & 64) + perm32(2 * row + ((px >> 5) & 1));
            uint8_t* const dst0 = ring + ln0 * LN_TILE + n * 128 + ((l8 ^ (n & 7)) << 4);
            const uint32_t src = sbase + P1_OFF_X + ((warp - 8) * 8 + (lane >> 3)) * (C_DIM * 2) + l8 * 16;
            int ph = 0;
            LAG_HERE(0);
#pragma unroll 1
            for (int i = ln0; i < NT128; i += LN_STEP, ph ^= 1) {
                TRACE(2, i / LN_STEP, 0);
                uint32_t off = 1;
#pragma unroll 1
                for (int ps = i == ln0 ? -2 : 0; ps < 2; ps += ps < 0 ? 2 : 1) {
                    if (ps == 0) {
                        if (i == ln0) asm volatile("barrier.cluster.wait.aligned;\n" ::: "memory");
                        mbar_wait(bar_xfull, ph);
                        asm volatile("ld.shared.u32 %0, [%1];\n" : "=r"(off) : "r"(bar_done + 8) : "memory");
                    }
                    if (ps == 0) TRACE(2, i / LN_STEP, 1);
                    if (i == ln0) {
#pragma unroll
                        for (int j = 0; j < 6; j++)
                            asm volatile("ld.shared.v4.u32 {%0,%1,%2,%3}, [%4];\n"
                                         : "=r"(d[j][0]), "=r"(d[j][1]), "=r"(d[j][2]), "=r"(d[j][3]) : "r"(sbase + P1_OFF_DW + j * 128 + l8 * 16) : "memory");
                    }
                    uint32_t v[6][4];
#pragma unroll
                    for (int j = 0; j < 6; j++)
                        asm volatile("ld.shared.v4.u32 {%0,%1,%2,%3}, [%4];\n"
                                     : "=r"(v[j][0]), "=r"(v[j][1]), "=r"(v[j][2]), "=r"(v[j][3]) : "r"(src + (ps & 1) * (4 * C_DIM * 2) + j * 128) : "memory");
                    ln_row(v, d, bar_pace + (warp - 8) * 8, off, zero, ps == 1 && lane == 0 ? bar_xempty : 0);
                    uint8_t* dst = dst0 + ph * (LN_STEP * LN_TILE) + (ps & 1) * 4096;
#pragma unroll
                    for (int j = 0; j < 6; j++) *reinterpret_cast<uint4*>(dst + j * 16384) = make_uint4(v[j][0], v[j][1], v[j][2], v[j][3]);
                    TRACE(2, i / LN_STEP, 3 + (ps & 1));
                }
                asm volatile("fence.proxy.async.global;\nfence.acq_rel.cta;\n" ::: "memory");
                __syncwarp();
                if (lane == 0) mbar_arrive(bar_done);
                TRACE(2, i / LN_STEP, 5);
                TRACE(2, i / LN_STEP, 2);
            }
        }
        __syncwarp();
        asm volatile("barrier.cluster.arrive.relaxed.aligned;\n" ::: "memory");
        return false;
    } else {
        const int wg = warp >> 2, w = warp & 3;
        auto load_w = [&](int i0, int i1) {
#pragma unroll 1
            for (int i = i0; i < i1; i++) {
                if (!(i & 1)) mbar_expect_tx(bar_w + (i >> 1) * 8, P1_W);
                tma2(sbase + (i & 2) * P1_W + (i >> 2) * P1_W + (i & 1) * (P1_W / 2), &wmap, cig * 256 + ((i >> 1) ^ (first & 1) * 2) * 64, (i & 1) * 192, bar_w + (i >> 1) * 8);
            }
        };
        if (warp == 4 && elect_one()) {
            mbar_init(bar_xfull, 3);
#pragma unroll
            for (int i = 0; i < 4; i++) mbar_init(bar_w + i * 8, 1);
            asm volatile("fence.mbarrier_init.release.cluster;\n" ::: "memory");
            mbar_expect_tx(bar_xfull, P1_X + C_DIM * 2);
            bulk_g2s(sbase + P1_OFF_X, xsrc, P1_X, bar_xfull);
            bulk_g2s(sbase + P1_OFF_DW, dw, C_DIM * 2, bar_xfull);
            load_w(0, 4);
            asm volatile("st.shared.u32 [%0], 1;\n" ::"r"(bar_done + 8) : "memory");
            mbar_arrive(bar_xfull);
            mbar_arrive(bar_xfull);
        }
        if (warp == 5 && elect_one()) {
#pragma unroll
            for (int i = 0; i < P1_NST; i++) {
                mbar_init(bar_full + i * 8, 1);
                mbar_init(bar_empty + i * 8, i ? 8 : 8 + rank);
                if (i < 4) mbar_init(bar_pace + i * 8, 1);
            }
            mbar_init(bar_xempty, 4);
            mbar_init(bar_done, 4);
            asm volatile("fence.mbarrier_init.release.cluster;\n" ::: "memory");
        }
        __syncwarp();
        asm volatile("barrier.cluster.arrive.relaxed.aligned;\n" ::: "memory");
        reg_inc<192>();
        TRACEW(110 + warp, 1);
        LAG_HERE(0);
        uint32_t a[24][4];
        const uint32_t src = sbase + wg * P1_W + ((lane >> 4) * 8 + (lane & 7)) * 128 + (((2 * w + ((lane >> 3) & 1)) ^ (lane & 7)) << 4);
        const uint32_t s_ex = sbase + P1_OFF_EX + ((wg ^ (first & 1)) * 128 + w * 16 + (lane >> 2)) * 4;
        uint32_t sc2[2], ex[2];
        if (wg == 1) bar_arrive(1, 256);
#pragma unroll 1
        for (int it = 0; it < 2; it++) {
          if (it != wg) asm volatile("barrier.cluster.wait.aligned;\n" ::: "memory");
          if (it < wg) {
              for (int n = 0; n < 64 && !mbar_test(bar_xfull, 0); n++) __nanosleep(40);
              if (w == 0 && elect_one()) load_w(4, 8);
              __syncwarp();
          }
          if (it || wg == 0) {
            float t[2] = {0.f, 0.f};
            if (it) {
                TRACEW(110 + warp, 2);
                mbar_wait(bar_w + wg * 16, 0);
            }
            TRACEW(110 + warp, 5);
#pragma unroll
            for (int k = 0; k < 24; k++) ldsm4t(a[k], src + k * 2048);
            TRACEW(110 + warp, 6);
            p1_squares(a, t);
            sc2[0] = p1_exponents(t, ex, s_ex, lane);
            if (it && lane < 6) mbar_arrive_cluster(mapa(bar_empty, lane & 1) + (wg * 3 + (lane >> 1)) * 8 + (sc2[0] & zero));
            p1_convert<24>(a, a, ex);
          }
          if (it || wg == 1) {
            float t[2] = {0.f, 0.f};
            TRACEW(100 + warp, 0);
            if (it) mbar_wait(bar_w + wg * 16 + 8, 0);
            TRACEW(100 + warp, 1);
            uint32_t v[8][4], o[8][4];
#pragma unroll 1
            for (int j = 0; j <= 2 * it; j++) {
#pragma unroll
                for (int k = 0; k < 8; k++) ldsm4t(v[k], src + P1_OFF_W + (8 * j + k) * 2048);
                p1_squares(v, t);
            }
            sc2[1] = p1_exponents(t, ex, s_ex + 256, lane);
#pragma unroll 1
            for (int j = 2 * it; j >= 0; j--) {
                p1_convert<8>(o, v, ex);
#pragma unroll
                for (int k = 0; k < 8; k++) {
                    if (j) ldsm4t(v[k], src + P1_OFF_W + (8 * j - 8 + k) * 2048);
                    if (it) asm volatile("stmatrix.sync.aligned.m8n8.x4.trans.shared.b16 [%0], {%1,%2,%3,%4};\n"
                                         ::"r"(src + P1_OFF_W + (8 * j + k) * 2048), "r"(o[k][0]), "r"(o[k][1]), "r"(o[k][2]), "r"(o[k][3]) : "memory");
                }
            }
          }
        }
        asm volatile("fence.proxy.async.shared::cta;\n" ::: "memory");
        TRACEW(110 + warp, 7);
        bar_sync(6 + wg, 128);
        const bool early = p1_consumer(a, sc2, sbase, wg, w, lane, zero);
        TSTAMP(0, 30);
        return early;
    }
}

constexpr int P2_B = 24576, P2_NB = 4;
constexpr int P2_A = 3072, P2_NA = 8;
constexpr int P2_XROW = C_DIM * 2;
constexpr int P2_OFF_A = P2_B * P2_NB;
constexpr int P2_OFF_X = P2_OFF_A + 3 * P2_NA * P2_A + 128;
constexpr int P2_LHALF = 2 * P2_NA * P2_A + 64;
constexpr int P2_XHALF = 32 * P2_XROW + 64;
constexpr int P2_OFF_GRN = P2_OFF_X + 64 * P2_XROW + 128;
constexpr int P2_OFF_BIAS = P2_OFF_GRN + HID * 2;
constexpr int P2_OFF_RED = P2_OFF_BIAS + C_DIM * 4;
constexpr int P2_OFF_BAR = P2_OFF_RED + 192;
constexpr int P2_SMEM = P2_OFF_BAR + (2 * P2_NB + 6 * P2_NA + 7) * 8;
constexpr int P2_S1 = 16, P2_S2 = 32;
constexpr int P2_NCL = NUM_CTAS / 2, P2_ITEMS = NT128 / P2_NCL, P2_SHARED = NT128 - P2_ITEMS * P2_NCL;
constexpr int P2_NPOS = 6 * 48 + P2_S1;
constexpr int P2_RAW = 16;
constexpr int P2_XC = 8 * P2_XROW;
constexpr int P2_T0 = 5;
constexpr int P2_TL = 8;
constexpr int P2_XP0 = 30;
constexpr int P2_XPN = 13;
constexpr int P2_XPD = 3;
constexpr int P2_AH = 2;
__device__ __forceinline__ int p2_start(int n) { return n < 0 ? 0 : n / 3 * 48 + (n % 3 == 1 ? P2_S1 : n % 3 * (P2_S2 / 2)); }
__device__ __forceinline__ int p2_tile(int cl, int n) {
    return n == 0 ? NT_EARLY - 1 - cl : n < 0 ? NT_EARLY + (cl >> 1) : cl + P2_NCL * (n - 1);
}

__device__ __forceinline__ void p2_epilogue(uint32_t (&acc0)[48], uint32_t (&acc1)[48], uint32_t up, uint32_t sx, uint32_t sb, uint8_t* so, int zero) {
    uint32_t v[12][3][4];
    auto load = [&](int t, int j) {
        if (t >= 12) return;
        uint32_t (&w)[4] = v[t][j];
        asm volatile("ld.shared.v4.u32 {%0,%1,%2,%3}, [%4];\n" : "=r"(w[0]), "=r"(w[1]), "=r"(w[2]), "=r"(w[3])
                     : "r"((j ? sx + (j - 1) * 4 * P2_XROW : sb) + t * 64) : "memory");
    };
    auto store = [&](int t, int r) {
        const uint32_t* w = (t < 6 ? acc0 : acc1) + 8 * (t % 6) + 4 * r;
        asm volatile("st.v4.u32 [%4], {%0,%1,%2,%3};\n" ::"r"(w[0]), "r"(w[1]), "r"(w[2]), "r"(w[3]), "l"(so + t * 64 + r * 4 * P2_XROW) : "memory");
    };
#pragma unroll
    for (int j = 0; j < 3; j++) load(0, j);
#pragma unroll
    for (int t = 0; t < 12; t++) {
        load(t + 1, 1);
        load(t + 1, 2);
        load(t + 1, 0);
        uint32_t* acc = (t < 6 ? acc0 : acc1) + 8 * (t % 6);
        uint32_t y[8];
#pragma unroll
        for (int e = 0; e < 8; e++) {
            y[e] = h2_add(acc[e], v[t][0][e >> 1]);
            y[e] = pack_bf16(h_lo(y[e]), h_hi(y[e]));
        }
#pragma unroll
        for (int e = 0; e < 8; e++) acc[(e & 1) * 4 + (e >> 1)] = bf2_fma(y[e], up, v[t][1 + (e & 1)][e >> 1]);
        store(t, 0);
        store(t, 1);
        if (t & 1) sched_break(zero);
    }
}

__device__ __forceinline__ void p2_unpack(uint32_t (&u)[4], uint32_t o1, uint32_t o2, uint32_t o3) {
    u[2] = o1 & ~SPARE;
    u[1] = o2 & ~SPARE;
    u[3] = o3 & ~SPARE;
    const uint32_t t = bitsel(prmt(o1, o2, 0x6341), prmt(o1, o3, 0x6240) << 3, 0x38383838u);
    u[0] = bitsel(t, prmt(o2, o3, 0x7351) << 1, 0x80808080u) & ~SPARE;
}

__device__ __forceinline__ void p2_redo_sums(int warp, int lane) {
    flag_wait<true>(g_prog[CNT_H], NUM_CTAS);
#pragma unroll 1
    for (int s = warp; s < 96; s += 12) {
        float t[2] = {0.f, 0.f};
#pragma unroll 1
        for (int tile = blockIdx.x; tile < 2 * NT128; tile += NUM_CTAS) {
            const uint32_t* p = reinterpret_cast<const uint32_t*>(reinterpret_cast<const uint8_t*>(g_h) + (size_t)(tile >> 1) * (2 * H_TILE) +
                                                                  (s >> 1) * H_STEP + (tile & 1) * H_HALF + (s & 1) * 1536) + lane * 4;
#pragma unroll
            for (int j = 0; j < 4; j++) {
                uint32_t u[4];
                p2_unpack(u, __ldcg(p + j), __ldcg(p + j + 128), __ldcg(p + j + 256));
#pragma unroll
                for (int c = 0; c < 4; c++) t[c >> 1] += h_lo(u[c]) * h_lo(u[c]) + h_hi(u[c]) * h_hi(u[c]);
            }
        }
#pragma unroll
        for (int r = 0; r < 2; r++) {
            const int ch = s * 16 + r * 8 + (lane >> 2);
            atomicAdd(&g_redo[ch], t[r] * (UNCHOP * UNCHOP));
        }
    }
    __threadfence();
    __syncwarp();
    if (lane == 0) asm volatile("red.release.gpu.global.add.u32 [%0], 1;\n" ::"l"(g_prog[CNT_REDO]) : "memory");
    flag_wait<true>(g_prog[CNT_REDO], 12 * NUM_CTAS);
}

static_assert(P2_OFF_GRN >= P1_OFF_X + P1_X && P1_OFF_BAR >= P2_SMEM, "barriers and tables keep their memory");
__device__ __forceinline__ void p2_init(uint32_t sbase) {
    const uint32_t bar = sbase + P2_OFF_BAR;
#pragma unroll 1
    for (int i = 0; i < 2 * P2_NB + 6 * P2_NA + 6; i++) {
        const int j = i - 2 * P2_NB;
        mbar_init(bar + i * 8, j < -P2_NB ? 1 : j < 0 ? 24 : j < 3 * P2_NA ? 1 : j >= 6 * P2_NA && j < 6 * P2_NA + 3 ? 2 : 4);
    }
    asm volatile("st.shared.v2.u32 [%0], {0, 0};\n" ::"r"(bar + (2 * P2_NB + 6 * P2_NA + 6) * 8) : "memory");
    asm volatile("fence.mbarrier_init.release.cluster;\nfence.acq_rel.cta;\n" ::: "memory");
}
template <int ROLE>
__device__ __forceinline__ void pass2(const __nv_bfloat16* __restrict__ x, const __nv_bfloat16* __restrict__ grn_g, __nv_bfloat16* __restrict__ out,
                                      uint8_t* smem, uint32_t sbase, bool early, int zero) {
    const uint32_t bar_bfull = sbase + P2_OFF_BAR, bar_bempty = bar_bfull + P2_NB * 8;
    const uint32_t bar_afull = bar_bempty + P2_NB * 8, bar_aempty = bar_afull + 3 * P2_NA * 8;
    const uint32_t bar_xfull = bar_aempty + 3 * P2_NA * 8, bar_oready = bar_xfull + 24, s_pos = bar_oready + 24;
    int tid;
    asm volatile("mov.u32 %0, %%tid.x;\n" : "=r"(tid));
    const int warp = __shfl_sync(0xffffffffu, tid >> 5, 0), lane = tid & 31;
    const uint32_t rank = cluster_rank();
    const int cl = blockIdx.x >> 1, pair = cl >> 1;
    const int half = pair < P2_SHARED, fin = half && (cl & 1);
    const int k0 = (pair + 3 * (cl & 1)) % 6 * 8;
    auto wait_pos = [&](int target) {
        int v;
        while (true) {
            asm volatile("ld.volatile.shared.u32 %0, [%1];\n" : "=r"(v) : "r"(s_pos) : "memory");
            if (v >= target) break;
            SAFE_BREAK;
            __nanosleep(100);
        }
    };

    TSTAMP(1, 0);
    LAG_HERE(1);
    if (ROLE == 2) {
        if (warp != 14) flag_wait<true>(g_prog[CNT_IMG0], P2_NCL);
        if (warp == 15) {
            float* pre = reinterpret_cast<float*>(smem + OFF_PRE);
            const float gs = w2_scale(__float_as_uint(__ldcg(&g_sums[C_DIM])));
            float mb = 0.f;
#pragma unroll 1
            for (int i = lane; i < C_DIM; i += 32) {
                pre[i] = __ldcg(&g_sums[i]) * gs;
                mb = fmaxf(mb, fabsf(pre[i]));
            }
            pre[C_DIM] = gs;
            pre[C_DIM + 1] = __uint_as_float(__reduce_max_sync(0xffffffffu, __float_as_uint(mb)));
            bar_sync(9, 288);
            flag_wait<false>(g_prog[CNT_LAST], NUM_CTAS * 8);
            bar_arrive(5, 416);
        }
        asm volatile("barrier.cluster.wait.aligned;\nfence.proxy.async;\n" ::: "memory");
        LAG_HERE(2);
        if (warp == 12) {
            const uint8_t* wsrc = reinterpret_cast<const uint8_t*>(g_w2img) + rank * (P2_B / 2);
            int kb = k0;
#pragma unroll 1
            for (int p = 0; p < P2_NPOS; p++) {
                const int st = p & 3;
                if (p == P2_RAW) {
                    flag_wait<true>(g_prog[CNT_IMG1], NUM_CTAS);
                    asm volatile("fence.proxy.async.global;\n" ::: "memory");
                    wsrc += sizeof(g_w2img[0]);
                }
                const int idle = (p < P2_S1 || p >= 6 * 48) + (p < P2_S2 ? !half || p >= 24 : p >= 5 * 48 + P2_S2);
                mbar_wait(bar_bempty + st * 8, (~p >> 2) & 1);
                TR2(3, p, 0);
                if (elect_one()) {
                    mbar_expect_tx(bar_bfull + st * 8, P2_B);
                    bulk_g2s_mc(sbase + st * P2_B + rank * (P2_B / 2), wsrc + kb * P2_B, P2_B / 2, bar_bfull + st * 8, (uint16_t)3);
                    asm volatile("st.volatile.shared.u32 [%0], %1;\n" ::"r"(s_pos), "r"(p) : "memory");
                    if (rank == 0) asm volatile("red.relaxed.gpu.global.add.u32 [%0], 1;\n" ::"l"(g_prog[CNT_POS]) : "memory");
                    if (idle) asm volatile("mbarrier.arrive.shared::cta.b64 _, [%0], %1;\n" ::"r"(bar_bempty + st * 8), "r"(8 * idle) : "memory");
                }
                __syncwarp();
                if (++kb == 48) kb = 0;
            }
            mbar_wait(bar_bempty, 1);
            if (lane == 0) mbar_arrive(bar_bfull);
        } else if (warp == 13) {
            const int w = lane % 3;
            const uint32_t dst0 = sbase + P2_OFF_A + w * P2_NA * P2_A;
            const uint32_t bf = bar_afull + w * P2_NA * 8, be = bar_aempty + w * P2_NA * 8;
            int n = (w == 2 && half ? -1 : w) - 3, left = 0, u = 0, c = 0;
            const uint8_t* src = nullptr;
            bool act = lane < 3;
            auto next = [&]() {
                n += 3;
                left = n >= P2_ITEMS ? -1 : n < 0 ? 24 : 48;
                u = (k0 + p2_start(n)) % 48;
                src = reinterpret_cast<const uint8_t*>(g_h) + (size_t)p2_tile(cl, n) * (2 * H_TILE) + rank * H_HALF + u * H_STEP;
            };
            next();
            flag_wait<true>(g_prog[CNT_EARLY], NUM_CTAS);
#pragma unroll 1
            for (int i = 3; i > 0; i--) {
                const int wi = i % 3;
                if (wi == 2) flag_wait<true>(g_prog[CNT_H], NUM_CTAS);
                asm volatile("fence.proxy.async.global;\n" ::: "memory");
                if (w == wi && lane < 24) {
                    mbar_expect_tx(bf + lane / 3 * 8, P2_A);
                    bulk_g2s(dst0 + lane / 3 * P2_A, src + lane / 3 * H_STEP, P2_A, bf + lane / 3 * 8);
                }
                __syncwarp();
            }
            c = 8;
            left -= 8;
            u += 8;
            src += 8 * H_STEP;
            if (u == 48) { u = 0; src -= 48 * H_STEP; }
            while (__any_sync(0xffffffffu, act)) {
                if (left == 0) next();
                const bool ok = act && mbar_test(be + ((c - 1) & 7) * 8, (~c >> 3) & 1);
                if (ok) {
                    const int st = c & 7;
                    if (left > 0) {
                        mbar_expect_tx(bf + st * 8, P2_A);
                        bulk_g2s(dst0 + st * P2_A, src, P2_A, bf + st * 8);
                    } else {
                        mbar_arrive(bf + st * 8);
                        act = false;
                    }
                    src += H_STEP;
                    if (++u == 48) { u = 0; src -= 48 * H_STEP; }
                    c++;
                    left--;
                }
                SAFE_BREAK;
                if (!__any_sync(0xffffffffu, ok)) __nanosleep(100);
            }
        } else if (warp == 14) {
            const uint32_t sx = sbase + P2_OFF_X;
            size_t o = 0;
            int wp = 0;
            uint32_t par = 0;
            if (fin) {
#pragma unroll 1
                for (int c = lane * 16; c < 64 * P2_XROW + 128; c += 512) asm volatile("st.shared.v4.u32 [%0], {0, 0, 0, 0};\n" ::"r"(sx + c) : "memory");
                __syncwarp();
            }
            wait_pos(6);
#pragma unroll 1
            for (int n = -half; n < P2_ITEMS; n++) {
                const int w = (n + 3) % 3, end = p2_start(n) + 48;
                const size_t on = (size_t)(2 * p2_tile(cl, n) + rank) * (64 * C_DIM * 2);
                const uint32_t xf = bar_xfull + w * 8;
                if (n < 2 || n > 12) { LAG_HERE(3); }
                bool st = n + half > 0;
                const bool ld = n < P2_ITEMS - 1 && !(n < 0 && fin);
                if (n == P2_ITEMS - 1 && lane == 0) {
                    mbar_expect_tx(xf, 64 * C_DIM * 2);
#pragma unroll 1
                    for (int c = 4; c < 12; c++) {
                        if (c >= 8) {
                            mbar_wait(bar_aempty + ((2 * c - 1) & 7) * 8, 1);
                            mbar_wait(bar_aempty + ((2 * c) & 7) * 8, 1);
                        }
                        bulk_g2s(sbase + P2_OFF_A + (c & 3) * P2_XC + (c < 8 ? P2_LHALF : 0), reinterpret_cast<const uint8_t*>(x) + on + (c & 7) * P2_XC, P2_XC, xf);
                    }
                    mbar_arrive(xf);
                }
                if (st) {
                    mbar_wait(bar_oready + wp * 8, (par >> wp) & 1);
                    par ^= 1u << wp;
                }
                if (lane == 0) {
                    if (n < P2_ITEMS - 1) mbar_expect_tx(xf, ld ? 64 * C_DIM * 2 : 0);
                    const int t0 = (n ? p2_start(n - 1) + 48 : P2_S2) + (n == P2_ITEMS - 1 ? P2_TL : P2_T0), dt = end - t0;
                    int t = st ? 16 * t0 : -4096;
                    if (n == 0 && half) {
                        if (fin) {
                            flag_wait<true>(&g_half[pair][rank], 1);
                            asm volatile("fence.proxy.async.global;\n" ::: "memory");
                        }
#pragma unroll 1
                        for (int c = 0; c < 2; c++) {
                            uint8_t* dst = reinterpret_cast<uint8_t*>(out) + o + c * 32 * P2_XROW;
                            if (!fin) bulk_s2g(dst, sx + c * P2_XHALF, 32 * P2_XROW);
                            else asm volatile("cp.reduce.async.bulk.global.shared::cta.bulk_group.add.noftz.bf16 [%0], [%1], %2;\n"
                                              ::"l"(dst), "r"(sx + c * P2_XHALF), "r"(32 * P2_XROW) : "memory");
                        }
                        asm volatile("cp.async.bulk.commit_group;\n" ::: "memory");
                        if (!fin) {
                            asm volatile("cp.async.bulk.wait_group 0;\nfence.proxy.async.global;\n" ::: "memory");
                            asm volatile("st.release.gpu.global.u32 [%0], 1;\n" ::"l"(&g_half[pair][rank]) : "memory");
                        }
                        st = false;
                    }
#pragma unroll 1
                    for (int c = 0; c < 64 * P2_XROW; c += P2_XC, t += 2 * dt) {
                        const uint32_t sp = sx + c + (c >= 32 * P2_XROW ? 64 : 0);
                        wait_pos(t >> 4);
                        if (st) bulk_s2g(reinterpret_cast<uint8_t*>(out) + o + c, sp, P2_XC);
                        asm volatile("cp.async.bulk.commit_group;\n" ::: "memory");
                        if (ld) {
                            wait_pos((t + dt) >> 4);
                            asm volatile("cp.async.bulk.wait_group.read 0;\n" ::: "memory");
                            bulk_g2s(sp, reinterpret_cast<const uint8_t*>(x) + on + c, P2_XC, xf);
                        }
                    }
                    if (rank == 0 && n > 0 && n < P2_ITEMS - 2) flag_wait<false>(g_prog[CNT_POS], P2_NCL * (end - 1));
                    if (n < P2_ITEMS - 1) mbar_arrive(xf);
                }
                __syncwarp();
                o = on;
                wp = w;
            }
            asm volatile("cp.async.bulk.wait_group.read 0;\n" ::: "memory");
        } else {
            if (blockIdx.x == 120) {
                wait_pos(P2_RAW);
                for (int i = lane; i < (LN_RING + 6) * 2; i += 32) (&g_flag[0][0][0])[i * 8] = 0;
                for (int i = lane; i < HID; i += 32) g_sq[i] = 0;
                for (int i = lane; i < 512; i += 32) g_sums[i] = 0.f;
            }
            int t = 4 * P2_XP0;
#pragma unroll 1
            for (int n = 0; n < P2_ITEMS && lane == 0; n++) {
                const uint8_t* xn = reinterpret_cast<const uint8_t*>(x) + (size_t)(2 * p2_tile(cl, n) + rank) * (64 * C_DIM * 2);
#pragma unroll 1
                for (int c = 0; c < 16; c++, t += n < P2_XPN ? 4 : P2_XPD) {
                    wait_pos(t >> 2);
                    asm volatile("cp.async.bulk.prefetch.L2.global [%0], %1;\n" ::"l"(xn + c * (P2_XC / 2)), "r"(P2_XC / 2) : "memory");
                }
            }
        }
        __syncwarp();
        cluster_sync_relaxed();
    } else {
        const int wg = warp >> 2, w = warp & 3, q = lane & 3;
        const uint32_t af = bar_afull + wg * P2_NA * 8;
        const uint32_t s_a = sbase + P2_OFF_A + wg * P2_NA * P2_A + (lane >> 3) * 512 + (lane & 7) * 64 + ((w ^ ((lane & 7) >> 1)) << 4);
        uint32_t acc0[48], acc1[48], up;
        uint4 a[2][2];

        __nv_bfloat16 gg[4];
#pragma unroll
        for (int i = 0; i < 4; i++) gg[i] = grn_g[tid + 384 * i];
#pragma unroll 1
        for (int it = !early;; it++) {
            float* s_red = reinterpret_cast<float*>(smem + P2_OFF_RED);
            float gx[4], part = 0.f;
            if (it == 1) {
                TSTAMP(1, 27);
                bar_sync(5, 416);
            }
            unsigned long long v[4];
#pragma unroll
            for (int i = 0; i < 4; i++) gx[i] = __ldcg(&g_scale[tid + 384 * i]);
            while (true) {
#pragma unroll
                for (int i = 0; i < 4; i++) asm volatile("ld.relaxed.gpu.global.u64 %0, [%1];\n" : "=l"(v[i]) : "l"(&g_sq[tid + 384 * i]) : "memory");
                SAFE_BREAK;
                if (!it || !__any_sync(0xffffffffu, min(min(v[0], v[1]), min(v[2], v[3])) < (unsigned long long)NGRP << 56)) break;
            }
            TSTAMP(1, 1);
            const float bias = reinterpret_cast<const float*>(smem + OFF_PRE)[tid];
            const float2 pre = *reinterpret_cast<const float2*>(smem + OFF_PRE + C_DIM * 4);
            bool tiny = false;
#pragma unroll
            for (int i = 0; i < 4; i++) {
                const float t = it == 2 ? __ldcg(&g_redo[tid + 384 * i]) : __ull2float_rn(v[i] << 8) * 0x1p-40f;
                tiny |= t < M_TOTAL * 0x1p-19f;
                gx[i] *= gx[i] * t;
            }
            float mg = 0.f;
#pragma unroll
            for (int i = 0; i < 4; i++) {
                asm("sqrt.approx.f32 %0, %1;\n" : "=f"(gx[i]) : "f"(gx[i] * (HSCALE * HSCALE) + 1e-6f));
                part += gx[i];
                gx[i] *= __bfloat162float(gg[i]);
                mg = fmaxf(mg, fabsf(gx[i]));
            }
#pragma unroll
            for (int o = 16; o > 0; o >>= 1) part += __shfl_xor_sync(0xffffffffu, part, o);
            const uint32_t mgw = __reduce_max_sync(0xffffffffu, __float_as_uint(mg));
            TSTAMP(1, 26);
            if (lane == 0) *reinterpret_cast<float2*>(s_red + warp * 2) = make_float2(part, __uint_as_float(mgw));
            if (it) {
                uint32_t redo;
                asm volatile("{\n.reg .pred p;\nsetp.ne.u32 p, %1, 0;\nbar.red.or.pred p, 4, 384, p;\nselp.u32 %0, 1, 0, p;\n}\n"
                             : "=r"(redo) : "r"((uint32_t)(tiny && it == 1)) : "memory");
                if (__shfl_sync(0xffffffffu, redo, 0)) {
                    p2_redo_sums(warp, lane);
                    continue;
                }
            }
            float tot = 0.f;
#pragma unroll
            for (int i = 0; i < 6; i++) {
                const float4 t = *reinterpret_cast<const float4*>(s_red + i * 4);
                tot += t.x + t.z;
                mg = fmaxf(mg, fmaxf(t.y, t.w));
            }
            const float inv = __fdividef(1.0f, tot * (1.0f / HID) + 1e-6f);
            const uint32_t ej = min((__float_as_uint(fmaxf(fmaf(mg, inv, 1.0f) * (HSCALE * UNCHOP), pre.y * 0x1p-13f)) >> 23) + 1, 250u);
            const float dn = __uint_as_float((254u - ej) << 23);
            up = min(ej + 127u - (__float_as_uint(pre.x) >> 23), 254u) * 0x00800080u;
            reinterpret_cast<uint16_t*>(smem + P2_OFF_BIAS + C_DIM * 2)[tid] = 0;
            *reinterpret_cast<__half*>(smem + P2_OFF_BIAS + (tid >> 5) * 64 + (tid & 6) * 8 + (tid & 24) / 2 + (tid & 1) * 2) = __float2half_rn(bias * dn);
#pragma unroll
            for (int i = 0; i < 4; i++) {
                const int k = tid + 384 * i;
                *reinterpret_cast<__half*>(smem + P2_OFF_GRN + (k >> 4) * 32 + (k & 6) * 4 + (k & 8) / 2 + (k & 1) * 2) =
                    __float2half_rn(fmaf(gx[i], inv, 1.0f) * (HSCALE * UNCHOP * dn));
            }
            TSTAMP(1, 25);
            if (it) break;
        }
        bar_sync(4, 384);
        asm volatile("barrier.cluster.wait.aligned;\n" ::: "memory");
        TSTAMP(1, 28);
        LAG_HERE(2);
        if (wg == 1) {
            constexpr int N = sizeof(g_w2img[0]) / 16, PER = (N + NUM_CTAS - 1) / NUM_CTAS;
            uint4 v[5];
#pragma unroll
            for (int i = 0; i < 5; i++) v[i] = __ldcg(&g_w2img[0][min(blockIdx.x * PER + (tid & 127) + 128 * i, N - 1)]);
#pragma unroll
            for (int i = 0; i < 5; i++) {
                const int j = min(blockIdx.x * PER + (tid & 127) + 128 * i, N - 1);
                const uint32_t* t = reinterpret_cast<const uint32_t*>(smem + P2_OFF_GRN + (j / 768) * 32 + (j & 8) / 2);
                auto sc = [&](uint32_t u, int e) { return (h2_mul(u, t[2 * e]) + 0x00040004u) & 0xfff8fff8u; };
                g_w2img[1][j] = make_uint4(sc(v[i].x, 0), sc(v[i].y, 1), sc(v[i].z, 2), sc(v[i].w, 3));
            }
            asm volatile("fence.proxy.async.global;\n" ::: "memory");
            bar_sync(2, 128);
            if (tid == 128) asm volatile("fence.acq_rel.gpu;\nred.release.gpu.global.add.u32 [%0], 1;\n" ::"l"(g_prog[CNT_IMG1]) : "memory");
        }

        const int who = __shfl_sync(0xffffffffu, lane == 2 ? 0 : lane < 2 ? 1 : 2, lane);
        const uint32_t rel0 = who ? mapa(bar_bempty, lane & 1) : mapa(bar_aempty + wg * P2_NA * 8, rank), rel1 = rel0 + (who ? 0 : 32);
        auto publish = [&]() {
            asm volatile("fence.proxy.async.shared::cta;\n" ::: "memory");
            __syncwarp();
            if (who == 0) mbar_arrive(bar_oready + wg * 8);
        };
        bool ok_a, pend = false;
        uint32_t pa = 0, s_t;
        auto fetch = [&](int j, bool raw) {
            uint32_t o[6], u0[4], u1[4];
            uint2 t0 = make_uint2(0, 0), t1 = t0;
            if (raw) {
                asm volatile("ld.shared.v2.u32 {%0,%1}, [%2];\n" : "=r"(t0.x), "=r"(t0.y) : "r"(s_t + j * 64) : "memory");
                asm volatile("ld.shared.v2.u32 {%0,%1}, [%2];\n" : "=r"(t1.x), "=r"(t1.y) : "r"(s_t + j * 64 + 32) : "memory");
            }
            const bool ok_b = mbar_test(bar_bfull + (j & 3) * 8, j >> 2);
            if (j == 7) pa ^= 1;
            ok_a = mbar_test(af + ((j + 1) & 7) * 8, pa);
            asm volatile("ldmatrix.sync.aligned.m8n8.x4.trans.shared.b16 {%0,%1,%2,%3}, [%4];\n"
                         : "=r"(o[0]), "=r"(o[1]), "=r"(o[2]), "=r"(o[3]) : "r"(s_a + j * P2_A) : "memory");
            asm volatile("ldmatrix.sync.aligned.m8n8.x2.trans.shared.b16 {%0,%1}, [%2];\n"
                         : "=r"(o[4]), "=r"(o[5]) : "r"(s_a + j * P2_A + 2048) : "memory");
            p2_unpack(u0, o[0], o[1], o[2]);
            p2_unpack(u1, o[3], o[4], o[5]);
            if (raw) {
                u0[0] = h2_mul(u0[0], t0.x); u0[1] = h2_mul(u0[1], t0.x); u0[2] = h2_mul(u0[2], t0.y); u0[3] = h2_mul(u0[3], t0.y);
                u1[0] = h2_mul(u1[0], t1.x); u1[1] = h2_mul(u1[1], t1.x); u1[2] = h2_mul(u1[2], t1.y); u1[3] = h2_mul(u1[3], t1.y);
            }
            a[j & 1][0] = make_uint4(u0[0], u0[1], u0[2], u0[3]);
            a[j & 1][1] = make_uint4(u1[0], u1[1], u1[2], u1[3]);
            if (!ok_b) mbar_wait(bar_bfull + (j & 3) * 8, j >> 2);
        };
        auto table = [&](int pos) { s_t = sbase + P2_OFF_GRN + q * 8 + (k0 + pos) % 48 * 64; };
        const uint32_t db0 = (uint32_t)make_desc(sbase, 128, 256);
        auto block8 = [&](bool raw, int pos, int thr0, int mode) {
#pragma unroll
            for (int j = 0; j < 8; j++) {
                const uint32_t db = db0 + (j & 3) * (P2_B / 16);
                if (j == 8 - P2_AH && mode == 1) bar_sync(4, 384);
                TR2(wg, pos + j, 0);
                wg_fence();
                mma_rs_n192(acc0, a[j & 1][0], db);
                mma_rs_n192(acc1, a[j & 1][0], db + 384);
                mma_rs_n192(acc0, a[j & 1][1], db + 768);
                mma_rs_n192(acc1, a[j & 1][1], db + 768 + 384);
                wg_commit();
                if (j == 7 && mode == 2) bar_arrive(4, 384);
                const uint32_t rel = ((j - 1) & 4 ? rel1 : rel0) + ((j - 1) & 3) * 8;
                TR2(wg, pos + j, 1);
                wg_wait<1>();
                TR2(wg, pos + j, 2);
                if (who < (j ? 2 : thr0)) mbar_arrive_cluster(rel);
                if (!ok_a) {
                    if (j == 0 && pend) { publish(); pend = false; }
                    mbar_wait(af + ((j + 1) & 7) * 8, pa);
                }
                TR2(wg, pos + j, 3);
                if (raw && j == 7) table(pos + 8);
                fetch((j + 1) & 7, raw && (j < 7 || pos + 8 < P2_RAW));
            }
        };
        int n = wg == 2 && half ? -1 : wg, pos = p2_start(n);
        uint32_t px = 0;
        wait_pos(pos);
        mbar_wait(af, 0);
        table(pos);
        fetch(0, pos < P2_RAW);
#pragma unroll 1
        for (;; n += 3) {
            TSTAMP(1, 2 + n);
            const int end = pos + (n < 0 ? 24 : 48);
#pragma unroll
            for (int i = 0; i < 48; i += 2) {
                asm volatile("mov.b64 {%0, %1}, 0;\n" : "=r"(acc0[i]), "=r"(acc0[i + 1]));
                asm volatile("mov.b64 {%0, %1}, 0;\n" : "=r"(acc1[i]), "=r"(acc1[i + 1]));
            }
            int thr = 1;
#pragma unroll 1
            for (; pos < P2_RAW; pos += 8, thr = 2) block8(true, pos, thr, 0);
#pragma unroll 1
            for (; pos < end; pos += 8, thr = 2) {
                const int e = pos + 8, r = e % 48;
                block8(false, pos, thr, e < 48 || e > 256 || (r != 0 && r != P2_S1 && r != P2_S2) ? 0 : e == end ? 2 : 1);
            }
            TR2(wg, pos - 1, 4);
            if (n < 2 || n > 12) { LAG_HERE(3); }
            wg_wait<0>();
            TR2(wg, pos - 1, 5);
            if (who == 1) mbar_arrive_cluster(rel0 + 24);
            mbar_wait(bar_xfull + wg * 8, px);
            TR2(wg, pos - 1, 6);
            px ^= 1;
            __syncwarp();
            const bool last = n == P2_ITEMS - 1;
            uint32_t l;
            asm volatile("mov.u32 %0, %%laneid;\n" : "=r"(l));
            const uint32_t q16 = (l & 3) * 16, odd = (l >> 2) & 1, row = (w * 8 + (l >> 3)) * P2_XROW + q16;
            uint8_t* so = last ? reinterpret_cast<uint8_t*>(out) + (size_t)(2 * p2_tile(cl, n) + rank) * (64 * P2_XROW) : smem + P2_OFF_X;
            p2_epilogue(acc0, acc1, up, sbase + row + (last ? P2_OFF_A + odd * P2_LHALF : P2_OFF_X + odd * P2_XHALF),
                        sbase + P2_OFF_BIAS + q16 + (n < 0 && fin ? C_DIM * 2 : 0), so + (row + odd * (last ? 32 * P2_XROW : P2_XHALF)), zero);
            if (last) break;
            TR2(wg, pos - 1, 7);
            if (n + 3 >= P2_ITEMS) { publish(); break; }
            if (n < 0) {
                publish();
                pos = P2_S2;
                wait_pos(pos);
                mbar_wait(bar_bfull, 0);
            } else {
                pend = true;
                ok_a = false;
            }
        }
        TSTAMP(1, 29);
        cluster_sync_relaxed();
        TSTAMP(1, 30);
    }
}

__global__ void __cluster_dims__(2, 1, 1) __launch_bounds__(512, 1)
block_kernel(const __grid_constant__ CUtensorMap wmap, const __nv_bfloat16* __restrict__ x, const __nv_bfloat16* __restrict__ dw,
             const __nv_bfloat16* __restrict__ w2, const __nv_bfloat16* __restrict__ grn_g, const __nv_bfloat16* __restrict__ grn_b,
             __nv_bfloat16* __restrict__ out, int zero) {
    extern __shared__ __align__(1024) uint8_t smem[];
    const uint32_t sbase = smem_u32(smem);
    const int warp = __shfl_sync(0xffffffffu, threadIdx.x >> 5, 0), lane = threadIdx.x & 31;
    if (warp >= 12) {
        pass1<2>(wmap, x, dw, w2, grn_b, sbase, warp, lane, zero);
        pass2<2>(x, grn_g, out, smem, sbase, false, zero);
    } else {
        bool early = false;
        if (warp >= 8) {
            pass1<1>(wmap, x, dw, w2, grn_b, sbase, warp, lane, zero);
            reg_inc<160>();
        } else {
            early = pass1<0>(wmap, x, dw, w2, grn_b, sbase, warp, lane, zero);
            reg_dec<160>();
        }
        pass2<0>(x, grn_g, out, smem, sbase, early, zero);
    }
}

}

extern "C" void kernel_launch(void* const* d_in, const int* in_sizes, int n_in, void* d_out, int out_size) {
    const __nv_bfloat16* x = (const __nv_bfloat16*)d_in[0];
    const __nv_bfloat16* dw = (const __nv_bfloat16*)d_in[1];
    const __nv_bfloat16* w1 = (const __nv_bfloat16*)d_in[2];
    const __nv_bfloat16* w2 = (const __nv_bfloat16*)d_in[3];
    const __nv_bfloat16* grn_g = (const __nv_bfloat16*)d_in[4];
    const __nv_bfloat16* grn_b = (const __nv_bfloat16*)d_in[5];
    __nv_bfloat16* out = (__nv_bfloat16*)d_out;

    cudaFuncSetAttribute(block_kernel, cudaFuncAttributeMaxDynamicSharedMemorySize, SMEM_BYTES);

    typedef CUresult (*EncodeFn)(CUtensorMap*, CUtensorMapDataType, cuuint32_t, void*, const cuuint64_t*, const cuuint64_t*,
                                 const cuuint32_t*, const cuuint32_t*, CUtensorMapInterleave, CUtensorMapSwizzle,
                                 CUtensorMapL2promotion, CUtensorMapFloatOOBfill);
    static EncodeFn encode = nullptr;
    if (!encode) {
        cudaDriverEntryPointQueryResult qres;
        cudaGetDriverEntryPoint("cuTensorMapEncodeTiled", (void**)&encode, cudaEnableDefault, &qres);
    }
    CUtensorMap wmap;
    const cuuint64_t gdim[2] = {HID, C_DIM};
    const cuuint64_t gstr[1] = {HID * 2};
    const cuuint32_t box[2] = {64, 192}, estr[2] = {1, 1};
    CUresult er = encode(&wmap, CU_TENSOR_MAP_DATA_TYPE_BFLOAT16, 2, (void*)w1, gdim, gstr, box, estr, CU_TENSOR_MAP_INTERLEAVE_NONE,
           CU_TENSOR_MAP_SWIZZLE_128B, CU_TENSOR_MAP_L2_PROMOTION_L2_128B, CU_TENSOR_MAP_FLOAT_OOB_FILL_NONE);
    if (er != CUDA_SUCCESS) printf("tensor map encode failed %d\n", (int)er);

    block_kernel<<<NUM_CTAS, 512, SMEM_BYTES>>>(wmap, x, dw, w2, grn_g, grn_b, out, 0);
}
```

```cpp
#include <cuda.h>
#include <cuda_runtime.h>
#include <cuda_bf16.h>
#include <cuda_fp16.h>
#include <stdint.h>
#include <stdio.h>

namespace {

constexpr int M_TOTAL = 384 * 384;
constexpr int C_DIM   = 384;
constexpr int HID     = 1536;
constexpr int NT128   = M_TOTAL / 128;
constexpr int NUM_CTAS = 132;

constexpr int NGRP = 22, GRP_CTAS = 6;
constexpr int NT_EARLY = NT128 - 30;
constexpr int LN_STEP = NUM_CTAS / 4, LN_RING = 2 * LN_STEP;
constexpr int LN_TILE = 128 * C_DIM * 2;
constexpr int H_PAGES = NT128 / 4;

__device__ __align__(1024) uint4 g_h[(size_t)(H_PAGES + 1) << 17];
__device__ unsigned g_page[H_PAGES];
__device__ unsigned g_epoch;
__device__ __align__(1024) uint4 g_ln[LN_RING * LN_TILE / 16];
__device__ __align__(1024) uint4 g_w2img[2][HID * C_DIM * 2 / 16];
__device__ __align__(16) unsigned long long g_sq[HID];
__device__ __align__(16) float g_sums[512];
__device__ float g_scale[HID];
__device__ float g_redo[HID];
enum { CNT_POS, CNT_IMG1, CNT_REDO, CNT_IMG0, CNT_LAST, CNT_H, CNT_EARLY, NUM_CNT };
__device__ __align__(128) unsigned g_prog[NUM_CNT][32];
__device__ __align__(128) unsigned g_half[32][2];
__device__ unsigned g_flag[LN_RING + 6][2][8];
#define TSTAMP(k, i)
#define TRACE(wg, pos, i)
#define TRACEW(pos, i)

#define TR2(wg, pos, i)
__host__ __device__ __forceinline__ int perm32(int n) {
    return (n & ~31) | (((n >> 1) & 3) << 3) | (((n >> 3) & 3) << 1) | (n & 1);
}

constexpr int H_FIXED = 16;
__device__ __forceinline__ uint8_t* h_base() { return reinterpret_cast<uint8_t*>((reinterpret_cast<size_t>(g_h) + 0x1fffff) & ~(size_t)0x1fffff); }
__device__ __forceinline__ uint32_t h_tile(int t, unsigned tag = 0) {
    unsigned v = 0;
    if (t >= 4 * H_FIXED) {
        do {
            asm volatile("ld.relaxed.gpu.global.u32 %0, [%1];\n" : "=r"(v) : "l"(&g_page[t >> 2]) : "memory");
        } while (tag && (v & ~1u) != tag);
    }
    return (t >> 1) << 20 | ((t ^ v) & 1) << 12 | (t & 2) << 9;
}
__device__ __forceinline__ uint32_t h_block(int kb, int half) {
    return (kb >> 2) << 16 | (kb & 2) << 14 | half << 14 | (kb & 1) << 13 | (__popc(kb & 0x2d) & 1) << 12 | (kb & 1) << 10;
}
__device__ __forceinline__ unsigned* h_cell(int page, int c) {
    return reinterpret_cast<unsigned*>(h_base() + ((size_t)page << 21) + 0xd0000 + ((c >> 5) << 14) + (c & 31) * 128);
}
__device__ __forceinline__ unsigned near_half(unsigned* cell, int reps) {
    int votes = 0;
#pragma unroll 1
    for (int i = 0; i < 2 * reps; i++) {
        const unsigned a = atomicAdd(cell + (i & 1) * 1024, 1u), b = atomicAdd(cell + (~i & 1) * 1024, 1u);
        if (a == ~0u) break;
        const unsigned t0 = clock();
        if (b == ~0u) break;
        const int d = min((unsigned)clock() - t0, 250u);
        votes += i & 1 ? d : -d;
    }
    return votes > 0;
}

__device__ __forceinline__ uint32_t smem_u32(const void* p) { return (uint32_t)__cvta_generic_to_shared(p); }

__device__ __forceinline__ void mbar_init(uint32_t bar, uint32_t count) {
    asm volatile("mbarrier.init.shared::cta.b64 [%0], %1;\n" ::"r"(bar), "r"(count) : "memory");
}
__device__ __forceinline__ void mbar_expect_tx(uint32_t bar, uint32_t bytes) {
    asm volatile("mbarrier.arrive.expect_tx.shared::cta.b64 _, [%0], %1;\n" ::"r"(bar), "r"(bytes) : "memory");
}
__device__ __forceinline__ void mbar_arrive(uint32_t bar) {
    asm volatile("mbarrier.arrive.shared::cta.b64 _, [%0];\n" ::"r"(bar) : "memory");
}
__device__ __forceinline__ void mbar_arrive_cluster(uint32_t bar_cluster_addr) {
    asm volatile("mbarrier.arrive.shared::cluster.b64 _, [%0];\n" ::"r"(bar_cluster_addr) : "memory");
}
#define LAG_HERE(k)
#define SAFE_BREAK
__device__ __forceinline__ void mbar_wait(uint32_t bar, uint32_t parity) {
    asm volatile(
        "{\n"
        ".reg .pred p;\n"
        "LAB_WAIT:\n"
        "mbarrier.try_wait.parity.shared::cta.b64 p, [%0], %1;\n"
        "@!p bra LAB_WAIT;\n"
        "}\n" ::"r"(bar), "r"(parity) : "memory");
}
__device__ __forceinline__ bool mbar_test(uint32_t bar, uint32_t parity) {
    uint32_t ok;
    asm volatile("{\n.reg .pred p;\n"
                 "mbarrier.test_wait.parity.shared::cta.b64 p, [%1], %2;\n"
                 "selp.u32 %0, 1, 0, p;\n}\n" : "=r"(ok) : "r"(bar), "r"(parity) : "memory");
    return ok != 0;
}
__device__ __forceinline__ uint32_t mapa(uint32_t addr, uint32_t rank) {
    uint32_t r;
    asm volatile("mapa.shared::cluster.u32 %0, %1, %2;\n" : "=r"(r) : "r"(addr), "r"(rank));
    return r;
}
__device__ __forceinline__ void bulk_g2s(uint32_t dst, const void* src, uint32_t bytes, uint32_t bar) {
    asm volatile("cp.async.bulk.shared::cluster.global.mbarrier::complete_tx::bytes [%0], [%1], %2, [%3];\n"
                 ::"r"(dst), "l"(src), "r"(bytes), "r"(bar) : "memory");
}
__device__ __forceinline__ void bulk_g2s_mc(uint32_t dst, const void* src, uint32_t bytes, uint32_t bar, uint16_t mask) {
    asm volatile("cp.async.bulk.shared::cluster.global.mbarrier::complete_tx::bytes.multicast::cluster [%0], [%1], %2, [%3], %4;\n"
                 ::"r"(dst), "l"(src), "r"(bytes), "r"(bar), "h"(mask) : "memory");
}
__device__ __forceinline__ void tma2(uint32_t dst, const CUtensorMap* map, int c0, int c1, uint32_t bar) {
    asm volatile("cp.async.bulk.tensor.2d.shared::cluster.global.tile.mbarrier::complete_tx::bytes [%0], [%1, {%2, %3}], [%4];\n"
                 ::"r"(dst), "l"(map), "r"(c0), "r"(c1), "r"(bar) : "memory");
}
template <bool ACQ>
__device__ __forceinline__ uint32_t flag_wait(const unsigned* p, unsigned target) {
    unsigned v, n = 0;
    do {
        if (ACQ) asm volatile("ld.acquire.gpu.global.u32 %0, [%1];\n" : "=r"(v) : "l"(p) : "memory");
        else asm volatile("ld.relaxed.gpu.global.u32 %0, [%1];\n" : "=r"(v) : "l"(p) : "memory");
        n++;
    } while (v < target);
    return n == 1;
}
__device__ __forceinline__ void ldsm4t(uint32_t (&r)[4], uint32_t addr) {
    asm volatile("ldmatrix.sync.aligned.m8n8.x4.trans.shared.b16 {%0,%1,%2,%3}, [%4];\n"
                 : "=r"(r[0]), "=r"(r[1]), "=r"(r[2]), "=r"(r[3]) : "r"(addr) : "memory");
}
__device__ __forceinline__ void bulk_s2g(void* dst, uint32_t src, uint32_t bytes) {
    asm volatile("cp.async.bulk.global.shared::cta.bulk_group [%0], [%1], %2;\n" ::"l"(dst), "r"(src), "r"(bytes) : "memory");
}
__device__ __forceinline__ void cluster_sync_relaxed() {
    asm volatile("barrier.cluster.arrive.relaxed.aligned;\nbarrier.cluster.wait.aligned;\n" ::: "memory");
}
__device__ __forceinline__ uint32_t cluster_rank() {
    uint32_t r;
    asm volatile("mov.u32 %0, %%cluster_ctarank;\n" : "=r"(r));
    return r;
}
__device__ __forceinline__ bool elect_one() {
    uint32_t pred;
    asm volatile("{\n.reg .pred p;\nelect.sync _|p, 0xffffffff;\nselp.u32 %0, 1, 0, p;\n}\n" : "=r"(pred));
    return pred != 0;
}
__device__ __forceinline__ void wg_fence() { asm volatile("wgmma.fence.sync.aligned;\n" ::: "memory"); }
__device__ __forceinline__ void wg_commit() { asm volatile("wgmma.commit_group.sync.aligned;\n" ::: "memory"); }
template <int N> __device__ __forceinline__ void wg_wait() {
    asm volatile("wgmma.wait_group.sync.aligned %0;\n" ::"n"(N) : "memory");
}
template <int R> __device__ __forceinline__ void reg_inc() { asm volatile("setmaxnreg.inc.sync.aligned.u32 %0;\n" ::"n"(R)); }
template <int R> __device__ __forceinline__ void reg_dec() { asm volatile("setmaxnreg.dec.sync.aligned.u32 %0;\n" ::"n"(R)); }
__device__ __forceinline__ void bar_sync(int id, int n) { asm volatile("bar.sync %0, %1;\n" ::"r"(id), "r"(n) : "memory"); }
__device__ __forceinline__ void bar_arrive(int id, int n) { asm volatile("bar.arrive %0, %1;\n" ::"r"(id), "r"(n) : "memory"); }

__device__ __forceinline__ uint64_t make_desc(uint32_t saddr, uint32_t lbo, uint32_t sbo) {
    return (uint64_t)((saddr & 0x3FFFF) >> 4) | ((uint64_t)(lbo >> 4) << 16) | ((uint64_t)(sbo >> 4) << 32);
}

__device__ __forceinline__ void stg128_cs(void* p, uint32_t a, uint32_t b, uint32_t c, uint32_t d) {
    asm volatile("st.global.cs.v4.u32 [%0], {%1,%2,%3,%4};\n" ::"l"(p), "r"(a), "r"(b), "r"(c), "r"(d) : "memory");
}
__device__ __forceinline__ uint32_t pack_bf16(float lo, float hi) {
    uint32_t r;
    asm("cvt.rn.bf16x2.f32 %0, %1, %2;\n" : "=r"(r) : "f"(hi), "f"(lo));
    return r;
}
__device__ __forceinline__ float bf_lo(uint32_t v) { return __uint_as_float(v << 16); }
__device__ __forceinline__ float bf_hi(uint32_t v) { return __uint_as_float(v & 0xffff0000u); }
__device__ __forceinline__ uint32_t bf2_mul(uint32_t a, uint32_t b) {
    uint32_t r;
    asm("mul.rn.bf16x2 %0, %1, %2;\n" : "=r"(r) : "r"(a), "r"(b));
    return r;
}
__device__ __forceinline__ uint32_t bf2_fma(uint32_t a, uint32_t b, uint32_t c) {
    uint32_t r;
    asm("fma.rn.bf16x2 %0, %1, %2, %3;\n" : "=r"(r) : "r"(a), "r"(b), "r"(c));
    return r;
}
__device__ __forceinline__ uint32_t bf2_add(uint32_t a, uint32_t b) {
    uint32_t r;
    asm("add.rn.bf16x2 %0, %1, %2;\n" : "=r"(r) : "r"(a), "r"(b));
    return r;
}
__device__ __forceinline__ uint32_t h2_mul(uint32_t a, uint32_t b) {
    uint32_t r;
    asm("mul.rn.f16x2 %0, %1, %2;\n" : "=r"(r) : "r"(a), "r"(b));
    return r;
}
__device__ __forceinline__ uint32_t h2_fma(uint32_t a, uint32_t b, uint32_t c) {
    uint32_t r;
    asm("fma.rn.f16x2 %0, %1, %2, %3;\n" : "=r"(r) : "r"(a), "r"(b), "r"(c));
    return r;
}
__device__ __forceinline__ uint32_t h2_add(uint32_t a, uint32_t b) {
    uint32_t r;
    asm("add.rn.f16x2 %0, %1, %2;\n" : "=r"(r) : "r"(a), "r"(b));
    return r;
}
__device__ __forceinline__ uint32_t pack_f16(float lo, float hi) {
    uint32_t r;
    asm("cvt.rn.f16x2.f32 %0, %1, %2;\n" : "=r"(r) : "f"(hi), "f"(lo));
    return r;
}
__device__ __forceinline__ float h_lo(uint32_t v) { return __low2float(*reinterpret_cast<const __half2*>(&v)); }
__device__ __forceinline__ float h_hi(uint32_t v) { return __high2float(*reinterpret_cast<const __half2*>(&v)); }
__device__ __forceinline__ uint32_t bf2_to_h2(uint32_t v) { return (v & 0x7fff7fffu) * 7u + v; }
__device__ __forceinline__ uint32_t prmt(uint32_t a, uint32_t b, uint32_t sel) {
    uint32_t r;
    asm("prmt.b32 %0, %1, %2, %3;\n" : "=r"(r) : "r"(a), "r"(b), "r"(sel));
    return r;
}
__device__ __forceinline__ uint32_t bitsel(uint32_t a, uint32_t b, uint32_t m) {
    uint32_t r;
    asm("lop3.b32 %0, %1, %2, %3, 0xd8;\n" : "=r"(r) : "r"(a), "r"(b), "r"(m));
    return r;
}
constexpr float KAPPA = 0.3292034911525734f;
constexpr uint32_t GELU_C2 = 0x40d940d9u;
constexpr float HSCALE = 1.0f / (2.0f * KAPPA);
__device__ __forceinline__ float w2_scale(uint32_t m) { return __uint_as_float((257u - max(m >> 23, 16u)) << 23); }
__device__ __forceinline__ void sched_break(int zero) {
    asm volatile("{\n.reg .pred p;\nsetp.ne.s32 p, %0, 0;\nSB_LOOP:\n@p nanosleep.u32 1;\n@p bra SB_LOOP;\n}\n" ::"r"(zero));
}

#define ACC8(d, o) "+r"(d[o + 0]), "+r"(d[o + 1]), "+r"(d[o + 2]), "+r"(d[o + 3]), "+r"(d[o + 4]), "+r"(d[o + 5]), "+r"(d[o + 6]), "+r"(d[o + 7])

__device__ __forceinline__ void mma_rs_n128(uint32_t (&d)[32], const uint32_t (&a)[4], uint64_t desc, int scale_d) {
    asm volatile(
        "{\n.reg .pred p;\nsetp.ne.b32 p, %37, 0;\n"
        "wgmma.mma_async.sync.aligned.m64n128k16.f16.f16.f16 "
        "{%0,%1,%2,%3,%4,%5,%6,%7,%8,%9,%10,%11,%12,%13,%14,%15,"
        "%16,%17,%18,%19,%20,%21,%22,%23,%24,%25,%26,%27,%28,%29,%30,%31},"
        "{%32,%33,%34,%35}, %36, p, 1, 1, 0;\n}\n"
        : ACC8(d, 0), ACC8(d, 8), ACC8(d, 16), ACC8(d, 24)
        : "r"(a[0]), "r"(a[1]), "r"(a[2]), "r"(a[3]), "l"(desc), "r"(scale_d));
}

__device__ __forceinline__ void mma_ss_n128(uint32_t (&d)[32], uint64_t da, uint64_t db, int scale_d) {
    asm volatile(
        "{\n.reg .pred p;\nsetp.ne.b32 p, %34, 0;\n"
        "wgmma.mma_async.sync.aligned.m64n128k16.f16.f16.f16 "
        "{%0,%1,%2,%3,%4,%5,%6,%7,%8,%9,%10,%11,%12,%13,%14,%15,"
        "%16,%17,%18,%19,%20,%21,%22,%23,%24,%25,%26,%27,%28,%29,%30,%31},"
        "%32, %33, p, 1, 1, 1, 0;\n}\n"
        : ACC8(d, 0), ACC8(d, 8), ACC8(d, 16), ACC8(d, 24)
        : "l"(da), "l"(db), "r"(scale_d));
}

__device__ __forceinline__ void mma_rs_n192(uint32_t (&d)[48], const uint4& a, uint64_t db) {
    asm volatile(
        "wgmma.mma_async.sync.aligned.m64n192k16.f16.f16.f16 "
        "{%0,%1,%2,%3,%4,%5,%6,%7,%8,%9,%10,%11,%12,%13,%14,%15,"
        "%16,%17,%18,%19,%20,%21,%22,%23,%24,%25,%26,%27,%28,%29,%30,%31,"
        "%32,%33,%34,%35,%36,%37,%38,%39,%40,%41,%42,%43,%44,%45,%46,%47},"
        "{%48,%49,%50,%51}, %52, 1, 1, 1, 0;\n"
        : ACC8(d, 0), ACC8(d, 8), ACC8(d, 16), ACC8(d, 24), ACC8(d, 32), ACC8(d, 40)
        : "r"(a.x), "r"(a.y), "r"(a.z), "r"(a.w), "l"(db));
}

constexpr int P1_SPLIT = 6;
constexpr int P1_SLOT = LN_TILE / 6, P1_NST = 6;
constexpr int P1_W = 64 * C_DIM * 2;
constexpr int P1_X = 32 * C_DIM * 2;
constexpr int P1_OFF_W = LN_TILE;
constexpr int P1_OFF_X = P1_OFF_W + 2 * P1_W;
constexpr int P1_OFF_BAR = 227328;
constexpr int P1_OFF_TILE = P1_OFF_BAR + (2 * P1_NST + 4 + 4 + 4) * 8;
constexpr int P1_OFF_EX = P1_OFF_TILE + 64;
constexpr int P1_OFF_DW = P1_OFF_EX + 256 * 4;
constexpr int OFF_PRE = P1_OFF_DW + C_DIM * 2;
constexpr int SMEM_BYTES = OFF_PRE + C_DIM * 4 + 16;

__device__ __forceinline__ float rsqrt_fast(float x) {
    float r;
    asm("rsqrt.approx.ftz.f32 %0, %1;\n" : "=f"(r) : "f"(x));
    return r;
}
__device__ __forceinline__ float row_sum(const uint32_t (&c)[4]) {
    const uint32_t u = bf2_add(bf2_add(c[0], c[1]), bf2_add(c[2], c[3]));
    float s = bf_lo(u) + bf_hi(u);
#pragma unroll
    for (int o = 1; o < 8; o <<= 1) s += __shfl_xor_sync(0xffffffffu, s, o);
    return s;
}
__device__ __forceinline__ uint32_t pace(uint32_t bar, uint32_t off, uint32_t val, int zero) {
    asm volatile(
        "{\n.reg .pred p, q;\n.reg .b32 par;\n"
        "lop3.b32 par, %0, %2, %3, 0xea;\n"
        "setp.eq.u32 q, par, 0;\n"
        "mov.pred p, 0;\n"
        "@q mbarrier.test_wait.parity.shared::cta.b64 p, [%1], par;\n"
        "selp.u32 par, 1, 0, p;\n"
        "@q mbarrier.try_wait.parity.shared::cta.b64 p, [%1], par, 1000;\n"
        "@p or.b32 %0, %0, %2;\n"
        "}\n" : "+r"(val) : "r"(bar), "r"(zero), "r"(off));
    return val;
}
__device__ __forceinline__ void ln_row(uint32_t (&v)[6][4], const uint32_t (&d)[6][4], uint32_t bar, uint32_t off, int zero, uint32_t bar_read) {
    const float inv = 1.0f / C_DIM;
    uint32_t c[4];
#pragma unroll
    for (int i = 0; i < 6; i++)
#pragma unroll
        for (int k = 0; k < 4; k++) c[k] = bf2_fma(v[i][k], d[i][k], i ? c[k] : 0);
    const float m = row_sum(c) * inv;
    uint32_t nm = pack_bf16(-m, -m);
    const float e = m + bf_lo(nm);
    if (bar_read) mbar_arrive(bar_read + (nm & zero));
    nm = pace(bar, off, nm, zero);
#pragma unroll
    for (int i = 0; i < 6; i++) {
#pragma unroll
        for (int k = 0; k < 4; k++) {
            v[i][k] = bf2_fma(v[i][k], d[i][k], nm);
            c[k] = i ? bf2_fma(v[i][k], v[i][k], c[k]) : bf2_mul(v[i][k], v[i][k]);
        }
    }
    float r = KAPPA * rsqrt_fast(fmaxf(fmaf(-e, e, row_sum(c) * inv), 0.f) + 1e-5f);
    const float er = -e * r * 0x1p-112f;
    if (__any_sync(0xffffffffu, r < 0x1p-8f)) {
        const uint32_t p2 = __float_as_uint(r) & 0x7f800000u;
        r = __uint_as_float((__float_as_uint(r) & 0x007fffffu) | 0x3f800000u);
#pragma unroll
        for (int i = 0; i < 6; i++)
#pragma unroll
            for (int k = 0; k < 4; k++) v[i][k] = bf2_mul(v[i][k], p2 | p2 >> 16);
    }
    const uint32_t rs = pack_bf16(r * 0x1p-112f, r * 0x1p-112f), sh = pack_bf16(er, er);
#pragma unroll
    for (int i = 0; i < 6; i++)
#pragma unroll
        for (int k = 0; k < 4; k++) v[i][k] = bf2_to_h2(bf2_fma(v[i][k], rs, sh));
}

template <int R>
__device__ __forceinline__ uint32_t gelu2(uint32_t a, uint32_t sc2) {
    uint32_t y, t;
    if (R) asm("{\n.reg .b16 l, h;\n.reg .b32 f;\nmov.b32 {l, h}, %2;\nmov.b32 f, {h, h};\nmul.rn.f16x2 %0, %1, f;\n}\n" : "=r"(y) : "r"(a), "r"(sc2));
    else asm("{\n.reg .b16 l, h;\n.reg .b32 f;\nmov.b32 {l, h}, %2;\nmov.b32 f, {l, l};\nmul.rn.f16x2 %0, %1, f;\n}\n" : "=r"(y) : "r"(a), "r"(sc2));
    asm("tanh.approx.f16x2 %0, %1;\n" : "=r"(t) : "r"(h2_mul(y, h2_fma(y, y, GELU_C2))));
    return h2_fma(a, t, a);
}
constexpr uint32_t SPARE = 0x40074007u;
constexpr float UNCHOP = 1.0023f;

__device__ __forceinline__ uint32_t p1_exponents(float (&t)[2], uint32_t (&ex)[2], uint32_t saddr, int lane) {
#pragma unroll
    for (int r = 0; r < 2; r++) {
        t[r] += __shfl_xor_sync(0xffffffffu, t[r], 1);
        t[r] += __shfl_xor_sync(0xffffffffu, t[r], 2);
        ex[r] = min(max(((__float_as_uint(193.3f * t[r]) >> 23) + 127u) >> 1, 72u), 198u);
        asm volatile("st.shared.u32 [%0], %1;\n" ::"r"(saddr + r * 32), "r"(ex[r] << 23) : "memory");
    }
    return pack_f16(__uint_as_float(min(ex[0], 142u) << 23), __uint_as_float(min(ex[1], 142u) << 23));
}
template <int N>
__device__ __forceinline__ void p1_convert(uint32_t (&o)[N][4], uint32_t (&v)[N][4], const uint32_t (&ex)[2]) {
    if (__any_sync(0xffffffffu, max(ex[0], ex[1]) > 141u)) {
#pragma unroll
        for (int k = 0; k < 4 * N; k++) v[k >> 2][k & 3] = bf2_mul(v[k >> 2][k & 3], ex[k & 1] > 141u ? 0x1f801f80u : 0x3f803f80u);
    }
#pragma unroll
    for (int k = 0; k < 4 * N; k++) {
        const uint32_t u = bf2_mul(v[k >> 2][k & 3], ((ex[k & 1] > 141u ? 206u : 142u) - ex[k & 1]) * 0x00800080u);
        asm volatile("mad.lo.u32 %0, %1, 7, %2;\n" : "=r"(o[k >> 2][k & 3]) : "r"(u & 0x7fff7fffu), "r"(u));
    }
}
template <int N>
__device__ __forceinline__ void p1_squares(const uint32_t (&v)[N][4], float (&t)[2]) {
#pragma unroll
    for (int j = 0; j < N / 2; j++) {
        const int r = j & 1, b = (j >> 1) * 4;
        uint32_t c = bf2_mul(v[b][r], v[b][r]);
#pragma unroll
        for (int k = 1; k < 8; k++) c = bf2_fma(v[b + k / 2][r + (k & 1) * 2], v[b + k / 2][r + (k & 1) * 2], c);
        t[r] += bf_lo(c) + bf_hi(c);
    }
}
__device__ __forceinline__ void p1_epilogue(const uint32_t (&acc)[2][32], const uint32_t (&sc2)[2], float (&ssq)[4], uint8_t* hp, int zero) {
    uint32_t sq[2], h[16][4];
#pragma unroll
    for (int i2 = 0; i2 < 9; i2++) {
#pragma unroll
        for (int c = 2 * i2 - 2; c < 2 * i2; c++) {
            if (c >= 0 && (c & 3)) {
                uint32_t o[4];
#pragma unroll
                for (int u = 0; u < 4; u++) {
                    const uint32_t v = h[c & 12][u];
                    o[u] = bitsel(h[c][u], (c & 3) == 2 ? prmt(v, v, 0xa381) : prmt(v >> 3, v, (c & 3) == 1 ? 0x6240 : 0xf3d1), SPARE);
                }
                stg128_cs(hp + (c >> 2) * 0x4000 + ((c & 3) - 1) * 512, o[0], o[1], o[2], o[3]);
            }
        }
        if (i2 < 8) {
#pragma unroll
            for (int u = 0; u < 4; u++) {
                h[2 * i2][u] = gelu2<0>(acc[i2 >> 2][8 * (i2 & 3) + 2 * u], sc2[i2 >> 2]);
                h[2 * i2 + 1][u] = gelu2<1>(acc[i2 >> 2][8 * (i2 & 3) + 2 * u + 1], sc2[i2 >> 2]);
#pragma unroll
                for (int r = 0; r < 2; r++) {
                    const uint32_t v = h[2 * i2 + r][u];
                    sq[r] = ((i2 & 3) | u) ? h2_fma(v, v, sq[r]) : h2_mul(v, v);
                }
            }
            if ((i2 & 3) == 3) {
#pragma unroll
                for (int r = 0; r < 2; r++) ssq[(i2 >> 2) * 2 + r] += h_lo(sq[r]) + h_hi(sq[r]);
            }
            sched_break(zero);
        }
    }
}
template <int WG>
__device__ __forceinline__ void p1_mma(uint32_t (&acc)[2][32], const uint32_t (&a)[24][4], uint32_t sbase, uint32_t empty_remote, int i, int lane, bool pass, int zero) {
    const uint32_t bar_full = sbase + P1_OFF_BAR;
    const uint64_t db = make_desc(sbase, 16, 1024 + zero) | (1ull << 62), da = db + (P1_OFF_W + WG * P1_W) / 16;
    if (WG == 0) mbar_wait(bar_full, i & 1);
    bar_sync(1 + WG, 256);
    TRACE(WG, i, 1);
    wg_fence();
#pragma unroll
    for (int k = 0; k < 24; k++) {
        if (WG == 0 && k && k % 4 == 0) mbar_wait(bar_full + (k >> 2) * 8, i & 1);
        mma_rs_n128(acc[0], a[k], db + (k >> 2) * 1024 + (k & 3) * 2, k != 0);
        mma_ss_n128(acc[1], da + k * 128, db + (k >> 2) * 1024 + (k & 3) * 2, k != 0);
        if (k == 23 && pass) bar_arrive(2 - WG, 256);
        if (k == 23 || (WG == 1 && k % 4 == 3)) wg_commit();
        if (WG == 1 && k % 4 == 3 && k > 3) {
            wg_wait<1>();
            if (lane < 2) mbar_arrive_cluster(empty_remote + ((k >> 2) - 1) * 8);
        }
    }
    TRACE(WG, i, 2);
    wg_wait<0>();
    if (WG == 1 && lane < 2) mbar_arrive_cluster(empty_remote + 5 * 8);
}
__device__ __forceinline__ bool p1_consumer(const uint32_t (&a)[24][4], const uint32_t (&sc2)[2], uint32_t sbase, int WG, int w, int lane, int zero) {
    const uint32_t bar_full = sbase + P1_OFF_BAR, bar_empty = bar_full + P1_NST * 8;
    const uint32_t empty_remote = mapa(bar_empty, lane & 1);
    const uint32_t bar_pace = bar_empty + P1_NST * 8 + 32 + w * 8;
    const int g = lane >> 2, q = lane & 3, half = WG ^ ((blockIdx.x / GRP_CTAS) & 1), cb = (blockIdx.x % GRP_CTAS) * 4 + half * 2;
    uint32_t acc[2][32];
    float ssq[4] = {0.f, 0.f, 0.f, 0.f};
    TSTAMP(0, 1);

    uint8_t* const hp0 = h_base() + (w & 1) * 1536 + g * 64 + (q ^ (g >> 1)) * 16;
    const uint32_t blk = h_block(cb * 2 + (w >> 1), 0);
    int i = 0;
    uint32_t more = 3, both;
#pragma unroll 1
    for (;; i++) {
        TRACE(WG, i, 0);
        both = more & 2;
        if (WG == 0) p1_mma<0>(acc, a, sbase, empty_remote, i, lane, both, zero);
        else p1_mma<1>(acc, a, sbase, empty_remote, i, lane, true, zero);
        TRACE(WG, i, 4);
        uint32_t step;
        asm volatile("ld.shared.v2.u32 {%0, %1}, [%2];\n" : "=r"(step), "=r"(more) : "r"(sbase + P1_OFF_TILE + (i & 3) * 16) : "memory");
        uint8_t* hp = hp0 + (step ^ blk);
        if (i < 2 || more != 3) { LAG_HERE(4); }
        if (!(more >> WG & 1) && lane == 0) asm volatile("red.relaxed.gpu.global.add.u32 [%0], 1;\n" ::"l"(g_prog[CNT_LAST]) : "memory");
        p1_epilogue(acc, sc2, ssq, hp, zero);
        if (lane == 0) mbar_arrive(bar_pace);
        if (more & 4) {
            asm volatile("fence.proxy.async.global;\n" ::: "memory");
            bar_arrive(8, 288);
            bar_arrive(9, 288);
        }
        if (!(more >> WG & 1)) break;
    }
    TSTAMP(0, 21);
    if (WG == 0 && both) bar_sync(1, 256);
#pragma unroll
    for (int r = 0; r < 4; r++) {
        ssq[r] += __shfl_xor_sync(0xffffffffu, ssq[r], 1);
        ssq[r] += __shfl_xor_sync(0xffffffffu, ssq[r], 2);
    }
    const float t = q == 0 ? ssq[0] : q == 1 ? ssq[1] : q == 2 ? ssq[2] : ssq[3];
    atomicAdd(&g_sq[cb * 64 + (q >> 1) * 64 + w * 16 + (q & 1) * 8 + g], (1ull << 56) + __float2ull_rn(fminf(t, 0x1p19f) * 0x1p32f));
    asm volatile("fence.proxy.async.global;\n" ::: "memory");
    bar_arrive(3, 288);
    asm volatile("barrier.cluster.arrive.relaxed.aligned;\n" ::: "memory");
    return WG ? more & 1 : both;
}

__device__ __forceinline__ void p2_init(uint32_t sbase);
template <int ROLE>
__device__ __forceinline__ bool pass1(const CUtensorMap& wmap, const __nv_bfloat16* __restrict__ x, const __nv_bfloat16* __restrict__ dw,
                                      const __nv_bfloat16* __restrict__ w2, const __nv_bfloat16* __restrict__ grn_b, uint32_t sbase,
                                      int warp, int lane, int zero) {
    const uint32_t bar_full = sbase + P1_OFF_BAR, bar_empty = bar_full + P1_NST * 8, bar_w = bar_empty + P1_NST * 8;
    const uint32_t rank = cluster_rank();
    const int cig = blockIdx.x % GRP_CTAS;
    uint8_t* const ring = reinterpret_cast<uint8_t*>(g_ln);

    TSTAMP(0, 0);
    TRACEW(110 + warp, 0);
    const uint32_t bar_pace = bar_w + 32, bar_xfull = bar_pace + 32, bar_xempty = bar_xfull + 8, bar_done = bar_xfull + 16;
    const uint32_t s_side = bar_done + 12;
    const int ln0 = blockIdx.x >> 2, first = blockIdx.x / GRP_CTAS;
    const uint8_t* xsrc = reinterpret_cast<const uint8_t*>(x) + (size_t)blockIdx.x * P1_X;

    if (ROLE == 2) {
        reg_dec<32>();
        asm volatile("barrier.cluster.arrive.relaxed.aligned;\n" ::: "memory");
        asm volatile("barrier.cluster.wait.aligned;\n" ::: "memory");
        LAG_HERE(0);
        if (warp == 12) {
            int t = first, sent = 0;
            const unsigned tag = 2 * __ldcg(&g_epoch) + 2;
            const uint32_t rbase = mapa(sbase, lane & 1);
#pragma unroll 1
            for (int i = 0; t < NT128; i++) {
                const int round = t / LN_RING, slot = t - round * LN_RING;
                const uint8_t* src = ring + slot * LN_TILE + rank * (P1_SLOT / 2);
                int next = 0;
                int more = 0;
                uint32_t ht = 0;
                if (rank == 0 && lane == 0) {
                    constexpr unsigned LIM = (NT128 - P1_SPLIT - NGRP) / 2;
                    unsigned* cnt = &g_flag[LN_RING + (cig >> 1)][0][0];
                    next = NT128;
                    if (t < NT128 - P1_SPLIT) {
                        unsigned sd;
                        asm volatile("ld.volatile.shared.u32 %0, [%1];\n" : "=r"(sd) : "r"(s_side) : "memory");
                        const unsigned a = __ldcg(cnt + sd * 8);
                        unsigned b = __ldcg(cnt + (sd ^ 1) * 8);
                        if (a > b + 4) { sd ^= 1; b = a; }
                        unsigned u = atomicAdd(cnt + sd * 8, 1u);
                        if (u >= LIM) { sd ^= 1; b = u; u = atomicAdd(cnt + sd * 8, 1u); }
                        next = u < LIM ? NGRP + 2 * u + sd : NT128 - P1_SPLIT + atomicAdd(&g_flag[LN_RING + 3 + (cig >> 1)][first & 1][0], 1u);
                        more = u < LIM ? 3 : next < NT128;
                        if (!sent && min(u, b) >= (NT_EARLY - NGRP) / 2) { sent = 1; more += 4; }
                    }
                    ht = h_tile(t, tag);
                }
                flag_wait<true>(&g_flag[slot][0][0], 4 * round + 4);
                TRACEW(i, 2);
                asm volatile("fence.proxy.async.global;\n" ::: "memory");
                next = __shfl_sync(0xffffffffu, next, 0);
                more = __shfl_sync(0xffffffffu, more, 0);
                ht = __shfl_sync(0xffffffffu, ht, 0);
#pragma unroll 1
                for (int h = 0; h < P1_NST; h++) {
                    mbar_wait(bar_empty + h * 8, i & 1);
                    if (h == 0) TRACEW(i, 4);
                    if (h == 5) TRACEW(i, 5);
                    if (elect_one()) {
                        mbar_expect_tx(bar_full + h * 8, h ? P1_SLOT : P1_SLOT + 16);
                        bulk_g2s_mc(sbase + h * P1_SLOT + rank * (P1_SLOT / 2), src + h * P1_SLOT, P1_SLOT / 2, bar_full + h * 8, (uint16_t)3);
                    }
                    __syncwarp();
                    if (h == 0 && rank == 0 && lane < 2)
                        asm volatile("st.async.shared::cluster.mbarrier::complete_tx::bytes.v4.u32 [%0], {%1, %2, %3, %3}, [%4];\n"
                                     ::"r"(rbase + P1_OFF_TILE + (i & 3) * 16), "r"(ht), "r"(more), "r"(next),
                                       "r"(rbase + P1_OFF_BAR) : "memory");
                }
                t = next;
                if (rank != 0) {
                    mbar_wait(bar_full, i & 1);
                    asm volatile("ld.shared.u32 %0, [%1];\n" : "=r"(t) : "r"(sbase + P1_OFF_TILE + (i & 3) * 16 + 8) : "memory");
                }
            }
        } else if (warp == 13) {
            int ph = 0;
            unsigned target = 0;
#pragma unroll 1
            for (int i = ln0 + LN_STEP; i < NT128; i += LN_STEP, ph ^= 1) {
                target += ph * (GRP_CTAS / 2);
                xsrc += (size_t)NUM_CTAS * P1_X;
                mbar_wait(bar_xempty, ph);
                if (elect_one()) {
                    mbar_expect_tx(bar_xfull, P1_X);
                    bulk_g2s(sbase + P1_OFF_X, xsrc, P1_X, bar_xfull);
                }
                __syncwarp();
                const uint32_t off = flag_wait<false>(&g_flag[ln0 + (ph ^ 1) * LN_STEP][1][0], target);
                if (elect_one()) {
                    asm volatile("st.shared.u32 [%0], %1;\n" ::"r"(bar_done + 8), "r"(off) : "memory");
                    mbar_arrive(bar_xfull);
                }
                __syncwarp();
            }
        } else if (warp == 15) {
            int t = first;
            if (rank == 1 && lane == 0) mbar_arrive(bar_empty);
#pragma unroll 1
            for (int i = 0; rank == 1 && t < NT128; i++) {
#pragma unroll 1
                for (int h = 0; h < P1_NST; h++) mbar_wait(bar_full + h * 8, i & 1);
                if (lane == 0) asm volatile("red.relaxed.gpu.global.add.u32 [%0], 1;\n" ::"l"(&g_flag[t % LN_RING][1][0]) : "memory");
                asm volatile("ld.shared.u32 %0, [%1];\n" : "=r"(t) : "r"(sbase + P1_OFF_TILE + (i & 3) * 16 + 8) : "memory");
                if (lane == 0) mbar_arrive(bar_empty);
                TRACEW(i, 3);
            }
            if (rank == 0) {
                {
                    const int me = blockIdx.x >> 1;
                    const int page = lane < 2 ? 0 : H_FIXED + me + (lane / 2 - 1) * (NUM_CTAS / 2);
                    if (page < H_PAGES) h_cell(page, me)[(lane & 1) * 1024] = 0;
                    __syncwarp();
                    mbar_wait(bar_full, 0);
                    if (lane == 0) {
                        const unsigned tag = 2 * __ldcg(&g_epoch) + 2;
                        const unsigned side = near_half(h_cell(0, me), 5);
                        asm volatile("st.volatile.shared.u32 [%0], %1;\n" ::"r"(s_side), "r"(side) : "memory");
#pragma unroll 1
                        for (int p = H_FIXED + me; p < H_PAGES; p += NUM_CTAS / 2)
                            asm volatile("st.relaxed.gpu.global.u32 [%0], %1;\n" ::"l"(&g_page[p]), "r"(tag + (near_half(h_cell(p, me), p < H_FIXED + NUM_CTAS / 2 ? 2 : 3) ^ side)) : "memory");
                        const unsigned u = atomicAdd(reinterpret_cast<unsigned*>(g_sums) + C_DIM + 64 + side, 1u);
                        const unsigned cl = u < NUM_CTAS / 4 ? 2 * u + side : NUM_CTAS - 2 - 2 * u + (side ^ 1);
#pragma unroll
                        for (int r = 0; r < 2; r++) asm volatile("st.shared::cluster.u32 [%0], %1;\n" ::"r"(mapa(sbase + OFF_PRE + C_DIM * 4 + 8, r)), "r"(cl) : "memory");
                    }
                    __syncwarp();
                }
                TRACEW(110 + warp, 3);
                mbar_wait(bar_full, 1);
                float* sums = g_sums;
                unsigned* flag = reinterpret_cast<unsigned*>(sums + C_DIM);
                if (blockIdx.x == 0) reinterpret_cast<uint2*>(g_half)[lane] = make_uint2(0, 0);
                if (blockIdx.x == 2 && lane < NUM_CNT) g_prog[lane][0] = 0;
                if (blockIdx.x < 96) g_redo[blockIdx.x * 16 + lane] = 0.f;
                float gs = 0.f;
#pragma unroll 1
                for (int pass = 0; pass < 2; pass++) {
                    float mx = 0.f;
#pragma unroll 1
                    for (int it = (blockIdx.x + zero) / GRP_CTAS; it < 96; it += NGRP) {
                        const int nb = it % 12, k0 = (cig * 4 + it / 12) * 64 + (lane >> 2);
                        const uint32_t sc = mapa(sbase + P1_OFF_EX + (k0 & 255) * 4, it / 48);
                        uint32_t* dst = reinterpret_cast<uint32_t*>(g_w2img[0]) + (k0 >> 4) * 3072 + nb * 256 + lane;
                        float bs[8] = {};
#pragma unroll 1
                        for (int c = 0; c < 8; c++) {
                            const uint4 u = __ldg(reinterpret_cast<const uint4*>(w2 + (size_t)(k0 + c * 8) * C_DIM + nb * 32) + (lane & 3));
                            const float b = __bfloat162float(grn_b[k0 + c * 8]);
                            float t;
                            asm volatile("ld.shared::cluster.f32 %0, [%1];\n" : "=f"(t) : "r"(sc + c * 32) : "memory");
                            if (nb == 0) g_scale[k0 + c * 8] = t;
#pragma unroll
                            for (int j = 0; j < 4; j++) {
                                const uint32_t v = j == 0 ? u.x : j == 1 ? u.y : j == 2 ? u.z : u.w;
                                mx = fmaxf(mx, fmaxf(fabsf(bf_lo(v)), fabsf(bf_hi(v))) * t);
                                if (pass) {
                                    bs[2 * j] = fmaf(b, bf_lo(v), bs[2 * j]);
                                    bs[2 * j + 1] = fmaf(b, bf_hi(v), bs[2 * j + 1]);
                                    uint32_t h = pack_f16(bf_lo(v) * t * gs, bf_hi(v) * t * gs);
                                    asm volatile("movmatrix.sync.aligned.m8n8.trans.b16 %0, %0;\n" : "+r"(h));
                                    dst[(c >> 1) * 3072 + (c & 1) * 32 + j * 64] = h;
                                }
                            }
                        }
                        if (pass) {
#pragma unroll
                            for (int j = 0; j < 8; j++) {
#pragma unroll
                                for (int o = 4; o < 32; o <<= 1) bs[j] += __shfl_xor_sync(0xffffffffu, bs[j], o);
                                if (lane >> 2 == j) atomicAdd(&sums[nb * 32 + (j >> 1) * 8 + (lane & 3) * 2 + (j & 1)], bs[j]);
                            }
                        }
                    }
                    if (!pass) {
                        const uint32_t m = __reduce_max_sync(0xffffffffu, __float_as_uint(mx));
                        __threadfence();
                        __syncwarp();
                        if (lane == 0) {
                            atomicMax(flag, m);
                            asm volatile("red.release.gpu.global.add.u32 [%0], 1;\n" ::"l"(flag + 32) : "memory");
                        }
                        flag_wait<true>(flag + 32, NUM_CTAS / 2);
                        gs = w2_scale(__ldcg(flag));
                    }
                }
                asm volatile("fence.proxy.async.global;\nfence.acq_rel.gpu;\n" ::: "memory");
                __syncwarp();
                if (lane == 0) asm volatile("red.relaxed.gpu.global.add.u32 [%0], 1;\n" ::"l"(g_prog[CNT_IMG0]) : "memory");
            }
        } else if (warp == 14) {
            int ph = 0;
#pragma unroll 1
            for (int i = ln0; i < NT128; i += LN_STEP, ph ^= 1) {
                mbar_wait(bar_done, ph);
                if (lane == 0) mbar_arrive(bar_xfull);
                TRACEW(i / LN_STEP, 0);
                asm volatile("fence.proxy.async.global;\n" ::: "memory");
                if (elect_one()) asm volatile("red.release.gpu.global.add.u32 [%0], 1;\n" ::"l"(&g_flag[ln0 + ph * LN_STEP][0][0]) : "memory");
                __syncwarp();
                TRACEW(i / LN_STEP, 1);
            }
            if (lane == 0) p2_init(sbase);
#pragma unroll 1
            for (int i = CNT_EARLY; i >= CNT_H; i--) {
                bar_sync(i == CNT_EARLY ? 8 : 3, 288);
                asm volatile("fence.proxy.async.global;\n" ::: "memory");
                if (lane == 0) asm volatile("red.release.gpu.global.add.u32 [%0], 1;\n" ::"l"(&g_prog[i][0]) : "memory");
                __syncwarp();
            }
        }
        __syncwarp();
        asm volatile("barrier.cluster.arrive.relaxed.aligned;\n" ::: "memory");
        return false;
    } else if (ROLE == 1) {
        reg_dec<96>();
        asm volatile("barrier.cluster.arrive.relaxed.aligned;\n" ::: "memory");
        {
            const int l8 = lane & 7, row = (warp - 8) * 4 + (lane >> 3), px = (blockIdx.x & 3) * 32 + row;
            uint32_t d[6][4];
            const int n = (px & 64) + perm32(2 * row + ((px >> 5) & 1));
            uint8_t* const dst0 = ring + ln0 * LN_TILE + n * 128 + ((l8 ^ (n & 7)) << 4);
            const uint32_t src = sbase + P1_OFF_X + ((warp - 8) * 8 + (lane >> 3)) * (C_DIM * 2) + l8 * 16;
            int ph = 0;
            LAG_HERE(0);
#pragma unroll 1
            for (int i = ln0; i < NT128; i += LN_STEP, ph ^= 1) {
                TRACE(2, i / LN_STEP, 0);
                uint32_t off = 1;
#pragma unroll 1
                for (int ps = i == ln0 ? -2 : 0; ps < 2; ps += ps < 0 ? 2 : 1) {
                    if (ps == 0) {
                        if (i == ln0) asm volatile("barrier.cluster.wait.aligned;\n" ::: "memory");
                        mbar_wait(bar_xfull, ph);
                        asm volatile("ld.shared.u32 %0, [%1];\n" : "=r"(off) : "r"(bar_done + 8) : "memory");
                    }
                    if (ps == 0) TRACE(2, i / LN_STEP, 1);
                    if (i == ln0) {
#pragma unroll
                        for (int j = 0; j < 6; j++)
                            asm volatile("ld.shared.v4.u32 {%0,%1,%2,%3}, [%4];\n"
                                         : "=r"(d[j][0]), "=r"(d[j][1]), "=r"(d[j][2]), "=r"(d[j][3]) : "r"(sbase + P1_OFF_DW + j * 128 + l8 * 16) : "memory");
                    }
                    uint32_t v[6][4];
#pragma unroll
                    for (int j = 0; j < 6; j++)
                        asm volatile("ld.shared.v4.u32 {%0,%1,%2,%3}, [%4];\n"
                                     : "=r"(v[j][0]), "=r"(v[j][1]), "=r"(v[j][2]), "=r"(v[j][3]) : "r"(src + (ps & 1) * (4 * C_DIM * 2) + j * 128) : "memory");
                    ln_row(v, d, bar_pace + (warp - 8) * 8, off, zero, ps == 1 && lane == 0 ? bar_xempty : 0);
                    uint8_t* dst = dst0 + ph * (LN_STEP * LN_TILE) + (ps & 1) * 4096;
#pragma unroll
                    for (int j = 0; j < 6; j++) *reinterpret_cast<uint4*>(dst + j * 16384) = make_uint4(v[j][0], v[j][1], v[j][2], v[j][3]);
                    TRACE(2, i / LN_STEP, 3 + (ps & 1));
                }
                asm volatile("fence.proxy.async.global;\nfence.acq_rel.cta;\n" ::: "memory");
                __syncwarp();
                if (lane == 0) mbar_arrive(bar_done);
                TRACE(2, i / LN_STEP, 5);
                TRACE(2, i / LN_STEP, 2);
            }
        }
        __syncwarp();
        asm volatile("barrier.cluster.arrive.relaxed.aligned;\n" ::: "memory");
        return false;
    } else {
        const int wg = warp >> 2, w = warp & 3;
        auto load_w = [&](int i0, int i1) {
#pragma unroll 1
            for (int i = i0; i < i1; i++) {
                if (!(i & 1)) mbar_expect_tx(bar_w + (i >> 1) * 8, P1_W);
                tma2(sbase + (i & 2) * P1_W + (i >> 2) * P1_W + (i & 1) * (P1_W / 2), &wmap, cig * 256 + ((i >> 1) ^ (first & 1) * 2) * 64, (i & 1) * 192, bar_w + (i >> 1) * 8);
            }
        };
        if (warp == 4 && elect_one()) {
            mbar_init(bar_xfull, 3);
#pragma unroll
            for (int i = 0; i < 4; i++) mbar_init(bar_w + i * 8, 1);
            asm volatile("fence.mbarrier_init.release.cluster;\n" ::: "memory");
            mbar_expect_tx(bar_xfull, P1_X + C_DIM * 2);
            bulk_g2s(sbase + P1_OFF_X, xsrc, P1_X, bar_xfull);
            bulk_g2s(sbase + P1_OFF_DW, dw, C_DIM * 2, bar_xfull);
            load_w(0, 4);
            asm volatile("st.shared.u32 [%0], 1;\n" ::"r"(bar_done + 8) : "memory");
            mbar_arrive(bar_xfull);
            mbar_arrive(bar_xfull);
        }
        if (warp == 5 && elect_one()) {
#pragma unroll
            for (int i = 0; i < P1_NST; i++) {
                mbar_init(bar_full + i * 8, 1);
                mbar_init(bar_empty + i * 8, i ? 8 : 8 + rank);
                if (i < 4) mbar_init(bar_pace + i * 8, 1);
            }
            mbar_init(bar_xempty, 4);
            mbar_init(bar_done, 4);
            asm volatile("st.shared.u32 [%0], %1;\n" ::"r"(s_side), "r"(first & 1) : "memory");
            asm volatile("fence.mbarrier_init.release.cluster;\n" ::: "memory");
        }
        __syncwarp();
        asm volatile("barrier.cluster.arrive.relaxed.aligned;\n" ::: "memory");
        reg_inc<192>();
        TRACEW(110 + warp, 1);
        LAG_HERE(0);
        uint32_t a[24][4];
        const uint32_t src = sbase + wg * P1_W + ((lane >> 4) * 8 + (lane & 7)) * 128 + (((2 * w + ((lane >> 3) & 1)) ^ (lane & 7)) << 4);
        const uint32_t s_ex = sbase + P1_OFF_EX + ((wg ^ (first & 1)) * 128 + w * 16 + (lane >> 2)) * 4;
        uint32_t sc2[2], ex[2];
        if (wg == 1) bar_arrive(1, 256);
#pragma unroll 1
        for (int it = 0; it < 2; it++) {
          if (it != wg) asm volatile("barrier.cluster.wait.aligned;\n" ::: "memory");
          if (it < wg) {
#pragma unroll 1
              for (int n = 0; n < 64 && !mbar_test(bar_xfull, 0); n++) __nanosleep(40);
              if (w == 0 && elect_one()) load_w(4, 8);
              __syncwarp();
          }
          if (it || wg == 0) {
            float t[2] = {0.f, 0.f};
            if (it) {
                TRACEW(110 + warp, 2);
                mbar_wait(bar_w + wg * 16, 0);
            }
            TRACEW(110 + warp, 5);
#pragma unroll
            for (int k = 0; k < 24; k++) ldsm4t(a[k], src + k * 2048);
            TRACEW(110 + warp, 6);
            p1_squares(a, t);
            sc2[0] = p1_exponents(t, ex, s_ex, lane);
            if (it && lane < 6) mbar_arrive_cluster(mapa(bar_empty, lane & 1) + (wg * 3 + (lane >> 1)) * 8 + (sc2[0] & zero));
            p1_convert<24>(a, a, ex);
          }
          if (it || wg == 1) {
            float t[2] = {0.f, 0.f};
            TRACEW(100 + warp, 0);
            if (it) mbar_wait(bar_w + wg * 16 + 8, 0);
            TRACEW(100 + warp, 1);
            uint32_t v[8][4], o[8][4];
#pragma unroll 1
            for (int j = 0; j <= 2 * it; j++) {
#pragma unroll
                for (int k = 0; k < 8; k++) ldsm4t(v[k], src + P1_OFF_W + (8 * j + k) * 2048);
                p1_squares(v, t);
            }
            sc2[1] = p1_exponents(t, ex, s_ex + 256, lane);
#pragma unroll 1
            for (int j = 2 * it; j >= 0; j--) {
                p1_convert<8>(o, v, ex);
#pragma unroll
                for (int k = 0; k < 8; k++) {
                    if (j) ldsm4t(v[k], src + P1_OFF_W + (8 * j - 8 + k) * 2048);
                    if (it) asm volatile("stmatrix.sync.aligned.m8n8.x4.trans.shared.b16 [%0], {%1,%2,%3,%4};\n"
                                         ::"r"(src + P1_OFF_W + (8 * j + k) * 2048), "r"(o[k][0]), "r"(o[k][1]), "r"(o[k][2]), "r"(o[k][3]) : "memory");
                }
            }
          }
        }
        asm volatile("fence.proxy.async.shared::cta;\n" ::: "memory");
        TRACEW(110 + warp, 7);
        bar_sync(6 + wg, 128);
        const bool early = p1_consumer(a, sc2, sbase, wg, w, lane, zero);
        TSTAMP(0, 30);
        return early;
    }
}

constexpr int P2_B = 24576, P2_NB = 4;
constexpr int P2_A = 3072, P2_NA = 8;
constexpr int P2_XROW = C_DIM * 2;
constexpr int P2_OFF_A = P2_B * P2_NB;
constexpr int P2_OFF_X = P2_OFF_A + 3 * P2_NA * P2_A + 128;
constexpr int P2_LHALF = 2 * P2_NA * P2_A + 64;
constexpr int P2_XHALF = 32 * P2_XROW + 64;
constexpr int P2_OFF_GRN = P2_OFF_X + 64 * P2_XROW + 128;
constexpr int P2_OFF_BIAS = P2_OFF_GRN + HID * 2;
constexpr int P2_OFF_RED = P2_OFF_BIAS + C_DIM * 4;
constexpr int P2_OFF_BAR = P2_OFF_RED + 192;
constexpr int P2_SMEM = P2_OFF_BAR + (2 * P2_NB + 6 * P2_NA + 7) * 8;
constexpr int P2_S1 = 16, P2_S2 = 32;
constexpr int P2_NCL = NUM_CTAS / 2, P2_ITEMS = NT128 / P2_NCL, P2_SHARED = NT128 - P2_ITEMS * P2_NCL;
constexpr int P2_NPOS = 6 * 48 + P2_S1;
constexpr int P2_RAW = 16;
constexpr int P2_XC = 8 * P2_XROW;
constexpr int P2_T0 = 5;
constexpr int P2_TL = 8;
constexpr int P2_XP0 = 30;
constexpr int P2_XPN = 13;
constexpr int P2_XPD = 3;
constexpr int P2_AH = 2;
__device__ __forceinline__ int p2_start(int n) { return n < 0 ? 0 : n / 3 * 48 + (n % 3 == 1 ? P2_S1 : n % 3 * (P2_S2 / 2)); }
__device__ __forceinline__ int p2_tile(int cl, int n) {
    return n == 0 ? NT_EARLY - P2_NCL + cl : n < 0 ? NT_EARLY + (cl >> 2) * 2 + (cl & 1) : cl + P2_NCL * (n - 1);
}

__device__ __forceinline__ void p2_epilogue(uint32_t (&acc0)[48], uint32_t (&acc1)[48], uint32_t up, uint32_t sx, uint32_t sb, uint8_t* so, int zero) {
    uint32_t v[12][3][4];
    auto load = [&](int t, int j) {
        if (t >= 12) return;
        uint32_t (&w)[4] = v[t][j];
        asm volatile("ld.shared.v4.u32 {%0,%1,%2,%3}, [%4];\n" : "=r"(w[0]), "=r"(w[1]), "=r"(w[2]), "=r"(w[3])
                     : "r"((j ? sx + (j - 1) * 4 * P2_XROW : sb) + t * 64) : "memory");
    };
    auto store = [&](int t, int r) {
        const uint32_t* w = (t < 6 ? acc0 : acc1) + 8 * (t % 6) + 4 * r;
        asm volatile("st.v4.u32 [%4], {%0,%1,%2,%3};\n" ::"r"(w[0]), "r"(w[1]), "r"(w[2]), "r"(w[3]), "l"(so + t * 64 + r * 4 * P2_XROW) : "memory");
    };
#pragma unroll
    for (int j = 0; j < 3; j++) load(0, j);
#pragma unroll
    for (int t = 0; t < 12; t++) {
        load(t + 1, 1);
        load(t + 1, 2);
        load(t + 1, 0);
        uint32_t* acc = (t < 6 ? acc0 : acc1) + 8 * (t % 6);
        uint32_t y[8];
#pragma unroll
        for (int e = 0; e < 8; e++) {
            y[e] = h2_add(acc[e], v[t][0][e >> 1]);
            y[e] = pack_bf16(h_lo(y[e]), h_hi(y[e]));
        }
#pragma unroll
        for (int e = 0; e < 8; e++) acc[(e & 1) * 4 + (e >> 1)] = bf2_fma(y[e], up, v[t][1 + (e & 1)][e >> 1]);
        store(t, 0);
        store(t, 1);
        if (t & 1) sched_break(zero);
    }
}

__device__ __forceinline__ void p2_unpack(uint32_t (&u)[4], uint32_t o1, uint32_t o2, uint32_t o3) {
    u[2] = o1 & ~SPARE;
    u[1] = o2 & ~SPARE;
    u[3] = o3 & ~SPARE;
    const uint32_t t = bitsel(prmt(o1, o2, 0x6341), prmt(o1, o3, 0x6240) << 3, 0x38383838u);
    u[0] = bitsel(t, prmt(o2, o3, 0x7351) << 1, 0x80808080u) & ~SPARE;
}

__device__ __forceinline__ void p2_redo_sums(int warp, int lane) {
    flag_wait<true>(g_prog[CNT_H], NUM_CTAS);
#pragma unroll 1
    for (int s = warp; s < 96; s += 12) {
        float t[2] = {0.f, 0.f};
#pragma unroll 1
        for (int tile = blockIdx.x; tile < 2 * NT128; tile += NUM_CTAS) {
            const uint32_t* p = reinterpret_cast<const uint32_t*>(h_base() + (h_tile(tile >> 1) ^ h_block(s >> 1, tile & 1)) + (s & 1) * 1536) + lane * 4;
#pragma unroll
            for (int j = 0; j < 4; j++) {
                uint32_t u[4];
                p2_unpack(u, __ldcg(p + j), __ldcg(p + j + 128), __ldcg(p + j + 256));
#pragma unroll
                for (int c = 0; c < 4; c++) t[c >> 1] += h_lo(u[c]) * h_lo(u[c]) + h_hi(u[c]) * h_hi(u[c]);
            }
        }
#pragma unroll
        for (int r = 0; r < 2; r++) {
            const int ch = s * 16 + r * 8 + (lane >> 2);
            atomicAdd(&g_redo[ch], t[r] * (UNCHOP * UNCHOP));
        }
    }
    __threadfence();
    __syncwarp();
    if (lane == 0) asm volatile("red.release.gpu.global.add.u32 [%0], 1;\n" ::"l"(g_prog[CNT_REDO]) : "memory");
    flag_wait<true>(g_prog[CNT_REDO], 12 * NUM_CTAS);
}

static_assert(P2_OFF_GRN >= P1_OFF_X + P1_X && P1_OFF_BAR >= P2_SMEM, "barriers and tables keep their memory");
__device__ __forceinline__ void p2_init(uint32_t sbase) {
    const uint32_t bar = sbase + P2_OFF_BAR;
#pragma unroll 1
    for (int i = 0; i < 2 * P2_NB + 6 * P2_NA + 6; i++) {
        const int j = i - 2 * P2_NB;
        mbar_init(bar + i * 8, j < -P2_NB ? 1 : j < 0 ? 24 : j < 3 * P2_NA ? 1 : j >= 6 * P2_NA && j < 6 * P2_NA + 3 ? 2 : 4);
    }
    asm volatile("st.shared.v2.u32 [%0], {0, 0};\n" ::"r"(bar + (2 * P2_NB + 6 * P2_NA + 6) * 8) : "memory");
    asm volatile("fence.mbarrier_init.release.cluster;\nfence.acq_rel.cta;\n" ::: "memory");
}
template <int ROLE>
__device__ __forceinline__ void pass2(const __nv_bfloat16* __restrict__ x, const __nv_bfloat16* __restrict__ grn_g, __nv_bfloat16* __restrict__ out,
                                      uint8_t* smem, uint32_t sbase, bool early, int zero) {
    const uint32_t bar_bfull = sbase + P2_OFF_BAR, bar_bempty = bar_bfull + P2_NB * 8;
    const uint32_t bar_afull = bar_bempty + P2_NB * 8, bar_aempty = bar_afull + 3 * P2_NA * 8;
    const uint32_t bar_xfull = bar_aempty + 3 * P2_NA * 8, bar_oready = bar_xfull + 24, s_pos = bar_oready + 24;
    int tid;
    asm volatile("mov.u32 %0, %%tid.x;\n" : "=r"(tid));
    const int warp = __shfl_sync(0xffffffffu, tid >> 5, 0), lane = tid & 31;
    const uint32_t rank = cluster_rank();
    int cl, pair, half, fin, k0;
    auto join = [&]() {
        asm volatile("barrier.cluster.wait.aligned;\nld.shared.u32 %0, [%1];\n" : "=r"(cl) : "r"(sbase + OFF_PRE + C_DIM * 4 + 8) : "memory");
        cl = __shfl_sync(0xffffffffu, cl, 0);
        pair = (cl >> 2) * 2 + (cl & 1);
        half = pair < P2_SHARED;
        fin = half && (cl & 2);
        k0 = (pair + 3 * ((cl >> 1) & 1)) % 6 * 8;
    };
    auto wait_pos = [&](int target) {
        int v;
        while (true) {
            asm volatile("ld.volatile.shared.u32 %0, [%1];\n" : "=r"(v) : "r"(s_pos) : "memory");
            if (v >= target) break;
            SAFE_BREAK;
            __nanosleep(100);
        }
    };

    TSTAMP(1, 0);
    LAG_HERE(1);
    if (ROLE == 2) {
        if (warp != 14) flag_wait<true>(g_prog[CNT_IMG0], P2_NCL);
        if (warp == 15) {
            float* pre = reinterpret_cast<float*>(smem + OFF_PRE);
            const float gs = w2_scale(__float_as_uint(__ldcg(&g_sums[C_DIM])));
            float mb = 0.f;
#pragma unroll 1
            for (int i = lane; i < C_DIM; i += 32) {
                pre[i] = __ldcg(&g_sums[i]) * gs;
                mb = fmaxf(mb, fabsf(pre[i]));
            }
            pre[C_DIM] = gs;
            pre[C_DIM + 1] = __uint_as_float(__reduce_max_sync(0xffffffffu, __float_as_uint(mb)));
            bar_sync(9, 288);
            flag_wait<false>(g_prog[CNT_LAST], NUM_CTAS * 8);
            bar_arrive(5, 416);
        }
        join();
        asm volatile("fence.proxy.async;\n" ::: "memory");
        LAG_HERE(2);
        if (warp == 12) {
            const uint8_t* wsrc = reinterpret_cast<const uint8_t*>(g_w2img) + rank * (P2_B / 2);
            int kb = k0;
#pragma unroll 1
            for (int p = 0; p < P2_NPOS; p++) {
                const int st = p & 3;
                if (p == P2_RAW) {
                    flag_wait<true>(g_prog[CNT_IMG1], NUM_CTAS);
                    asm volatile("fence.proxy.async.global;\n" ::: "memory");
                    wsrc += sizeof(g_w2img[0]);
                }
                const int idle = (p < P2_S1 || p >= 6 * 48) + (p < P2_S2 ? !half || p >= 24 : p >= 5 * 48 + P2_S2);
                mbar_wait(bar_bempty + st * 8, (~p >> 2) & 1);
                TR2(3, p, 0);
                if (elect_one()) {
                    mbar_expect_tx(bar_bfull + st * 8, P2_B);
                    bulk_g2s_mc(sbase + st * P2_B + rank * (P2_B / 2), wsrc + kb * P2_B, P2_B / 2, bar_bfull + st * 8, (uint16_t)3);
                    asm volatile("st.volatile.shared.u32 [%0], %1;\n" ::"r"(s_pos), "r"(p) : "memory");
                    if (rank == 0) asm volatile("red.relaxed.gpu.global.add.u32 [%0], 1;\n" ::"l"(g_prog[CNT_POS]) : "memory");
                    if (idle) asm volatile("mbarrier.arrive.shared::cta.b64 _, [%0], %1;\n" ::"r"(bar_bempty + st * 8), "r"(8 * idle) : "memory");
                }
                __syncwarp();
                if (++kb == 48) kb = 0;
            }
            mbar_wait(bar_bempty, 1);
            if (lane == 0) mbar_arrive(bar_bfull);
        } else if (warp == 13) {
            const int w = lane % 3;
            const uint32_t dst0 = sbase + P2_OFF_A + w * P2_NA * P2_A;
            const uint32_t bf = bar_afull + w * P2_NA * 8, be = bar_aempty + w * P2_NA * 8;
            int n = (w == 2 && half ? -1 : w) - 3, left = 0, u = 0, c = 0;
            const uint8_t* const hb = h_base();
            uint32_t ht = 0;
            bool act = lane < 3;
            auto next = [&]() {
                n += 3;
                left = n >= P2_ITEMS ? -1 : n < 0 ? 24 : 48;
                u = (k0 + p2_start(n)) % 48;
                if (left > 0) ht = h_tile(p2_tile(cl, n));
            };
            next();
            flag_wait<true>(g_prog[CNT_EARLY], NUM_CTAS);
#pragma unroll 1
            for (int i = 3; i > 0; i--) {
                const int wi = i % 3;
                if (wi == 2) flag_wait<true>(g_prog[CNT_H], NUM_CTAS);
                asm volatile("fence.proxy.async.global;\n" ::: "memory");
                if (w == wi && lane < 24) {
                    mbar_expect_tx(bf + lane / 3 * 8, P2_A);
                    bulk_g2s(dst0 + lane / 3 * P2_A, hb + (ht ^ h_block(u + lane / 3, rank)), P2_A, bf + lane / 3 * 8);
                }
                __syncwarp();
            }
            c = 8;
            left -= 8;
            u += 8;
            if (u == 48) u = 0;
            while (__any_sync(0xffffffffu, act)) {
                if (left == 0) next();
                const bool ok = act && mbar_test(be + ((c - 1) & 7) * 8, (~c >> 3) & 1);
                if (ok) {
                    const int st = c & 7;
                    if (left > 0) {
                        mbar_expect_tx(bf + st * 8, P2_A);
                        bulk_g2s(dst0 + st * P2_A, hb + (ht ^ h_block(u, rank)), P2_A, bf + st * 8);
                    } else {
                        mbar_arrive(bf + st * 8);
                        act = false;
                    }
                    if (++u == 48) u = 0;
                    c++;
                    left--;
                }
                SAFE_BREAK;
                if (!__any_sync(0xffffffffu, ok)) __nanosleep(100);
            }
        } else if (warp == 14) {
            const uint32_t sx = sbase + P2_OFF_X;
            size_t o = 0;
            int wp = 0;
            uint32_t par = 0;
            if (fin) {
#pragma unroll 1
                for (int c = lane * 16; c < 64 * P2_XROW + 128; c += 512) asm volatile("st.shared.v4.u32 [%0], {0, 0, 0, 0};\n" ::"r"(sx + c) : "memory");
                __syncwarp();
            }
            wait_pos(6);
#pragma unroll 1
            for (int n = -half; n < P2_ITEMS; n++) {
                const int w = (n + 3) % 3, end = p2_start(n) + 48;
                const size_t on = (size_t)(2 * p2_tile(cl, n) + rank) * (64 * C_DIM * 2);
                const uint32_t xf = bar_xfull + w * 8;
                if (n < 2 || n > 12) { LAG_HERE(3); }
                bool st = n + half > 0;
                const bool ld = n < P2_ITEMS - 1 && !(n < 0 && fin);
                if (n == P2_ITEMS - 1 && lane == 0) {
                    mbar_expect_tx(xf, 64 * C_DIM * 2);
#pragma unroll 1
                    for (int c = 4; c < 12; c++) {
                        if (c >= 8) {
                            mbar_wait(bar_aempty + ((2 * c - 1) & 7) * 8, 1);
                            mbar_wait(bar_aempty + ((2 * c) & 7) * 8, 1);
                        }
                        bulk_g2s(sbase + P2_OFF_A + (c & 3) * P2_XC + (c < 8 ? P2_LHALF : 0), reinterpret_cast<const uint8_t*>(x) + on + (c & 7) * P2_XC, P2_XC, xf);
                    }
                    mbar_arrive(xf);
                }
                if (st) {
                    mbar_wait(bar_oready + wp * 8, (par >> wp) & 1);
                    par ^= 1u << wp;
                }
                if (lane == 0) {
                    if (n < P2_ITEMS - 1) mbar_expect_tx(xf, ld ? 64 * C_DIM * 2 : 0);
                    const int t0 = (n ? p2_start(n - 1) + 48 : P2_S2) + (n == P2_ITEMS - 1 ? P2_TL : P2_T0), dt = end - t0;
                    int t = st ? 16 * t0 : -4096;
                    if (n == 0 && half) {
                        if (fin) {
                            flag_wait<true>(&g_half[pair][rank], 1);
                            asm volatile("fence.proxy.async.global;\n" ::: "memory");
                        }
#pragma unroll 1
                        for (int c = 0; c < 2; c++) {
                            uint8_t* dst = reinterpret_cast<uint8_t*>(out) + o + c * 32 * P2_XROW;
                            if (!fin) bulk_s2g(dst, sx + c * P2_XHALF, 32 * P2_XROW);
                            else asm volatile("cp.reduce.async.bulk.global.shared::cta.bulk_group.add.noftz.bf16 [%0], [%1], %2;\n"
                                              ::"l"(dst), "r"(sx + c * P2_XHALF), "r"(32 * P2_XROW) : "memory");
                        }
                        asm volatile("cp.async.bulk.commit_group;\n" ::: "memory");
                        if (!fin) {
                            asm volatile("cp.async.bulk.wait_group 0;\nfence.proxy.async.global;\n" ::: "memory");
                            asm volatile("st.release.gpu.global.u32 [%0], 1;\n" ::"l"(&g_half[pair][rank]) : "memory");
                        }
                        st = false;
                    }
#pragma unroll 1
                    for (int c = 0; c < 64 * P2_XROW; c += P2_XC, t += 2 * dt) {
                        const uint32_t sp = sx + c + (c >= 32 * P2_XROW ? 64 : 0);
                        wait_pos(t >> 4);
                        if (st) bulk_s2g(reinterpret_cast<uint8_t*>(out) + o + c, sp, P2_XC);
                        asm volatile("cp.async.bulk.commit_group;\n" ::: "memory");
                        if (ld) {
                            wait_pos((t + dt) >> 4);
                            asm volatile("cp.async.bulk.wait_group.read 0;\n" ::: "memory");
                            bulk_g2s(sp, reinterpret_cast<const uint8_t*>(x) + on + c, P2_XC, xf);
                        }
                    }
                    if (rank == 0 && n > 0 && n < P2_ITEMS - 2) flag_wait<false>(g_prog[CNT_POS], P2_NCL * (end - 1));
                    if (n < P2_ITEMS - 1) mbar_arrive(xf);
                }
                __syncwarp();
                o = on;
                wp = w;
            }
            asm volatile("cp.async.bulk.wait_group.read 0;\n" ::: "memory");
        } else {
            if (blockIdx.x == 120) {
                wait_pos(P2_RAW);
                for (int i = lane; i < (LN_RING + 6) * 2; i += 32) (&g_flag[0][0][0])[i * 8] = 0;
                for (int i = lane; i < HID; i += 32) g_sq[i] = 0;
                for (int i = lane; i < 512; i += 32) g_sums[i] = 0.f;
                if (lane == 0) g_epoch++;
            }
            int t = 4 * P2_XP0;
#pragma unroll 1
            for (int n = 0; n < P2_ITEMS && lane == 0; n++) {
                const uint8_t* xn = reinterpret_cast<const uint8_t*>(x) + (size_t)(2 * p2_tile(cl, n) + rank) * (64 * C_DIM * 2);
#pragma unroll 1
                for (int c = 0; c < 16; c++, t += n < P2_XPN ? 4 : P2_XPD) {
                    wait_pos(t >> 2);
                    asm volatile("cp.async.bulk.prefetch.L2.global [%0], %1;\n" ::"l"(xn + c * (P2_XC / 2)), "r"(P2_XC / 2) : "memory");
                }
            }
        }
        __syncwarp();
        cluster_sync_relaxed();
    } else {
        const int wg = warp >> 2, w = warp & 3, q = lane & 3;
        const uint32_t af = bar_afull + wg * P2_NA * 8;
        const uint32_t s_a = sbase + P2_OFF_A + wg * P2_NA * P2_A + (lane >> 3) * 512 + (lane & 7) * 64 + ((w ^ ((lane & 7) >> 1)) << 4);
        uint32_t acc0[48], acc1[48], up;
        uint4 a[2][2];

        __nv_bfloat16 gg[4];
#pragma unroll
        for (int i = 0; i < 4; i++) gg[i] = grn_g[tid + 384 * i];
#pragma unroll 1
        for (int it = !early;; it++) {
            float* s_red = reinterpret_cast<float*>(smem + P2_OFF_RED);
            float gx[4], part = 0.f;
            if (it == 1) {
                TSTAMP(1, 27);
                bar_sync(5, 416);
            }
            unsigned long long v[4];
#pragma unroll
            for (int i = 0; i < 4; i++) gx[i] = __ldcg(&g_scale[tid + 384 * i]);
            while (true) {
#pragma unroll
                for (int i = 0; i < 4; i++) asm volatile("ld.relaxed.gpu.global.u64 %0, [%1];\n" : "=l"(v[i]) : "l"(&g_sq[tid + 384 * i]) : "memory");
                SAFE_BREAK;
                if (!it || !__any_sync(0xffffffffu, min(min(v[0], v[1]), min(v[2], v[3])) < (unsigned long long)NGRP << 56)) break;
            }
            TSTAMP(1, 1);
            const float bias = reinterpret_cast<const float*>(smem + OFF_PRE)[tid];
            const float2 pre = *reinterpret_cast<const float2*>(smem + OFF_PRE + C_DIM * 4);
            bool tiny = false;
#pragma unroll
            for (int i = 0; i < 4; i++) {
                const float t = it == 2 ? __ldcg(&g_redo[tid + 384 * i]) : __ull2float_rn(v[i] << 8) * 0x1p-40f;
                tiny |= t < M_TOTAL * 0x1p-19f;
                gx[i] *= gx[i] * t;
            }
            float mg = 0.f;
#pragma unroll
            for (int i = 0; i < 4; i++) {
                asm("sqrt.approx.f32 %0, %1;\n" : "=f"(gx[i]) : "f"(gx[i] * (HSCALE * HSCALE) + 1e-6f));
                part += gx[i];
                gx[i] *= __bfloat162float(gg[i]);
                mg = fmaxf(mg, fabsf(gx[i]));
            }
#pragma unroll
            for (int o = 16; o > 0; o >>= 1) part += __shfl_xor_sync(0xffffffffu, part, o);
            const uint32_t mgw = __reduce_max_sync(0xffffffffu, __float_as_uint(mg));
            TSTAMP(1, 26);
            if (lane == 0) *reinterpret_cast<float2*>(s_red + warp * 2) = make_float2(part, __uint_as_float(mgw));
            if (it) {
                uint32_t redo;
                asm volatile("{\n.reg .pred p;\nsetp.ne.u32 p, %1, 0;\nbar.red.or.pred p, 4, 384, p;\nselp.u32 %0, 1, 0, p;\n}\n"
                             : "=r"(redo) : "r"((uint32_t)(tiny && it == 1)) : "memory");
                if (__shfl_sync(0xffffffffu, redo, 0)) {
                    p2_redo_sums(warp, lane);
                    continue;
                }
            }
            float tot = 0.f;
#pragma unroll
            for (int i = 0; i < 6; i++) {
                const float4 t = *reinterpret_cast<const float4*>(s_red + i * 4);
                tot += t.x + t.z;
                mg = fmaxf(mg, fmaxf(t.y, t.w));
            }
            const float inv = __fdividef(1.0f, tot * (1.0f / HID) + 1e-6f);
            const uint32_t ej = min((__float_as_uint(fmaxf(fmaf(mg, inv, 1.0f) * (HSCALE * UNCHOP), pre.y * 0x1p-13f)) >> 23) + 1, 250u);
            const float dn = __uint_as_float((254u - ej) << 23);
            up = min(ej + 127u - (__float_as_uint(pre.x) >> 23), 254u) * 0x00800080u;
            reinterpret_cast<uint16_t*>(smem + P2_OFF_BIAS + C_DIM * 2)[tid] = 0;
            *reinterpret_cast<__half*>(smem + P2_OFF_BIAS + (tid >> 5) * 64 + (tid & 6) * 8 + (tid & 24) / 2 + (tid & 1) * 2) = __float2half_rn(bias * dn);
#pragma unroll
            for (int i = 0; i < 4; i++) {
                const int k = tid + 384 * i;
                *reinterpret_cast<__half*>(smem + P2_OFF_GRN + (k >> 4) * 32 + (k & 6) * 4 + (k & 8) / 2 + (k & 1) * 2) =
                    __float2half_rn(fmaf(gx[i], inv, 1.0f) * (HSCALE * UNCHOP * dn));
            }
            TSTAMP(1, 25);
            if (it) break;
        }
        join();
        bar_sync(4, 384);
        TSTAMP(1, 28);
        LAG_HERE(2);
        if (wg == 1) {
            constexpr int N = sizeof(g_w2img[0]) / 16, PER = (N + NUM_CTAS - 1) / NUM_CTAS;
            uint4 v[5];
#pragma unroll
            for (int i = 0; i < 5; i++) v[i] = __ldcg(&g_w2img[0][min(blockIdx.x * PER + (tid & 127) + 128 * i, N - 1)]);
#pragma unroll
            for (int i = 0; i < 5; i++) {
                const int j = min(blockIdx.x * PER + (tid & 127) + 128 * i, N - 1);
                const uint32_t* t = reinterpret_cast<const uint32_t*>(smem + P2_OFF_GRN + (j / 768) * 32 + (j & 8) / 2);
                auto sc = [&](uint32_t u, int e) { return (h2_mul(u, t[2 * e]) + 0x00040004u) & 0xfff8fff8u; };
                g_w2img[1][j] = make_uint4(sc(v[i].x, 0), sc(v[i].y, 1), sc(v[i].z, 2), sc(v[i].w, 3));
            }
            asm volatile("fence.proxy.async.global;\n" ::: "memory");
            bar_sync(2, 128);
            if (tid == 128) asm volatile("fence.acq_rel.gpu;\nred.release.gpu.global.add.u32 [%0], 1;\n" ::"l"(g_prog[CNT_IMG1]) : "memory");
        }

        const int who = __shfl_sync(0xffffffffu, lane == 2 ? 0 : lane < 2 ? 1 : 2, lane);
        const uint32_t rel0 = who ? mapa(bar_bempty, lane & 1) : mapa(bar_aempty + wg * P2_NA * 8, rank), rel1 = rel0 + (who ? 0 : 32);
        auto publish = [&]() {
            asm volatile("fence.proxy.async.shared::cta;\n" ::: "memory");
            __syncwarp();
            if (who == 0) mbar_arrive(bar_oready + wg * 8);
        };
        bool ok_a, pend = false;
        uint32_t pa = 0, s_t;
        auto fetch = [&](int j, bool raw) {
            uint32_t o[6], u0[4], u1[4];
            uint2 t0 = make_uint2(0, 0), t1 = t0;
            if (raw) {
                asm volatile("ld.shared.v2.u32 {%0,%1}, [%2];\n" : "=r"(t0.x), "=r"(t0.y) : "r"(s_t + j * 64) : "memory");
                asm volatile("ld.shared.v2.u32 {%0,%1}, [%2];\n" : "=r"(t1.x), "=r"(t1.y) : "r"(s_t + j * 64 + 32) : "memory");
            }
            const bool ok_b = mbar_test(bar_bfull + (j & 3) * 8, j >> 2);
            if (j == 7) pa ^= 1;
            ok_a = mbar_test(af + ((j + 1) & 7) * 8, pa);
            asm volatile("ldmatrix.sync.aligned.m8n8.x4.trans.shared.b16 {%0,%1,%2,%3}, [%4];\n"
                         : "=r"(o[0]), "=r"(o[1]), "=r"(o[2]), "=r"(o[3]) : "r"(s_a + j * P2_A) : "memory");
            asm volatile("ldmatrix.sync.aligned.m8n8.x2.trans.shared.b16 {%0,%1}, [%2];\n"
                         : "=r"(o[4]), "=r"(o[5]) : "r"(s_a + j * P2_A + 2048) : "memory");
            p2_unpack(u0, o[0], o[1], o[2]);
            p2_unpack(u1, o[3], o[4], o[5]);
            if (raw) {
                u0[0] = h2_mul(u0[0], t0.x); u0[1] = h2_mul(u0[1], t0.x); u0[2] = h2_mul(u0[2], t0.y); u0[3] = h2_mul(u0[3], t0.y);
                u1[0] = h2_mul(u1[0], t1.x); u1[1] = h2_mul(u1[1], t1.x); u1[2] = h2_mul(u1[2], t1.y); u1[3] = h2_mul(u1[3], t1.y);
            }
            a[j & 1][0] = make_uint4(u0[0], u0[1], u0[2], u0[3]);
            a[j & 1][1] = make_uint4(u1[0], u1[1], u1[2], u1[3]);
            if (!ok_b) mbar_wait(bar_bfull + (j & 3) * 8, j >> 2);
        };
        auto table = [&](int pos) { s_t = sbase + P2_OFF_GRN + q * 8 + (k0 + pos) % 48 * 64; };
        const uint64_t db0 = make_desc(sbase, 128, 256 + zero);
        auto block8 = [&](bool raw, int pos, int thr0, int mode) {
#pragma unroll
            for (int j = 0; j < 8; j++) {
                const uint64_t db = db0 + (j & 3) * (P2_B / 16);
                if (j == 8 - P2_AH && mode == 1) bar_sync(4, 384);
                TR2(wg, pos + j, 0);
                wg_fence();
                mma_rs_n192(acc0, a[j & 1][0], db);
                mma_rs_n192(acc1, a[j & 1][0], db + 384);
                mma_rs_n192(acc0, a[j & 1][1], db + 768);
                mma_rs_n192(acc1, a[j & 1][1], db + 768 + 384);
                wg_commit();
                if (j == 7 && mode == 2) bar_arrive(4, 384);
                const uint32_t rel = ((j - 1) & 4 ? rel1 : rel0) + ((j - 1) & 3) * 8;
                TR2(wg, pos + j, 1);
                wg_wait<1>();
                TR2(wg, pos + j, 2);
                if (who < (j ? 2 : thr0)) mbar_arrive_cluster(rel);
                if (!ok_a) {
                    if (j == 0 && pend) { publish(); pend = false; }
                    mbar_wait(af + ((j + 1) & 7) * 8, pa);
                }
                TR2(wg, pos + j, 3);
                if (raw && j == 7) table(pos + 8);
                fetch((j + 1) & 7, raw && (j < 7 || pos + 8 < P2_RAW));
            }
        };
        int n = wg == 2 && half ? -1 : wg, pos = p2_start(n);
        uint32_t px = 0;
        wait_pos(pos);
        mbar_wait(af, 0);
        table(pos);
        fetch(0, pos < P2_RAW);
#pragma unroll 1
        for (;; n += 3) {
            TSTAMP(1, 2 + n);
            const int end = pos + (n < 0 ? 24 : 48);
#pragma unroll
            for (int i = 0; i < 48; i += 2) {
                asm volatile("mov.b64 {%0, %1}, 0;\n" : "=r"(acc0[i]), "=r"(acc0[i + 1]));
                asm volatile("mov.b64 {%0, %1}, 0;\n" : "=r"(acc1[i]), "=r"(acc1[i + 1]));
            }
            int thr = 1;
#pragma unroll 1
            for (; pos < P2_RAW; pos += 8, thr = 2) block8(true, pos, thr, 0);
#pragma unroll 1
            for (; pos < end; pos += 8, thr = 2) {
                const int e = pos + 8, r = e % 48;
                block8(false, pos, thr, e < 48 || e > 256 || (r != 0 && r != P2_S1 && r != P2_S2) ? 0 : e == end ? 2 : 1);
            }
            TR2(wg, pos - 1, 4);
            if (n < 2 || n > 12) { LAG_HERE(3); }
            wg_wait<0>();
            TR2(wg, pos - 1, 5);
            if (who == 1) mbar_arrive_cluster(rel0 + 24);
            mbar_wait(bar_xfull + wg * 8, px);
            TR2(wg, pos - 1, 6);
            px ^= 1;
            __syncwarp();
            const bool last = n == P2_ITEMS - 1;
            uint32_t l;
            asm volatile("mov.u32 %0, %%laneid;\n" : "=r"(l));
            const uint32_t q16 = (l & 3) * 16, odd = (l >> 2) & 1, row = (w * 8 + (l >> 3)) * P2_XROW + q16;
            uint8_t* so = last ? reinterpret_cast<uint8_t*>(out) + (size_t)(2 * p2_tile(cl, n) + rank) * (64 * P2_XROW) : smem + P2_OFF_X;
            p2_epilogue(acc0, acc1, up, sbase + row + (last ? P2_OFF_A + odd * P2_LHALF : P2_OFF_X + odd * P2_XHALF),
                        sbase + P2_OFF_BIAS + q16 + (n < 0 && fin ? C_DIM * 2 : 0), so + (row + odd * (last ? 32 * P2_XROW : P2_XHALF)), zero);
            if (last) break;
            TR2(wg, pos - 1, 7);
            if (n + 3 >= P2_ITEMS) { publish(); break; }
            if (n < 0) {
                publish();
                pos = P2_S2;
                wait_pos(pos);
                mbar_wait(bar_bfull, 0);
            } else {
                pend = true;
                ok_a = false;
            }
        }
        TSTAMP(1, 29);
        cluster_sync_relaxed();
        TSTAMP(1, 30);
    }
}

__global__ void __cluster_dims__(2, 1, 1) __launch_bounds__(512, 1)
block_kernel(const __grid_constant__ CUtensorMap wmap, const __nv_bfloat16* __restrict__ x, const __nv_bfloat16* __restrict__ dw,
             const __nv_bfloat16* __restrict__ w2, const __nv_bfloat16* __restrict__ grn_g, const __nv_bfloat16* __restrict__ grn_b,
             __nv_bfloat16* __restrict__ out, int zero) {
    extern __shared__ __align__(1024) uint8_t smem[];
    const uint32_t sbase = smem_u32(smem);
    const int warp = __shfl_sync(0xffffffffu, threadIdx.x >> 5, 0), lane = threadIdx.x & 31;
    if (warp >= 12) {
        pass1<2>(wmap, x, dw, w2, grn_b, sbase, warp, lane, zero);
        pass2<2>(x, grn_g, out, smem, sbase, false, zero);
    } else {
        bool early = false;
        if (warp >= 8) {
            pass1<1>(wmap, x, dw, w2, grn_b, sbase, warp, lane, zero);
            reg_inc<160>();
        } else {
            early = pass1<0>(wmap, x, dw, w2, grn_b, sbase, warp, lane, zero);
            reg_dec<160>();
        }
        pass2<0>(x, grn_g, out, smem, sbase, early, zero);
    }
}

}

extern "C" void kernel_launch(void* const* d_in, const int* in_sizes, int n_in, void* d_out, int out_size) {
    const __nv_bfloat16* x = (const __nv_bfloat16*)d_in[0];
    const __nv_bfloat16* dw = (const __nv_bfloat16*)d_in[1];
    const __nv_bfloat16* w1 = (const __nv_bfloat16*)d_in[2];
    const __nv_bfloat16* w2 = (const __nv_bfloat16*)d_in[3];
    const __nv_bfloat16* grn_g = (const __nv_bfloat16*)d_in[4];
    const __nv_bfloat16* grn_b = (const __nv_bfloat16*)d_in[5];
    __nv_bfloat16* out = (__nv_bfloat16*)d_out;

    cudaFuncSetAttribute(block_kernel, cudaFuncAttributeMaxDynamicSharedMemorySize, SMEM_BYTES);

    typedef CUresult (*EncodeFn)(CUtensorMap*, CUtensorMapDataType, cuuint32_t, void*, const cuuint64_t*, const cuuint64_t*,
                                 const cuuint32_t*, const cuuint32_t*, CUtensorMapInterleave, CUtensorMapSwizzle,
                                 CUtensorMapL2promotion, CUtensorMapFloatOOBfill);
    static EncodeFn encode = nullptr;
    if (!encode) {
        cudaDriverEntryPointQueryResult qres;
        cudaGetDriverEntryPoint("cuTensorMapEncodeTiled", (void**)&encode, cudaEnableDefault, &qres);
    }
    CUtensorMap wmap;
    const cuuint64_t gdim[2] = {HID, C_DIM};
    const cuuint64_t gstr[1] = {HID * 2};
    const cuuint32_t box[2] = {64, 192}, estr[2] = {1, 1};
    CUresult er = encode(&wmap, CU_TENSOR_MAP_DATA_TYPE_BFLOAT16, 2, (void*)w1, gdim, gstr, box, estr, CU_TENSOR_MAP_INTERLEAVE_NONE,
           CU_TENSOR_MAP_SWIZZLE_128B, CU_TENSOR_MAP_L2_PROMOTION_L2_128B, CU_TENSOR_MAP_FLOAT_OOB_FILL_NONE);
    if (er != CUDA_SUCCESS) printf("tensor map encode failed %d\n", (int)er);

    block_kernel<<<NUM_CTAS, 512, SMEM_BYTES>>>(wmap, x, dw, w2, grn_g, grn_b, out, 0);
}
```

```cpp
#include <cuda.h>
#include <cuda_runtime.h>
#include <cuda_bf16.h>
#include <cuda_fp16.h>
#include <stdint.h>
#include <stdio.h>

namespace {

constexpr int M_TOTAL = 384 * 384;
constexpr int C_DIM   = 384;
constexpr int HID     = 1536;
constexpr int NT128   = M_TOTAL / 128;
constexpr int NUM_CTAS = 132;

constexpr int NGRP = 22, GRP_CTAS = 6;
constexpr int NT_EARLY = NT128 - 30;
constexpr int LN_STEP = NUM_CTAS / 4, LN_RING = 2 * LN_STEP;
constexpr int LN_TILE = 128 * C_DIM * 2;
constexpr int H_PAGES = NT128 / 4;

__device__ __align__(1024) uint4 g_h[(size_t)(H_PAGES + 1) << 17];
__device__ unsigned g_page[H_PAGES];
__device__ unsigned g_epoch;
__device__ __align__(1024) uint4 g_w2img[2][HID * C_DIM * 2 / 16];
__device__ __align__(16) unsigned long long g_sq[HID];
__device__ __align__(16) float g_sums[512];
__device__ float g_scale[HID];
__device__ float g_redo[HID];
enum { CNT_POS, CNT_IMG1, CNT_REDO, CNT_IMG0, CNT_LAST, CNT_H, CNT_EARLY, NUM_CNT };
__device__ __align__(128) unsigned g_prog[NUM_CNT][32];
__device__ __align__(128) unsigned g_half[32][2];
__device__ unsigned g_flag[LN_RING + 6][2][8];
#define TSTAMP(k, i)
#define TRACE(wg, pos, i)
#define TRACEW(pos, i)

#define TR2(wg, pos, i)
__host__ __device__ __forceinline__ int perm32(int n) {
    return (n & ~31) | (((n >> 1) & 3) << 3) | (((n >> 3) & 3) << 1) | (n & 1);
}

constexpr int H_FIXED = 17;
#define LN_SW 132
__device__ __forceinline__ uint8_t* h_base() { return reinterpret_cast<uint8_t*>((reinterpret_cast<size_t>(g_h) + 0x1fffff) & ~(size_t)0x1fffff); }
__device__ __forceinline__ unsigned page_bit(int page, unsigned tag) {
    unsigned v = 0;
    if (page >= H_FIXED) {
        do {
            asm volatile("ld.relaxed.gpu.global.u32 %0, [%1];\n" : "=r"(v) : "l"(&g_page[page]) : "memory");
        } while (tag && (v & ~1u) != tag);
    }
    return v;
}
__device__ __forceinline__ uint32_t h_tile(int t, unsigned bit) { return (t >> 1) << 20 | ((t ^ bit) & 1) << 12 | (t & 2) << 9; }
__device__ __forceinline__ uint32_t h_tile(int t) { return h_tile(t, page_bit(t >> 2, 0)); }
__device__ __forceinline__ int ln_page(int t) { return (t < LN_SW ? 0 : H_FIXED) + (t % LN_RING >> 2); }
__device__ __forceinline__ uint32_t ln_tile(int t, unsigned bit) {
    const int slot = t % LN_RING;
    return ln_page(t) << 21 | 0xc0000 | (slot & 2) << 16 | ((~t ^ bit ^ (slot >> 1)) & 1) << 12;
}
__device__ __forceinline__ constexpr uint32_t ln_rows(int group) { return (group & 1) * 0x3000 ^ (group >> 1) * 0x11000; }
__device__ __forceinline__ constexpr uint32_t ln_block(int j) { return (j & 3) << 14 | (j >> 2) << 20; }
__device__ __forceinline__ uint32_t h_block(int kb, int half) {
    return (kb >> 2) << 16 | (kb & 2) << 14 | half << 14 | (kb & 1) << 13 | (__popc(kb & 0x2d) & 1) << 12 | (kb & 1) << 10;
}
__device__ __forceinline__ unsigned* h_cell(int page, int c) {
    return reinterpret_cast<unsigned*>(h_base() + ((size_t)page << 21) + 0x1d8000 + ((c >> 6) << 14) + (c & 63) * 64);
}
__device__ __forceinline__ unsigned near_half(unsigned* cell, int reps) {
    int votes = 0;
#pragma unroll 1
    for (int i = 0; i < 2 * reps; i++) {
        const unsigned a = atomicAdd(cell + (i & 1) * 1024, 1u), b = atomicAdd(cell + (~i & 1) * 1024, 1u);
        if (a == ~0u) break;
        const unsigned t0 = clock();
        if (b == ~0u) break;
        const int d = min((unsigned)clock() - t0, 250u);
        votes += i & 1 ? d : -d;
    }
    return votes > 0;
}

__device__ __forceinline__ uint32_t smem_u32(const void* p) { return (uint32_t)__cvta_generic_to_shared(p); }

__device__ __forceinline__ void mbar_init(uint32_t bar, uint32_t count) {
    asm volatile("mbarrier.init.shared::cta.b64 [%0], %1;\n" ::"r"(bar), "r"(count) : "memory");
}
__device__ __forceinline__ void mbar_expect_tx(uint32_t bar, uint32_t bytes) {
    asm volatile("mbarrier.arrive.expect_tx.shared::cta.b64 _, [%0], %1;\n" ::"r"(bar), "r"(bytes) : "memory");
}
__device__ __forceinline__ void mbar_arrive(uint32_t bar) {
    asm volatile("mbarrier.arrive.shared::cta.b64 _, [%0];\n" ::"r"(bar) : "memory");
}
__device__ __forceinline__ void mbar_arrive_cluster(uint32_t bar_cluster_addr) {
    asm volatile("mbarrier.arrive.shared::cluster.b64 _, [%0];\n" ::"r"(bar_cluster_addr) : "memory");
}
#define LAG_HERE(k)
#define SAFE_BREAK
__device__ __forceinline__ void mbar_wait(uint32_t bar, uint32_t parity) {
    asm volatile(
        "{\n"
        ".reg .pred p;\n"
        "LAB_WAIT:\n"
        "mbarrier.try_wait.parity.shared::cta.b64 p, [%0], %1;\n"
        "@!p bra LAB_WAIT;\n"
        "}\n" ::"r"(bar), "r"(parity) : "memory");
}
__device__ __forceinline__ bool mbar_test(uint32_t bar, uint32_t parity) {
    uint32_t ok;
    asm volatile("{\n.reg .pred p;\n"
                 "mbarrier.test_wait.parity.shared::cta.b64 p, [%1], %2;\n"
                 "selp.u32 %0, 1, 0, p;\n}\n" : "=r"(ok) : "r"(bar), "r"(parity) : "memory");
    return ok != 0;
}
__device__ __forceinline__ uint32_t mapa(uint32_t addr, uint32_t rank) {
    uint32_t r;
    asm volatile("mapa.shared::cluster.u32 %0, %1, %2;\n" : "=r"(r) : "r"(addr), "r"(rank));
    return r;
}
__device__ __forceinline__ void bulk_g2s(uint32_t dst, const void* src, uint32_t bytes, uint32_t bar) {
    asm volatile("cp.async.bulk.shared::cluster.global.mbarrier::complete_tx::bytes [%0], [%1], %2, [%3];\n"
                 ::"r"(dst), "l"(src), "r"(bytes), "r"(bar) : "memory");
}
__device__ __forceinline__ void bulk_g2s_mc(uint32_t dst, const void* src, uint32_t bytes, uint32_t bar, uint16_t mask) {
    asm volatile("cp.async.bulk.shared::cluster.global.mbarrier::complete_tx::bytes.multicast::cluster [%0], [%1], %2, [%3], %4;\n"
                 ::"r"(dst), "l"(src), "r"(bytes), "r"(bar), "h"(mask) : "memory");
}
__device__ __forceinline__ void tma2(uint32_t dst, const CUtensorMap* map, int c0, int c1, uint32_t bar) {
    asm volatile("cp.async.bulk.tensor.2d.shared::cluster.global.tile.mbarrier::complete_tx::bytes [%0], [%1, {%2, %3}], [%4];\n"
                 ::"r"(dst), "l"(map), "r"(c0), "r"(c1), "r"(bar) : "memory");
}
template <bool ACQ>
__device__ __forceinline__ uint32_t flag_wait(const unsigned* p, unsigned target) {
    unsigned v, n = 0;
    do {
        if (ACQ) asm volatile("ld.acquire.gpu.global.u32 %0, [%1];\n" : "=r"(v) : "l"(p) : "memory");
        else asm volatile("ld.relaxed.gpu.global.u32 %0, [%1];\n" : "=r"(v) : "l"(p) : "memory");
        n++;
    } while (v < target);
    return n == 1;
}
__device__ __forceinline__ void ldsm4t(uint32_t (&r)[4], uint32_t addr) {
    asm volatile("ldmatrix.sync.aligned.m8n8.x4.trans.shared.b16 {%0,%1,%2,%3}, [%4];\n"
                 : "=r"(r[0]), "=r"(r[1]), "=r"(r[2]), "=r"(r[3]) : "r"(addr) : "memory");
}
__device__ __forceinline__ void bulk_s2g(void* dst, uint32_t src, uint32_t bytes) {
    asm volatile("cp.async.bulk.global.shared::cta.bulk_group [%0], [%1], %2;\n" ::"l"(dst), "r"(src), "r"(bytes) : "memory");
}
__device__ __forceinline__ void cluster_sync_relaxed() {
    asm volatile("barrier.cluster.arrive.relaxed.aligned;\nbarrier.cluster.wait.aligned;\n" ::: "memory");
}
__device__ __forceinline__ uint32_t cluster_rank() {
    uint32_t r;
    asm volatile("mov.u32 %0, %%cluster_ctarank;\n" : "=r"(r));
    return r;
}
__device__ __forceinline__ bool elect_one() {
    uint32_t pred;
    asm volatile("{\n.reg .pred p;\nelect.sync _|p, 0xffffffff;\nselp.u32 %0, 1, 0, p;\n}\n" : "=r"(pred));
    return pred != 0;
}
__device__ __forceinline__ void wg_fence() { asm volatile("wgmma.fence.sync.aligned;\n" ::: "memory"); }
__device__ __forceinline__ void wg_commit() { asm volatile("wgmma.commit_group.sync.aligned;\n" ::: "memory"); }
template <int N> __device__ __forceinline__ void wg_wait() {
    asm volatile("wgmma.wait_group.sync.aligned %0;\n" ::"n"(N) : "memory");
}
template <int R> __device__ __forceinline__ void reg_inc() { asm volatile("setmaxnreg.inc.sync.aligned.u32 %0;\n" ::"n"(R)); }
template <int R> __device__ __forceinline__ void reg_dec() { asm volatile("setmaxnreg.dec.sync.aligned.u32 %0;\n" ::"n"(R)); }
__device__ __forceinline__ void bar_sync(int id, int n) { asm volatile("bar.sync %0, %1;\n" ::"r"(id), "r"(n) : "memory"); }
__device__ __forceinline__ void bar_arrive(int id, int n) { asm volatile("bar.arrive %0, %1;\n" ::"r"(id), "r"(n) : "memory"); }

__device__ __forceinline__ uint64_t make_desc(uint32_t saddr, uint32_t lbo, uint32_t sbo) {
    return (uint64_t)((saddr & 0x3FFFF) >> 4) | ((uint64_t)(lbo >> 4) << 16) | ((uint64_t)(sbo >> 4) << 32);
}

__device__ __forceinline__ void stg128_cs(void* p, uint32_t a, uint32_t b, uint32_t c, uint32_t d) {
    asm volatile("st.global.cs.v4.u32 [%0], {%1,%2,%3,%4};\n" ::"l"(p), "r"(a), "r"(b), "r"(c), "r"(d) : "memory");
}
__device__ __forceinline__ uint32_t pack_bf16(float lo, float hi) {
    uint32_t r;
    asm("cvt.rn.bf16x2.f32 %0, %1, %2;\n" : "=r"(r) : "f"(hi), "f"(lo));
    return r;
}
__device__ __forceinline__ float bf_lo(uint32_t v) { return __uint_as_float(v << 16); }
__device__ __forceinline__ float bf_hi(uint32_t v) { return __uint_as_float(v & 0xffff0000u); }
__device__ __forceinline__ uint32_t bf2_mul(uint32_t a, uint32_t b) {
    uint32_t r;
    asm("mul.rn.bf16x2 %0, %1, %2;\n" : "=r"(r) : "r"(a), "r"(b));
    return r;
}
__device__ __forceinline__ uint32_t bf2_fma(uint32_t a, uint32_t b, uint32_t c) {
    uint32_t r;
    asm("fma.rn.bf16x2 %0, %1, %2, %3;\n" : "=r"(r) : "r"(a), "r"(b), "r"(c));
    return r;
}
__device__ __forceinline__ uint32_t bf2_add(uint32_t a, uint32_t b) {
    uint32_t r;
    asm("add.rn.bf16x2 %0, %1, %2;\n" : "=r"(r) : "r"(a), "r"(b));
    return r;
}
__device__ __forceinline__ uint32_t h2_mul(uint32_t a, uint32_t b) {
    uint32_t r;
    asm("mul.rn.f16x2 %0, %1, %2;\n" : "=r"(r) : "r"(a), "r"(b));
    return r;
}
__device__ __forceinline__ uint32_t h2_fma(uint32_t a, uint32_t b, uint32_t c) {
    uint32_t r;
    asm("fma.rn.f16x2 %0, %1, %2, %3;\n" : "=r"(r) : "r"(a), "r"(b), "r"(c));
    return r;
}
__device__ __forceinline__ uint32_t h2_add(uint32_t a, uint32_t b) {
    uint32_t r;
    asm("add.rn.f16x2 %0, %1, %2;\n" : "=r"(r) : "r"(a), "r"(b));
    return r;
}
__device__ __forceinline__ uint32_t pack_f16(float lo, float hi) {
    uint32_t r;
    asm("cvt.rn.f16x2.f32 %0, %1, %2;\n" : "=r"(r) : "f"(hi), "f"(lo));
    return r;
}
__device__ __forceinline__ float h_lo(uint32_t v) { return __low2float(*reinterpret_cast<const __half2*>(&v)); }
__device__ __forceinline__ float h_hi(uint32_t v) { return __high2float(*reinterpret_cast<const __half2*>(&v)); }
__device__ __forceinline__ uint32_t bf2_to_h2(uint32_t v) { return (v & 0x7fff7fffu) * 7u + v; }
__device__ __forceinline__ uint32_t prmt(uint32_t a, uint32_t b, uint32_t sel) {
    uint32_t r;
    asm("prmt.b32 %0, %1, %2, %3;\n" : "=r"(r) : "r"(a), "r"(b), "r"(sel));
    return r;
}
__device__ __forceinline__ uint32_t bitsel(uint32_t a, uint32_t b, uint32_t m) {
    uint32_t r;
    asm("lop3.b32 %0, %1, %2, %3, 0xd8;\n" : "=r"(r) : "r"(a), "r"(b), "r"(m));
    return r;
}
constexpr float KAPPA = 0.3292034911525734f;
constexpr uint32_t GELU_C2 = 0x40d940d9u;
constexpr float HSCALE = 1.0f / (2.0f * KAPPA);
__device__ __forceinline__ float w2_scale(uint32_t m) { return __uint_as_float((257u - max(m >> 23, 16u)) << 23); }
__device__ __forceinline__ void sched_break(int zero) {
    asm volatile("{\n.reg .pred p;\nsetp.ne.s32 p, %0, 0;\nSB_LOOP:\n@p nanosleep.u32 1;\n@p bra SB_LOOP;\n}\n" ::"r"(zero));
}

#define ACC8(d, o) "+r"(d[o + 0]), "+r"(d[o + 1]), "+r"(d[o + 2]), "+r"(d[o + 3]), "+r"(d[o + 4]), "+r"(d[o + 5]), "+r"(d[o + 6]), "+r"(d[o + 7])

__device__ __forceinline__ void mma_rs_n128(uint32_t (&d)[32], const uint32_t (&a)[4], uint64_t desc, int scale_d) {
    asm volatile(
        "{\n.reg .pred p;\nsetp.ne.b32 p, %37, 0;\n"
        "wgmma.mma_async.sync.aligned.m64n128k16.f16.f16.f16 "
        "{%0,%1,%2,%3,%4,%5,%6,%7,%8,%9,%10,%11,%12,%13,%14,%15,"
        "%16,%17,%18,%19,%20,%21,%22,%23,%24,%25,%26,%27,%28,%29,%30,%31},"
        "{%32,%33,%34,%35}, %36, p, 1, 1, 0;\n}\n"
        : ACC8(d, 0), ACC8(d, 8), ACC8(d, 16), ACC8(d, 24)
        : "r"(a[0]), "r"(a[1]), "r"(a[2]), "r"(a[3]), "l"(desc), "r"(scale_d));
}

__device__ __forceinline__ void mma_ss_n128(uint32_t (&d)[32], uint64_t da, uint64_t db, int scale_d) {
    asm volatile(
        "{\n.reg .pred p;\nsetp.ne.b32 p, %34, 0;\n"
        "wgmma.mma_async.sync.aligned.m64n128k16.f16.f16.f16 "
        "{%0,%1,%2,%3,%4,%5,%6,%7,%8,%9,%10,%11,%12,%13,%14,%15,"
        "%16,%17,%18,%19,%20,%21,%22,%23,%24,%25,%26,%27,%28,%29,%30,%31},"
        "%32, %33, p, 1, 1, 1, 0;\n}\n"
        : ACC8(d, 0), ACC8(d, 8), ACC8(d, 16), ACC8(d, 24)
        : "l"(da), "l"(db), "r"(scale_d));
}

__device__ __forceinline__ void mma_rs_n192(uint32_t (&d)[48], const uint4& a, uint64_t db) {
    asm volatile(
        "wgmma.mma_async.sync.aligned.m64n192k16.f16.f16.f16 "
        "{%0,%1,%2,%3,%4,%5,%6,%7,%8,%9,%10,%11,%12,%13,%14,%15,"
        "%16,%17,%18,%19,%20,%21,%22,%23,%24,%25,%26,%27,%28,%29,%30,%31,"
        "%32,%33,%34,%35,%36,%37,%38,%39,%40,%41,%42,%43,%44,%45,%46,%47},"
        "{%48,%49,%50,%51}, %52, 1, 1, 1, 0;\n"
        : ACC8(d, 0), ACC8(d, 8), ACC8(d, 16), ACC8(d, 24), ACC8(d, 32), ACC8(d, 40)
        : "r"(a.x), "r"(a.y), "r"(a.z), "r"(a.w), "l"(db));
}

constexpr int P1_SPLIT = 6;
constexpr int P1_SLOT = LN_TILE / 6, P1_NST = 6;
constexpr int P1_W = 64 * C_DIM * 2;
constexpr int P1_X = 32 * C_DIM * 2;
constexpr int P1_OFF_W = LN_TILE;
constexpr int P1_OFF_X = P1_OFF_W + 2 * P1_W;
constexpr int P1_OFF_BAR = 227328;
constexpr int P1_OFF_TILE = P1_OFF_BAR + (2 * P1_NST + 4 + 4 + 4) * 8;
constexpr int P1_OFF_EX = P1_OFF_TILE + 96;
constexpr int P1_OFF_DW = P1_OFF_EX + 256 * 4;
constexpr int OFF_PRE = P1_OFF_DW + C_DIM * 2;
constexpr int SMEM_BYTES = OFF_PRE + C_DIM * 4 + 16;

__device__ __forceinline__ float rsqrt_fast(float x) {
    float r;
    asm("rsqrt.approx.ftz.f32 %0, %1;\n" : "=f"(r) : "f"(x));
    return r;
}
__device__ __forceinline__ float row_sum(const uint32_t (&c)[4]) {
    const uint32_t u = bf2_add(bf2_add(c[0], c[1]), bf2_add(c[2], c[3]));
    float s = bf_lo(u) + bf_hi(u);
#pragma unroll
    for (int o = 1; o < 8; o <<= 1) s += __shfl_xor_sync(0xffffffffu, s, o);
    return s;
}
__device__ __forceinline__ uint32_t pace(uint32_t bar, uint32_t off, uint32_t val, int zero) {
    asm volatile(
        "{\n.reg .pred p, q;\n.reg .b32 par;\n"
        "lop3.b32 par, %0, %2, %3, 0xea;\n"
        "setp.eq.u32 q, par, 0;\n"
        "mov.pred p, 0;\n"
        "@q mbarrier.test_wait.parity.shared::cta.b64 p, [%1], par;\n"
        "selp.u32 par, 1, 0, p;\n"
        "@q mbarrier.try_wait.parity.shared::cta.b64 p, [%1], par, 1000;\n"
        "@p or.b32 %0, %0, %2;\n"
        "}\n" : "+r"(val) : "r"(bar), "r"(zero), "r"(off));
    return val;
}
__device__ __forceinline__ void ln_row(uint32_t (&v)[6][4], const uint32_t (&d)[6][4], uint32_t bar, uint32_t off, int zero, uint32_t bar_read) {
    const float inv = 1.0f / C_DIM;
    uint32_t c[4];
#pragma unroll
    for (int i = 0; i < 6; i++)
#pragma unroll
        for (int k = 0; k < 4; k++) c[k] = bf2_fma(v[i][k], d[i][k], i ? c[k] : 0);
    const float m = row_sum(c) * inv;
    uint32_t nm = pack_bf16(-m, -m);
    const float e = m + bf_lo(nm);
    if (bar_read) mbar_arrive(bar_read + (nm & zero));
    nm = pace(bar, off, nm, zero);
#pragma unroll
    for (int i = 0; i < 6; i++) {
#pragma unroll
        for (int k = 0; k < 4; k++) {
            v[i][k] = bf2_fma(v[i][k], d[i][k], nm);
            c[k] = i ? bf2_fma(v[i][k], v[i][k], c[k]) : bf2_mul(v[i][k], v[i][k]);
        }
    }
    float r = KAPPA * rsqrt_fast(fmaxf(fmaf(-e, e, row_sum(c) * inv), 0.f) + 1e-5f);
    const float er = -e * r * 0x1p-112f;
    if (__any_sync(0xffffffffu, r < 0x1p-8f)) {
        const uint32_t p2 = __float_as_uint(r) & 0x7f800000u;
        r = __uint_as_float((__float_as_uint(r) & 0x007fffffu) | 0x3f800000u);
#pragma unroll
        for (int i = 0; i < 6; i++)
#pragma unroll
            for (int k = 0; k < 4; k++) v[i][k] = bf2_mul(v[i][k], p2 | p2 >> 16);
    }
    const uint32_t rs = pack_bf16(r * 0x1p-112f, r * 0x1p-112f), sh = pack_bf16(er, er);
#pragma unroll
    for (int i = 0; i < 6; i++)
#pragma unroll
        for (int k = 0; k < 4; k++) v[i][k] = bf2_to_h2(bf2_fma(v[i][k], rs, sh));
}

template <int R>
__device__ __forceinline__ uint32_t gelu2(uint32_t a, uint32_t sc2) {
    uint32_t y, t;
    if (R) asm("{\n.reg .b16 l, h;\n.reg .b32 f;\nmov.b32 {l, h}, %2;\nmov.b32 f, {h, h};\nmul.rn.f16x2 %0, %1, f;\n}\n" : "=r"(y) : "r"(a), "r"(sc2));
    else asm("{\n.reg .b16 l, h;\n.reg .b32 f;\nmov.b32 {l, h}, %2;\nmov.b32 f, {l, l};\nmul.rn.f16x2 %0, %1, f;\n}\n" : "=r"(y) : "r"(a), "r"(sc2));
    asm("tanh.approx.f16x2 %0, %1;\n" : "=r"(t) : "r"(h2_mul(y, h2_fma(y, y, GELU_C2))));
    return h2_fma(a, t, a);
}
constexpr uint32_t SPARE = 0x40074007u;
constexpr float UNCHOP = 1.0023f;

__device__ __forceinline__ uint32_t p1_exponents(float (&t)[2], uint32_t (&ex)[2], uint32_t saddr, int lane) {
#pragma unroll
    for (int r = 0; r < 2; r++) {
        t[r] += __shfl_xor_sync(0xffffffffu, t[r], 1);
        t[r] += __shfl_xor_sync(0xffffffffu, t[r], 2);
        ex[r] = min(max(((__float_as_uint(193.3f * t[r]) >> 23) + 127u) >> 1, 72u), 198u);
        asm volatile("st.shared.u32 [%0], %1;\n" ::"r"(saddr + r * 32), "r"(ex[r] << 23) : "memory");
    }
    return pack_f16(__uint_as_float(min(ex[0], 142u) << 23), __uint_as_float(min(ex[1], 142u) << 23));
}
template <int N>
__device__ __forceinline__ void p1_convert(uint32_t (&o)[N][4], uint32_t (&v)[N][4], const uint32_t (&ex)[2]) {
    if (__any_sync(0xffffffffu, max(ex[0], ex[1]) > 141u)) {
#pragma unroll
        for (int k = 0; k < 4 * N; k++) v[k >> 2][k & 3] = bf2_mul(v[k >> 2][k & 3], ex[k & 1] > 141u ? 0x1f801f80u : 0x3f803f80u);
    }
#pragma unroll
    for (int k = 0; k < 4 * N; k++) {
        const uint32_t u = bf2_mul(v[k >> 2][k & 3], ((ex[k & 1] > 141u ? 206u : 142u) - ex[k & 1]) * 0x00800080u);
        asm volatile("mad.lo.u32 %0, %1, 7, %2;\n" : "=r"(o[k >> 2][k & 3]) : "r"(u & 0x7fff7fffu), "r"(u));
    }
}
template <int N>
__device__ __forceinline__ void p1_squares(const uint32_t (&v)[N][4], float (&t)[2]) {
#pragma unroll
    for (int j = 0; j < N / 2; j++) {
        const int r = j & 1, b = (j >> 1) * 4;
        uint32_t c = bf2_mul(v[b][r], v[b][r]);
#pragma unroll
        for (int k = 1; k < 8; k++) c = bf2_fma(v[b + k / 2][r + (k & 1) * 2], v[b + k / 2][r + (k & 1) * 2], c);
        t[r] += bf_lo(c) + bf_hi(c);
    }
}
__device__ __forceinline__ void p1_epilogue(const uint32_t (&acc)[2][32], const uint32_t (&sc2)[2], float (&ssq)[4], uint8_t* hp, int zero) {
    uint32_t sq[2], h[16][4];
#pragma unroll
    for (int i2 = 0; i2 < 9; i2++) {
#pragma unroll
        for (int c = 2 * i2 - 2; c < 2 * i2; c++) {
            if (c >= 0 && (c & 3)) {
                uint32_t o[4];
#pragma unroll
                for (int u = 0; u < 4; u++) {
                    const uint32_t v = h[c & 12][u];
                    o[u] = bitsel(h[c][u], (c & 3) == 2 ? prmt(v, v, 0xa381) : prmt(v >> 3, v, (c & 3) == 1 ? 0x6240 : 0xf3d1), SPARE);
                }
                stg128_cs(hp + (c >> 2) * 0x4000 + ((c & 3) - 1) * 512, o[0], o[1], o[2], o[3]);
            }
        }
        if (i2 < 8) {
#pragma unroll
            for (int u = 0; u < 4; u++) {
                h[2 * i2][u] = gelu2<0>(acc[i2 >> 2][8 * (i2 & 3) + 2 * u], sc2[i2 >> 2]);
                h[2 * i2 + 1][u] = gelu2<1>(acc[i2 >> 2][8 * (i2 & 3) + 2 * u + 1], sc2[i2 >> 2]);
#pragma unroll
                for (int r = 0; r < 2; r++) {
                    const uint32_t v = h[2 * i2 + r][u];
                    sq[r] = ((i2 & 3) | u) ? h2_fma(v, v, sq[r]) : h2_mul(v, v);
                }
            }
            if ((i2 & 3) == 3) {
#pragma unroll
                for (int r = 0; r < 2; r++) ssq[(i2 >> 2) * 2 + r] += h_lo(sq[r]) + h_hi(sq[r]);
            }
            sched_break(zero);
        }
    }
}
template <int WG>
__device__ __forceinline__ void p1_mma(uint32_t (&acc)[2][32], const uint32_t (&a)[24][4], uint32_t sbase, uint32_t empty_remote, int i, int lane, bool pass, int zero) {
    const uint32_t bar_full = sbase + P1_OFF_BAR;
    const uint64_t db = make_desc(sbase, 16, 1024 + zero) | (1ull << 62), da = db + (P1_OFF_W + WG * P1_W) / 16;
    if (WG == 0) mbar_wait(bar_full, i & 1);
    bar_sync(1 + WG, 256);
    TRACE(WG, i, 1);
    wg_fence();
#pragma unroll
    for (int k = 0; k < 24; k++) {
        if (WG == 0 && k && k % 4 == 0) mbar_wait(bar_full + (k >> 2) * 8, i & 1);
        mma_rs_n128(acc[0], a[k], db + (k >> 2) * 1024 + (k & 3) * 2, k != 0);
        mma_ss_n128(acc[1], da + k * 128, db + (k >> 2) * 1024 + (k & 3) * 2, k != 0);
        if (k == 23 && pass) bar_arrive(2 - WG, 256);
        if (k == 23 || (WG == 1 && k % 4 == 3)) wg_commit();
        if (WG == 1 && k % 4 == 3 && k > 3) {
            wg_wait<1>();
            if (lane < 2) mbar_arrive_cluster(empty_remote + ((k >> 2) - 1) * 8);
        }
    }
    TRACE(WG, i, 2);
    wg_wait<0>();
    if (WG == 1 && lane < 2) mbar_arrive_cluster(empty_remote + 5 * 8);
}
__device__ __forceinline__ bool p1_consumer(const uint32_t (&a)[24][4], const uint32_t (&sc2)[2], uint32_t sbase, int WG, int w, int lane, int zero) {
    const uint32_t bar_full = sbase + P1_OFF_BAR, bar_empty = bar_full + P1_NST * 8;
    const uint32_t empty_remote = mapa(bar_empty, lane & 1);
    const uint32_t bar_pace = bar_empty + P1_NST * 8 + 32 + w * 8;
    const int g = lane >> 2, q = lane & 3, half = WG ^ ((blockIdx.x / GRP_CTAS) & 1), cb = (blockIdx.x % GRP_CTAS) * 4 + half * 2;
    uint32_t acc[2][32];
    float ssq[4] = {0.f, 0.f, 0.f, 0.f};
    TSTAMP(0, 1);

    uint8_t* const hp0 = h_base() + (w & 1) * 1536 + g * 64 + (q ^ (g >> 1)) * 16;
    const uint32_t blk = h_block(cb * 2 + (w >> 1), 0);
    int i = 0;
    uint32_t more = 3, both;
#pragma unroll 1
    for (;; i++) {
        TRACE(WG, i, 0);
        both = more & 2;
        if (WG == 0) p1_mma<0>(acc, a, sbase, empty_remote, i, lane, both, zero);
        else p1_mma<1>(acc, a, sbase, empty_remote, i, lane, true, zero);
        TRACE(WG, i, 4);
        uint32_t step;
        asm volatile("ld.shared.v2.u32 {%0, %1}, [%2];\n" : "=r"(step), "=r"(more) : "r"(sbase + P1_OFF_TILE + (i & 3) * 16) : "memory");
        uint8_t* hp = hp0 + (step ^ blk);
        if (i < 2 || more != 3) { LAG_HERE(4); }
        if (!(more >> WG & 1) && lane == 0) asm volatile("red.relaxed.gpu.global.add.u32 [%0], 1;\n" ::"l"(g_prog[CNT_LAST]) : "memory");
        p1_epilogue(acc, sc2, ssq, hp, zero);
        if (lane == 0) mbar_arrive(bar_pace);
        if (more & 4) {
            asm volatile("fence.proxy.async.global;\n" ::: "memory");
            bar_arrive(8, 288);
            bar_arrive(9, 288);
        }
        if (!(more >> WG & 1)) break;
    }
    TSTAMP(0, 21);
    if (WG == 0 && both) bar_sync(1, 256);
#pragma unroll
    for (int r = 0; r < 4; r++) {
        ssq[r] += __shfl_xor_sync(0xffffffffu, ssq[r], 1);
        ssq[r] += __shfl_xor_sync(0xffffffffu, ssq[r], 2);
    }
    const float t = q == 0 ? ssq[0] : q == 1 ? ssq[1] : q == 2 ? ssq[2] : ssq[3];
    atomicAdd(&g_sq[cb * 64 + (q >> 1) * 64 + w * 16 + (q & 1) * 8 + g], (1ull << 56) + __float2ull_rn(fminf(t, 0x1p19f) * 0x1p32f));
    asm volatile("fence.proxy.async.global;\n" ::: "memory");
    bar_arrive(3, 288);
    asm volatile("barrier.cluster.arrive.relaxed.aligned;\n" ::: "memory");
    return WG ? more & 1 : both;
}

__device__ __forceinline__ void p2_init(uint32_t sbase);
template <int ROLE>
__device__ __forceinline__ bool pass1(const CUtensorMap& wmap, const __nv_bfloat16* __restrict__ x, const __nv_bfloat16* __restrict__ dw,
                                      const __nv_bfloat16* __restrict__ w2, const __nv_bfloat16* __restrict__ grn_b, uint32_t sbase,
                                      int warp, int lane, int zero) {
    const uint32_t bar_full = sbase + P1_OFF_BAR, bar_empty = bar_full + P1_NST * 8, bar_w = bar_empty + P1_NST * 8;
    const uint32_t rank = cluster_rank();
    const int cig = blockIdx.x % GRP_CTAS;

    TSTAMP(0, 0);
    TRACEW(110 + warp, 0);
    const uint32_t bar_pace = bar_w + 32, bar_xfull = bar_pace + 32, bar_xempty = bar_xfull + 8, bar_done = bar_xfull + 16;
    const uint32_t s_side = bar_done + 12;
    const uint32_t s_item = sbase + P1_OFF_TILE + 64, s_cl = sbase + OFF_PRE + C_DIM * 4 + 8;
    auto ln_place = [](int q, unsigned tag) { return ln_tile(q >> 2, page_bit(ln_page(q >> 2), tag)) ^ ln_rows(q & 2) ^ (q & 1) * 0x90; };
    const int first = blockIdx.x / GRP_CTAS;

    if (ROLE == 2) {
        reg_dec<32>();
        asm volatile("barrier.cluster.arrive.relaxed.aligned;\n" ::: "memory");
        asm volatile("barrier.cluster.wait.aligned;\n" ::: "memory");
        LAG_HERE(0);
        if (warp == 12) {
            int t = first, sent = 0;
            const unsigned tag = 2 * __ldcg(&g_epoch) + 2;
            const uint32_t rbase = mapa(sbase, lane & 1);
#pragma unroll 1
            for (int i = 0; t < NT128; i++) {
                const int round = t / LN_RING, slot = t - round * LN_RING;
                constexpr unsigned LIM = (NT128 - P1_SPLIT - NGRP) / 2;
                unsigned* cnt = &g_flag[LN_RING + (cig >> 1)][0][0];
                const int page = lane & 1 ? ln_page(t) : t >> 2;
                unsigned v, sd, u = 0;
                do {
                    asm volatile("ld.relaxed.gpu.global.u32 %0, [%1];\n" : "=r"(v) : "l"(lane & 2 ? &g_page[page] : cnt + (lane & 1) * 8) : "memory");
                    if ((lane & 2) && page < H_FIXED) v = tag;
                    SAFE_BREAK;
                } while (__any_sync(0xffffffffu, (lane & 2) && (v & ~1u) != tag));
                asm volatile("ld.volatile.shared.u32 %0, [%1];\n" : "=r"(sd) : "r"(s_side) : "memory");
                if (__shfl_sync(0xffffffffu, v, sd) > __shfl_sync(0xffffffffu, v, sd ^ 1) + 4) sd ^= 1;
                unsigned b = __shfl_sync(0xffffffffu, v, sd ^ 1);
                const bool draw = rank == 0 && lane == 0 && t < NT128 - P1_SPLIT;
                if (draw) u = atomicAdd(cnt + sd * 8, 1u);
                flag_wait<true>(&g_flag[slot][0][0], 4 * round + 4);
                TRACEW(i, 2);
                asm volatile("fence.proxy.async.global;\n" ::: "memory");
                int next = NT128, more = 0;
                if (draw) {
                    if (u >= LIM) { sd ^= 1; b = u; u = atomicAdd(cnt + sd * 8, 1u); }
                    next = u < LIM ? NGRP + 2 * u + sd : NT128 - P1_SPLIT + atomicAdd(&g_flag[LN_RING + 3 + (cig >> 1)][first & 1][0], 1u);
                    more = u < LIM ? 3 : next < NT128;
                    if (!sent && min(u, b) >= (NT_EARLY - NGRP) / 2) { sent = 1; more += 4; }
                }
                next = __shfl_sync(0xffffffffu, next, 0);
                more = __shfl_sync(0xffffffffu, more, 0);
                const uint32_t ht = h_tile(t, __shfl_sync(0xffffffffu, v, 2));
                const uint32_t src = ln_tile(t, __shfl_sync(0xffffffffu, v, 3)) ^ ln_rows(2 * rank);
#pragma unroll 1
                for (int h = 0; h < P1_NST; h++) {
                    mbar_wait(bar_empty + h * 8, i & 1);
                    if (h == 0) TRACEW(i, 4);
                    if (h == 5) TRACEW(i, 5);
                    if (elect_one()) {
                        mbar_expect_tx(bar_full + h * 8, h ? P1_SLOT : P1_SLOT + 16);
#pragma unroll
                        for (int e = 0; e < 2; e++)
                            bulk_g2s_mc(sbase + h * P1_SLOT + (2 * rank + e) * 4096, h_base() + ((src ^ ln_rows(e)) + ln_block(h)), 4096, bar_full + h * 8, (uint16_t)3);
                    }
                    __syncwarp();
                    if (h == 0 && rank == 0 && lane < 2)
                        asm volatile("st.async.shared::cluster.mbarrier::complete_tx::bytes.v4.u32 [%0], {%1, %2, %3, %3}, [%4];\n"
                                     ::"r"(rbase + P1_OFF_TILE + (i & 3) * 16), "r"(ht), "r"(more), "r"(next),
                                       "r"(rbase + P1_OFF_BAR) : "memory");
                }
                t = next;
                if (rank != 0) {
                    mbar_wait(bar_full, i & 1);
                    asm volatile("ld.shared.u32 %0, [%1];\n" : "=r"(t) : "r"(sbase + P1_OFF_TILE + (i & 3) * 16 + 8) : "memory");
                }
            }
        } else if (warp == 13) {
            const unsigned tag = 2 * __ldcg(&g_epoch) + 2;
            int u = -1, side = 0;
            auto item = [&](int k) {
                if (k < LN_SW / LN_STEP) return (int)blockIdx.x + k * NUM_CTAS;
                while (u < 0) {
                    asm volatile("ld.volatile.shared.u32 %0, [%1];\n" : "=r"(u) : "r"(s_cl) : "memory");
                    side = u & 1;
                    if (u >= 0) u = (u & ~1) + rank;
                    SAFE_BREAK;
                }
                const int v = u + (k - LN_SW / LN_STEP) * (NUM_CTAS / 2);
                return 4 * LN_SW + (v >> 2) * 8 + side * 4 + (v & 3);
            };
#pragma unroll 1
            for (int k = 1;; k++) {
                const int q = item(k), round = q / (4 * LN_RING), slot = (q >> 2) - round * LN_RING;
                mbar_wait(bar_xempty, ~k & 1);
                if (elect_one()) {
                    mbar_expect_tx(bar_xfull, P1_X);
                    bulk_g2s(sbase + P1_OFF_X, reinterpret_cast<const uint8_t*>(x) + (size_t)q * P1_X, P1_X, bar_xfull);
                }
                __syncwarp();
                const uint32_t place = ln_place(q, tag), more = k < LN_SW / LN_STEP || item(k + 1) < 4 * NT128;
                const uint32_t off = flag_wait<false>(&g_flag[slot][1][0], round * (GRP_CTAS / 2));
                if (elect_one()) {
                    asm volatile("st.shared.v4.u32 [%0], {%1, %2, %3, %4};\n" ::"r"(s_item + (k & 1) * 16), "r"(off), "r"(place), "r"(slot), "r"(more) : "memory");
                    mbar_arrive(bar_xfull);
                }
                __syncwarp();
                if (!more) break;
            }
        } else if (warp == 15) {
            int t = first;
            if (rank == 1 && lane == 0) mbar_arrive(bar_empty);
#pragma unroll 1
            for (int i = 0; rank == 1 && t < NT128; i++) {
#pragma unroll 1
                for (int h = 0; h < P1_NST; h++) mbar_wait(bar_full + h * 8, i & 1);
                if (lane == 0) asm volatile("red.relaxed.gpu.global.add.u32 [%0], 1;\n" ::"l"(&g_flag[t % LN_RING][1][0]) : "memory");
                asm volatile("ld.shared.u32 %0, [%1];\n" : "=r"(t) : "r"(sbase + P1_OFF_TILE + (i & 3) * 16 + 8) : "memory");
                if (lane == 0) mbar_arrive(bar_empty);
                TRACEW(i, 3);
            }
            if (rank == 0) {
                {
                    const int me = blockIdx.x >> 1;
                    const int page = lane < 2 ? 0 : H_FIXED + me + (lane / 2 - 1) * (NUM_CTAS / 2);
                    mbar_wait(bar_full, 0);
                    if (page < H_PAGES) h_cell(page, me)[(lane & 1) * 1024] = 0;
                    __syncwarp();
                    if (lane == 0) {
                        const unsigned tag = 2 * __ldcg(&g_epoch) + 2;
                        const unsigned side = near_half(h_cell(0, me), 5);
                        asm volatile("st.volatile.shared.u32 [%0], %1;\n" ::"r"(s_side), "r"(side) : "memory");
                        const unsigned u = atomicAdd(reinterpret_cast<unsigned*>(g_sums) + C_DIM + 64 + side, 1u);
                        const unsigned cl = u < NUM_CTAS / 4 ? 2 * u + side : NUM_CTAS - 2 - 2 * u + (side ^ 1);
#pragma unroll
                        for (int r = 0; r < 2; r++) asm volatile("st.shared::cluster.u32 [%0], %1;\n" ::"r"(mapa(s_cl, r)), "r"(cl) : "memory");
#pragma unroll 1
                        for (int p = H_FIXED + me; p < H_PAGES; p += NUM_CTAS / 2)
                            asm volatile("st.relaxed.gpu.global.u32 [%0], %1;\n" ::"l"(&g_page[p]), "r"(tag + (near_half(h_cell(p, me), p < H_FIXED + NUM_CTAS / 2 ? 2 : 3) ^ side)) : "memory");
                    }
                    __syncwarp();
                }
                TRACEW(110 + warp, 3);
                mbar_wait(bar_full, 1);
                float* sums = g_sums;
                unsigned* flag = reinterpret_cast<unsigned*>(sums + C_DIM);
                if (blockIdx.x == 0) reinterpret_cast<uint2*>(g_half)[lane] = make_uint2(0, 0);
                if (blockIdx.x == 2 && lane < NUM_CNT) g_prog[lane][0] = 0;
                if (blockIdx.x < 96) g_redo[blockIdx.x * 16 + lane] = 0.f;
                float gs = 0.f;
#pragma unroll 1
                for (int pass = 0; pass < 2; pass++) {
                    float mx = 0.f;
#pragma unroll 1
                    for (int it = (blockIdx.x + zero) / GRP_CTAS; it < 96; it += NGRP) {
                        const int nb = it % 12, k0 = (cig * 4 + it / 12) * 64 + (lane >> 2);
                        const uint32_t sc = mapa(sbase + P1_OFF_EX + (k0 & 255) * 4, it / 48);
                        uint32_t* dst = reinterpret_cast<uint32_t*>(g_w2img[0]) + (k0 >> 4) * 3072 + nb * 256 + lane;
                        float bs[8] = {};
#pragma unroll 1
                        for (int c = 0; c < 8; c++) {
                            const uint4 u = __ldg(reinterpret_cast<const uint4*>(w2 + (size_t)(k0 + c * 8) * C_DIM + nb * 32) + (lane & 3));
                            const float b = __bfloat162float(grn_b[k0 + c * 8]);
                            float t;
                            asm volatile("ld.shared::cluster.f32 %0, [%1];\n" : "=f"(t) : "r"(sc + c * 32) : "memory");
                            if (nb == 0) g_scale[k0 + c * 8] = t;
#pragma unroll
                            for (int j = 0; j < 4; j++) {
                                const uint32_t v = j == 0 ? u.x : j == 1 ? u.y : j == 2 ? u.z : u.w;
                                mx = fmaxf(mx, fmaxf(fabsf(bf_lo(v)), fabsf(bf_hi(v))) * t);
                                if (pass) {
                                    bs[2 * j] = fmaf(b, bf_lo(v), bs[2 * j]);
                                    bs[2 * j + 1] = fmaf(b, bf_hi(v), bs[2 * j + 1]);
                                    uint32_t h = pack_f16(bf_lo(v) * t * gs, bf_hi(v) * t * gs);
                                    asm volatile("movmatrix.sync.aligned.m8n8.trans.b16 %0, %0;\n" : "+r"(h));
                                    dst[(c >> 1) * 3072 + (c & 1) * 32 + j * 64] = h;
                                }
                            }
                        }
                        if (pass) {
#pragma unroll
                            for (int j = 0; j < 8; j++) {
#pragma unroll
                                for (int o = 4; o < 32; o <<= 1) bs[j] += __shfl_xor_sync(0xffffffffu, bs[j], o);
                                if (lane >> 2 == j) atomicAdd(&sums[nb * 32 + (j >> 1) * 8 + (lane & 3) * 2 + (j & 1)], bs[j]);
                            }
                        }
                    }
                    if (!pass) {
                        const uint32_t m = __reduce_max_sync(0xffffffffu, __float_as_uint(mx));
                        __threadfence();
                        __syncwarp();
                        if (lane == 0) {
                            atomicMax(flag, m);
                            asm volatile("red.release.gpu.global.add.u32 [%0], 1;\n" ::"l"(flag + 32) : "memory");
                        }
                        flag_wait<true>(flag + 32, NUM_CTAS / 2);
                        gs = w2_scale(__ldcg(flag));
                    }
                }
                asm volatile("fence.proxy.async.global;\nfence.acq_rel.gpu;\n" ::: "memory");
                __syncwarp();
                if (lane == 0) asm volatile("red.relaxed.gpu.global.add.u32 [%0], 1;\n" ::"l"(g_prog[CNT_IMG0]) : "memory");
            }
        } else if (warp == 14) {
#pragma unroll 1
            for (uint32_t k = 0, more = 1; more; k++) {
                uint32_t slot;
                mbar_wait(bar_done, k & 1);
                asm volatile("ld.shared.v2.u32 {%0, %1}, [%2];\n" : "=r"(slot), "=r"(more) : "r"(s_item + (k & 1) * 16 + 8) : "memory");
                if (lane == 0) mbar_arrive(bar_xfull + (slot & zero));
                TRACEW(k, 0);
                asm volatile("fence.proxy.async.global;\n" ::: "memory");
                if (elect_one()) asm volatile("red.release.gpu.global.add.u32 [%0], 1;\n" ::"l"(&g_flag[slot][0][0]) : "memory");
                __syncwarp();
                TRACEW(k, 1);
            }
            if (lane == 0) p2_init(sbase);
#pragma unroll 1
            for (int i = CNT_EARLY; i >= CNT_H; i--) {
                bar_sync(i == CNT_EARLY ? 8 : 3, 288);
                asm volatile("fence.proxy.async.global;\n" ::: "memory");
                if (lane == 0) asm volatile("red.release.gpu.global.add.u32 [%0], 1;\n" ::"l"(&g_prog[i][0]) : "memory");
                __syncwarp();
            }
        }
        __syncwarp();
        asm volatile("barrier.cluster.arrive.relaxed.aligned;\n" ::: "memory");
        return false;
    } else if (ROLE == 1) {
        reg_dec<96>();
        asm volatile("barrier.cluster.arrive.relaxed.aligned;\n" ::: "memory");
        {
            const int l8 = lane & 7;
            uint32_t d[6][4];
            const int n = perm32(2 * ((warp - 8) * 4 + (lane >> 3)));
            const uint32_t dst0 = n * 128 + ((l8 ^ (n & 7)) << 4);
            const uint32_t src = sbase + P1_OFF_X + ((warp - 8) * 8 + (lane >> 3)) * (C_DIM * 2) + l8 * 16;
            uint32_t off = 1, place = ln_place(blockIdx.x, 0), more = 1;
            LAG_HERE(0);
#pragma unroll 1
            for (int i = 0; more; i++) {
                TRACE(2, i, 0);
#pragma unroll 1
                for (int ps = i == 0 ? -2 : 0; ps < 2; ps += ps < 0 ? 2 : 1) {
                    if (ps == 0) {
                        uint32_t slot;
                        if (i == 0) asm volatile("barrier.cluster.wait.aligned;\n" ::: "memory");
                        mbar_wait(bar_xfull, i & 1);
                        asm volatile("ld.shared.v4.u32 {%0, %1, %2, %3}, [%4];\n" : "=r"(off), "=r"(place), "=r"(slot), "=r"(more) : "r"(s_item + (i & 1) * 16) : "memory");
                    }
                    if (ps == 0) TRACE(2, i, 1);
                    if (i == 0) {
#pragma unroll
                        for (int j = 0; j < 6; j++)
                            asm volatile("ld.shared.v4.u32 {%0,%1,%2,%3}, [%4];\n"
                                         : "=r"(d[j][0]), "=r"(d[j][1]), "=r"(d[j][2]), "=r"(d[j][3]) : "r"(sbase + P1_OFF_DW + j * 128 + l8 * 16) : "memory");
                    }
                    uint32_t v[6][4];
#pragma unroll
                    for (int j = 0; j < 6; j++)
                        asm volatile("ld.shared.v4.u32 {%0,%1,%2,%3}, [%4];\n"
                                     : "=r"(v[j][0]), "=r"(v[j][1]), "=r"(v[j][2]), "=r"(v[j][3]) : "r"(src + (ps & 1) * (4 * C_DIM * 2) + j * 128) : "memory");
                    ln_row(v, d, bar_pace + (warp - 8) * 8, off, zero, ps == 1 && lane == 0 ? bar_xempty : 0);
                    uint8_t* dst = h_base() + (place ^ dst0 ^ ln_rows(ps & 1));
#pragma unroll
                    for (int j = 0; j < 6; j++)
                        asm volatile("st.global.v4.u32 [%0], {%1,%2,%3,%4};\n" ::"l"(dst + ln_block(j)), "r"(v[j][0]), "r"(v[j][1]), "r"(v[j][2]), "r"(v[j][3]) : "memory");
                    TRACE(2, i, 3 + (ps & 1));
                }
                asm volatile("fence.proxy.async.global;\nfence.acq_rel.cta;\n" ::: "memory");
                __syncwarp();
                if (lane == 0) mbar_arrive(bar_done);
                TRACE(2, i, 5);
                TRACE(2, i, 2);
            }
        }
        __syncwarp();
        asm volatile("barrier.cluster.arrive.relaxed.aligned;\n" ::: "memory");
        return false;
    } else {
        const int wg = warp >> 2, w = warp & 3;
        auto load_w = [&](int i0, int i1) {
#pragma unroll 1
            for (int i = i0; i < i1; i++) {
                if (!(i & 1)) mbar_expect_tx(bar_w + (i >> 1) * 8, P1_W);
                tma2(sbase + (i & 2) * P1_W + (i >> 2) * P1_W + (i & 1) * (P1_W / 2), &wmap, cig * 256 + ((i >> 1) ^ (first & 1) * 2) * 64, (i & 1) * 192, bar_w + (i >> 1) * 8);
            }
        };
        if (warp == 4 && elect_one()) {
            mbar_init(bar_xfull, 3);
#pragma unroll
            for (int i = 0; i < 4; i++) mbar_init(bar_w + i * 8, 1);
            asm volatile("fence.mbarrier_init.release.cluster;\n" ::: "memory");
            mbar_expect_tx(bar_xfull, P1_X + C_DIM * 2);
            bulk_g2s(sbase + P1_OFF_X, reinterpret_cast<const uint8_t*>(x) + (size_t)blockIdx.x * P1_X, P1_X, bar_xfull);
            bulk_g2s(sbase + P1_OFF_DW, dw, C_DIM * 2, bar_xfull);
            load_w(0, 4);
            asm volatile("st.shared.v4.u32 [%0], {1, %1, %2, 1};\n" ::"r"(s_item), "r"(ln_place(blockIdx.x, 0)), "r"(blockIdx.x >> 2) : "memory");
            mbar_arrive(bar_xfull);
            mbar_arrive(bar_xfull);
        }
        if (warp == 5 && elect_one()) {
#pragma unroll
            for (int i = 0; i < P1_NST; i++) {
                mbar_init(bar_full + i * 8, 1);
                mbar_init(bar_empty + i * 8, i ? 8 : 8 + rank);
                if (i < 4) mbar_init(bar_pace + i * 8, 1);
            }
            mbar_init(bar_xempty, 4);
            mbar_init(bar_done, 4);
            asm volatile("st.shared.u32 [%0], %1;\n" ::"r"(s_side), "r"(first & 1) : "memory");
            asm volatile("st.shared.u32 [%0], -1;\n" ::"r"(s_cl) : "memory");
            asm volatile("fence.mbarrier_init.release.cluster;\n" ::: "memory");
        }
        __syncwarp();
        asm volatile("barrier.cluster.arrive.relaxed.aligned;\n" ::: "memory");
        reg_inc<192>();
        TRACEW(110 + warp, 1);
        LAG_HERE(0);
        uint32_t a[24][4];
        const uint32_t src = sbase + wg * P1_W + ((lane >> 4) * 8 + (lane & 7)) * 128 + (((2 * w + ((lane >> 3) & 1)) ^ (lane & 7)) << 4);
        const uint32_t s_ex = sbase + P1_OFF_EX + ((wg ^ (first & 1)) * 128 + w * 16 + (lane >> 2)) * 4;
        uint32_t sc2[2], ex[2];
        if (wg == 1) bar_arrive(1, 256);
#pragma unroll 1
        for (int it = 0; it < 2; it++) {
          if (it != wg) asm volatile("barrier.cluster.wait.aligned;\n" ::: "memory");
          if (it < wg) {
#pragma unroll 1
              for (int n = 0; n < 64 && !mbar_test(bar_xfull, 0); n++) __nanosleep(40);
              if (w == 0 && elect_one()) load_w(4, 8);
              __syncwarp();
          }
          if (it || wg == 0) {
            float t[2] = {0.f, 0.f};
            if (it) {
                TRACEW(110 + warp, 2);
                mbar_wait(bar_w + wg * 16, 0);
            }
            TRACEW(110 + warp, 5);
#pragma unroll
            for (int k = 0; k < 24; k++) ldsm4t(a[k], src + k * 2048);
            TRACEW(110 + warp, 6);
            p1_squares(a, t);
            sc2[0] = p1_exponents(t, ex, s_ex, lane);
            if (it && lane < 6) mbar_arrive_cluster(mapa(bar_empty, lane & 1) + (wg * 3 + (lane >> 1)) * 8 + (sc2[0] & zero));
            p1_convert<24>(a, a, ex);
          }
          if (it || wg == 1) {
            float t[2] = {0.f, 0.f};
            TRACEW(100 + warp, 0);
            if (it) mbar_wait(bar_w + wg * 16 + 8, 0);
            TRACEW(100 + warp, 1);
            uint32_t v[8][4], o[8][4];
#pragma unroll 1
            for (int j = 0; j <= 2 * it; j++) {
#pragma unroll
                for (int k = 0; k < 8; k++) ldsm4t(v[k], src + P1_OFF_W + (8 * j + k) * 2048);
                p1_squares(v, t);
            }
            sc2[1] = p1_exponents(t, ex, s_ex + 256, lane);
#pragma unroll 1
            for (int j = 2 * it; j >= 0; j--) {
                p1_convert<8>(o, v, ex);
#pragma unroll
                for (int k = 0; k < 8; k++) {
                    if (j) ldsm4t(v[k], src + P1_OFF_W + (8 * j - 8 + k) * 2048);
                    if (it) asm volatile("stmatrix.sync.aligned.m8n8.x4.trans.shared.b16 [%0], {%1,%2,%3,%4};\n"
                                         ::"r"(src + P1_OFF_W + (8 * j + k) * 2048), "r"(o[k][0]), "r"(o[k][1]), "r"(o[k][2]), "r"(o[k][3]) : "memory");
                }
            }
          }
        }
        asm volatile("fence.proxy.async.shared::cta;\n" ::: "memory");
        TRACEW(110 + warp, 7);
        bar_sync(6 + wg, 128);
        const bool early = p1_consumer(a, sc2, sbase, wg, w, lane, zero);
        TSTAMP(0, 30);
        return early;
    }
}

constexpr int P2_B = 24576, P2_NB = 4;
constexpr int P2_A = 3072, P2_NA = 8;
constexpr int P2_XROW = C_DIM * 2;
constexpr int P2_OFF_A = P2_B * P2_NB;
constexpr int P2_OFF_X = P2_OFF_A + 3 * P2_NA * P2_A + 128;
constexpr int P2_LHALF = 2 * P2_NA * P2_A + 64;
constexpr int P2_XHALF = 32 * P2_XROW + 64;
constexpr int P2_OFF_GRN = P2_OFF_X + 64 * P2_XROW + 128;
constexpr int P2_OFF_BIAS = P2_OFF_GRN + HID * 2;
constexpr int P2_OFF_RED = P2_OFF_BIAS + C_DIM * 4;
constexpr int P2_OFF_BAR = P2_OFF_RED + 192;
constexpr int P2_SMEM = P2_OFF_BAR + (2 * P2_NB + 6 * P2_NA + 7) * 8;
constexpr int P2_S1 = 16, P2_S2 = 32;
constexpr int P2_NCL = NUM_CTAS / 2, P2_ITEMS = NT128 / P2_NCL, P2_SHARED = NT128 - P2_ITEMS * P2_NCL;
constexpr int P2_NPOS = 6 * 48 + P2_S1;
constexpr int P2_RAW = 16;
constexpr int P2_XC = 8 * P2_XROW;
constexpr int P2_T0 = 5;
constexpr int P2_TL = 8;
constexpr int P2_XP0 = 30;
constexpr int P2_XPN = 13;
constexpr int P2_XPD = 3;
constexpr int P2_AH = 2;
__device__ __forceinline__ int p2_start(int n) { return n < 0 ? 0 : n / 3 * 48 + (n % 3 == 1 ? P2_S1 : n % 3 * (P2_S2 / 2)); }
__device__ __forceinline__ int p2_tile(int cl, int n) {
    return n == 0 ? NT_EARLY - P2_NCL + cl : n < 0 ? NT_EARLY + (cl >> 2) * 2 + (cl & 1) : cl + P2_NCL * (n - 1);
}

__device__ __forceinline__ void p2_epilogue(uint32_t (&acc0)[48], uint32_t (&acc1)[48], uint32_t up, uint32_t sx, uint32_t sb, uint8_t* so, int zero) {
    uint32_t v[12][3][4];
    auto load = [&](int t, int j) {
        if (t >= 12) return;
        uint32_t (&w)[4] = v[t][j];
        asm volatile("ld.shared.v4.u32 {%0,%1,%2,%3}, [%4];\n" : "=r"(w[0]), "=r"(w[1]), "=r"(w[2]), "=r"(w[3])
                     : "r"((j ? sx + (j - 1) * 4 * P2_XROW : sb) + t * 64) : "memory");
    };
    auto store = [&](int t, int r) {
        const uint32_t* w = (t < 6 ? acc0 : acc1) + 8 * (t % 6) + 4 * r;
        asm volatile("st.v4.u32 [%4], {%0,%1,%2,%3};\n" ::"r"(w[0]), "r"(w[1]), "r"(w[2]), "r"(w[3]), "l"(so + t * 64 + r * 4 * P2_XROW) : "memory");
    };
#pragma unroll
    for (int j = 0; j < 3; j++) load(0, j);
#pragma unroll
    for (int t = 0; t < 12; t++) {
        load(t + 1, 1);
        load(t + 1, 2);
        load(t + 1, 0);
        uint32_t* acc = (t < 6 ? acc0 : acc1) + 8 * (t % 6);
        uint32_t y[8];
#pragma unroll
        for (int e = 0; e < 8; e++) {
            y[e] = h2_add(acc[e], v[t][0][e >> 1]);
            y[e] = pack_bf16(h_lo(y[e]), h_hi(y[e]));
        }
#pragma unroll
        for (int e = 0; e < 8; e++) acc[(e & 1) * 4 + (e >> 1)] = bf2_fma(y[e], up, v[t][1 + (e & 1)][e >> 1]);
        store(t, 0);
        store(t, 1);
        if (t & 1) sched_break(zero);
    }
}

__device__ __forceinline__ void p2_unpack(uint32_t (&u)[4], uint32_t o1, uint32_t o2, uint32_t o3) {
    u[2] = o1 & ~SPARE;
    u[1] = o2 & ~SPARE;
    u[3] = o3 & ~SPARE;
    const uint32_t t = bitsel(prmt(o1, o2, 0x6341), prmt(o1, o3, 0x6240) << 3, 0x38383838u);
    u[0] = bitsel(t, prmt(o2, o3, 0x7351) << 1, 0x80808080u) & ~SPARE;
}

__device__ __forceinline__ void p2_redo_sums(int warp, int lane) {
    flag_wait<true>(g_prog[CNT_H], NUM_CTAS);
#pragma unroll 1
    for (int s = warp; s < 96; s += 12) {
        float t[2] = {0.f, 0.f};
#pragma unroll 1
        for (int tile = blockIdx.x; tile < 2 * NT128; tile += NUM_CTAS) {
            const uint32_t* p = reinterpret_cast<const uint32_t*>(h_base() + (h_tile(tile >> 1) ^ h_block(s >> 1, tile & 1)) + (s & 1) * 1536) + lane * 4;
#pragma unroll
            for (int j = 0; j < 4; j++) {
                uint32_t u[4];
                p2_unpack(u, __ldcg(p + j), __ldcg(p + j + 128), __ldcg(p + j + 256));
#pragma unroll
                for (int c = 0; c < 4; c++) t[c >> 1] += h_lo(u[c]) * h_lo(u[c]) + h_hi(u[c]) * h_hi(u[c]);
            }
        }
#pragma unroll
        for (int r = 0; r < 2; r++) {
            const int ch = s * 16 + r * 8 + (lane >> 2);
            atomicAdd(&g_redo[ch], t[r] * (UNCHOP * UNCHOP));
        }
    }
    __threadfence();
    __syncwarp();
    if (lane == 0) asm volatile("red.release.gpu.global.add.u32 [%0], 1;\n" ::"l"(g_prog[CNT_REDO]) : "memory");
    flag_wait<true>(g_prog[CNT_REDO], 12 * NUM_CTAS);
}

static_assert(P2_OFF_GRN >= P1_OFF_X + P1_X && P1_OFF_BAR >= P2_SMEM, "barriers and tables keep their memory");
__device__ __forceinline__ void p2_init(uint32_t sbase) {
    const uint32_t bar = sbase + P2_OFF_BAR;
#pragma unroll 1
    for (int i = 0; i < 2 * P2_NB + 6 * P2_NA + 6; i++) {
        const int j = i - 2 * P2_NB;
        mbar_init(bar + i * 8, j < -P2_NB ? 1 : j < 0 ? 24 : j < 3 * P2_NA ? 1 : j >= 6 * P2_NA && j < 6 * P2_NA + 3 ? 2 : 4);
    }
    asm volatile("st.shared.v2.u32 [%0], {0, 0};\n" ::"r"(bar + (2 * P2_NB + 6 * P2_NA + 6) * 8) : "memory");
    asm volatile("fence.mbarrier_init.release.cluster;\nfence.acq_rel.cta;\n" ::: "memory");
}
template <int ROLE>
__device__ __forceinline__ void pass2(const __nv_bfloat16* __restrict__ x, const __nv_bfloat16* __restrict__ grn_g, __nv_bfloat16* __restrict__ out,
                                      uint8_t* smem, uint32_t sbase, bool early, int zero) {
    const uint32_t bar_bfull = sbase + P2_OFF_BAR, bar_bempty = bar_bfull + P2_NB * 8;
    const uint32_t bar_afull = bar_bempty + P2_NB * 8, bar_aempty = bar_afull + 3 * P2_NA * 8;
    const uint32_t bar_xfull = bar_aempty + 3 * P2_NA * 8, bar_oready = bar_xfull + 24, s_pos = bar_oready + 24;
    int tid;
    asm volatile("mov.u32 %0, %%tid.x;\n" : "=r"(tid));
    const int warp = __shfl_sync(0xffffffffu, tid >> 5, 0), lane = tid & 31;
    const uint32_t rank = cluster_rank();
    int cl, pair, half, fin, k0;
    auto join = [&]() {
        asm volatile("barrier.cluster.wait.aligned;\nld.shared.u32 %0, [%1];\n" : "=r"(cl) : "r"(sbase + OFF_PRE + C_DIM * 4 + 8) : "memory");
        cl = __shfl_sync(0xffffffffu, cl, 0);
        pair = (cl >> 2) * 2 + (cl & 1);
        half = pair < P2_SHARED;
        fin = half && (cl & 2);
        k0 = (pair + 3 * ((cl >> 1) & 1)) % 6 * 8;
    };
    auto wait_pos = [&](int target) {
        int v;
        while (true) {
            asm volatile("ld.volatile.shared.u32 %0, [%1];\n" : "=r"(v) : "r"(s_pos) : "memory");
            if (v >= target) break;
            SAFE_BREAK;
            __nanosleep(100);
        }
    };

    TSTAMP(1, 0);
    LAG_HERE(1);
    if (ROLE == 2) {
        if (warp != 14) flag_wait<true>(g_prog[CNT_IMG0], P2_NCL);
        if (warp == 15) {
            float* pre = reinterpret_cast<float*>(smem + OFF_PRE);
            const float gs = w2_scale(__float_as_uint(__ldcg(&g_sums[C_DIM])));
            float mb = 0.f;
#pragma unroll 1
            for (int i = lane; i < C_DIM; i += 32) {
                pre[i] = __ldcg(&g_sums[i]) * gs;
                mb = fmaxf(mb, fabsf(pre[i]));
            }
            pre[C_DIM] = gs;
            pre[C_DIM + 1] = __uint_as_float(__reduce_max_sync(0xffffffffu, __float_as_uint(mb)));
            bar_sync(9, 288);
            flag_wait<false>(g_prog[CNT_LAST], NUM_CTAS * 8);
            bar_arrive(5, 416);
        }
        join();
        asm volatile("fence.proxy.async;\n" ::: "memory");
        LAG_HERE(2);
        if (warp == 12) {
            const uint8_t* wsrc = reinterpret_cast<const uint8_t*>(g_w2img) + rank * (P2_B / 2);
            int kb = k0;
#pragma unroll 1
            for (int p = 0; p < P2_NPOS; p++) {
                const int st = p & 3;
                if (p == P2_RAW) {
                    flag_wait<true>(g_prog[CNT_IMG1], NUM_CTAS);
                    asm volatile("fence.proxy.async.global;\n" ::: "memory");
                    wsrc += sizeof(g_w2img[0]);
                }
                const int idle = (p < P2_S1 || p >= 6 * 48) + (p < P2_S2 ? !half || p >= 24 : p >= 5 * 48 + P2_S2);
                mbar_wait(bar_bempty + st * 8, (~p >> 2) & 1);
                TR2(3, p, 0);
                if (elect_one()) {
                    mbar_expect_tx(bar_bfull + st * 8, P2_B);
                    bulk_g2s_mc(sbase + st * P2_B + rank * (P2_B / 2), wsrc + kb * P2_B, P2_B / 2, bar_bfull + st * 8, (uint16_t)3);
                    asm volatile("st.volatile.shared.u32 [%0], %1;\n" ::"r"(s_pos), "r"(p) : "memory");
                    if (rank == 0) asm volatile("red.relaxed.gpu.global.add.u32 [%0], 1;\n" ::"l"(g_prog[CNT_POS]) : "memory");
                    if (idle) asm volatile("mbarrier.arrive.shared::cta.b64 _, [%0], %1;\n" ::"r"(bar_bempty + st * 8), "r"(8 * idle) : "memory");
                }
                __syncwarp();
                if (++kb == 48) kb = 0;
            }
            mbar_wait(bar_bempty, 1);
            if (lane == 0) mbar_arrive(bar_bfull);
        } else if (warp == 13) {
            const int w = lane % 3;
            const uint32_t dst0 = sbase + P2_OFF_A + w * P2_NA * P2_A;
            const uint32_t bf = bar_afull + w * P2_NA * 8, be = bar_aempty + w * P2_NA * 8;
            int n = (w == 2 && half ? -1 : w) - 3, left = 0, u = 0, c = 0;
            const uint8_t* const hb = h_base();
            uint32_t ht = 0;
            bool act = lane < 3;
            auto next = [&]() {
                n += 3;
                left = n >= P2_ITEMS ? -1 : n < 0 ? 24 : 48;
                u = (k0 + p2_start(n)) % 48;
                if (left > 0) ht = h_tile(p2_tile(cl, n));
            };
            next();
            flag_wait<true>(g_prog[CNT_EARLY], NUM_CTAS);
#pragma unroll 1
            for (int i = 3; i > 0; i--) {
                const int wi = i % 3;
                if (wi == 2) flag_wait<true>(g_prog[CNT_H], NUM_CTAS);
                asm volatile("fence.proxy.async.global;\n" ::: "memory");
                if (w == wi && lane < 24) {
                    mbar_expect_tx(bf + lane / 3 * 8, P2_A);
                    bulk_g2s(dst0 + lane / 3 * P2_A, hb + (ht ^ h_block(u + lane / 3, rank)), P2_A, bf + lane / 3 * 8);
                }
                __syncwarp();
            }
            c = 8;
            left -= 8;
            u += 8;
            if (u == 48) u = 0;
            while (__any_sync(0xffffffffu, act)) {
                if (left == 0) next();
                const bool ok = act && mbar_test(be + ((c - 1) & 7) * 8, (~c >> 3) & 1);
                if (ok) {
                    const int st = c & 7;
                    if (left > 0) {
                        mbar_expect_tx(bf + st * 8, P2_A);
                        bulk_g2s(dst0 + st * P2_A, hb + (ht ^ h_block(u, rank)), P2_A, bf + st * 8);
                    } else {
                        mbar_arrive(bf + st * 8);
                        act = false;
                    }
                    if (++u == 48) u = 0;
                    c++;
                    left--;
                }
                SAFE_BREAK;
                if (!__any_sync(0xffffffffu, ok)) __nanosleep(100);
            }
        } else if (warp == 14) {
            const uint32_t sx = sbase + P2_OFF_X;
            size_t o = 0;
            int wp = 0;
            uint32_t par = 0;
            if (fin) {
#pragma unroll 1
                for (int c = lane * 16; c < 64 * P2_XROW + 128; c += 512) asm volatile("st.shared.v4.u32 [%0], {0, 0, 0, 0};\n" ::"r"(sx + c) : "memory");
                __syncwarp();
            }
            wait_pos(6);
#pragma unroll 1
            for (int n = -half; n < P2_ITEMS; n++) {
                const int w = (n + 3) % 3, end = p2_start(n) + 48;
                const size_t on = (size_t)(2 * p2_tile(cl, n) + rank) * (64 * C_DIM * 2);
                const uint32_t xf = bar_xfull + w * 8;
                if (n < 2 || n > 12) { LAG_HERE(3); }
                bool st = n + half > 0;
                const bool ld = n < P2_ITEMS - 1 && !(n < 0 && fin);
                if (n == P2_ITEMS - 1 && lane == 0) {
                    mbar_expect_tx(xf, 64 * C_DIM * 2);
#pragma unroll 1
                    for (int c = 4; c < 12; c++) {
                        if (c >= 8) {
                            mbar_wait(bar_aempty + ((2 * c - 1) & 7) * 8, 1);
                            mbar_wait(bar_aempty + ((2 * c) & 7) * 8, 1);
                        }
                        bulk_g2s(sbase + P2_OFF_A + (c & 3) * P2_XC + (c < 8 ? P2_LHALF : 0), reinterpret_cast<const uint8_t*>(x) + on + (c & 7) * P2_XC, P2_XC, xf);
                    }
                    mbar_arrive(xf);
                }
                if (st) {
                    mbar_wait(bar_oready + wp * 8, (par >> wp) & 1);
                    par ^= 1u << wp;
                }
                if (lane == 0) {
                    if (n < P2_ITEMS - 1) mbar_expect_tx(xf, ld ? 64 * C_DIM * 2 : 0);
                    const int t0 = (n ? p2_start(n - 1) + 48 : P2_S2) + (n == P2_ITEMS - 1 ? P2_TL : P2_T0), dt = end - t0;
                    int t = st ? 16 * t0 : -4096;
                    if (n == 0 && half) {
                        if (fin) {
                            flag_wait<true>(&g_half[pair][rank], 1);
                            asm volatile("fence.proxy.async.global;\n" ::: "memory");
                        }
#pragma unroll 1
                        for (int c = 0; c < 2; c++) {
                            uint8_t* dst = reinterpret_cast<uint8_t*>(out) + o + c * 32 * P2_XROW;
                            if (!fin) bulk_s2g(dst, sx + c * P2_XHALF, 32 * P2_XROW);
                            else asm volatile("cp.reduce.async.bulk.global.shared::cta.bulk_group.add.noftz.bf16 [%0], [%1], %2;\n"
                                              ::"l"(dst), "r"(sx + c * P2_XHALF), "r"(32 * P2_XROW) : "memory");
                        }
                        asm volatile("cp.async.bulk.commit_group;\n" ::: "memory");
                        if (!fin) {
                            asm volatile("cp.async.bulk.wait_group 0;\nfence.proxy.async.global;\n" ::: "memory");
                            asm volatile("st.release.gpu.global.u32 [%0], 1;\n" ::"l"(&g_half[pair][rank]) : "memory");
                        }
                        st = false;
                    }
#pragma unroll 1
                    for (int c = 0; c < 64 * P2_XROW; c += P2_XC, t += 2 * dt) {
                        const uint32_t sp = sx + c + (c >= 32 * P2_XROW ? 64 : 0);
                        wait_pos(t >> 4);
                        if (st) bulk_s2g(reinterpret_cast<uint8_t*>(out) + o + c, sp, P2_XC);
                        asm volatile("cp.async.bulk.commit_group;\n" ::: "memory");
                        if (ld) {
                            wait_pos((t + dt) >> 4);
                            asm volatile("cp.async.bulk.wait_group.read 0;\n" ::: "memory");
                            bulk_g2s(sp, reinterpret_cast<const uint8_t*>(x) + on + c, P2_XC, xf);
                        }
                    }
                    if (rank == 0 && n > 0 && n < P2_ITEMS - 2) flag_wait<false>(g_prog[CNT_POS], P2_NCL * (end - 1));
                    if (n < P2_ITEMS - 1) mbar_arrive(xf);
                }
                __syncwarp();
                o = on;
                wp = w;
            }
            asm volatile("cp.async.bulk.wait_group.read 0;\n" ::: "memory");
        } else {
            if (blockIdx.x == 120) {
                wait_pos(P2_RAW);
                for (int i = lane; i < (LN_RING + 6) * 2; i += 32) (&g_flag[0][0][0])[i * 8] = 0;
                for (int i = lane; i < HID; i += 32) g_sq[i] = 0;
                for (int i = lane; i < 512; i += 32) g_sums[i] = 0.f;
                if (lane == 0) g_epoch++;
            }
            int t = 4 * P2_XP0;
#pragma unroll 1
            for (int n = 0; n < P2_ITEMS && lane == 0; n++) {
                const uint8_t* xn = reinterpret_cast<const uint8_t*>(x) + (size_t)(2 * p2_tile(cl, n) + rank) * (64 * C_DIM * 2);
#pragma unroll 1
                for (int c = 0; c < 16; c++, t += n < P2_XPN ? 4 : P2_XPD) {
                    wait_pos(t >> 2);
                    asm volatile("cp.async.bulk.prefetch.L2.global [%0], %1;\n" ::"l"(xn + c * (P2_XC / 2)), "r"(P2_XC / 2) : "memory");
                }
            }
        }
        __syncwarp();
        cluster_sync_relaxed();
    } else {
        const int wg = warp >> 2, w = warp & 3, q = lane & 3;
        const uint32_t af = bar_afull + wg * P2_NA * 8;
        const uint32_t s_a = sbase + P2_OFF_A + wg * P2_NA * P2_A + (lane >> 3) * 512 + (lane & 7) * 64 + ((w ^ ((lane & 7) >> 1)) << 4);
        uint32_t acc0[48], acc1[48], up;
        uint4 a[2][2];

        __nv_bfloat16 gg[4];
#pragma unroll
        for (int i = 0; i < 4; i++) gg[i] = grn_g[tid + 384 * i];
#pragma unroll 1
        for (int it = !early;; it++) {
            float* s_red = reinterpret_cast<float*>(smem + P2_OFF_RED);
            float gx[4], part = 0.f;
            if (it == 1) {
                TSTAMP(1, 27);
                bar_sync(5, 416);
            }
            unsigned long long v[4];
#pragma unroll
            for (int i = 0; i < 4; i++) gx[i] = __ldcg(&g_scale[tid + 384 * i]);
            while (true) {
#pragma unroll
                for (int i = 0; i < 4; i++) asm volatile("ld.relaxed.gpu.global.u64 %0, [%1];\n" : "=l"(v[i]) : "l"(&g_sq[tid + 384 * i]) : "memory");
                SAFE_BREAK;
                if (!it || !__any_sync(0xffffffffu, min(min(v[0], v[1]), min(v[2], v[3])) < (unsigned long long)NGRP << 56)) break;
            }
            TSTAMP(1, 1);
            const float bias = reinterpret_cast<const float*>(smem + OFF_PRE)[tid];
            const float2 pre = *reinterpret_cast<const float2*>(smem + OFF_PRE + C_DIM * 4);
            bool tiny = false;
#pragma unroll
            for (int i = 0; i < 4; i++) {
                const float t = it == 2 ? __ldcg(&g_redo[tid + 384 * i]) : __ull2float_rn(v[i] << 8) * 0x1p-40f;
                tiny |= t < M_TOTAL * 0x1p-19f;
                gx[i] *= gx[i] * t;
            }
            float mg = 0.f;
#pragma unroll
            for (int i = 0; i < 4; i++) {
                asm("sqrt.approx.f32 %0, %1;\n" : "=f"(gx[i]) : "f"(gx[i] * (HSCALE * HSCALE) + 1e-6f));
                part += gx[i];
                gx[i] *= __bfloat162float(gg[i]);
                mg = fmaxf(mg, fabsf(gx[i]));
            }
#pragma unroll
            for (int o = 16; o > 0; o >>= 1) part += __shfl_xor_sync(0xffffffffu, part, o);
            const uint32_t mgw = __reduce_max_sync(0xffffffffu, __float_as_uint(mg));
            TSTAMP(1, 26);
            if (lane == 0) *reinterpret_cast<float2*>(s_red + warp * 2) = make_float2(part, __uint_as_float(mgw));
            if (it) {
                uint32_t redo;
                asm volatile("{\n.reg .pred p;\nsetp.ne.u32 p, %1, 0;\nbar.red.or.pred p, 4, 384, p;\nselp.u32 %0, 1, 0, p;\n}\n"
                             : "=r"(redo) : "r"((uint32_t)(tiny && it == 1)) : "memory");
                if (__shfl_sync(0xffffffffu, redo, 0)) {
                    p2_redo_sums(warp, lane);
                    continue;
                }
            }
            float tot = 0.f;
#pragma unroll
            for (int i = 0; i < 6; i++) {
                const float4 t = *reinterpret_cast<const float4*>(s_red + i * 4);
                tot += t.x + t.z;
                mg = fmaxf(mg, fmaxf(t.y, t.w));
            }
            const float inv = __fdividef(1.0f, tot * (1.0f / HID) + 1e-6f);
            const uint32_t ej = min((__float_as_uint(fmaxf(fmaf(mg, inv, 1.0f) * (HSCALE * UNCHOP), pre.y * 0x1p-13f)) >> 23) + 1, 250u);
            const float dn = __uint_as_float((254u - ej) << 23);
            up = min(ej + 127u - (__float_as_uint(pre.x) >> 23), 254u) * 0x00800080u;
            reinterpret_cast<uint16_t*>(smem + P2_OFF_BIAS + C_DIM * 2)[tid] = 0;
            *reinterpret_cast<__half*>(smem + P2_OFF_BIAS + (tid >> 5) * 64 + (tid & 6) * 8 + (tid & 24) / 2 + (tid & 1) * 2) = __float2half_rn(bias * dn);
#pragma unroll
            for (int i = 0; i < 4; i++) {
                const int k = tid + 384 * i;
                *reinterpret_cast<__half*>(smem + P2_OFF_GRN + (k >> 4) * 32 + (k & 6) * 4 + (k & 8) / 2 + (k & 1) * 2) =
                    __float2half_rn(fmaf(gx[i], inv, 1.0f) * (HSCALE * UNCHOP * dn));
            }
            TSTAMP(1, 25);
            if (it) break;
        }
        join();
        bar_sync(4, 384);
        TSTAMP(1, 28);
        LAG_HERE(2);
        if (wg == 1) {
            constexpr int N = sizeof(g_w2img[0]) / 16, PER = (N + NUM_CTAS - 1) / NUM_CTAS;
            uint4 v[5];
#pragma unroll
            for (int i = 0; i < 5; i++) v[i] = __ldcg(&g_w2img[0][min(blockIdx.x * PER + (tid & 127) + 128 * i, N - 1)]);
#pragma unroll
            for (int i = 0; i < 5; i++) {
                const int j = min(blockIdx.x * PER + (tid & 127) + 128 * i, N - 1);
                const uint32_t* t = reinterpret_cast<const uint32_t*>(smem + P2_OFF_GRN + (j / 768) * 32 + (j & 8) / 2);
                auto sc = [&](uint32_t u, int e) { return (h2_mul(u, t[2 * e]) + 0x00040004u) & 0xfff8fff8u; };
                g_w2img[1][j] = make_uint4(sc(v[i].x, 0), sc(v[i].y, 1), sc(v[i].z, 2), sc(v[i].w, 3));
            }
            asm volatile("fence.proxy.async.global;\n" ::: "memory");
            bar_sync(2, 128);
            if (tid == 128) asm volatile("fence.acq_rel.gpu;\nred.release.gpu.global.add.u32 [%0], 1;\n" ::"l"(g_prog[CNT_IMG1]) : "memory");
        }

        const int who = __shfl_sync(0xffffffffu, lane == 2 ? 0 : lane < 2 ? 1 : 2, lane);
        const uint32_t rel0 = who ? mapa(bar_bempty, lane & 1) : mapa(bar_aempty + wg * P2_NA * 8, rank), rel1 = rel0 + (who ? 0 : 32);
        auto publish = [&]() {
            asm volatile("fence.proxy.async.shared::cta;\n" ::: "memory");
            __syncwarp();
            if (who == 0) mbar_arrive(bar_oready + wg * 8);
        };
        bool ok_a, pend = false;
        uint32_t pa = 0, s_t;
        auto fetch = [&](int j, bool raw) {
            uint32_t o[6], u0[4], u1[4];
            uint2 t0 = make_uint2(0, 0), t1 = t0;
            if (raw) {
                asm volatile("ld.shared.v2.u32 {%0,%1}, [%2];\n" : "=r"(t0.x), "=r"(t0.y) : "r"(s_t + j * 64) : "memory");
                asm volatile("ld.shared.v2.u32 {%0,%1}, [%2];\n" : "=r"(t1.x), "=r"(t1.y) : "r"(s_t + j * 64 + 32) : "memory");
            }
            const bool ok_b = mbar_test(bar_bfull + (j & 3) * 8, j >> 2);
            if (j == 7) pa ^= 1;
            ok_a = mbar_test(af + ((j + 1) & 7) * 8, pa);
            asm volatile("ldmatrix.sync.aligned.m8n8.x4.trans.shared.b16 {%0,%1,%2,%3}, [%4];\n"
                         : "=r"(o[0]), "=r"(o[1]), "=r"(o[2]), "=r"(o[3]) : "r"(s_a + j * P2_A) : "memory");
            asm volatile("ldmatrix.sync.aligned.m8n8.x2.trans.shared.b16 {%0,%1}, [%2];\n"
                         : "=r"(o[4]), "=r"(o[5]) : "r"(s_a + j * P2_A + 2048) : "memory");
            p2_unpack(u0, o[0], o[1], o[2]);
            p2_unpack(u1, o[3], o[4], o[5]);
            if (raw) {
                u0[0] = h2_mul(u0[0], t0.x); u0[1] = h2_mul(u0[1], t0.x); u0[2] = h2_mul(u0[2], t0.y); u0[3] = h2_mul(u0[3], t0.y);
                u1[0] = h2_mul(u1[0], t1.x); u1[1] = h2_mul(u1[1], t1.x); u1[2] = h2_mul(u1[2], t1.y); u1[3] = h2_mul(u1[3], t1.y);
            }
            a[j & 1][0] = make_uint4(u0[0], u0[1], u0[2], u0[3]);
            a[j & 1][1] = make_uint4(u1[0], u1[1], u1[2], u1[3]);
            if (!ok_b) mbar_wait(bar_bfull + (j & 3) * 8, j >> 2);
        };
        auto table = [&](int pos) { s_t = sbase + P2_OFF_GRN + q * 8 + (k0 + pos) % 48 * 64; };
        const uint64_t db0 = make_desc(sbase, 128, 256 + zero);
        auto block8 = [&](bool raw, int pos, int thr0, int mode) {
#pragma unroll
            for (int j = 0; j < 8; j++) {
                const uint64_t db = db0 + (j & 3) * (P2_B / 16);
                if (j == 8 - P2_AH && mode == 1) bar_sync(4, 384);
                TR2(wg, pos + j, 0);
                wg_fence();
                mma_rs_n192(acc0, a[j & 1][0], db);
                mma_rs_n192(acc1, a[j & 1][0], db + 384);
                mma_rs_n192(acc0, a[j & 1][1], db + 768);
                mma_rs_n192(acc1, a[j & 1][1], db + 768 + 384);
                wg_commit();
                if (j == 7 && mode == 2) bar_arrive(4, 384);
                const uint32_t rel = ((j - 1) & 4 ? rel1 : rel0) + ((j - 1) & 3) * 8;
                TR2(wg, pos + j, 1);
                wg_wait<1>();
                TR2(wg, pos + j, 2);
                if (who < (j ? 2 : thr0)) mbar_arrive_cluster(rel);
                if (!ok_a) {
                    if (j == 0 && pend) { publish(); pend = false; }
                    mbar_wait(af + ((j + 1) & 7) * 8, pa);
                }
                TR2(wg, pos + j, 3);
                if (raw && j == 7) table(pos + 8);
                fetch((j + 1) & 7, raw && (j < 7 || pos + 8 < P2_RAW));
            }
        };
        int n = wg == 2 && half ? -1 : wg, pos = p2_start(n);
        uint32_t px = 0;
        wait_pos(pos);
        mbar_wait(af, 0);
        table(pos);
        fetch(0, pos < P2_RAW);
#pragma unroll 1
        for (;; n += 3) {
            TSTAMP(1, 2 + n);
            const int end = pos + (n < 0 ? 24 : 48);
#pragma unroll
            for (int i = 0; i < 48; i += 2) {
                asm volatile("mov.b64 {%0, %1}, 0;\n" : "=r"(acc0[i]), "=r"(acc0[i + 1]));
                asm volatile("mov.b64 {%0, %1}, 0;\n" : "=r"(acc1[i]), "=r"(acc1[i + 1]));
            }
            int thr = 1;
#pragma unroll 1
            for (; pos < P2_RAW; pos += 8, thr = 2) block8(true, pos, thr, 0);
#pragma unroll 1
            for (; pos < end; pos += 8, thr = 2) {
                const int e = pos + 8, r = e % 48;
                block8(false, pos, thr, e < 48 || e > 256 || (r != 0 && r != P2_S1 && r != P2_S2) ? 0 : e == end ? 2 : 1);
            }
            TR2(wg, pos - 1, 4);
            if (n < 2 || n > 12) { LAG_HERE(3); }
            wg_wait<0>();
            TR2(wg, pos - 1, 5);
            if (who == 1) mbar_arrive_cluster(rel0 + 24);
            mbar_wait(bar_xfull + wg * 8, px);
            TR2(wg, pos - 1, 6);
            px ^= 1;
            __syncwarp();
            const bool last = n == P2_ITEMS - 1;
            uint32_t l;
            asm volatile("mov.u32 %0, %%laneid;\n" : "=r"(l));
            const uint32_t q16 = (l & 3) * 16, odd = (l >> 2) & 1, row = (w * 8 + (l >> 3)) * P2_XROW + q16;
            uint8_t* so = last ? reinterpret_cast<uint8_t*>(out) + (size_t)(2 * p2_tile(cl, n) + rank) * (64 * P2_XROW) : smem + P2_OFF_X;
            p2_epilogue(acc0, acc1, up, sbase + row + (last ? P2_OFF_A + odd * P2_LHALF : P2_OFF_X + odd * P2_XHALF),
                        sbase + P2_OFF_BIAS + q16 + (n < 0 && fin ? C_DIM * 2 : 0), so + (row + odd * (last ? 32 * P2_XROW : P2_XHALF)), zero);
            if (last) break;
            TR2(wg, pos - 1, 7);
            if (n + 3 >= P2_ITEMS) { publish(); break; }
            if (n < 0) {
                publish();
                pos = P2_S2;
                wait_pos(pos);
                mbar_wait(bar_bfull, 0);
            } else {
                pend = true;
                ok_a = false;
            }
        }
        TSTAMP(1, 29);
        cluster_sync_relaxed();
        TSTAMP(1, 30);
    }
}

__global__ void __cluster_dims__(2, 1, 1) __launch_bounds__(512, 1)
block_kernel(const __grid_constant__ CUtensorMap wmap, const __nv_bfloat16* __restrict__ x, const __nv_bfloat16* __restrict__ dw,
             const __nv_bfloat16* __restrict__ w2, const __nv_bfloat16* __restrict__ grn_g, const __nv_bfloat16* __restrict__ grn_b,
             __nv_bfloat16* __restrict__ out, int zero) {
    extern __shared__ __align__(1024) uint8_t smem[];
    const uint32_t sbase = smem_u32(smem);
    const int warp = __shfl_sync(0xffffffffu, threadIdx.x >> 5, 0), lane = threadIdx.x & 31;
    if (warp >= 12) {
        pass1<2>(wmap, x, dw, w2, grn_b, sbase, warp, lane, zero);
        pass2<2>(x, grn_g, out, smem, sbase, false, zero);
    } else {
        bool early = false;
        if (warp >= 8) {
            pass1<1>(wmap, x, dw, w2, grn_b, sbase, warp, lane, zero);
            reg_inc<160>();
        } else {
            early = pass1<0>(wmap, x, dw, w2, grn_b, sbase, warp, lane, zero);
            reg_dec<160>();
        }
        pass2<0>(x, grn_g, out, smem, sbase, early, zero);
    }
}

}

extern "C" void kernel_launch(void* const* d_in, const int* in_sizes, int n_in, void* d_out, int out_size) {
    const __nv_bfloat16* x = (const __nv_bfloat16*)d_in[0];
    const __nv_bfloat16* dw = (const __nv_bfloat16*)d_in[1];
    const __nv_bfloat16* w1 = (const __nv_bfloat16*)d_in[2];
    const __nv_bfloat16* w2 = (const __nv_bfloat16*)d_in[3];
    const __nv_bfloat16* grn_g = (const __nv_bfloat16*)d_in[4];
    const __nv_bfloat16* grn_b = (const __nv_bfloat16*)d_in[5];
    __nv_bfloat16* out = (__nv_bfloat16*)d_out;

    cudaFuncSetAttribute(block_kernel, cudaFuncAttributeMaxDynamicSharedMemorySize, SMEM_BYTES);

    typedef CUresult (*EncodeFn)(CUtensorMap*, CUtensorMapDataType, cuuint32_t, void*, const cuuint64_t*, const cuuint64_t*,
                                 const cuuint32_t*, const cuuint32_t*, CUtensorMapInterleave, CUtensorMapSwizzle,
                                 CUtensorMapL2promotion, CUtensorMapFloatOOBfill);
    static EncodeFn encode = nullptr;
    if (!encode) {
        cudaDriverEntryPointQueryResult qres;
        cudaGetDriverEntryPoint("cuTensorMapEncodeTiled", (void**)&encode, cudaEnableDefault, &qres);
    }
    CUtensorMap wmap;
    const cuuint64_t gdim[2] = {HID, C_DIM};
    const cuuint64_t gstr[1] = {HID * 2};
    const cuuint32_t box[2] = {64, 192}, estr[2] = {1, 1};
    CUresult er = encode(&wmap, CU_TENSOR_MAP_DATA_TYPE_BFLOAT16, 2, (void*)w1, gdim, gstr, box, estr, CU_TENSOR_MAP_INTERLEAVE_NONE,
           CU_TENSOR_MAP_SWIZZLE_128B, CU_TENSOR_MAP_L2_PROMOTION_L2_128B, CU_TENSOR_MAP_FLOAT_OOB_FILL_NONE);
    if (er != CUDA_SUCCESS) printf("tensor map encode failed %d\n", (int)er);

    block_kernel<<<NUM_CTAS, 512, SMEM_BYTES>>>(wmap, x, dw, w2, grn_g, grn_b, out, 0);
}
```

```cpp
#include <cuda.h>
#include <cuda_runtime.h>
#include <cuda_bf16.h>
#include <cuda_fp16.h>
#include <stdint.h>
#include <stdio.h>

namespace {

constexpr int M_TOTAL = 384 * 384;
constexpr int C_DIM   = 384;
constexpr int HID     = 1536;
constexpr int NT128   = M_TOTAL / 128;
constexpr int NUM_CTAS = 132;

constexpr int NGRP = 22, GRP_CTAS = 6;
constexpr int NT_EARLY = NT128 - 30;
constexpr int LN_STEP = NUM_CTAS / 4, LN_RING = 2 * LN_STEP;
constexpr int LN_TILE = 128 * C_DIM * 2;
constexpr int H_PAGES = NT128 / 4;

__device__ __align__(1024) uint4 g_h[(size_t)(H_PAGES + 1) << 17];
__device__ unsigned g_page[H_PAGES];
__device__ unsigned g_epoch;
__device__ __align__(1024) uint4 g_w2img[2][HID * C_DIM * 2 / 16];
__device__ __align__(16) unsigned long long g_sq[HID];
__device__ __align__(16) float g_sums[512];
__device__ float g_scale[HID];
__device__ float g_redo[HID];
enum { CNT_POS, CNT_IMG1, CNT_REDO, CNT_IMG0, CNT_LAST, CNT_H, CNT_EARLY, NUM_CNT };
__device__ __align__(128) unsigned g_prog[NUM_CNT][32];
__device__ __align__(128) unsigned g_half[32][2];
__device__ unsigned g_flag[LN_RING + 6][2][8];
#define TSTAMP(k, i)
#define TRACE(wg, pos, i)
#define TRACEW(pos, i)

#define TR2(wg, pos, i)
__host__ __device__ __forceinline__ int perm32(int n) {
    return (n & ~31) | (((n >> 1) & 3) << 3) | (((n >> 3) & 3) << 1) | (n & 1);
}

constexpr int H_FIXED = 12;
constexpr int LN_SW = LN_RING;
__device__ __forceinline__ uint8_t* h_base() { return reinterpret_cast<uint8_t*>((reinterpret_cast<size_t>(g_h) + 0x1fffff) & ~(size_t)0x1fffff); }
__device__ __forceinline__ unsigned page_bit(int page, unsigned tag) {
    unsigned v = 0;
    if (page >= H_FIXED) {
        do {
            asm volatile("ld.relaxed.gpu.global.u32 %0, [%1];\n" : "=r"(v) : "l"(&g_page[page]) : "memory");
        } while (tag && (v & ~1u) != tag);
    }
    return v;
}
__device__ __forceinline__ uint32_t h_tile(int t, unsigned bit) { return (t >> 1) << 20 | ((t ^ bit) & 1) << 12 | (t & 2) << 9; }
__device__ __forceinline__ uint32_t h_tile(int t) { return h_tile(t, page_bit(t >> 2, 0)); }
__device__ __forceinline__ int ln_page(int t) { return (t < LN_SW ? 0 : 17) + (t % LN_RING >> 2); }
__device__ __forceinline__ int ln_probed(int t) { return t < LN_SW ? 0 : ln_page(t); }
__device__ __forceinline__ uint32_t ln_tile(int t, unsigned bit) {
    const int slot = t % LN_RING;
    return ln_page(t) << 21 | 0xc0000 | (slot & 2) << 16 | ((~t ^ bit ^ (slot >> 1)) & 1) << 12;
}
__device__ __forceinline__ constexpr uint32_t ln_rows(int group) { return (group & 1) * 0x3000 ^ (group >> 1) * 0x11000; }
__device__ __forceinline__ constexpr uint32_t ln_block(int j) { return (j & 3) << 14 | (j >> 2) << 20; }
__device__ __forceinline__ uint32_t h_block(int kb, int half) {
    return (kb >> 2) << 16 | (kb & 2) << 14 | half << 14 | (kb & 1) << 13 | (__popc(kb & 0x2d) & 1) << 12 | (kb & 1) << 10;
}
__device__ __forceinline__ unsigned* h_cell(int page, int c) {
    return reinterpret_cast<unsigned*>(h_base() + ((size_t)page << 21) + 0x1d8000 + ((c >> 6) << 14) + (c & 63) * 64);
}
__device__ __forceinline__ unsigned near_half(unsigned* cell) {
    int votes = 0;
#pragma unroll 1
    for (int i = 0; i < 6; i++) {
        const unsigned a = atomicAdd(cell + (i & 1) * 1024, 1u), b = atomicAdd(cell + (~i & 1) * 1024, 1u);
        if (a == ~0u) break;
        const unsigned t0 = clock();
        if (b == ~0u) break;
        const int d = min((unsigned)clock() - t0, 250u);
        votes += i & 1 ? d : -d;
    }
    return votes > 0;
}

__device__ __forceinline__ uint32_t smem_u32(const void* p) { return (uint32_t)__cvta_generic_to_shared(p); }

__device__ __forceinline__ void mbar_init(uint32_t bar, uint32_t count) {
    asm volatile("mbarrier.init.shared::cta.b64 [%0], %1;\n" ::"r"(bar), "r"(count) : "memory");
}
__device__ __forceinline__ void mbar_expect_tx(uint32_t bar, uint32_t bytes) {
    asm volatile("mbarrier.arrive.expect_tx.shared::cta.b64 _, [%0], %1;\n" ::"r"(bar), "r"(bytes) : "memory");
}
__device__ __forceinline__ void mbar_arrive(uint32_t bar) {
    asm volatile("mbarrier.arrive.shared::cta.b64 _, [%0];\n" ::"r"(bar) : "memory");
}
__device__ __forceinline__ void mbar_arrive_cluster(uint32_t bar_cluster_addr) {
    asm volatile("mbarrier.arrive.shared::cluster.b64 _, [%0];\n" ::"r"(bar_cluster_addr) : "memory");
}
#define LAG_HERE(k)
#define SAFE_BREAK
__device__ __forceinline__ void mbar_wait(uint32_t bar, uint32_t parity) {
    asm volatile(
        "{\n"
        ".reg .pred p;\n"
        "LAB_WAIT:\n"
        "mbarrier.try_wait.parity.shared::cta.b64 p, [%0], %1;\n"
        "@!p bra LAB_WAIT;\n"
        "}\n" ::"r"(bar), "r"(parity) : "memory");
}
__device__ __forceinline__ bool mbar_test(uint32_t bar, uint32_t parity) {
    uint32_t ok;
    asm volatile("{\n.reg .pred p;\n"
                 "mbarrier.test_wait.parity.shared::cta.b64 p, [%1], %2;\n"
                 "selp.u32 %0, 1, 0, p;\n}\n" : "=r"(ok) : "r"(bar), "r"(parity) : "memory");
    return ok != 0;
}
__device__ __forceinline__ uint32_t mapa(uint32_t addr, uint32_t rank) {
    uint32_t r;
    asm volatile("mapa.shared::cluster.u32 %0, %1, %2;\n" : "=r"(r) : "r"(addr), "r"(rank));
    return r;
}
__device__ __forceinline__ void bulk_g2s(uint32_t dst, const void* src, uint32_t bytes, uint32_t bar) {
    asm volatile("cp.async.bulk.shared::cluster.global.mbarrier::complete_tx::bytes [%0], [%1], %2, [%3];\n"
                 ::"r"(dst), "l"(src), "r"(bytes), "r"(bar) : "memory");
}
__device__ __forceinline__ void bulk_g2s_mc(uint32_t dst, const void* src, uint32_t bytes, uint32_t bar, uint16_t mask) {
    asm volatile("cp.async.bulk.shared::cluster.global.mbarrier::complete_tx::bytes.multicast::cluster [%0], [%1], %2, [%3], %4;\n"
                 ::"r"(dst), "l"(src), "r"(bytes), "r"(bar), "h"(mask) : "memory");
}
__device__ __forceinline__ void tma2(uint32_t dst, const CUtensorMap* map, int c0, int c1, uint32_t bar) {
    asm volatile("cp.async.bulk.tensor.2d.shared::cluster.global.tile.mbarrier::complete_tx::bytes [%0], [%1, {%2, %3}], [%4];\n"
                 ::"r"(dst), "l"(map), "r"(c0), "r"(c1), "r"(bar) : "memory");
}
template <bool ACQ>
__device__ __forceinline__ uint32_t flag_wait(const unsigned* p, unsigned target) {
    unsigned v, n = 0;
    do {
        if (ACQ) asm volatile("ld.acquire.gpu.global.u32 %0, [%1];\n" : "=r"(v) : "l"(p) : "memory");
        else asm volatile("ld.relaxed.gpu.global.u32 %0, [%1];\n" : "=r"(v) : "l"(p) : "memory");
        n++;
    } while (v < target);
    return n == 1;
}
__device__ __forceinline__ void ldsm4t(uint32_t (&r)[4], uint32_t addr) {
    asm volatile("ldmatrix.sync.aligned.m8n8.x4.trans.shared.b16 {%0,%1,%2,%3}, [%4];\n"
                 : "=r"(r[0]), "=r"(r[1]), "=r"(r[2]), "=r"(r[3]) : "r"(addr) : "memory");
}
__device__ __forceinline__ void bulk_s2g(void* dst, uint32_t src, uint32_t bytes) {
    asm volatile("cp.async.bulk.global.shared::cta.bulk_group [%0], [%1], %2;\n" ::"l"(dst), "r"(src), "r"(bytes) : "memory");
}
__device__ __forceinline__ void cluster_sync_relaxed() {
    asm volatile("barrier.cluster.arrive.relaxed.aligned;\nbarrier.cluster.wait.aligned;\n" ::: "memory");
}
__device__ __forceinline__ uint32_t cluster_rank() {
    uint32_t r;
    asm volatile("mov.u32 %0, %%cluster_ctarank;\n" : "=r"(r));
    return r;
}
__device__ __forceinline__ bool elect_one() {
    uint32_t pred;
    asm volatile("{\n.reg .pred p;\nelect.sync _|p, 0xffffffff;\nselp.u32 %0, 1, 0, p;\n}\n" : "=r"(pred));
    return pred != 0;
}
__device__ __forceinline__ void wg_fence() { asm volatile("wgmma.fence.sync.aligned;\n" ::: "memory"); }
__device__ __forceinline__ void wg_commit() { asm volatile("wgmma.commit_group.sync.aligned;\n" ::: "memory"); }
template <int N> __device__ __forceinline__ void wg_wait() {
    asm volatile("wgmma.wait_group.sync.aligned %0;\n" ::"n"(N) : "memory");
}
template <int R> __device__ __forceinline__ void reg_inc() { asm volatile("setmaxnreg.inc.sync.aligned.u32 %0;\n" ::"n"(R)); }
template <int R> __device__ __forceinline__ void reg_dec() { asm volatile("setmaxnreg.dec.sync.aligned.u32 %0;\n" ::"n"(R)); }
__device__ __forceinline__ void bar_sync(int id, int n) { asm volatile("bar.sync %0, %1;\n" ::"r"(id), "r"(n) : "memory"); }
__device__ __forceinline__ void bar_arrive(int id, int n) { asm volatile("bar.arrive %0, %1;\n" ::"r"(id), "r"(n) : "memory"); }

__device__ __forceinline__ uint64_t make_desc(uint32_t saddr, uint32_t lbo, uint32_t sbo) {
    return (uint64_t)((saddr & 0x3FFFF) >> 4) | ((uint64_t)(lbo >> 4) << 16) | ((uint64_t)(sbo >> 4) << 32);
}

__device__ __forceinline__ void stg128_cs(void* p, uint32_t a, uint32_t b, uint32_t c, uint32_t d) {
    asm volatile("st.global.cs.v4.u32 [%0], {%1,%2,%3,%4};\n" ::"l"(p), "r"(a), "r"(b), "r"(c), "r"(d) : "memory");
}
__device__ __forceinline__ uint32_t pack_bf16(float lo, float hi) {
    uint32_t r;
    asm("cvt.rn.bf16x2.f32 %0, %1, %2;\n" : "=r"(r) : "f"(hi), "f"(lo));
    return r;
}
__device__ __forceinline__ float bf_lo(uint32_t v) { return __uint_as_float(v << 16); }
__device__ __forceinline__ float bf_hi(uint32_t v) { return __uint_as_float(v & 0xffff0000u); }
__device__ __forceinline__ uint32_t bf2_mul(uint32_t a, uint32_t b) {
    uint32_t r;
    asm("mul.rn.bf16x2 %0, %1, %2;\n" : "=r"(r) : "r"(a), "r"(b));
    return r;
}
__device__ __forceinline__ uint32_t bf2_fma(uint32_t a, uint32_t b, uint32_t c) {
    uint32_t r;
    asm("fma.rn.bf16x2 %0, %1, %2, %3;\n" : "=r"(r) : "r"(a), "r"(b), "r"(c));
    return r;
}
__device__ __forceinline__ uint32_t bf2_add(uint32_t a, uint32_t b) {
    uint32_t r;
    asm("add.rn.bf16x2 %0, %1, %2;\n" : "=r"(r) : "r"(a), "r"(b));
    return r;
}
__device__ __forceinline__ uint32_t h2_mul(uint32_t a, uint32_t b) {
    uint32_t r;
    asm("mul.rn.f16x2 %0, %1, %2;\n" : "=r"(r) : "r"(a), "r"(b));
    return r;
}
__device__ __forceinline__ uint32_t h2_fma(uint32_t a, uint32_t b, uint32_t c) {
    uint32_t r;
    asm("fma.rn.f16x2 %0, %1, %2, %3;\n" : "=r"(r) : "r"(a), "r"(b), "r"(c));
    return r;
}
__device__ __forceinline__ uint32_t h2_add(uint32_t a, uint32_t b) {
    uint32_t r;
    asm("add.rn.f16x2 %0, %1, %2;\n" : "=r"(r) : "r"(a), "r"(b));
    return r;
}
__device__ __forceinline__ uint32_t pack_f16(float lo, float hi) {
    uint32_t r;
    asm("cvt.rn.f16x2.f32 %0, %1, %2;\n" : "=r"(r) : "f"(hi), "f"(lo));
    return r;
}
__device__ __forceinline__ float h_lo(uint32_t v) { return __low2float(*reinterpret_cast<const __half2*>(&v)); }
__device__ __forceinline__ float h_hi(uint32_t v) { return __high2float(*reinterpret_cast<const __half2*>(&v)); }
__device__ __forceinline__ uint32_t bf2_to_h2(uint32_t v) { return (v & 0x7fff7fffu) * 7u + v; }
__device__ __forceinline__ uint32_t prmt(uint32_t a, uint32_t b, uint32_t sel) {
    uint32_t r;
    asm("prmt.b32 %0, %1, %2, %3;\n" : "=r"(r) : "r"(a), "r"(b), "r"(sel));
    return r;
}
__device__ __forceinline__ uint32_t bitsel(uint32_t a, uint32_t b, uint32_t m) {
    uint32_t r;
    asm("lop3.b32 %0, %1, %2, %3, 0xd8;\n" : "=r"(r) : "r"(a), "r"(b), "r"(m));
    return r;
}
constexpr float KAPPA = 0.3292034911525734f;
constexpr uint32_t GELU_C2 = 0x40d940d9u;
constexpr float HSCALE = 1.0f / (2.0f * KAPPA);
__device__ __forceinline__ float w2_scale(uint32_t m) { return __uint_as_float((257u - max(m >> 23, 16u)) << 23); }
__device__ __forceinline__ void sched_break(int zero) {
    asm volatile("{\n.reg .pred p;\nsetp.ne.s32 p, %0, 0;\nSB_LOOP:\n@p nanosleep.u32 1;\n@p bra SB_LOOP;\n}\n" ::"r"(zero));
}

#define ACC8(d, o) "+r"(d[o + 0]), "+r"(d[o + 1]), "+r"(d[o + 2]), "+r"(d[o + 3]), "+r"(d[o + 4]), "+r"(d[o + 5]), "+r"(d[o + 6]), "+r"(d[o + 7])

__device__ __forceinline__ void mma_rs_n128(uint32_t (&d)[32], const uint32_t (&a)[4], uint64_t desc, int scale_d) {
    asm volatile(
        "{\n.reg .pred p;\nsetp.ne.b32 p, %37, 0;\n"
        "wgmma.mma_async.sync.aligned.m64n128k16.f16.f16.f16 "
        "{%0,%1,%2,%3,%4,%5,%6,%7,%8,%9,%10,%11,%12,%13,%14,%15,"
        "%16,%17,%18,%19,%20,%21,%22,%23,%24,%25,%26,%27,%28,%29,%30,%31},"
        "{%32,%33,%34,%35}, %36, p, 1, 1, 0;\n}\n"
        : ACC8(d, 0), ACC8(d, 8), ACC8(d, 16), ACC8(d, 24)
        : "r"(a[0]), "r"(a[1]), "r"(a[2]), "r"(a[3]), "l"(desc), "r"(scale_d));
}

__device__ __forceinline__ void mma_ss_n128(uint32_t (&d)[32], uint64_t da, uint64_t db, int scale_d) {
    asm volatile(
        "{\n.reg .pred p;\nsetp.ne.b32 p, %34, 0;\n"
        "wgmma.mma_async.sync.aligned.m64n128k16.f16.f16.f16 "
        "{%0,%1,%2,%3,%4,%5,%6,%7,%8,%9,%10,%11,%12,%13,%14,%15,"
        "%16,%17,%18,%19,%20,%21,%22,%23,%24,%25,%26,%27,%28,%29,%30,%31},"
        "%32, %33, p, 1, 1, 1, 0;\n}\n"
        : ACC8(d, 0), ACC8(d, 8), ACC8(d, 16), ACC8(d, 24)
        : "l"(da), "l"(db), "r"(scale_d));
}

__device__ __forceinline__ void mma_rs_n192(uint32_t (&d)[48], const uint4& a, uint64_t db) {
    asm volatile(
        "wgmma.mma_async.sync.aligned.m64n192k16.f16.f16.f16 "
        "{%0,%1,%2,%3,%4,%5,%6,%7,%8,%9,%10,%11,%12,%13,%14,%15,"
        "%16,%17,%18,%19,%20,%21,%22,%23,%24,%25,%26,%27,%28,%29,%30,%31,"
        "%32,%33,%34,%35,%36,%37,%38,%39,%40,%41,%42,%43,%44,%45,%46,%47},"
        "{%48,%49,%50,%51}, %52, 1, 1, 1, 0;\n"
        : ACC8(d, 0), ACC8(d, 8), ACC8(d, 16), ACC8(d, 24), ACC8(d, 32), ACC8(d, 40)
        : "r"(a.x), "r"(a.y), "r"(a.z), "r"(a.w), "l"(db));
}

constexpr int P1_SPLIT = 6;
constexpr int P1_SLOT = LN_TILE / 6, P1_NST = 6;
constexpr int P1_W = 64 * C_DIM * 2;
constexpr int P1_X = 32 * C_DIM * 2;
constexpr int P1_OFF_W = LN_TILE;
constexpr int P1_OFF_X = P1_OFF_W + 2 * P1_W;
constexpr int P1_OFF_BAR = 227328;
constexpr int P1_OFF_TILE = P1_OFF_BAR + (2 * P1_NST + 4 + 4 + 4) * 8;
constexpr int P1_OFF_EX = P1_OFF_TILE + 96;
constexpr int P1_OFF_DW = P1_OFF_EX + 256 * 4;
constexpr int OFF_PRE = P1_OFF_DW + C_DIM * 2;
constexpr int SMEM_BYTES = OFF_PRE + C_DIM * 4 + 16;

__device__ __forceinline__ float rsqrt_fast(float x) {
    float r;
    asm("rsqrt.approx.ftz.f32 %0, %1;\n" : "=f"(r) : "f"(x));
    return r;
}
__device__ __forceinline__ float row_sum(const uint32_t (&c)[4]) {
    const uint32_t u = bf2_add(bf2_add(c[0], c[1]), bf2_add(c[2], c[3]));
    float s = bf_lo(u) + bf_hi(u);
#pragma unroll
    for (int o = 1; o < 8; o <<= 1) s += __shfl_xor_sync(0xffffffffu, s, o);
    return s;
}
__device__ __forceinline__ uint32_t pace(uint32_t bar, uint32_t off, uint32_t val, int zero) {
    asm volatile(
        "{\n.reg .pred p, q;\n.reg .b32 par;\n"
        "lop3.b32 par, %0, %2, %3, 0xea;\n"
        "setp.eq.u32 q, par, 0;\n"
        "mov.pred p, 0;\n"
        "@q mbarrier.test_wait.parity.shared::cta.b64 p, [%1], par;\n"
        "selp.u32 par, 1, 0, p;\n"
        "@q mbarrier.try_wait.parity.shared::cta.b64 p, [%1], par, 1000;\n"
        "@p or.b32 %0, %0, %2;\n"
        "}\n" : "+r"(val) : "r"(bar), "r"(zero), "r"(off));
    return val;
}
__device__ __forceinline__ void ln_row(uint32_t (&v)[6][4], const uint32_t (&d)[6][4], uint32_t bar, uint32_t off, int zero, uint32_t bar_read) {
    const float inv = 1.0f / C_DIM;
    uint32_t c[4];
#pragma unroll
    for (int i = 0; i < 6; i++)
#pragma unroll
        for (int k = 0; k < 4; k++) c[k] = bf2_fma(v[i][k], d[i][k], i ? c[k] : 0);
    const float m = row_sum(c) * inv;
    uint32_t nm = pack_bf16(-m, -m);
    const float e = m + bf_lo(nm);
    if (bar_read) mbar_arrive(bar_read + (nm & zero));
    nm = pace(bar, off, nm, zero);
#pragma unroll
    for (int i = 0; i < 6; i++) {
#pragma unroll
        for (int k = 0; k < 4; k++) {
            v[i][k] = bf2_fma(v[i][k], d[i][k], nm);
            c[k] = i ? bf2_fma(v[i][k], v[i][k], c[k]) : bf2_mul(v[i][k], v[i][k]);
        }
    }
    float r = KAPPA * rsqrt_fast(fmaxf(fmaf(-e, e, row_sum(c) * inv), 0.f) + 1e-5f);
    const float er = -e * r * 0x1p-112f;
    if (__any_sync(0xffffffffu, r < 0x1p-8f)) {
        const uint32_t p2 = __float_as_uint(r) & 0x7f800000u;
        r = __uint_as_float((__float_as_uint(r) & 0x007fffffu) | 0x3f800000u);
#pragma unroll
        for (int i = 0; i < 6; i++)
#pragma unroll
            for (int k = 0; k < 4; k++) v[i][k] = bf2_mul(v[i][k], p2 | p2 >> 16);
    }
    const uint32_t rs = pack_bf16(r * 0x1p-112f, r * 0x1p-112f), sh = pack_bf16(er, er);
#pragma unroll
    for (int i = 0; i < 6; i++)
#pragma unroll
        for (int k = 0; k < 4; k++) v[i][k] = bf2_to_h2(bf2_fma(v[i][k], rs, sh));
}

template <int R>
__device__ __forceinline__ uint32_t gelu2(uint32_t a, uint32_t sc2) {
    uint32_t y, t;
    if (R) asm("{\n.reg .b16 l, h;\n.reg .b32 f;\nmov.b32 {l, h}, %2;\nmov.b32 f, {h, h};\nmul.rn.f16x2 %0, %1, f;\n}\n" : "=r"(y) : "r"(a), "r"(sc2));
    else asm("{\n.reg .b16 l, h;\n.reg .b32 f;\nmov.b32 {l, h}, %2;\nmov.b32 f, {l, l};\nmul.rn.f16x2 %0, %1, f;\n}\n" : "=r"(y) : "r"(a), "r"(sc2));
    asm("tanh.approx.f16x2 %0, %1;\n" : "=r"(t) : "r"(h2_mul(y, h2_fma(y, y, GELU_C2))));
    return h2_fma(a, t, a);
}
constexpr uint32_t SPARE = 0x40074007u;
constexpr float UNCHOP = 1.0023f;

__device__ __forceinline__ uint32_t p1_exponents(float (&t)[2], uint32_t (&ex)[2], uint32_t saddr, int lane) {
#pragma unroll
    for (int r = 0; r < 2; r++) {
        t[r] += __shfl_xor_sync(0xffffffffu, t[r], 1);
        t[r] += __shfl_xor_sync(0xffffffffu, t[r], 2);
        ex[r] = min(max(((__float_as_uint(193.3f * t[r]) >> 23) + 127u) >> 1, 72u), 198u);
        asm volatile("st.shared.u32 [%0], %1;\n" ::"r"(saddr + r * 32), "r"(ex[r] << 23) : "memory");
    }
    return pack_f16(__uint_as_float(min(ex[0], 142u) << 23), __uint_as_float(min(ex[1], 142u) << 23));
}
template <int N>
__device__ __forceinline__ void p1_convert(uint32_t (&o)[N][4], uint32_t (&v)[N][4], const uint32_t (&ex)[2]) {
    if (__any_sync(0xffffffffu, max(ex[0], ex[1]) > 141u)) {
#pragma unroll
        for (int k = 0; k < 4 * N; k++) v[k >> 2][k & 3] = bf2_mul(v[k >> 2][k & 3], ex[k & 1] > 141u ? 0x1f801f80u : 0x3f803f80u);
    }
#pragma unroll
    for (int k = 0; k < 4 * N; k++) {
        const uint32_t u = bf2_mul(v[k >> 2][k & 3], ((ex[k & 1] > 141u ? 206u : 142u) - ex[k & 1]) * 0x00800080u);
        asm volatile("mad.lo.u32 %0, %1, 7, %2;\n" : "=r"(o[k >> 2][k & 3]) : "r"(u & 0x7fff7fffu), "r"(u));
    }
}
template <int N>
__device__ __forceinline__ void p1_squares(const uint32_t (&v)[N][4], float (&t)[2]) {
#pragma unroll
    for (int j = 0; j < N / 2; j++) {
        const int r = j & 1, b = (j >> 1) * 4;
        uint32_t c = bf2_mul(v[b][r], v[b][r]);
#pragma unroll
        for (int k = 1; k < 8; k++) c = bf2_fma(v[b + k / 2][r + (k & 1) * 2], v[b + k / 2][r + (k & 1) * 2], c);
        t[r] += bf_lo(c) + bf_hi(c);
    }
}
__device__ __forceinline__ void p1_epilogue(const uint32_t (&acc)[2][32], const uint32_t (&sc2)[2], float (&ssq)[4], uint8_t* hp, int zero) {
    uint32_t sq[2], h[16][4];
#pragma unroll
    for (int i2 = 0; i2 < 9; i2++) {
#pragma unroll
        for (int c = 2 * i2 - 2; c < 2 * i2; c++) {
            if (c >= 0 && (c & 3)) {
                uint32_t o[4];
#pragma unroll
                for (int u = 0; u < 4; u++) {
                    const uint32_t v = h[c & 12][u];
                    o[u] = bitsel(h[c][u], (c & 3) == 2 ? prmt(v, v, 0xa381) : prmt(v >> 3, v, (c & 3) == 1 ? 0x6240 : 0xf3d1), SPARE);
                }
                stg128_cs(hp + (c >> 2) * 0x4000 + ((c & 3) - 1) * 512, o[0], o[1], o[2], o[3]);
            }
        }
        if (i2 < 8) {
#pragma unroll
            for (int u = 0; u < 4; u++) {
                h[2 * i2][u] = gelu2<0>(acc[i2 >> 2][8 * (i2 & 3) + 2 * u], sc2[i2 >> 2]);
                h[2 * i2 + 1][u] = gelu2<1>(acc[i2 >> 2][8 * (i2 & 3) + 2 * u + 1], sc2[i2 >> 2]);
#pragma unroll
                for (int r = 0; r < 2; r++) {
                    const uint32_t v = h[2 * i2 + r][u];
                    sq[r] = ((i2 & 3) | u) ? h2_fma(v, v, sq[r]) : h2_mul(v, v);
                }
            }
            if ((i2 & 3) == 3) {
#pragma unroll
                for (int r = 0; r < 2; r++) ssq[(i2 >> 2) * 2 + r] += h_lo(sq[r]) + h_hi(sq[r]);
            }
            sched_break(zero);
        }
    }
}
template <int WG>
__device__ __forceinline__ void p1_mma(uint32_t (&acc)[2][32], const uint32_t (&a)[24][4], uint32_t sbase, uint32_t empty_remote, int i, int lane, bool pass, int zero) {
    const uint32_t bar_full = sbase + P1_OFF_BAR;
    const uint64_t db = make_desc(sbase, 16, 1024 + zero) | (1ull << 62), da = db + (P1_OFF_W + WG * P1_W) / 16;
    if (WG == 0) mbar_wait(bar_full, i & 1);
    bar_sync(1 + WG, 256);
    TRACE(WG, i, 1);
    wg_fence();
#pragma unroll
    for (int k = 0; k < 24; k++) {
        if (WG == 0 && k && k % 4 == 0) mbar_wait(bar_full + (k >> 2) * 8, i & 1);
        mma_rs_n128(acc[0], a[k], db + (k >> 2) * 1024 + (k & 3) * 2, k != 0);
        mma_ss_n128(acc[1], da + k * 128, db + (k >> 2) * 1024 + (k & 3) * 2, k != 0);
        if (k == 23 && pass) bar_arrive(2 - WG, 256);
        if (k == 23 || (WG == 1 && k % 4 == 3)) wg_commit();
        if (WG == 1 && k % 4 == 3 && k > 3) {
            wg_wait<1>();
            if (lane < 2) mbar_arrive_cluster(empty_remote + ((k >> 2) - 1) * 8);
        }
    }
    TRACE(WG, i, 2);
    wg_wait<0>();
    if (WG == 1 && lane < 2) mbar_arrive_cluster(empty_remote + 5 * 8);
}
__device__ __forceinline__ bool p1_consumer(const uint32_t (&a)[24][4], const uint32_t (&sc2)[2], uint32_t sbase, int WG, int w, int lane, int zero) {
    const uint32_t bar_full = sbase + P1_OFF_BAR, bar_empty = bar_full + P1_NST * 8;
    const uint32_t empty_remote = mapa(bar_empty, lane & 1);
    const uint32_t bar_pace = bar_empty + P1_NST * 8 + 32 + w * 8;
    const int g = lane >> 2, q = lane & 3, half = WG ^ ((blockIdx.x / GRP_CTAS) & 1), cb = (blockIdx.x % GRP_CTAS) * 4 + half * 2;
    uint32_t acc[2][32];
    float ssq[4] = {0.f, 0.f, 0.f, 0.f};
    TSTAMP(0, 1);

    uint8_t* const hp0 = h_base() + (w & 1) * 1536 + g * 64 + (q ^ (g >> 1)) * 16;
    const uint32_t blk = h_block(cb * 2 + (w >> 1), 0);
    int i = 0;
    uint32_t more = 3, both;
#pragma unroll 1
    for (;; i++) {
        TRACE(WG, i, 0);
        both = more & 2;
        if (WG == 0) p1_mma<0>(acc, a, sbase, empty_remote, i, lane, both, zero);
        else p1_mma<1>(acc, a, sbase, empty_remote, i, lane, true, zero);
        TRACE(WG, i, 4);
        uint32_t step;
        asm volatile("ld.shared.v2.u32 {%0, %1}, [%2];\n" : "=r"(step), "=r"(more) : "r"(sbase + P1_OFF_TILE + (i & 3) * 16) : "memory");
        uint8_t* hp = hp0 + (step ^ blk);
        if (i < 2 || more != 3) { LAG_HERE(4); }
        if (!(more >> WG & 1) && lane == 0) asm volatile("red.relaxed.gpu.global.add.u32 [%0], 1;\n" ::"l"(g_prog[CNT_LAST]) : "memory");
        p1_epilogue(acc, sc2, ssq, hp, zero);
        if (lane == 0) mbar_arrive(bar_pace);
        if (more & 4) {
            asm volatile("fence.proxy.async.global;\n" ::: "memory");
            bar_arrive(8, 288);
            bar_arrive(9, 288);
        }
        if (!(more >> WG & 1)) break;
    }
    TSTAMP(0, 21);
    if (WG == 0 && both) bar_sync(1, 256);
#pragma unroll
    for (int r = 0; r < 4; r++) {
        ssq[r] += __shfl_xor_sync(0xffffffffu, ssq[r], 1);
        ssq[r] += __shfl_xor_sync(0xffffffffu, ssq[r], 2);
    }
    const float t = q == 0 ? ssq[0] : q == 1 ? ssq[1] : q == 2 ? ssq[2] : ssq[3];
    atomicAdd(&g_sq[cb * 64 + (q >> 1) * 64 + w * 16 + (q & 1) * 8 + g], (1ull << 56) + __float2ull_rn(fminf(t, 0x1p19f) * 0x1p32f));
    asm volatile("fence.proxy.async.global;\n" ::: "memory");
    bar_arrive(3, 288);
    asm volatile("barrier.cluster.arrive.relaxed.aligned;\n" ::: "memory");
    return WG ? more & 1 : both;
}

__device__ __forceinline__ void p2_init(uint32_t sbase);
template <int ROLE>
__device__ __forceinline__ bool pass1(const CUtensorMap& wmap, const __nv_bfloat16* __restrict__ x, const __nv_bfloat16* __restrict__ dw,
                                      const __nv_bfloat16* __restrict__ w2, const __nv_bfloat16* __restrict__ grn_b, uint32_t sbase,
                                      int warp, int lane, int zero) {
    const uint32_t bar_full = sbase + P1_OFF_BAR, bar_empty = bar_full + P1_NST * 8, bar_w = bar_empty + P1_NST * 8;
    const uint32_t rank = cluster_rank();
    const int cig = blockIdx.x % GRP_CTAS;

    TSTAMP(0, 0);
    TRACEW(110 + warp, 0);
    const uint32_t bar_pace = bar_w + 32, bar_xfull = bar_pace + 32, bar_xempty = bar_xfull + 8, bar_done = bar_xfull + 16;
    const uint32_t s_side = bar_done + 12;
    const uint32_t s_item = sbase + P1_OFF_TILE + 64, s_cl = sbase + OFF_PRE + C_DIM * 4 + 8;
    auto ln_place = [](int q, unsigned tag) { return ln_tile(q >> 2, page_bit(ln_probed(q >> 2), tag)) ^ ln_rows(q & 2) ^ (q & 1) * 0x90; };
    const int first = blockIdx.x / GRP_CTAS;

    if (ROLE == 2) {
        reg_dec<32>();
        asm volatile("barrier.cluster.arrive.relaxed.aligned;\n" ::: "memory");
        asm volatile("barrier.cluster.wait.aligned;\n" ::: "memory");
        LAG_HERE(0);
        if (warp == 12) {
            int t = first, sent = 0;
            const unsigned tag = 2 * __ldcg(&g_epoch) + 2;
            const uint32_t rbase = mapa(sbase, lane & 1);
#pragma unroll 1
            for (int i = 0; t < NT128; i++) {
                const int round = t / LN_RING, slot = t - round * LN_RING;
                constexpr unsigned LIM = (NT128 - P1_SPLIT - NGRP) / 2;
                unsigned* cnt = &g_flag[LN_RING + (cig >> 1)][0][0];
                const int page = lane & 1 ? ln_probed(t) : t >> 2;
                unsigned v, sd, u = 0;
                do {
                    asm volatile("ld.relaxed.gpu.global.u32 %0, [%1];\n" : "=r"(v) : "l"(lane & 2 ? &g_page[page] : cnt + (lane & 1) * 8) : "memory");
                    if ((lane & 2) && page < H_FIXED) v = tag;
                    SAFE_BREAK;
                } while (__any_sync(0xffffffffu, (lane & 2) && (v & ~1u) != tag));
                asm volatile("ld.volatile.shared.u32 %0, [%1];\n" : "=r"(sd) : "r"(s_side) : "memory");
                if (__shfl_sync(0xffffffffu, v, sd) > __shfl_sync(0xffffffffu, v, sd ^ 1) + 4) sd ^= 1;
                unsigned b = __shfl_sync(0xffffffffu, v, sd ^ 1);
                const bool draw = rank == 0 && lane == 0 && t < NT128 - P1_SPLIT;
                if (draw) u = atomicAdd(cnt + sd * 8, 1u);
                flag_wait<true>(&g_flag[slot][0][0], 4 * round + 4);
                TRACEW(i, 2);
                asm volatile("fence.proxy.async.global;\n" ::: "memory");
                int next = NT128, more = 0;
                if (draw) {
                    if (u >= LIM) { sd ^= 1; b = u; u = atomicAdd(cnt + sd * 8, 1u); }
                    next = u < LIM ? NGRP + 2 * u + sd : NT128 - P1_SPLIT + atomicAdd(&g_flag[LN_RING + 3 + (cig >> 1)][first & 1][0], 1u);
                    more = u < LIM ? 3 : next < NT128;
                    if (!sent && min(u, b) >= (NT_EARLY - NGRP) / 2) { sent = 1; more += 4; }
                }
                next = __shfl_sync(0xffffffffu, next, 0);
                more = __shfl_sync(0xffffffffu, more, 0);
                const uint32_t ht = h_tile(t, __shfl_sync(0xffffffffu, v, 2));
                const uint32_t src = ln_tile(t, __shfl_sync(0xffffffffu, v, 3)) ^ ln_rows(2 * rank);
#pragma unroll 1
                for (int h = 0; h < P1_NST; h++) {
                    mbar_wait(bar_empty + h * 8, i & 1);
                    if (h == 0) TRACEW(i, 4);
                    if (h == 5) TRACEW(i, 5);
                    if (elect_one()) {
                        mbar_expect_tx(bar_full + h * 8, h ? P1_SLOT : P1_SLOT + 16);
#pragma unroll
                        for (int e = 0; e < 2; e++)
                            bulk_g2s_mc(sbase + h * P1_SLOT + (2 * rank + e) * 4096, h_base() + ((src ^ ln_rows(e)) + ln_block(h)), 4096, bar_full + h * 8, (uint16_t)3);
                    }
                    __syncwarp();
                    if (h == 0 && rank == 0 && lane < 2)
                        asm volatile("st.async.shared::cluster.mbarrier::complete_tx::bytes.v4.u32 [%0], {%1, %2, %3, %3}, [%4];\n"
                                     ::"r"(rbase + P1_OFF_TILE + (i & 3) * 16), "r"(ht), "r"(more), "r"(next),
                                       "r"(rbase + P1_OFF_BAR) : "memory");
                }
                t = next;
                if (rank != 0) {
                    mbar_wait(bar_full, i & 1);
                    asm volatile("ld.shared.u32 %0, [%1];\n" : "=r"(t) : "r"(sbase + P1_OFF_TILE + (i & 3) * 16 + 8) : "memory");
                }
            }
        } else if (warp == 13) {
            const unsigned tag = 2 * __ldcg(&g_epoch) + 2;
            int u = -1, side = 0;
            auto item = [&](int k) {
                if (k < LN_SW / LN_STEP) return (int)blockIdx.x + k * NUM_CTAS;
                while (u < 0) {
                    asm volatile("ld.volatile.shared.u32 %0, [%1];\n" : "=r"(u) : "r"(s_cl) : "memory");
                    side = u & 1;
                    if (u >= 0) u = (u & ~1) + rank;
                    SAFE_BREAK;
                }
                const int v = u + (k - LN_SW / LN_STEP) * (NUM_CTAS / 2);
                return 4 * LN_SW + (v >> 2) * 8 + side * 4 + (v & 3);
            };
#pragma unroll 1
            for (int k = 1;; k++) {
                const int q = item(k), round = q / (4 * LN_RING), slot = (q >> 2) - round * LN_RING;
                mbar_wait(bar_xempty, ~k & 1);
                if (elect_one()) {
                    mbar_expect_tx(bar_xfull, P1_X);
                    bulk_g2s(sbase + P1_OFF_X, reinterpret_cast<const uint8_t*>(x) + (size_t)q * P1_X, P1_X, bar_xfull);
                }
                __syncwarp();
                const uint32_t place = ln_place(q, tag), more = k < LN_SW / LN_STEP || item(k + 1) < 4 * NT128;
                const uint32_t off = flag_wait<false>(&g_flag[slot][1][0], round * (GRP_CTAS / 2));
                if (elect_one()) {
                    asm volatile("st.shared.v4.u32 [%0], {%1, %2, %3, %4};\n" ::"r"(s_item + (k & 1) * 16), "r"(off), "r"(place), "r"(slot), "r"(more) : "memory");
                    mbar_arrive(bar_xfull);
                }
                __syncwarp();
                if (!more) break;
            }
        } else if (warp == 15) {
            int t = first;
            if (rank == 1 && lane == 0) mbar_arrive(bar_empty);
#pragma unroll 1
            for (int i = 0; rank == 1 && t < NT128; i++) {
#pragma unroll 1
                for (int h = 0; h < P1_NST; h++) mbar_wait(bar_full + h * 8, i & 1);
                if (lane == 0) asm volatile("red.relaxed.gpu.global.add.u32 [%0], 1;\n" ::"l"(&g_flag[t % LN_RING][1][0]) : "memory");
                asm volatile("ld.shared.u32 %0, [%1];\n" : "=r"(t) : "r"(sbase + P1_OFF_TILE + (i & 3) * 16 + 8) : "memory");
                if (lane == 0) mbar_arrive(bar_empty);
                TRACEW(i, 3);
            }
            if (rank == 0) {
                {
                    const int me = blockIdx.x >> 1;
                    const int page = lane < 2 ? 0 : H_FIXED + me + (lane / 2 - 1) * (NUM_CTAS / 2);
                    if (page < H_PAGES) h_cell(page, me)[(lane & 1) * 1024] = 0;
                    __syncwarp();
                    if (lane == 0) {
                        const unsigned tag = 2 * __ldcg(&g_epoch) + 2;
                        const unsigned side = near_half(h_cell(0, me));
                        asm volatile("st.volatile.shared.u32 [%0], %1;\n" ::"r"(s_side), "r"(side) : "memory");
                        const unsigned u = atomicAdd(reinterpret_cast<unsigned*>(g_sums) + C_DIM + 64 + side, 1u);
                        const unsigned cl = u < NUM_CTAS / 4 ? 2 * u + side : NUM_CTAS - 2 - 2 * u + (side ^ 1);
#pragma unroll
                        for (int r = 0; r < 2; r++) asm volatile("st.shared::cluster.u32 [%0], %1;\n" ::"r"(mapa(s_cl, r)), "r"(cl) : "memory");
#pragma unroll 1
                        for (int p = H_FIXED + me; p < H_PAGES; p += NUM_CTAS / 2)
                            asm volatile("st.relaxed.gpu.global.u32 [%0], %1;\n" ::"l"(&g_page[p]), "r"(tag + (near_half(h_cell(p, me)) ^ side)) : "memory");
                    }
                    __syncwarp();
                }
                TRACEW(110 + warp, 3);
                mbar_wait(bar_full, 0);
                mbar_wait(bar_full, 1);
                float* sums = g_sums;
                unsigned* flag = reinterpret_cast<unsigned*>(sums + C_DIM);
                if (blockIdx.x == 0) reinterpret_cast<uint2*>(g_half)[lane] = make_uint2(0, 0);
                if (blockIdx.x == 2 && lane < NUM_CNT) g_prog[lane][0] = 0;
                if (blockIdx.x < 96) g_redo[blockIdx.x * 16 + lane] = 0.f;
                float gs = 0.f;
#pragma unroll 1
                for (int pass = 0; pass < 2; pass++) {
                    float mx = 0.f;
#pragma unroll 1
                    for (int it = (blockIdx.x + zero) / GRP_CTAS; it < 96; it += NGRP) {
                        const int nb = it % 12, k0 = (cig * 4 + it / 12) * 64 + (lane >> 2);
                        const uint32_t sc = mapa(sbase + P1_OFF_EX + (k0 & 255) * 4, it / 48);
                        uint32_t* dst = reinterpret_cast<uint32_t*>(g_w2img[0]) + (k0 >> 4) * 3072 + nb * 256 + lane;
                        float bs[8] = {};
#pragma unroll 1
                        for (int c = 0; c < 8; c++) {
                            const uint4 u = __ldg(reinterpret_cast<const uint4*>(w2 + (size_t)(k0 + c * 8) * C_DIM + nb * 32) + (lane & 3));
                            const float b = __bfloat162float(grn_b[k0 + c * 8]);
                            float t;
                            asm volatile("ld.shared::cluster.f32 %0, [%1];\n" : "=f"(t) : "r"(sc + c * 32) : "memory");
                            if (nb == 0) g_scale[k0 + c * 8] = t;
#pragma unroll
                            for (int j = 0; j < 4; j++) {
                                const uint32_t v = j == 0 ? u.x : j == 1 ? u.y : j == 2 ? u.z : u.w;
                                mx = fmaxf(mx, fmaxf(fabsf(bf_lo(v)), fabsf(bf_hi(v))) * t);
                                if (pass) {
                                    bs[2 * j] = fmaf(b, bf_lo(v), bs[2 * j]);
                                    bs[2 * j + 1] = fmaf(b, bf_hi(v), bs[2 * j + 1]);
                                    uint32_t h = pack_f16(bf_lo(v) * t * gs, bf_hi(v) * t * gs);
                                    asm volatile("movmatrix.sync.aligned.m8n8.trans.b16 %0, %0;\n" : "+r"(h));
                                    dst[(c >> 1) * 3072 + (c & 1) * 32 + j * 64] = h;
                                }
                            }
                        }
                        if (pass) {
#pragma unroll
                            for (int j = 0; j < 8; j++) {
#pragma unroll
                                for (int o = 4; o < 32; o <<= 1) bs[j] += __shfl_xor_sync(0xffffffffu, bs[j], o);
                                if (lane >> 2 == j) atomicAdd(&sums[nb * 32 + (j >> 1) * 8 + (lane & 3) * 2 + (j & 1)], bs[j]);
                            }
                        }
                    }
                    if (!pass) {
                        const uint32_t m = __reduce_max_sync(0xffffffffu, __float_as_uint(mx));
                        __threadfence();
                        __syncwarp();
                        if (lane == 0) {
                            atomicMax(flag, m);
                            asm volatile("red.release.gpu.global.add.u32 [%0], 1;\n" ::"l"(flag + 32) : "memory");
                        }
                        flag_wait<true>(flag + 32, NUM_CTAS / 2);
                        gs = w2_scale(__ldcg(flag));
                    }
                }
                asm volatile("fence.proxy.async.global;\nfence.acq_rel.gpu;\n" ::: "memory");
                __syncwarp();
                if (lane == 0) asm volatile("red.relaxed.gpu.global.add.u32 [%0], 1;\n" ::"l"(g_prog[CNT_IMG0]) : "memory");
            }
        } else if (warp == 14) {
#pragma unroll 1
            for (uint32_t k = 0, more = 1; more; k++) {
                uint32_t slot;
                mbar_wait(bar_done, k & 1);
                asm volatile("ld.shared.v2.u32 {%0, %1}, [%2];\n" : "=r"(slot), "=r"(more) : "r"(s_item + (k & 1) * 16 + 8) : "memory");
                if (lane == 0) mbar_arrive(bar_xfull + (slot & zero));
                TRACEW(k, 0);
                asm volatile("fence.proxy.async.global;\n" ::: "memory");
                if (elect_one()) asm volatile("red.release.gpu.global.add.u32 [%0], 1;\n" ::"l"(&g_flag[slot][0][0]) : "memory");
                __syncwarp();
                TRACEW(k, 1);
            }
            if (lane == 0) p2_init(sbase);
#pragma unroll 1
            for (int i = CNT_EARLY; i >= CNT_H; i--) {
                bar_sync(i == CNT_EARLY ? 8 : 3, 288);
                asm volatile("fence.proxy.async.global;\n" ::: "memory");
                if (lane == 0) asm volatile("red.release.gpu.global.add.u32 [%0], 1;\n" ::"l"(&g_prog[i][0]) : "memory");
                __syncwarp();
            }
        }
        __syncwarp();
        asm volatile("barrier.cluster.arrive.relaxed.aligned;\n" ::: "memory");
        return false;
    } else if (ROLE == 1) {
        reg_dec<96>();
        asm volatile("barrier.cluster.arrive.relaxed.aligned;\n" ::: "memory");
        {
            const int l8 = lane & 7;
            uint32_t d[6][4];
            const int n = perm32(2 * ((warp - 8) * 4 + (lane >> 3)));
            const uint32_t dst0 = n * 128 + ((l8 ^ (n & 7)) << 4);
            const uint32_t src = sbase + P1_OFF_X + ((warp - 8) * 8 + (lane >> 3)) * (C_DIM * 2) + l8 * 16;
            uint32_t off = 1, place = ln_place(blockIdx.x & 255, 0), more = 1;
            LAG_HERE(0);
#pragma unroll 1
            for (int i = 0; more; i++) {
                TRACE(2, i, 0);
#pragma unroll 1
                for (int ps = i == 0 ? -2 : 0; ps < 2; ps += ps < 0 ? 2 : 1) {
                    if (ps == 0) {
                        uint32_t slot;
                        if (i == 0) asm volatile("barrier.cluster.wait.aligned;\n" ::: "memory");
                        mbar_wait(bar_xfull, i & 1);
                        asm volatile("ld.shared.v4.u32 {%0, %1, %2, %3}, [%4];\n" : "=r"(off), "=r"(place), "=r"(slot), "=r"(more) : "r"(s_item + (i & 1) * 16) : "memory");
                    }
                    if (ps == 0) TRACE(2, i, 1);
                    if (i == 0) {
#pragma unroll
                        for (int j = 0; j < 6; j++)
                            asm volatile("ld.shared.v4.u32 {%0,%1,%2,%3}, [%4];\n"
                                         : "=r"(d[j][0]), "=r"(d[j][1]), "=r"(d[j][2]), "=r"(d[j][3]) : "r"(sbase + P1_OFF_DW + j * 128 + l8 * 16) : "memory");
                    }
                    uint32_t v[6][4];
#pragma unroll
                    for (int j = 0; j < 6; j++)
                        asm volatile("ld.shared.v4.u32 {%0,%1,%2,%3}, [%4];\n"
                                     : "=r"(v[j][0]), "=r"(v[j][1]), "=r"(v[j][2]), "=r"(v[j][3]) : "r"(src + (ps & 1) * (4 * C_DIM * 2) + j * 128) : "memory");
                    ln_row(v, d, bar_pace + (warp - 8) * 8, off, zero, ps == 1 && lane == 0 ? bar_xempty : 0);
                    uint8_t* dst = h_base() + (place ^ dst0 ^ ln_rows(ps & 1));
#pragma unroll
                    for (int j = 0; j < 6; j++)
                        asm volatile("st.global.v4.u32 [%0], {%1,%2,%3,%4};\n" ::"l"(dst + ln_block(j)), "r"(v[j][0]), "r"(v[j][1]), "r"(v[j][2]), "r"(v[j][3]) : "memory");
                    TRACE(2, i, 3 + (ps & 1));
                }
                asm volatile("fence.proxy.async.global;\nfence.acq_rel.cta;\n" ::: "memory");
                __syncwarp();
                if (lane == 0) mbar_arrive(bar_done);
                TRACE(2, i, 5);
                TRACE(2, i, 2);
            }
        }
        __syncwarp();
        asm volatile("barrier.cluster.arrive.relaxed.aligned;\n" ::: "memory");
        return false;
    } else {
        const int wg = warp >> 2, w = warp & 3;
        auto load_w = [&](int i0, int i1) {
#pragma unroll 1
            for (int i = i0; i < i1; i++) {
                if (!(i & 1)) mbar_expect_tx(bar_w + (i >> 1) * 8, P1_W);
                tma2(sbase + (i & 2) * P1_W + (i >> 2) * P1_W + (i & 1) * (P1_W / 2), &wmap, cig * 256 + ((i >> 1) ^ (first & 1) * 2) * 64, (i & 1) * 192, bar_w + (i >> 1) * 8);
            }
        };
        if (warp == 4 && elect_one()) {
            mbar_init(bar_xfull, 3);
#pragma unroll
            for (int i = 0; i < 4; i++) mbar_init(bar_w + i * 8, 1);
            asm volatile("fence.mbarrier_init.release.cluster;\n" ::: "memory");
            mbar_expect_tx(bar_xfull, P1_X + C_DIM * 2);
            bulk_g2s(sbase + P1_OFF_X, reinterpret_cast<const uint8_t*>(x) + (size_t)blockIdx.x * P1_X, P1_X, bar_xfull);
            bulk_g2s(sbase + P1_OFF_DW, dw, C_DIM * 2, bar_xfull);
            load_w(0, 4);
            asm volatile("st.shared.v4.u32 [%0], {1, %1, %2, 1};\n" ::"r"(s_item), "r"(ln_place(blockIdx.x & 255, 0)), "r"(blockIdx.x >> 2) : "memory");
            mbar_arrive(bar_xfull);
            mbar_arrive(bar_xfull);
        }
        if (warp == 5 && elect_one()) {
#pragma unroll
            for (int i = 0; i < P1_NST; i++) {
                mbar_init(bar_full + i * 8, 1);
                mbar_init(bar_empty + i * 8, i ? 8 : 8 + rank);
                if (i < 4) mbar_init(bar_pace + i * 8, 1);
            }
            mbar_init(bar_xempty, 4);
            mbar_init(bar_done, 4);
            asm volatile("st.shared.u32 [%0], %1;\n" ::"r"(s_side), "r"(first & 1) : "memory");
            asm volatile("st.shared.u32 [%0], -1;\n" ::"r"(s_cl) : "memory");
            asm volatile("fence.mbarrier_init.release.cluster;\n" ::: "memory");
        }
        __syncwarp();
        asm volatile("barrier.cluster.arrive.relaxed.aligned;\n" ::: "memory");
        reg_inc<192>();
        TRACEW(110 + warp, 1);
        LAG_HERE(0);
        uint32_t a[24][4];
        const uint32_t src = sbase + wg * P1_W + ((lane >> 4) * 8 + (lane & 7)) * 128 + (((2 * w + ((lane >> 3) & 1)) ^ (lane & 7)) << 4);
        const uint32_t s_ex = sbase + P1_OFF_EX + ((wg ^ (first & 1)) * 128 + w * 16 + (lane >> 2)) * 4;
        uint32_t sc2[2], ex[2];
        if (wg == 1) bar_arrive(1, 256);
#pragma unroll 1
        for (int it = 0; it < 2; it++) {
          if (it != wg) asm volatile("barrier.cluster.wait.aligned;\n" ::: "memory");
          if (it < wg) {
#pragma unroll 1
              for (int n = 0; n < 64 && !mbar_test(bar_xfull, 0); n++) __nanosleep(40);
              if (w == 0 && elect_one()) load_w(4, 8);
              __syncwarp();
          }
          if (it || wg == 0) {
            float t[2] = {0.f, 0.f};
            if (it) {
                TRACEW(110 + warp, 2);
                mbar_wait(bar_w + wg * 16, 0);
            }
            TRACEW(110 + warp, 5);
#pragma unroll
            for (int k = 0; k < 24; k++) ldsm4t(a[k], src + k * 2048);
            TRACEW(110 + warp, 6);
            p1_squares(a, t);
            sc2[0] = p1_exponents(t, ex, s_ex, lane);
            if (it && lane < 6) mbar_arrive_cluster(mapa(bar_empty, lane & 1) + (wg * 3 + (lane >> 1)) * 8 + (sc2[0] & zero));
            p1_convert<24>(a, a, ex);
          }
          if (it || wg == 1) {
            float t[2] = {0.f, 0.f};
            TRACEW(100 + warp, 0);
            if (it) mbar_wait(bar_w + wg * 16 + 8, 0);
            TRACEW(100 + warp, 1);
            uint32_t v[8][4], o[8][4];
#pragma unroll 1
            for (int j = 0; j <= 2 * it; j++) {
#pragma unroll
                for (int k = 0; k < 8; k++) ldsm4t(v[k], src + P1_OFF_W + (8 * j + k) * 2048);
                p1_squares(v, t);
            }
            sc2[1] = p1_exponents(t, ex, s_ex + 256, lane);
#pragma unroll 1
            for (int j = 2 * it; j >= 0; j--) {
                p1_convert<8>(o, v, ex);
#pragma unroll
                for (int k = 0; k < 8; k++) {
                    if (j) ldsm4t(v[k], src + P1_OFF_W + (8 * j - 8 + k) * 2048);
                    if (it) asm volatile("stmatrix.sync.aligned.m8n8.x4.trans.shared.b16 [%0], {%1,%2,%3,%4};\n"
                                         ::"r"(src + P1_OFF_W + (8 * j + k) * 2048), "r"(o[k][0]), "r"(o[k][1]), "r"(o[k][2]), "r"(o[k][3]) : "memory");
                }
            }
          }
        }
        asm volatile("fence.proxy.async.shared::cta;\n" ::: "memory");
        TRACEW(110 + warp, 7);
        bar_sync(6 + wg, 128);
        const bool early = p1_consumer(a, sc2, sbase, wg, w, lane, zero);
        TSTAMP(0, 30);
        return early;
    }
}

constexpr int P2_B = 24576, P2_NB = 4;
constexpr int P2_A = 3072, P2_NA = 8;
constexpr int P2_XROW = C_DIM * 2;
constexpr int P2_OFF_A = P2_B * P2_NB;
constexpr int P2_OFF_X = P2_OFF_A + 3 * P2_NA * P2_A + 128;
constexpr int P2_LHALF = 2 * P2_NA * P2_A + 64;
constexpr int P2_XHALF = 32 * P2_XROW + 64;
constexpr int P2_OFF_GRN = P2_OFF_X + 64 * P2_XROW + 128;
constexpr int P2_OFF_BIAS = P2_OFF_GRN + HID * 2;
constexpr int P2_OFF_RED = P2_OFF_BIAS + C_DIM * 4;
constexpr int P2_OFF_BAR = P2_OFF_RED + 192;
constexpr int P2_SMEM = P2_OFF_BAR + (2 * P2_NB + 6 * P2_NA + 7) * 8;
constexpr int P2_S1 = 16, P2_S2 = 32;
constexpr int P2_NCL = NUM_CTAS / 2, P2_ITEMS = NT128 / P2_NCL, P2_SHARED = NT128 - P2_ITEMS * P2_NCL;
constexpr int P2_NPOS = 6 * 48 + P2_S1;
constexpr int P2_RAW = 16;
constexpr int P2_XC = 8 * P2_XROW;
constexpr int P2_T0 = 5;
constexpr int P2_TL = 8;
constexpr int P2_XP0 = 30;
constexpr int P2_XPN = 13;
constexpr int P2_XPD = 3;
constexpr int P2_AH = 2;
__device__ __forceinline__ int p2_start(int n) { return n < 0 ? 0 : n / 3 * 48 + (n % 3 == 1 ? P2_S1 : n % 3 * (P2_S2 / 2)); }
__device__ __forceinline__ int p2_tile(int cl, int n) {
    return n == 0 ? NT_EARLY - P2_NCL + cl : n < 0 ? NT_EARLY + (cl >> 2) * 2 + (cl & 1) : cl + P2_NCL * (n - 1);
}

__device__ __forceinline__ void p2_epilogue(uint32_t (&acc0)[48], uint32_t (&acc1)[48], uint32_t up, uint32_t sx, uint32_t sb, uint8_t* so, int zero) {
    uint32_t v[12][3][4];
    auto load = [&](int t, int j) {
        if (t >= 12) return;
        uint32_t (&w)[4] = v[t][j];
        asm volatile("ld.shared.v4.u32 {%0,%1,%2,%3}, [%4];\n" : "=r"(w[0]), "=r"(w[1]), "=r"(w[2]), "=r"(w[3])
                     : "r"((j ? sx + (j - 1) * 4 * P2_XROW : sb) + t * 64) : "memory");
    };
    auto store = [&](int t, int r) {
        const uint32_t* w = (t < 6 ? acc0 : acc1) + 8 * (t % 6) + 4 * r;
        asm volatile("st.v4.u32 [%4], {%0,%1,%2,%3};\n" ::"r"(w[0]), "r"(w[1]), "r"(w[2]), "r"(w[3]), "l"(so + t * 64 + r * 4 * P2_XROW) : "memory");
    };
#pragma unroll
    for (int j = 0; j < 3; j++) load(0, j);
#pragma unroll
    for (int t = 0; t < 12; t++) {
        load(t + 1, 1);
        load(t + 1, 2);
        load(t + 1, 0);
        uint32_t* acc = (t < 6 ? acc0 : acc1) + 8 * (t % 6);
        uint32_t y[8];
#pragma unroll
        for (int e = 0; e < 8; e++) {
            y[e] = h2_add(acc[e], v[t][0][e >> 1]);
            y[e] = pack_bf16(h_lo(y[e]), h_hi(y[e]));
        }
#pragma unroll
        for (int e = 0; e < 8; e++) acc[(e & 1) * 4 + (e >> 1)] = bf2_fma(y[e], up, v[t][1 + (e & 1)][e >> 1]);
        store(t, 0);
        store(t, 1);
        if (t & 1) sched_break(zero);
    }
}

__device__ __forceinline__ void p2_unpack(uint32_t (&u)[4], uint32_t o1, uint32_t o2, uint32_t o3) {
    u[2] = o1 & ~SPARE;
    u[1] = o2 & ~SPARE;
    u[3] = o3 & ~SPARE;
    const uint32_t t = bitsel(prmt(o1, o2, 0x6341), prmt(o1, o3, 0x6240) << 3, 0x38383838u);
    u[0] = bitsel(t, prmt(o2, o3, 0x7351) << 1, 0x80808080u) & ~SPARE;
}

__device__ __forceinline__ void p2_redo_sums(int warp, int lane) {
    flag_wait<true>(g_prog[CNT_H], NUM_CTAS);
#pragma unroll 1
    for (int s = warp; s < 96; s += 12) {
        float t[2] = {0.f, 0.f};
#pragma unroll 1
        for (int tile = blockIdx.x; tile < 2 * NT128; tile += NUM_CTAS) {
            const uint32_t* p = reinterpret_cast<const uint32_t*>(h_base() + (h_tile(tile >> 1) ^ h_block(s >> 1, tile & 1)) + (s & 1) * 1536) + lane * 4;
#pragma unroll
            for (int j = 0; j < 4; j++) {
                uint32_t u[4];
                p2_unpack(u, __ldcg(p + j), __ldcg(p + j + 128), __ldcg(p + j + 256));
#pragma unroll
                for (int c = 0; c < 4; c++) t[c >> 1] += h_lo(u[c]) * h_lo(u[c]) + h_hi(u[c]) * h_hi(u[c]);
            }
        }
#pragma unroll
        for (int r = 0; r < 2; r++) {
            const int ch = s * 16 + r * 8 + (lane >> 2);
            atomicAdd(&g_redo[ch], t[r] * (UNCHOP * UNCHOP));
        }
    }
    __threadfence();
    __syncwarp();
    if (lane == 0) asm volatile("red.release.gpu.global.add.u32 [%0], 1;\n" ::"l"(g_prog[CNT_REDO]) : "memory");
    flag_wait<true>(g_prog[CNT_REDO], 12 * NUM_CTAS);
}

static_assert(P2_OFF_GRN >= P1_OFF_X + P1_X && P1_OFF_BAR >= P2_SMEM, "barriers and tables keep their memory");
__device__ __forceinline__ void p2_init(uint32_t sbase) {
    const uint32_t bar = sbase + P2_OFF_BAR;
#pragma unroll 1
    for (int i = 0; i < 2 * P2_NB + 6 * P2_NA + 6; i++) {
        const int j = i - 2 * P2_NB;
        mbar_init(bar + i * 8, j < -P2_NB ? 1 : j < 0 ? 24 : j < 3 * P2_NA ? 1 : j >= 6 * P2_NA && j < 6 * P2_NA + 3 ? 2 : 4);
    }
    asm volatile("st.shared.v2.u32 [%0], {0, 0};\n" ::"r"(bar + (2 * P2_NB + 6 * P2_NA + 6) * 8) : "memory");
    asm volatile("fence.mbarrier_init.release.cluster;\nfence.acq_rel.cta;\n" ::: "memory");
}
template <int ROLE>
__device__ __forceinline__ void pass2(const __nv_bfloat16* __restrict__ x, const __nv_bfloat16* __restrict__ grn_g, __nv_bfloat16* __restrict__ out,
                                      uint8_t* smem, uint32_t sbase, bool early, int zero) {
    const uint32_t bar_bfull = sbase + P2_OFF_BAR, bar_bempty = bar_bfull + P2_NB * 8;
    const uint32_t bar_afull = bar_bempty + P2_NB * 8, bar_aempty = bar_afull + 3 * P2_NA * 8;
    const uint32_t bar_xfull = bar_aempty + 3 * P2_NA * 8, bar_oready = bar_xfull + 24, s_pos = bar_oready + 24;
    int tid;
    asm volatile("mov.u32 %0, %%tid.x;\n" : "=r"(tid));
    const int warp = __shfl_sync(0xffffffffu, tid >> 5, 0), lane = tid & 31;
    const uint32_t rank = cluster_rank();
    int cl, pair, half, fin, k0;
    auto join = [&]() {
        asm volatile("barrier.cluster.wait.aligned;\nld.shared.u32 %0, [%1];\n" : "=r"(cl) : "r"(sbase + OFF_PRE + C_DIM * 4 + 8) : "memory");
        cl = __shfl_sync(0xffffffffu, cl, 0);
        pair = (cl >> 2) * 2 + (cl & 1);
        half = pair < P2_SHARED;
        fin = half && (cl & 2);
        k0 = (pair + 3 * ((cl >> 1) & 1)) % 6 * 8;
    };
    auto wait_pos = [&](int target) {
        int v;
        while (true) {
            asm volatile("ld.volatile.shared.u32 %0, [%1];\n" : "=r"(v) : "r"(s_pos) : "memory");
            if (v >= target) break;
            SAFE_BREAK;
            __nanosleep(100);
        }
    };

    TSTAMP(1, 0);
    LAG_HERE(1);
    if (ROLE == 2) {
        if (warp != 14) flag_wait<true>(g_prog[CNT_IMG0], P2_NCL);
        if (warp == 15) {
            float* pre = reinterpret_cast<float*>(smem + OFF_PRE);
            const float gs = w2_scale(__float_as_uint(__ldcg(&g_sums[C_DIM])));
            float mb = 0.f;
#pragma unroll 1
            for (int i = lane; i < C_DIM; i += 32) {
                pre[i] = __ldcg(&g_sums[i]) * gs;
                mb = fmaxf(mb, fabsf(pre[i]));
            }
            pre[C_DIM] = gs;
            pre[C_DIM + 1] = __uint_as_float(__reduce_max_sync(0xffffffffu, __float_as_uint(mb)));
            bar_sync(9, 288);
            flag_wait<false>(g_prog[CNT_LAST], NUM_CTAS * 8);
            bar_arrive(5, 416);
        }
        join();
        asm volatile("fence.proxy.async;\n" ::: "memory");
        LAG_HERE(2);
        if (warp == 12) {
            const uint8_t* wsrc = reinterpret_cast<const uint8_t*>(g_w2img) + rank * (P2_B / 2);
            int kb = k0;
#pragma unroll 1
            for (int p = 0; p < P2_NPOS; p++) {
                const int st = p & 3;
                if (p == P2_RAW) {
                    flag_wait<true>(g_prog[CNT_IMG1], NUM_CTAS);
                    asm volatile("fence.proxy.async.global;\n" ::: "memory");
                    wsrc += sizeof(g_w2img[0]);
                }
                const int idle = (p < P2_S1 || p >= 6 * 48) + (p < P2_S2 ? !half || p >= 24 : p >= 5 * 48 + P2_S2);
                mbar_wait(bar_bempty + st * 8, (~p >> 2) & 1);
                TR2(3, p, 0);
                if (elect_one()) {
                    mbar_expect_tx(bar_bfull + st * 8, P2_B);
                    bulk_g2s_mc(sbase + st * P2_B + rank * (P2_B / 2), wsrc + kb * P2_B, P2_B / 2, bar_bfull + st * 8, (uint16_t)3);
                    asm volatile("st.volatile.shared.u32 [%0], %1;\n" ::"r"(s_pos), "r"(p) : "memory");
                    if (rank == 0) asm volatile("red.relaxed.gpu.global.add.u32 [%0], 1;\n" ::"l"(g_prog[CNT_POS]) : "memory");
                    if (idle) asm volatile("mbarrier.arrive.shared::cta.b64 _, [%0], %1;\n" ::"r"(bar_bempty + st * 8), "r"(8 * idle) : "memory");
                }
                __syncwarp();
                if (++kb == 48) kb = 0;
            }
            mbar_wait(bar_bempty, 1);
            if (lane == 0) mbar_arrive(bar_bfull);
        } else if (warp == 13) {
            const int w = lane % 3;
            const uint32_t dst0 = sbase + P2_OFF_A + w * P2_NA * P2_A;
            const uint32_t bf = bar_afull + w * P2_NA * 8, be = bar_aempty + w * P2_NA * 8;
            int n = (w == 2 && half ? -1 : w) - 3, left = 0, u = 0, c = 0;
            const uint8_t* const hb = h_base();
            uint32_t ht = 0;
            bool act = lane < 3;
            auto next = [&]() {
                n += 3;
                left = n >= P2_ITEMS ? -1 : n < 0 ? 24 : 48;
                u = (k0 + p2_start(n)) % 48;
                if (left > 0) ht = h_tile(p2_tile(cl, n));
            };
            next();
            flag_wait<true>(g_prog[CNT_EARLY], NUM_CTAS);
#pragma unroll 1
            for (int i = 3; i > 0; i--) {
                const int wi = i % 3;
                if (wi == 2) flag_wait<true>(g_prog[CNT_H], NUM_CTAS);
                asm volatile("fence.proxy.async.global;\n" ::: "memory");
                if (w == wi && lane < 24) {
                    mbar_expect_tx(bf + lane / 3 * 8, P2_A);
                    bulk_g2s(dst0 + lane / 3 * P2_A, hb + (ht ^ h_block(u + lane / 3, rank)), P2_A, bf + lane / 3 * 8);
                }
                __syncwarp();
            }
            c = 8;
            left -= 8;
            u += 8;
            if (u == 48) u = 0;
            while (__any_sync(0xffffffffu, act)) {
                if (left == 0) next();
                const bool ok = act && mbar_test(be + ((c - 1) & 7) * 8, (~c >> 3) & 1);
                if (ok) {
                    const int st = c & 7;
                    if (left > 0) {
                        mbar_expect_tx(bf + st * 8, P2_A);
                        bulk_g2s(dst0 + st * P2_A, hb + (ht ^ h_block(u, rank)), P2_A, bf + st * 8);
                    } else {
                        mbar_arrive(bf + st * 8);
                        act = false;
                    }
                    if (++u == 48) u = 0;
                    c++;
                    left--;
                }
                SAFE_BREAK;
                if (!__any_sync(0xffffffffu, ok)) __nanosleep(100);
            }
        } else if (warp == 14) {
            const uint32_t sx = sbase + P2_OFF_X;
            size_t o = 0;
            int wp = 0;
            uint32_t par = 0;
            if (fin) {
#pragma unroll 1
                for (int c = lane * 16; c < 64 * P2_XROW + 128; c += 512) asm volatile("st.shared.v4.u32 [%0], {0, 0, 0, 0};\n" ::"r"(sx + c) : "memory");
                __syncwarp();
            }
            wait_pos(6);
#pragma unroll 1
            for (int n = -half; n < P2_ITEMS; n++) {
                const int w = (n + 3) % 3, end = p2_start(n) + 48;
                const size_t on = (size_t)(2 * p2_tile(cl, n) + rank) * (64 * C_DIM * 2);
                const uint32_t xf = bar_xfull + w * 8;
                if (n < 2 || n > 12) { LAG_HERE(3); }
                bool st = n + half > 0;
                const bool ld = n < P2_ITEMS - 1 && !(n < 0 && fin);
                if (n == P2_ITEMS - 1 && lane == 0) {
                    mbar_expect_tx(xf, 64 * C_DIM * 2);
#pragma unroll 1
                    for (int c = 4; c < 12; c++) {
                        if (c >= 8) {
                            mbar_wait(bar_aempty + ((2 * c - 1) & 7) * 8, 1);
                            mbar_wait(bar_aempty + ((2 * c) & 7) * 8, 1);
                        }
                        bulk_g2s(sbase + P2_OFF_A + (c & 3) * P2_XC + (c < 8 ? P2_LHALF : 0), reinterpret_cast<const uint8_t*>(x) + on + (c & 7) * P2_XC, P2_XC, xf);
                    }
                    mbar_arrive(xf);
                }
                if (st) {
                    mbar_wait(bar_oready + wp * 8, (par >> wp) & 1);
                    par ^= 1u << wp;
                }
                if (lane == 0) {
                    if (n < P2_ITEMS - 1) mbar_expect_tx(xf, ld ? 64 * C_DIM * 2 : 0);
                    const int t0 = (n ? p2_start(n - 1) + 48 : P2_S2) + (n == P2_ITEMS - 1 ? P2_TL : P2_T0), dt = end - t0;
                    int t = st ? 16 * t0 : -4096;
                    if (n == 0 && half) {
                        if (fin) {
                            flag_wait<true>(&g_half[pair][rank], 1);
                            asm volatile("fence.proxy.async.global;\n" ::: "memory");
                        }
#pragma unroll 1
                        for (int c = 0; c < 2; c++) {
                            uint8_t* dst = reinterpret_cast<uint8_t*>(out) + o + c * 32 * P2_XROW;
                            if (!fin) bulk_s2g(dst, sx + c * P2_XHALF, 32 * P2_XROW);
                            else asm volatile("cp.reduce.async.bulk.global.shared::cta.bulk_group.add.noftz.bf16 [%0], [%1], %2;\n"
                                              ::"l"(dst), "r"(sx + c * P2_XHALF), "r"(32 * P2_XROW) : "memory");
                        }
                        asm volatile("cp.async.bulk.commit_group;\n" ::: "memory");
                        if (!fin) {
                            asm volatile("cp.async.bulk.wait_group 0;\nfence.proxy.async.global;\n" ::: "memory");
                            asm volatile("st.release.gpu.global.u32 [%0], 1;\n" ::"l"(&g_half[pair][rank]) : "memory");
                        }
                        st = false;
                    }
#pragma unroll 1
                    for (int c = 0; c < 64 * P2_XROW; c += P2_XC, t += 2 * dt) {
                        const uint32_t sp = sx + c + (c >= 32 * P2_XROW ? 64 : 0);
                        wait_pos(t >> 4);
                        if (st) bulk_s2g(reinterpret_cast<uint8_t*>(out) + o + c, sp, P2_XC);
                        asm volatile("cp.async.bulk.commit_group;\n" ::: "memory");
                        if (ld) {
                            wait_pos((t + dt) >> 4);
                            asm volatile("cp.async.bulk.wait_group.read 0;\n" ::: "memory");
                            bulk_g2s(sp, reinterpret_cast<const uint8_t*>(x) + on + c, P2_XC, xf);
                        }
                    }
                    if (rank == 0 && n > 0 && n < P2_ITEMS - 2) flag_wait<false>(g_prog[CNT_POS], P2_NCL * (end - 1));
                    if (n < P2_ITEMS - 1) mbar_arrive(xf);
                }
                __syncwarp();
                o = on;
                wp = w;
            }
            asm volatile("cp.async.bulk.wait_group.read 0;\n" ::: "memory");
        } else {
            if (blockIdx.x == 120) {
                wait_pos(P2_RAW);
                for (int i = lane; i < (LN_RING + 6) * 2; i += 32) (&g_flag[0][0][0])[i * 8] = 0;
                for (int i = lane; i < HID; i += 32) g_sq[i] = 0;
                for (int i = lane; i < 512; i += 32) g_sums[i] = 0.f;
                if (lane == 0) g_epoch++;
            }
            int t = 4 * P2_XP0;
#pragma unroll 1
            for (int n = 0; n < P2_ITEMS && lane == 0; n++) {
                const uint8_t* xn = reinterpret_cast<const uint8_t*>(x) + (size_t)(2 * p2_tile(cl, n) + rank) * (64 * C_DIM * 2);
#pragma unroll 1
                for (int c = 0; c < 16; c++, t += n < P2_XPN ? 4 : P2_XPD) {
                    wait_pos(t >> 2);
                    asm volatile("cp.async.bulk.prefetch.L2.global [%0], %1;\n" ::"l"(xn + c * (P2_XC / 2)), "r"(P2_XC / 2) : "memory");
                }
            }
        }
        __syncwarp();
        cluster_sync_relaxed();
    } else {
        const int wg = warp >> 2, w = warp & 3, q = lane & 3;
        const uint32_t af = bar_afull + wg * P2_NA * 8;
        const uint32_t s_a = sbase + P2_OFF_A + wg * P2_NA * P2_A + (lane >> 3) * 512 + (lane & 7) * 64 + ((w ^ ((lane & 7) >> 1)) << 4);
        uint32_t acc0[48], acc1[48], up;
        uint4 a[2][2];

        __nv_bfloat16 gg[4];
#pragma unroll
        for (int i = 0; i < 4; i++) gg[i] = grn_g[tid + 384 * i];
#pragma unroll 1
        for (int it = !early;; it++) {
            float* s_red = reinterpret_cast<float*>(smem + P2_OFF_RED);
            float gx[4], part = 0.f;
            if (it == 1) {
                TSTAMP(1, 27);
                bar_sync(5, 416);
            }
            unsigned long long v[4];
#pragma unroll
            for (int i = 0; i < 4; i++) gx[i] = __ldcg(&g_scale[tid + 384 * i]);
            while (true) {
#pragma unroll
                for (int i = 0; i < 4; i++) asm volatile("ld.relaxed.gpu.global.u64 %0, [%1];\n" : "=l"(v[i]) : "l"(&g_sq[tid + 384 * i]) : "memory");
                SAFE_BREAK;
                if (!it || !__any_sync(0xffffffffu, min(min(v[0], v[1]), min(v[2], v[3])) < (unsigned long long)NGRP << 56)) break;
            }
            TSTAMP(1, 1);
            const float bias = reinterpret_cast<const float*>(smem + OFF_PRE)[tid];
            const float2 pre = *reinterpret_cast<const float2*>(smem + OFF_PRE + C_DIM * 4);
            bool tiny = false;
#pragma unroll
            for (int i = 0; i < 4; i++) {
                const float t = it == 2 ? __ldcg(&g_redo[tid + 384 * i]) : __ull2float_rn(v[i] << 8) * 0x1p-40f;
                tiny |= t < M_TOTAL * 0x1p-19f;
                gx[i] *= gx[i] * t;
            }
            float mg = 0.f;
#pragma unroll
            for (int i = 0; i < 4; i++) {
                asm("sqrt.approx.f32 %0, %1;\n" : "=f"(gx[i]) : "f"(gx[i] * (HSCALE * HSCALE) + 1e-6f));
                part += gx[i];
                gx[i] *= __bfloat162float(gg[i]);
                mg = fmaxf(mg, fabsf(gx[i]));
            }
#pragma unroll
            for (int o = 16; o > 0; o >>= 1) part += __shfl_xor_sync(0xffffffffu, part, o);
            const uint32_t mgw = __reduce_max_sync(0xffffffffu, __float_as_uint(mg));
            TSTAMP(1, 26);
            if (lane == 0) *reinterpret_cast<float2*>(s_red + warp * 2) = make_float2(part, __uint_as_float(mgw));
            if (it) {
                uint32_t redo;
                asm volatile("{\n.reg .pred p;\nsetp.ne.u32 p, %1, 0;\nbar.red.or.pred p, 4, 384, p;\nselp.u32 %0, 1, 0, p;\n}\n"
                             : "=r"(redo) : "r"((uint32_t)(tiny && it == 1)) : "memory");
                if (__shfl_sync(0xffffffffu, redo, 0)) {
                    p2_redo_sums(warp, lane);
                    continue;
                }
            }
            float tot = 0.f;
#pragma unroll
            for (int i = 0; i < 6; i++) {
                const float4 t = *reinterpret_cast<const float4*>(s_red + i * 4);
                tot += t.x + t.z;
                mg = fmaxf(mg, fmaxf(t.y, t.w));
            }
            const float inv = __fdividef(1.0f, tot * (1.0f / HID) + 1e-6f);
            const uint32_t ej = min((__float_as_uint(fmaxf(fmaf(mg, inv, 1.0f) * (HSCALE * UNCHOP), pre.y * 0x1p-13f)) >> 23) + 1, 250u);
            const float dn = __uint_as_float((254u - ej) << 23);
            up = min(ej + 127u - (__float_as_uint(pre.x) >> 23), 254u) * 0x00800080u;
            reinterpret_cast<uint16_t*>(smem + P2_OFF_BIAS + C_DIM * 2)[tid] = 0;
            *reinterpret_cast<__half*>(smem + P2_OFF_BIAS + (tid >> 5) * 64 + (tid & 6) * 8 + (tid & 24) / 2 + (tid & 1) * 2) = __float2half_rn(bias * dn);
#pragma unroll
            for (int i = 0; i < 4; i++) {
                const int k = tid + 384 * i;
                *reinterpret_cast<__half*>(smem + P2_OFF_GRN + (k >> 4) * 32 + (k & 6) * 4 + (k & 8) / 2 + (k & 1) * 2) =
                    __float2half_rn(fmaf(gx[i], inv, 1.0f) * (HSCALE * UNCHOP * dn));
            }
            TSTAMP(1, 25);
            if (it) break;
        }
        join();
        bar_sync(4, 384);
        TSTAMP(1, 28);
        LAG_HERE(2);
        if (wg == 1) {
            constexpr int N = sizeof(g_w2img[0]) / 16, PER = (N + NUM_CTAS - 1) / NUM_CTAS;
            uint4 v[5];
#pragma unroll
            for (int i = 0; i < 5; i++) v[i] = __ldcg(&g_w2img[0][min(blockIdx.x * PER + (tid & 127) + 128 * i, N - 1)]);
#pragma unroll
            for (int i = 0; i < 5; i++) {
                const int j = min(blockIdx.x * PER + (tid & 127) + 128 * i, N - 1);
                const uint32_t* t = reinterpret_cast<const uint32_t*>(smem + P2_OFF_GRN + (j / 768) * 32 + (j & 8) / 2);
                auto sc = [&](uint32_t u, int e) { return (h2_mul(u, t[2 * e]) + 0x00040004u) & 0xfff8fff8u; };
                g_w2img[1][j] = make_uint4(sc(v[i].x, 0), sc(v[i].y, 1), sc(v[i].z, 2), sc(v[i].w, 3));
            }
            asm volatile("fence.proxy.async.global;\n" ::: "memory");
            bar_sync(2, 128);
            if (tid == 128) asm volatile("fence.acq_rel.gpu;\nred.release.gpu.global.add.u32 [%0], 1;\n" ::"l"(g_prog[CNT_IMG1]) : "memory");
        }

        const int who = __shfl_sync(0xffffffffu, lane == 2 ? 0 : lane < 2 ? 1 : 2, lane);
        const uint32_t rel0 = who ? mapa(bar_bempty, lane & 1) : mapa(bar_aempty + wg * P2_NA * 8, rank), rel1 = rel0 + (who ? 0 : 32);
        auto publish = [&]() {
            asm volatile("fence.proxy.async.shared::cta;\n" ::: "memory");
            __syncwarp();
            if (who == 0) mbar_arrive(bar_oready + wg * 8);
        };
        bool ok_a, pend = false;
        uint32_t pa = 0, s_t;
        auto fetch = [&](int j, bool raw) {
            uint32_t o[6], u0[4], u1[4];
            uint2 t0 = make_uint2(0, 0), t1 = t0;
            if (raw) {
                asm volatile("ld.shared.v2.u32 {%0,%1}, [%2];\n" : "=r"(t0.x), "=r"(t0.y) : "r"(s_t + j * 64) : "memory");
                asm volatile("ld.shared.v2.u32 {%0,%1}, [%2];\n" : "=r"(t1.x), "=r"(t1.y) : "r"(s_t + j * 64 + 32) : "memory");
            }
            const bool ok_b = mbar_test(bar_bfull + (j & 3) * 8, j >> 2);
            if (j == 7) pa ^= 1;
            ok_a = mbar_test(af + ((j + 1) & 7) * 8, pa);
            asm volatile("ldmatrix.sync.aligned.m8n8.x4.trans.shared.b16 {%0,%1,%2,%3}, [%4];\n"
                         : "=r"(o[0]), "=r"(o[1]), "=r"(o[2]), "=r"(o[3]) : "r"(s_a + j * P2_A) : "memory");
            asm volatile("ldmatrix.sync.aligned.m8n8.x2.trans.shared.b16 {%0,%1}, [%2];\n"
                         : "=r"(o[4]), "=r"(o[5]) : "r"(s_a + j * P2_A + 2048) : "memory");
            p2_unpack(u0, o[0], o[1], o[2]);
            p2_unpack(u1, o[3], o[4], o[5]);
            if (raw) {
                u0[0] = h2_mul(u0[0], t0.x); u0[1] = h2_mul(u0[1], t0.x); u0[2] = h2_mul(u0[2], t0.y); u0[3] = h2_mul(u0[3], t0.y);
                u1[0] = h2_mul(u1[0], t1.x); u1[1] = h2_mul(u1[1], t1.x); u1[2] = h2_mul(u1[2], t1.y); u1[3] = h2_mul(u1[3], t1.y);
            }
            a[j & 1][0] = make_uint4(u0[0], u0[1], u0[2], u0[3]);
            a[j & 1][1] = make_uint4(u1[0], u1[1], u1[2], u1[3]);
            if (!ok_b) mbar_wait(bar_bfull + (j & 3) * 8, j >> 2);
        };
        auto table = [&](int pos) { s_t = sbase + P2_OFF_GRN + q * 8 + (k0 + pos) % 48 * 64; };
        const uint64_t db0 = make_desc(sbase, 128, 256 + zero);
        auto block8 = [&](bool raw, int pos, int thr0, int mode) {
#pragma unroll
            for (int j = 0; j < 8; j++) {
                const uint64_t db = db0 + (j & 3) * (P2_B / 16);
                if (j == 8 - P2_AH && mode == 1) bar_sync(4, 384);
                TR2(wg, pos + j, 0);
                wg_fence();
                mma_rs_n192(acc0, a[j & 1][0], db);
                mma_rs_n192(acc1, a[j & 1][0], db + 384);
                mma_rs_n192(acc0, a[j & 1][1], db + 768);
                mma_rs_n192(acc1, a[j & 1][1], db + 768 + 384);
                wg_commit();
                if (j == 7 && mode == 2) bar_arrive(4, 384);
                const uint32_t rel = ((j - 1) & 4 ? rel1 : rel0) + ((j - 1) & 3) * 8;
                TR2(wg, pos + j, 1);
                wg_wait<1>();
                TR2(wg, pos + j, 2);
                if (who < (j ? 2 : thr0)) mbar_arrive_cluster(rel);
                if (!ok_a) {
                    if (j == 0 && pend) { publish(); pend = false; }
                    mbar_wait(af + ((j + 1) & 7) * 8, pa);
                }
                TR2(wg, pos + j, 3);
                if (raw && j == 7) table(pos + 8);
                fetch((j + 1) & 7, raw && (j < 7 || pos + 8 < P2_RAW));
            }
        };
        int n = wg == 2 && half ? -1 : wg, pos = p2_start(n);
        uint32_t px = 0;
        wait_pos(pos);
        mbar_wait(af, 0);
        table(pos);
        fetch(0, pos < P2_RAW);
#pragma unroll 1
        for (;; n += 3) {
            TSTAMP(1, 2 + n);
            const int end = pos + (n < 0 ? 24 : 48);
#pragma unroll
            for (int i = 0; i < 48; i += 2) {
                asm volatile("mov.b64 {%0, %1}, 0;\n" : "=r"(acc0[i]), "=r"(acc0[i + 1]));
                asm volatile("mov.b64 {%0, %1}, 0;\n" : "=r"(acc1[i]), "=r"(acc1[i + 1]));
            }
            int thr = 1;
#pragma unroll 1
            for (; pos < P2_RAW; pos += 8, thr = 2) block8(true, pos, thr, 0);
#pragma unroll 1
            for (; pos < end; pos += 8, thr = 2) {
                const int e = pos + 8, r = e % 48;
                block8(false, pos, thr, e < 48 || e > 256 || (r != 0 && r != P2_S1 && r != P2_S2) ? 0 : e == end ? 2 : 1);
            }
            TR2(wg, pos - 1, 4);
            if (n < 2 || n > 12) { LAG_HERE(3); }
            wg_wait<0>();
            TR2(wg, pos - 1, 5);
            if (who == 1) mbar_arrive_cluster(rel0 + 24);
            mbar_wait(bar_xfull + wg * 8, px);
            TR2(wg, pos - 1, 6);
            px ^= 1;
            __syncwarp();
            const bool last = n == P2_ITEMS - 1;
            uint32_t l;
            asm volatile("mov.u32 %0, %%laneid;\n" : "=r"(l));
            const uint32_t q16 = (l & 3) * 16, odd = (l >> 2) & 1, row = (w * 8 + (l >> 3)) * P2_XROW + q16;
            uint8_t* so = last ? reinterpret_cast<uint8_t*>(out) + (size_t)(2 * p2_tile(cl, n) + rank) * (64 * P2_XROW) : smem + P2_OFF_X;
            p2_epilogue(acc0, acc1, up, sbase + row + (last ? P2_OFF_A + odd * P2_LHALF : P2_OFF_X + odd * P2_XHALF),
                        sbase + P2_OFF_BIAS + q16 + (n < 0 && fin ? C_DIM * 2 : 0), so + (row + odd * (last ? 32 * P2_XROW : P2_XHALF)), zero);
            if (last) break;
            TR2(wg, pos - 1, 7);
            if (n + 3 >= P2_ITEMS) { publish(); break; }
            if (n < 0) {
                publish();
                pos = P2_S2;
                wait_pos(pos);
                mbar_wait(bar_bfull, 0);
            } else {
                pend = true;
                ok_a = false;
            }
        }
        TSTAMP(1, 29);
        cluster_sync_relaxed();
        TSTAMP(1, 30);
    }
}

__global__ void __cluster_dims__(2, 1, 1) __launch_bounds__(512, 1)
block_kernel(const __grid_constant__ CUtensorMap wmap, const __nv_bfloat16* __restrict__ x, const __nv_bfloat16* __restrict__ dw,
             const __nv_bfloat16* __restrict__ w2, const __nv_bfloat16* __restrict__ grn_g, const __nv_bfloat16* __restrict__ grn_b,
             __nv_bfloat16* __restrict__ out, int zero) {
    extern __shared__ __align__(1024) uint8_t smem[];
    const uint32_t sbase = smem_u32(smem);
    const int warp = __shfl_sync(0xffffffffu, threadIdx.x >> 5, 0), lane = threadIdx.x & 31;
    if (warp >= 12) {
        pass1<2>(wmap, x, dw, w2, grn_b, sbase, warp, lane, zero);
        pass2<2>(x, grn_g, out, smem, sbase, false, zero);
    } else {
        bool early = false;
        if (warp >= 8) {
            pass1<1>(wmap, x, dw, w2, grn_b, sbase, warp, lane, zero);
            reg_inc<160>();
        } else {
            early = pass1<0>(wmap, x, dw, w2, grn_b, sbase, warp, lane, zero);
            reg_dec<160>();
        }
        pass2<0>(x, grn_g, out, smem, sbase, early, zero);
    }
}

}

extern "C" void kernel_launch(void* const* d_in, const int* in_sizes, int n_in, void* d_out, int out_size) {
    const __nv_bfloat16* x = (const __nv_bfloat16*)d_in[0];
    const __nv_bfloat16* dw = (const __nv_bfloat16*)d_in[1];
    const __nv_bfloat16* w1 = (const __nv_bfloat16*)d_in[2];
    const __nv_bfloat16* w2 = (const __nv_bfloat16*)d_in[3];
    const __nv_bfloat16* grn_g = (const __nv_bfloat16*)d_in[4];
    const __nv_bfloat16* grn_b = (const __nv_bfloat16*)d_in[5];
    __nv_bfloat16* out = (__nv_bfloat16*)d_out;

    cudaFuncSetAttribute(block_kernel, cudaFuncAttributeMaxDynamicSharedMemorySize, SMEM_BYTES);

    typedef CUresult (*EncodeFn)(CUtensorMap*, CUtensorMapDataType, cuuint32_t, void*, const cuuint64_t*, const cuuint64_t*,
                                 const cuuint32_t*, const cuuint32_t*, CUtensorMapInterleave, CUtensorMapSwizzle,
                                 CUtensorMapL2promotion, CUtensorMapFloatOOBfill);
    static EncodeFn encode = nullptr;
    if (!encode) {
        cudaDriverEntryPointQueryResult qres;
        cudaGetDriverEntryPoint("cuTensorMapEncodeTiled", (void**)&encode, cudaEnableDefault, &qres);
    }
    CUtensorMap wmap;
    const cuuint64_t gdim[2] = {HID, C_DIM};
    const cuuint64_t gstr[1] = {HID * 2};
    const cuuint32_t box[2] = {64, 192}, estr[2] = {1, 1};
    CUresult er = encode(&wmap, CU_TENSOR_MAP_DATA_TYPE_BFLOAT16, 2, (void*)w1, gdim, gstr, box, estr, CU_TENSOR_MAP_INTERLEAVE_NONE,
           CU_TENSOR_MAP_SWIZZLE_128B, CU_TENSOR_MAP_L2_PROMOTION_L2_128B, CU_TENSOR_MAP_FLOAT_OOB_FILL_NONE);
    if (er != CUDA_SUCCESS) printf("tensor map encode failed %d\n", (int)er);

    block_kernel<<<NUM_CTAS, 512, SMEM_BYTES>>>(wmap, x, dw, w2, grn_g, grn_b, out, 0);
}
```

```cpp
#include <cuda.h>
#include <cuda_runtime.h>
#include <cuda_bf16.h>
#include <cuda_fp16.h>
#include <stdint.h>
#include <stdio.h>

namespace {

constexpr int M_TOTAL = 384 * 384;
constexpr int C_DIM   = 384;
constexpr int HID     = 1536;
constexpr int NT128   = M_TOTAL / 128;
constexpr int NUM_CTAS = 132;

constexpr int NGRP = 22, GRP_CTAS = 6;
constexpr int NT_EARLY = NT128 - 30;
constexpr int LN_STEP = NUM_CTAS / 4, LN_RING = 2 * LN_STEP;
constexpr int LN_TILE = 128 * C_DIM * 2;
constexpr int H_PAGES = NT128 / 4;

__device__ __align__(1024) uint4 g_h[(size_t)(H_PAGES + 1) << 17];
__device__ unsigned g_page[H_PAGES];
__device__ unsigned g_epoch;
__device__ __align__(1024) uint4 g_w2img[2][HID * C_DIM * 2 / 16];
__device__ __align__(16) unsigned long long g_sq[HID];
__device__ __align__(16) float g_sums[512];
__device__ float g_scale[HID];
__device__ float g_redo[HID];
enum { CNT_POS, CNT_IMG1, CNT_REDO, CNT_IMG0, CNT_LAST, CNT_H, CNT_EARLY, NUM_CNT };
__device__ __align__(128) unsigned g_prog[NUM_CNT][32];
__device__ __align__(128) unsigned g_half[32][2];
__device__ unsigned g_flag[LN_RING + 6][2][8];
#define TSTAMP(k, i)
#define TRACE(wg, pos, i)
#define TRACEW(pos, i)

#define TR2(wg, pos, i)
__host__ __device__ __forceinline__ int perm32(int n) {
    return (n & ~31) | (((n >> 1) & 3) << 3) | (((n >> 3) & 3) << 1) | (n & 1);
}

constexpr int H_FIXED = 12;
constexpr int LN_SW = LN_RING;
__device__ __forceinline__ uint8_t* h_base() { return reinterpret_cast<uint8_t*>((reinterpret_cast<size_t>(g_h) + 0x1fffff) & ~(size_t)0x1fffff); }
__device__ __forceinline__ unsigned page_bit(int page, unsigned tag) {
    unsigned v = 0;
    if (page >= H_FIXED) {
        do {
            asm volatile("ld.relaxed.gpu.global.u32 %0, [%1];\n" : "=r"(v) : "l"(&g_page[page]) : "memory");
        } while (tag && (v & ~1u) != tag);
    }
    return v;
}
__device__ __forceinline__ uint32_t h_tile(int t, unsigned bit) { return (t >> 1) << 20 | ((t ^ bit) & 1) << 12 | (t & 2) << 9; }
__device__ __forceinline__ uint32_t h_tile(int t) { return h_tile(t, page_bit(t >> 2, 0)); }
__device__ __forceinline__ int ln_page(int t) { return (t < LN_SW ? 0 : 17) + (t % LN_RING >> 2); }
__device__ __forceinline__ int ln_probed(int t) { return t < LN_SW ? 0 : ln_page(t); }
__device__ __forceinline__ uint32_t ln_tile(int t, unsigned bit) {
    const int slot = t % LN_RING;
    return ln_page(t) << 21 | 0xc0000 | (slot & 2) << 16 | ((~t ^ bit ^ (slot >> 1)) & 1) << 12;
}
__device__ __forceinline__ constexpr uint32_t ln_rows(int group) { return (group & 1) * 0x3000 ^ (group >> 1) * 0x11000; }
__device__ __forceinline__ constexpr uint32_t ln_block(int j) { return (j & 3) << 14 | (j >> 2) << 20; }
__device__ __forceinline__ uint32_t h_block(int kb, int half) {
    return (kb >> 2) << 16 | (kb & 2) << 14 | half << 14 | (kb & 1) << 13 | (__popc(kb & 0x2d) & 1) << 12 | (kb & 1) << 10;
}
__device__ __forceinline__ unsigned* h_cell(int page, int c) {
    return reinterpret_cast<unsigned*>(h_base() + ((size_t)page << 21) + 0x1d8000 + ((c >> 6) << 14) + (c & 63) * 64);
}
__device__ __forceinline__ unsigned near_half(unsigned* cell) {
    int votes = 0;
#pragma unroll 1
    for (int i = 0; i < 6; i++) {
        const unsigned a = atomicAdd(cell + (i & 1) * 1024, 1u), b = atomicAdd(cell + (~i & 1) * 1024, 1u);
        if (a == ~0u) break;
        const unsigned t0 = clock();
        if (b == ~0u) break;
        const int d = min((unsigned)clock() - t0, 250u);
        votes += i & 1 ? d : -d;
    }
    return votes > 0;
}

__device__ __forceinline__ uint32_t smem_u32(const void* p) { return (uint32_t)__cvta_generic_to_shared(p); }

__device__ __forceinline__ void mbar_init(uint32_t bar, uint32_t count) {
    asm volatile("mbarrier.init.shared::cta.b64 [%0], %1;\n" ::"r"(bar), "r"(count) : "memory");
}
__device__ __forceinline__ void mbar_expect_tx(uint32_t bar, uint32_t bytes) {
    asm volatile("mbarrier.arrive.expect_tx.shared::cta.b64 _, [%0], %1;\n" ::"r"(bar), "r"(bytes) : "memory");
}
__device__ __forceinline__ void mbar_arrive(uint32_t bar) {
    asm volatile("mbarrier.arrive.shared::cta.b64 _, [%0];\n" ::"r"(bar) : "memory");
}
__device__ __forceinline__ void mbar_arrive_cluster(uint32_t bar_cluster_addr) {
    asm volatile("mbarrier.arrive.shared::cluster.b64 _, [%0];\n" ::"r"(bar_cluster_addr) : "memory");
}
#define LAG_HERE(k)
#define SAFE_BREAK
__device__ __forceinline__ void mbar_wait(uint32_t bar, uint32_t parity) {
    asm volatile(
        "{\n"
        ".reg .pred p;\n"
        "LAB_WAIT:\n"
        "mbarrier.try_wait.parity.shared::cta.b64 p, [%0], %1;\n"
        "@!p bra LAB_WAIT;\n"
        "}\n" ::"r"(bar), "r"(parity) : "memory");
}
__device__ __forceinline__ bool mbar_test(uint32_t bar, uint32_t parity) {
    uint32_t ok;
    asm volatile("{\n.reg .pred p;\n"
                 "mbarrier.test_wait.parity.shared::cta.b64 p, [%1], %2;\n"
                 "selp.u32 %0, 1, 0, p;\n}\n" : "=r"(ok) : "r"(bar), "r"(parity) : "memory");
    return ok != 0;
}
__device__ __forceinline__ uint32_t mapa(uint32_t addr, uint32_t rank) {
    uint32_t r;
    asm volatile("mapa.shared::cluster.u32 %0, %1, %2;\n" : "=r"(r) : "r"(addr), "r"(rank));
    return r;
}
__device__ __forceinline__ void bulk_g2s(uint32_t dst, const void* src, uint32_t bytes, uint32_t bar) {
    asm volatile("cp.async.bulk.shared::cluster.global.mbarrier::complete_tx::bytes [%0], [%1], %2, [%3];\n"
                 ::"r"(dst), "l"(src), "r"(bytes), "r"(bar) : "memory");
}
__device__ __forceinline__ void bulk_g2s_mc(uint32_t dst, const void* src, uint32_t bytes, uint32_t bar, uint16_t mask) {
    asm volatile("cp.async.bulk.shared::cluster.global.mbarrier::complete_tx::bytes.multicast::cluster [%0], [%1], %2, [%3], %4;\n"
                 ::"r"(dst), "l"(src), "r"(bytes), "r"(bar), "h"(mask) : "memory");
}
__device__ __forceinline__ void tma2(uint32_t dst, const CUtensorMap* map, int c0, int c1, uint32_t bar) {
    asm volatile("cp.async.bulk.tensor.2d.shared::cluster.global.tile.mbarrier::complete_tx::bytes [%0], [%1, {%2, %3}], [%4];\n"
                 ::"r"(dst), "l"(map), "r"(c0), "r"(c1), "r"(bar) : "memory");
}
template <bool ACQ>
__device__ __forceinline__ uint32_t flag_wait(const unsigned* p, unsigned target) {
    unsigned v, n = 0;
    do {
        if (ACQ) asm volatile("ld.acquire.gpu.global.u32 %0, [%1];\n" : "=r"(v) : "l"(p) : "memory");
        else asm volatile("ld.relaxed.gpu.global.u32 %0, [%1];\n" : "=r"(v) : "l"(p) : "memory");
        n++;
    } while (v < target);
    return n == 1;
}
__device__ __forceinline__ void ldsm4t(uint32_t (&r)[4], uint32_t addr) {
    asm volatile("ldmatrix.sync.aligned.m8n8.x4.trans.shared.b16 {%0,%1,%2,%3}, [%4];\n"
                 : "=r"(r[0]), "=r"(r[1]), "=r"(r[2]), "=r"(r[3]) : "r"(addr) : "memory");
}
__device__ __forceinline__ void bulk_s2g(void* dst, uint32_t src, uint32_t bytes) {
    asm volatile("cp.async.bulk.global.shared::cta.bulk_group [%0], [%1], %2;\n" ::"l"(dst), "r"(src), "r"(bytes) : "memory");
}
__device__ __forceinline__ void cluster_sync_relaxed() {
    asm volatile("barrier.cluster.arrive.relaxed.aligned;\nbarrier.cluster.wait.aligned;\n" ::: "memory");
}
__device__ __forceinline__ uint32_t cluster_rank() {
    uint32_t r;
    asm volatile("mov.u32 %0, %%cluster_ctarank;\n" : "=r"(r));
    return r;
}
__device__ __forceinline__ bool elect_one() {
    uint32_t pred;
    asm volatile("{\n.reg .pred p;\nelect.sync _|p, 0xffffffff;\nselp.u32 %0, 1, 0, p;\n}\n" : "=r"(pred));
    return pred != 0;
}
__device__ __forceinline__ void wg_fence() { asm volatile("wgmma.fence.sync.aligned;\n" ::: "memory"); }
__device__ __forceinline__ void wg_commit() { asm volatile("wgmma.commit_group.sync.aligned;\n" ::: "memory"); }
template <int N> __device__ __forceinline__ void wg_wait() {
    asm volatile("wgmma.wait_group.sync.aligned %0;\n" ::"n"(N) : "memory");
}
template <int R> __device__ __forceinline__ void reg_inc() { asm volatile("setmaxnreg.inc.sync.aligned.u32 %0;\n" ::"n"(R)); }
template <int R> __device__ __forceinline__ void reg_dec() { asm volatile("setmaxnreg.dec.sync.aligned.u32 %0;\n" ::"n"(R)); }
__device__ __forceinline__ void bar_sync(int id, int n) { asm volatile("bar.sync %0, %1;\n" ::"r"(id), "r"(n) : "memory"); }
__device__ __forceinline__ void bar_arrive(int id, int n) { asm volatile("bar.arrive %0, %1;\n" ::"r"(id), "r"(n) : "memory"); }

__device__ __forceinline__ uint64_t make_desc(uint32_t saddr, uint32_t lbo, uint32_t sbo) {
    return (uint64_t)((saddr & 0x3FFFF) >> 4) | ((uint64_t)(lbo >> 4) << 16) | ((uint64_t)(sbo >> 4) << 32);
}

__device__ __forceinline__ void stg128_cs(void* p, uint32_t a, uint32_t b, uint32_t c, uint32_t d) {
    asm volatile("st.global.cs.v4.u32 [%0], {%1,%2,%3,%4};\n" ::"l"(p), "r"(a), "r"(b), "r"(c), "r"(d) : "memory");
}
__device__ __forceinline__ uint32_t pack_bf16(float lo, float hi) {
    uint32_t r;
    asm("cvt.rn.bf16x2.f32 %0, %1, %2;\n" : "=r"(r) : "f"(hi), "f"(lo));
    return r;
}
__device__ __forceinline__ float bf_lo(uint32_t v) { return __uint_as_float(v << 16); }
__device__ __forceinline__ float bf_hi(uint32_t v) { return __uint_as_float(v & 0xffff0000u); }
__device__ __forceinline__ uint32_t bf2_mul(uint32_t a, uint32_t b) {
    uint32_t r;
    asm("mul.rn.bf16x2 %0, %1, %2;\n" : "=r"(r) : "r"(a), "r"(b));
    return r;
}
__device__ __forceinline__ uint32_t bf2_fma(uint32_t a, uint32_t b, uint32_t c) {
    uint32_t r;
    asm("fma.rn.bf16x2 %0, %1, %2, %3;\n" : "=r"(r) : "r"(a), "r"(b), "r"(c));
    return r;
}
__device__ __forceinline__ uint32_t bf2_add(uint32_t a, uint32_t b) {
    uint32_t r;
    asm("add.rn.bf16x2 %0, %1, %2;\n" : "=r"(r) : "r"(a), "r"(b));
    return r;
}
__device__ __forceinline__ uint32_t h2_mul(uint32_t a, uint32_t b) {
    uint32_t r;
    asm("mul.rn.f16x2 %0, %1, %2;\n" : "=r"(r) : "r"(a), "r"(b));
    return r;
}
__device__ __forceinline__ uint32_t h2_fma(uint32_t a, uint32_t b, uint32_t c) {
    uint32_t r;
    asm("fma.rn.f16x2 %0, %1, %2, %3;\n" : "=r"(r) : "r"(a), "r"(b), "r"(c));
    return r;
}
__device__ __forceinline__ uint32_t h2_add(uint32_t a, uint32_t b) {
    uint32_t r;
    asm("add.rn.f16x2 %0, %1, %2;\n" : "=r"(r) : "r"(a), "r"(b));
    return r;
}
__device__ __forceinline__ uint32_t pack_f16(float lo, float hi) {
    uint32_t r;
    asm("cvt.rn.f16x2.f32 %0, %1, %2;\n" : "=r"(r) : "f"(hi), "f"(lo));
    return r;
}
__device__ __forceinline__ float h_lo(uint32_t v) { return __low2float(*reinterpret_cast<const __half2*>(&v)); }
__device__ __forceinline__ float h_hi(uint32_t v) { return __high2float(*reinterpret_cast<const __half2*>(&v)); }
__device__ __forceinline__ uint32_t bf2_to_h2(uint32_t v) { return (v & 0x7fff7fffu) * 7u + v; }
__device__ __forceinline__ uint32_t prmt(uint32_t a, uint32_t b, uint32_t sel) {
    uint32_t r;
    asm("prmt.b32 %0, %1, %2, %3;\n" : "=r"(r) : "r"(a), "r"(b), "r"(sel));
    return r;
}
__device__ __forceinline__ uint32_t bitsel(uint32_t a, uint32_t b, uint32_t m) {
    uint32_t r;
    asm("lop3.b32 %0, %1, %2, %3, 0xd8;\n" : "=r"(r) : "r"(a), "r"(b), "r"(m));
    return r;
}
constexpr float KAPPA = 0.3292034911525734f;
constexpr uint32_t GELU_C2 = 0x40d940d9u;
constexpr float HSCALE = 1.0f / (2.0f * KAPPA);
__device__ __forceinline__ float w2_scale(uint32_t m) { return __uint_as_float((257u - max(m >> 23, 16u)) << 23); }
__device__ __forceinline__ void sched_break(int zero) {
    asm volatile("{\n.reg .pred p;\nsetp.ne.s32 p, %0, 0;\nSB_LOOP:\n@p nanosleep.u32 1;\n@p bra SB_LOOP;\n}\n" ::"r"(zero));
}

#define ACC8(d, o) "+r"(d[o + 0]), "+r"(d[o + 1]), "+r"(d[o + 2]), "+r"(d[o + 3]), "+r"(d[o + 4]), "+r"(d[o + 5]), "+r"(d[o + 6]), "+r"(d[o + 7])

__device__ __forceinline__ void mma_rs_n128(uint32_t (&d)[32], const uint32_t (&a)[4], uint64_t desc, int scale_d) {
    asm volatile(
        "{\n.reg .pred p;\nsetp.ne.b32 p, %37, 0;\n"
        "wgmma.mma_async.sync.aligned.m64n128k16.f16.f16.f16 "
        "{%0,%1,%2,%3,%4,%5,%6,%7,%8,%9,%10,%11,%12,%13,%14,%15,"
        "%16,%17,%18,%19,%20,%21,%22,%23,%24,%25,%26,%27,%28,%29,%30,%31},"
        "{%32,%33,%34,%35}, %36, p, 1, 1, 0;\n}\n"
        : ACC8(d, 0), ACC8(d, 8), ACC8(d, 16), ACC8(d, 24)
        : "r"(a[0]), "r"(a[1]), "r"(a[2]), "r"(a[3]), "l"(desc), "r"(scale_d));
}

__device__ __forceinline__ void mma_ss_n128(uint32_t (&d)[32], uint64_t da, uint64_t db, int scale_d) {
    asm volatile(
        "{\n.reg .pred p;\nsetp.ne.b32 p, %34, 0;\n"
        "wgmma.mma_async.sync.aligned.m64n128k16.f16.f16.f16 "
        "{%0,%1,%2,%3,%4,%5,%6,%7,%8,%9,%10,%11,%12,%13,%14,%15,"
        "%16,%17,%18,%19,%20,%21,%22,%23,%24,%25,%26,%27,%28,%29,%30,%31},"
        "%32, %33, p, 1, 1, 1, 0;\n}\n"
        : ACC8(d, 0), ACC8(d, 8), ACC8(d, 16), ACC8(d, 24)
        : "l"(da), "l"(db), "r"(scale_d));
}

__device__ __forceinline__ void mma_rs_n192(uint32_t (&d)[48], const uint4& a, uint64_t db) {
    asm volatile(
        "wgmma.mma_async.sync.aligned.m64n192k16.f16.f16.f16 "
        "{%0,%1,%2,%3,%4,%5,%6,%7,%8,%9,%10,%11,%12,%13,%14,%15,"
        "%16,%17,%18,%19,%20,%21,%22,%23,%24,%25,%26,%27,%28,%29,%30,%31,"
        "%32,%33,%34,%35,%36,%37,%38,%39,%40,%41,%42,%43,%44,%45,%46,%47},"
        "{%48,%49,%50,%51}, %52, 1, 1, 1, 0;\n"
        : ACC8(d, 0), ACC8(d, 8), ACC8(d, 16), ACC8(d, 24), ACC8(d, 32), ACC8(d, 40)
        : "r"(a.x), "r"(a.y), "r"(a.z), "r"(a.w), "l"(db));
}

constexpr int P1_SPLIT = 6;
constexpr int P1_SLOT = LN_TILE / 6, P1_NST = 6;
constexpr int P1_W = 64 * C_DIM * 2;
constexpr int P1_X = 32 * C_DIM * 2;
constexpr int P1_OFF_W = LN_TILE;
constexpr int P1_OFF_X = P1_OFF_W + 2 * P1_W;
constexpr int P1_OFF_BAR = 227328;
constexpr int P1_OFF_TILE = P1_OFF_BAR + (2 * P1_NST + 4 + 4 + 4) * 8;
constexpr int P1_OFF_EX = P1_OFF_TILE + 96;
constexpr int P1_OFF_DW = P1_OFF_EX + 256 * 4;
constexpr int OFF_PRE = P1_OFF_DW + C_DIM * 2;
constexpr int SMEM_BYTES = OFF_PRE + C_DIM * 4 + 16;

__device__ __forceinline__ float rsqrt_fast(float x) {
    float r;
    asm("rsqrt.approx.ftz.f32 %0, %1;\n" : "=f"(r) : "f"(x));
    return r;
}
__device__ __forceinline__ float row_sum(const uint32_t (&c)[4]) {
    const uint32_t u = bf2_add(bf2_add(c[0], c[1]), bf2_add(c[2], c[3]));
    float s = bf_lo(u) + bf_hi(u);
#pragma unroll
    for (int o = 1; o < 8; o <<= 1) s += __shfl_xor_sync(0xffffffffu, s, o);
    return s;
}
__device__ __forceinline__ uint32_t pace(uint32_t bar, uint32_t off, uint32_t val, int zero) {
    asm volatile(
        "{\n.reg .pred p, q;\n.reg .b32 par;\n"
        "lop3.b32 par, %0, %2, %3, 0xea;\n"
        "setp.eq.u32 q, par, 0;\n"
        "mov.pred p, 0;\n"
        "@q mbarrier.test_wait.parity.shared::cta.b64 p, [%1], par;\n"
        "selp.u32 par, 1, 0, p;\n"
        "@q mbarrier.try_wait.parity.shared::cta.b64 p, [%1], par, 1000;\n"
        "@p or.b32 %0, %0, %2;\n"
        "}\n" : "+r"(val) : "r"(bar), "r"(zero), "r"(off));
    return val;
}
__device__ __forceinline__ void ln_row(uint32_t (&v)[6][4], const uint32_t (&d)[6][4], uint32_t bar, uint32_t off, int zero, uint32_t bar_read) {
    const float inv = 1.0f / C_DIM;
    uint32_t c[4];
#pragma unroll
    for (int i = 0; i < 6; i++)
#pragma unroll
        for (int k = 0; k < 4; k++) c[k] = bf2_fma(v[i][k], d[i][k], i ? c[k] : 0);
    const float m = row_sum(c) * inv;
    uint32_t nm = pack_bf16(-m, -m);
    const float e = m + bf_lo(nm);
    if (bar_read) mbar_arrive(bar_read + (nm & zero));
    nm = pace(bar, off, nm, zero);
#pragma unroll
    for (int i = 0; i < 6; i++) {
#pragma unroll
        for (int k = 0; k < 4; k++) {
            v[i][k] = bf2_fma(v[i][k], d[i][k], nm);
            c[k] = i ? bf2_fma(v[i][k], v[i][k], c[k]) : bf2_mul(v[i][k], v[i][k]);
        }
    }
    float r = KAPPA * rsqrt_fast(fmaxf(fmaf(-e, e, row_sum(c) * inv), 0.f) + 1e-5f);
    const float er = -e * r * 0x1p-112f;
    if (__any_sync(0xffffffffu, r < 0x1p-8f)) {
        const uint32_t p2 = __float_as_uint(r) & 0x7f800000u;
        r = __uint_as_float((__float_as_uint(r) & 0x007fffffu) | 0x3f800000u);
#pragma unroll
        for (int i = 0; i < 6; i++)
#pragma unroll
            for (int k = 0; k < 4; k++) v[i][k] = bf2_mul(v[i][k], p2 | p2 >> 16);
    }
    const uint32_t rs = pack_bf16(r * 0x1p-112f, r * 0x1p-112f), sh = pack_bf16(er, er);
#pragma unroll
    for (int i = 0; i < 6; i++)
#pragma unroll
        for (int k = 0; k < 4; k++) v[i][k] = bf2_to_h2(bf2_fma(v[i][k], rs, sh));
}

template <int R>
__device__ __forceinline__ uint32_t gelu2(uint32_t a, uint32_t sc2) {
    uint32_t y, t;
    if (R) asm("{\n.reg .b16 l, h;\n.reg .b32 f;\nmov.b32 {l, h}, %2;\nmov.b32 f, {h, h};\nmul.rn.f16x2 %0, %1, f;\n}\n" : "=r"(y) : "r"(a), "r"(sc2));
    else asm("{\n.reg .b16 l, h;\n.reg .b32 f;\nmov.b32 {l, h}, %2;\nmov.b32 f, {l, l};\nmul.rn.f16x2 %0, %1, f;\n}\n" : "=r"(y) : "r"(a), "r"(sc2));
    asm("tanh.approx.f16x2 %0, %1;\n" : "=r"(t) : "r"(h2_mul(y, h2_fma(y, y, GELU_C2))));
    return h2_fma(a, t, a);
}
constexpr uint32_t SPARE = 0x40074007u;
constexpr float UNCHOP = 1.0023f;

__device__ __forceinline__ uint32_t p1_exponents(float (&t)[2], uint32_t (&ex)[2], uint32_t saddr, int lane) {
#pragma unroll
    for (int r = 0; r < 2; r++) {
        t[r] += __shfl_xor_sync(0xffffffffu, t[r], 1);
        t[r] += __shfl_xor_sync(0xffffffffu, t[r], 2);
        ex[r] = min(max(((__float_as_uint(193.3f * t[r]) >> 23) + 127u) >> 1, 72u), 198u);
        asm volatile("st.shared.u32 [%0], %1;\n" ::"r"(saddr + r * 32), "r"(ex[r] << 23) : "memory");
    }
    return pack_f16(__uint_as_float(min(ex[0], 142u) << 23), __uint_as_float(min(ex[1], 142u) << 23));
}
template <int N>
__device__ __forceinline__ void p1_convert(uint32_t (&o)[N][4], uint32_t (&v)[N][4], const uint32_t (&ex)[2]) {
    if (__any_sync(0xffffffffu, max(ex[0], ex[1]) > 141u)) {
#pragma unroll
        for (int k = 0; k < 4 * N; k++) v[k >> 2][k & 3] = bf2_mul(v[k >> 2][k & 3], ex[k & 1] > 141u ? 0x1f801f80u : 0x3f803f80u);
    }
#pragma unroll
    for (int k = 0; k < 4 * N; k++) {
        const uint32_t u = bf2_mul(v[k >> 2][k & 3], ((ex[k & 1] > 141u ? 206u : 142u) - ex[k & 1]) * 0x00800080u);
        asm volatile("mad.lo.u32 %0, %1, 7, %2;\n" : "=r"(o[k >> 2][k & 3]) : "r"(u & 0x7fff7fffu), "r"(u));
    }
}
template <int N>
__device__ __forceinline__ void p1_squares(const uint32_t (&v)[N][4], float (&t)[2]) {
#pragma unroll
    for (int j = 0; j < N / 2; j++) {
        const int r = j & 1, b = (j >> 1) * 4;
        uint32_t c = bf2_mul(v[b][r], v[b][r]);
#pragma unroll
        for (int k = 1; k < 8; k++) c = bf2_fma(v[b + k / 2][r + (k & 1) * 2], v[b + k / 2][r + (k & 1) * 2], c);
        t[r] += bf_lo(c) + bf_hi(c);
    }
}
__device__ __forceinline__ void p1_epilogue(const uint32_t (&acc)[2][32], const uint32_t (&sc2)[2], float (&ssq)[4], uint8_t* hp, int zero) {
    uint32_t sq[2], h[16][4];
#pragma unroll
    for (int i2 = 0; i2 < 9; i2++) {
#pragma unroll
        for (int c = 2 * i2 - 2; c < 2 * i2; c++) {
            if (c >= 0 && (c & 3)) {
                uint32_t o[4];
#pragma unroll
                for (int u = 0; u < 4; u++) {
                    const uint32_t v = h[c & 12][u];
                    o[u] = bitsel(h[c][u], (c & 3) == 2 ? prmt(v, v, 0xa381) : prmt(v >> 3, v, (c & 3) == 1 ? 0x6240 : 0xf3d1), SPARE);
                }
                stg128_cs(hp + (c >> 2) * 0x4000 + ((c & 3) - 1) * 512, o[0], o[1], o[2], o[3]);
            }
        }
        if (i2 < 8) {
#pragma unroll
            for (int u = 0; u < 4; u++) {
                h[2 * i2][u] = gelu2<0>(acc[i2 >> 2][8 * (i2 & 3) + 2 * u], sc2[i2 >> 2]);
                h[2 * i2 + 1][u] = gelu2<1>(acc[i2 >> 2][8 * (i2 & 3) + 2 * u + 1], sc2[i2 >> 2]);
#pragma unroll
                for (int r = 0; r < 2; r++) {
                    const uint32_t v = h[2 * i2 + r][u];
                    sq[r] = ((i2 & 3) | u) ? h2_fma(v, v, sq[r]) : h2_mul(v, v);
                }
            }
            if ((i2 & 3) == 3) {
#pragma unroll
                for (int r = 0; r < 2; r++) ssq[(i2 >> 2) * 2 + r] += h_lo(sq[r]) + h_hi(sq[r]);
            }
            sched_break(zero);
        }
    }
}
template <int WG>
__device__ __forceinline__ void p1_mma(uint32_t (&acc)[2][32], const uint32_t (&a)[24][4], uint32_t sbase, uint32_t empty_remote, int i, int lane, bool pass, int zero) {
    const uint32_t bar_full = sbase + P1_OFF_BAR;
    const uint64_t db = make_desc(sbase, 16, 1024 + zero) | (1ull << 62), da = db + (P1_OFF_W + WG * P1_W) / 16;
    if (WG == 0) mbar_wait(bar_full, i & 1);
    bar_sync(1 + WG, 256);
    TRACE(WG, i, 1);
    wg_fence();
#pragma unroll
    for (int k = 0; k < 24; k++) {
        if (WG == 0 && k && k % 4 == 0) mbar_wait(bar_full + (k >> 2) * 8, i & 1);
        mma_rs_n128(acc[0], a[k], db + (k >> 2) * 1024 + (k & 3) * 2, k != 0);
        mma_ss_n128(acc[1], da + k * 128, db + (k >> 2) * 1024 + (k & 3) * 2, k != 0);
        if (k == 23 && pass) bar_arrive(2 - WG, 256);
        if (k == 23 || (WG == 1 && k % 4 == 3)) wg_commit();
        if (WG == 1 && k % 4 == 3 && k > 3) {
            wg_wait<1>();
            if (lane < 2) mbar_arrive_cluster(empty_remote + ((k >> 2) - 1) * 8);
        }
    }
    TRACE(WG, i, 2);
    wg_wait<0>();
    if (WG == 1 && lane < 2) mbar_arrive_cluster(empty_remote + 5 * 8);
}
__device__ __forceinline__ bool p1_consumer(const uint32_t (&a)[24][4], const uint32_t (&sc2)[2], uint32_t sbase, int WG, int w, int lane, int zero) {
    const uint32_t bar_full = sbase + P1_OFF_BAR, bar_empty = bar_full + P1_NST * 8;
    const uint32_t empty_remote = mapa(bar_empty, lane & 1);
    const uint32_t bar_pace = bar_empty + P1_NST * 8 + 32 + w * 8;
    const int g = lane >> 2, q = lane & 3, half = WG ^ ((blockIdx.x / GRP_CTAS) & 1), cb = (blockIdx.x % GRP_CTAS) * 4 + half * 2;
    uint32_t acc[2][32];
    float ssq[4] = {0.f, 0.f, 0.f, 0.f};
    TSTAMP(0, 1);

    uint8_t* const hp0 = h_base() + (w & 1) * 1536 + g * 64 + (q ^ (g >> 1)) * 16;
    const uint32_t blk = h_block(cb * 2 + (w >> 1), 0);
    int i = 0;
    uint32_t more = 3, both;
#pragma unroll 1
    for (;; i++) {
        TRACE(WG, i, 0);
        both = more & 2;
        if (WG == 0) p1_mma<0>(acc, a, sbase, empty_remote, i, lane, both, zero);
        else p1_mma<1>(acc, a, sbase, empty_remote, i, lane, true, zero);
        TRACE(WG, i, 4);
        uint32_t step;
        asm volatile("ld.shared.v2.u32 {%0, %1}, [%2];\n" : "=r"(step), "=r"(more) : "r"(sbase + P1_OFF_TILE + (i & 3) * 16) : "memory");
        uint8_t* hp = hp0 + (step ^ blk);
        if (i < 2 || more != 3) { LAG_HERE(4); }
        if (!(more >> WG & 1) && lane == 0) asm volatile("red.relaxed.gpu.global.add.u32 [%0], 1;\n" ::"l"(g_prog[CNT_LAST]) : "memory");
        p1_epilogue(acc, sc2, ssq, hp, zero);
        if (lane == 0) mbar_arrive(bar_pace);
        if (more & 4) {
            asm volatile("fence.proxy.async.global;\n" ::: "memory");
            bar_arrive(8, 288);
            bar_arrive(9, 288);
        }
        if (!(more >> WG & 1)) break;
    }
    TSTAMP(0, 21);
    if (WG == 0 && both) bar_sync(1, 256);
#pragma unroll
    for (int r = 0; r < 4; r++) {
        ssq[r] += __shfl_xor_sync(0xffffffffu, ssq[r], 1);
        ssq[r] += __shfl_xor_sync(0xffffffffu, ssq[r], 2);
    }
    const float t = q == 0 ? ssq[0] : q == 1 ? ssq[1] : q == 2 ? ssq[2] : ssq[3];
    atomicAdd(&g_sq[cb * 64 + (q >> 1) * 64 + w * 16 + (q & 1) * 8 + g], (1ull << 56) + __float2ull_rn(fminf(t, 0x1p19f) * 0x1p32f));
    asm volatile("fence.proxy.async.global;\n" ::: "memory");
    bar_arrive(3, 288);
    asm volatile("barrier.cluster.arrive.relaxed.aligned;\n" ::: "memory");
    return WG ? more & 1 : both;
}

__device__ __forceinline__ void p2_init(uint32_t sbase);
template <int ROLE>
__device__ __forceinline__ bool pass1(const CUtensorMap& wmap, const __nv_bfloat16* __restrict__ x, const __nv_bfloat16* __restrict__ dw,
                                      const __nv_bfloat16* __restrict__ w2, const __nv_bfloat16* __restrict__ grn_b, uint32_t sbase,
                                      int warp, int lane, int zero) {
    const uint32_t bar_full = sbase + P1_OFF_BAR, bar_empty = bar_full + P1_NST * 8, bar_w = bar_empty + P1_NST * 8;
    const uint32_t rank = cluster_rank();
    const int cig = blockIdx.x % GRP_CTAS;

    TSTAMP(0, 0);
    TRACEW(110 + warp, 0);
    const uint32_t bar_pace = bar_w + 32, bar_xfull = bar_pace + 32, bar_xempty = bar_xfull + 8, bar_done = bar_xfull + 16;
    const uint32_t s_side = bar_done + 12;
    const uint32_t s_item = sbase + P1_OFF_TILE + 64, s_cl = sbase + OFF_PRE + C_DIM * 4 + 8;
    auto ln_place = [](int q, unsigned tag) { return ln_tile(q >> 2, page_bit(ln_probed(q >> 2), tag)) ^ ln_rows(q & 2) ^ (q & 1) * 0x90; };
    const int first = blockIdx.x / GRP_CTAS;

    if (ROLE == 2) {
        reg_dec<32>();
        asm volatile("barrier.cluster.arrive.relaxed.aligned;\n" ::: "memory");
        asm volatile("barrier.cluster.wait.aligned;\n" ::: "memory");
        LAG_HERE(0);
        if (warp == 12) {
            int t = first, sent = 0;
            const unsigned tag = 2 * __ldcg(&g_epoch) + 2;
            const uint32_t rbase = mapa(sbase, lane & 1);
#pragma unroll 1
            for (int i = 0; t < NT128; i++) {
                const int round = t / LN_RING, slot = t - round * LN_RING;
                constexpr unsigned LIM = (NT128 - P1_SPLIT - NGRP) / 2;
                unsigned* cnt = &g_flag[LN_RING + (cig >> 1)][0][0];
                const int page = lane & 1 ? ln_probed(t) : t >> 2;
                unsigned v, sd, u = 0;
                do {
                    asm volatile("ld.relaxed.gpu.global.u32 %0, [%1];\n" : "=r"(v) : "l"(lane & 2 ? &g_page[page] : cnt + (lane & 1) * 8) : "memory");
                    if ((lane & 2) && page < H_FIXED) v = tag;
                    SAFE_BREAK;
                } while (__any_sync(0xffffffffu, (lane & 2) && (v & ~1u) != tag));
                asm volatile("ld.volatile.shared.u32 %0, [%1];\n" : "=r"(sd) : "r"(s_side) : "memory");
                if (__shfl_sync(0xffffffffu, v, sd) > __shfl_sync(0xffffffffu, v, sd ^ 1) + 4) sd ^= 1;
                unsigned b = __shfl_sync(0xffffffffu, v, sd ^ 1);
                const bool draw = rank == 0 && lane == 0 && t < NT128 - P1_SPLIT;
                if (draw) u = atomicAdd(cnt + sd * 8, 1u);
                flag_wait<true>(&g_flag[slot][0][0], 4 * round + 4);
                TRACEW(i, 2);
                asm volatile("fence.proxy.async.global;\n" ::: "memory");
                int next = NT128, more = 0;
                if (draw) {
                    if (u >= LIM) { sd ^= 1; b = u; u = atomicAdd(cnt + sd * 8, 1u); }
                    next = u < LIM ? NGRP + 2 * u + sd : NT128 - P1_SPLIT + atomicAdd(&g_flag[LN_RING + 3 + (cig >> 1)][first & 1][0], 1u);
                    more = u < LIM ? 3 : next < NT128;
                    if (!sent && min(u, b) >= (NT_EARLY - NGRP) / 2) { sent = 1; more += 4; }
                }
                next = __shfl_sync(0xffffffffu, next, 0);
                more = __shfl_sync(0xffffffffu, more, 0);
                const uint32_t ht = h_tile(t, __shfl_sync(0xffffffffu, v, 2));
                const uint32_t src = ln_tile(t, __shfl_sync(0xffffffffu, v, 3)) ^ ln_rows(2 * rank);
#pragma unroll 1
                for (int h = 0; h < P1_NST; h++) {
                    mbar_wait(bar_empty + h * 8, i & 1);
                    if (h == 0) TRACEW(i, 4);
                    if (h == 5) TRACEW(i, 5);
                    if (elect_one()) {
                        mbar_expect_tx(bar_full + h * 8, h ? P1_SLOT : P1_SLOT + 16);
#pragma unroll
                        for (int e = 0; e < 2; e++)
                            bulk_g2s_mc(sbase + h * P1_SLOT + (2 * rank + e) * 4096, h_base() + ((src ^ ln_rows(e)) + ln_block(h)), 4096, bar_full + h * 8, (uint16_t)3);
                    }
                    __syncwarp();
                    if (h == 0 && rank == 0 && lane < 2)
                        asm volatile("st.async.shared::cluster.mbarrier::complete_tx::bytes.v4.u32 [%0], {%1, %2, %3, %3}, [%4];\n"
                                     ::"r"(rbase + P1_OFF_TILE + (i & 3) * 16), "r"(ht), "r"(more), "r"(next),
                                       "r"(rbase + P1_OFF_BAR) : "memory");
                }
                t = next;
                if (rank != 0) {
                    mbar_wait(bar_full, i & 1);
                    asm volatile("ld.shared.u32 %0, [%1];\n" : "=r"(t) : "r"(sbase + P1_OFF_TILE + (i & 3) * 16 + 8) : "memory");
                }
            }
        } else if (warp == 13) {
            const unsigned tag = 2 * __ldcg(&g_epoch) + 2;
            int u = -1, side = 0;
            auto item = [&](int k) {
                if (k < LN_SW / LN_STEP) return (int)blockIdx.x + k * NUM_CTAS;
                while (u < 0) {
                    asm volatile("ld.volatile.shared.u32 %0, [%1];\n" : "=r"(u) : "r"(s_cl) : "memory");
                    side = u & 1;
                    if (u >= 0) u = (u & ~1) + rank;
                    SAFE_BREAK;
                }
                const int v = u + (k - LN_SW / LN_STEP) * (NUM_CTAS / 2);
                return 4 * LN_SW + (v >> 2) * 8 + side * 4 + (v & 3);
            };
#pragma unroll 1
            for (int k = 1;; k++) {
                const int q = item(k), round = q / (4 * LN_RING), slot = (q >> 2) - round * LN_RING;
                if (k == 1 && lane == 0)
                    asm volatile("cp.async.bulk.prefetch.L2.global [%0], %1;\n" ::"l"(reinterpret_cast<const uint8_t*>(x) + (size_t)q * P1_X), "r"(P1_X) : "memory");
                mbar_wait(bar_xempty, ~k & 1);
                if (k == 1) bar_sync(10, 64);
                if (elect_one()) {
                    mbar_expect_tx(bar_xfull, P1_X);
                    bulk_g2s(sbase + P1_OFF_X, reinterpret_cast<const uint8_t*>(x) + (size_t)q * P1_X, P1_X, bar_xfull);
                }
                __syncwarp();
                const uint32_t place = ln_place(q, tag), more = k < LN_SW / LN_STEP || item(k + 1) < 4 * NT128;
                const uint32_t off = flag_wait<false>(&g_flag[slot][1][0], round * (GRP_CTAS / 2));
                if (elect_one()) {
                    asm volatile("st.shared.v4.u32 [%0], {%1, %2, %3, %4};\n" ::"r"(s_item + (k & 1) * 16), "r"(off), "r"(place), "r"(slot), "r"(more) : "memory");
                    mbar_arrive(bar_xfull);
                }
                __syncwarp();
                if (!more) break;
            }
        } else if (warp == 15) {
            int t = first;
            if (rank == 1 && lane == 0) mbar_arrive(bar_empty);
#pragma unroll 1
            for (int i = 0; rank == 1 && t < NT128; i++) {
#pragma unroll 1
                for (int h = 0; h < P1_NST; h++) mbar_wait(bar_full + h * 8, i & 1);
                if (lane == 0) asm volatile("red.relaxed.gpu.global.add.u32 [%0], 1;\n" ::"l"(&g_flag[t % LN_RING][1][0]) : "memory");
                asm volatile("ld.shared.u32 %0, [%1];\n" : "=r"(t) : "r"(sbase + P1_OFF_TILE + (i & 3) * 16 + 8) : "memory");
                if (lane == 0) mbar_arrive(bar_empty);
                TRACEW(i, 3);
            }
            if (rank == 0) {
                {
                    const int me = blockIdx.x >> 1;
                    const int page = lane < 2 ? 0 : H_FIXED + me + (lane / 2 - 1) * (NUM_CTAS / 2);
                    if (page < H_PAGES) h_cell(page, me)[(lane & 1) * 1024] = 0;
                    __syncwarp();
                    if (lane == 0) {
                        const unsigned tag = 2 * __ldcg(&g_epoch) + 2;
                        const unsigned side = near_half(h_cell(0, me));
                        asm volatile("st.volatile.shared.u32 [%0], %1;\n" ::"r"(s_side), "r"(side) : "memory");
                        const unsigned u = atomicAdd(reinterpret_cast<unsigned*>(g_sums) + C_DIM + 64 + side, 1u);
                        const unsigned cl = u < NUM_CTAS / 4 ? 2 * u + side : NUM_CTAS - 2 - 2 * u + (side ^ 1);
#pragma unroll
                        for (int r = 0; r < 2; r++) asm volatile("st.shared::cluster.u32 [%0], %1;\n" ::"r"(mapa(s_cl, r)), "r"(cl) : "memory");
#pragma unroll 1
                        for (int p = H_FIXED + me; p < H_PAGES; p += NUM_CTAS / 2)
                            asm volatile("st.relaxed.gpu.global.u32 [%0], %1;\n" ::"l"(&g_page[p]), "r"(tag + (near_half(h_cell(p, me)) ^ side)) : "memory");
                    }
                    __syncwarp();
                }
                TRACEW(110 + warp, 3);
                mbar_wait(bar_full, 0);
                mbar_wait(bar_full, 1);
                float* sums = g_sums;
                unsigned* flag = reinterpret_cast<unsigned*>(sums + C_DIM);
                if (blockIdx.x == 0) reinterpret_cast<uint2*>(g_half)[lane] = make_uint2(0, 0);
                if (blockIdx.x == 2 && lane < NUM_CNT) g_prog[lane][0] = 0;
                if (blockIdx.x < 96) g_redo[blockIdx.x * 16 + lane] = 0.f;
                float gs = 0.f;
#pragma unroll 1
                for (int pass = 0; pass < 2; pass++) {
                    float mx = 0.f;
#pragma unroll 1
                    for (int it = (blockIdx.x + zero) / GRP_CTAS; it < 96; it += NGRP) {
                        const int nb = it % 12, k0 = (cig * 4 + it / 12) * 64 + (lane >> 2);
                        const uint32_t sc = mapa(sbase + P1_OFF_EX + (k0 & 255) * 4, it / 48);
                        uint32_t* dst = reinterpret_cast<uint32_t*>(g_w2img[0]) + (k0 >> 4) * 3072 + nb * 256 + lane;
                        float bs[8] = {};
#pragma unroll 1
                        for (int c = 0; c < 8; c++) {
                            const uint4 u = __ldg(reinterpret_cast<const uint4*>(w2 + (size_t)(k0 + c * 8) * C_DIM + nb * 32) + (lane & 3));
                            const float b = __bfloat162float(grn_b[k0 + c * 8]);
                            float t;
                            asm volatile("ld.shared::cluster.f32 %0, [%1];\n" : "=f"(t) : "r"(sc + c * 32) : "memory");
                            if (nb == 0) g_scale[k0 + c * 8] = t;
#pragma unroll
                            for (int j = 0; j < 4; j++) {
                                const uint32_t v = j == 0 ? u.x : j == 1 ? u.y : j == 2 ? u.z : u.w;
                                mx = fmaxf(mx, fmaxf(fabsf(bf_lo(v)), fabsf(bf_hi(v))) * t);
                                if (pass) {
                                    bs[2 * j] = fmaf(b, bf_lo(v), bs[2 * j]);
                                    bs[2 * j + 1] = fmaf(b, bf_hi(v), bs[2 * j + 1]);
                                    uint32_t h = pack_f16(bf_lo(v) * t * gs, bf_hi(v) * t * gs);
                                    asm volatile("movmatrix.sync.aligned.m8n8.trans.b16 %0, %0;\n" : "+r"(h));
                                    dst[(c >> 1) * 3072 + (c & 1) * 32 + j * 64] = h;
                                }
                            }
                        }
                        if (pass) {
#pragma unroll
                            for (int j = 0; j < 8; j++) {
#pragma unroll
                                for (int o = 4; o < 32; o <<= 1) bs[j] += __shfl_xor_sync(0xffffffffu, bs[j], o);
                                if (lane >> 2 == j) atomicAdd(&sums[nb * 32 + (j >> 1) * 8 + (lane & 3) * 2 + (j & 1)], bs[j]);
                            }
                        }
                    }
                    if (!pass) {
                        const uint32_t m = __reduce_max_sync(0xffffffffu, __float_as_uint(mx));
                        __threadfence();
                        __syncwarp();
                        if (lane == 0) {
                            atomicMax(flag, m);
                            asm volatile("red.release.gpu.global.add.u32 [%0], 1;\n" ::"l"(flag + 32) : "memory");
                        }
                        flag_wait<true>(flag + 32, NUM_CTAS / 2);
                        gs = w2_scale(__ldcg(flag));
                    }
                }
                asm volatile("fence.proxy.async.global;\nfence.acq_rel.gpu;\n" ::: "memory");
                __syncwarp();
                if (lane == 0) asm volatile("red.relaxed.gpu.global.add.u32 [%0], 1;\n" ::"l"(g_prog[CNT_IMG0]) : "memory");
            }
        } else if (warp == 14) {
#pragma unroll 1
            for (uint32_t k = 0, more = 1; more; k++) {
                uint32_t slot;
                mbar_wait(bar_done, k & 1);
                asm volatile("ld.shared.v2.u32 {%0, %1}, [%2];\n" : "=r"(slot), "=r"(more) : "r"(s_item + (k & 1) * 16 + 8) : "memory");
                if (lane == 0) mbar_arrive(bar_xfull + (slot & zero));
                TRACEW(k, 0);
                asm volatile("fence.proxy.async.global;\n" ::: "memory");
                if (elect_one()) asm volatile("red.release.gpu.global.add.u32 [%0], 1;\n" ::"l"(&g_flag[slot][0][0]) : "memory");
                if (k == 0) bar_arrive(10, 64);
                __syncwarp();
                TRACEW(k, 1);
            }
            if (lane == 0) p2_init(sbase);
#pragma unroll 1
            for (int i = CNT_EARLY; i >= CNT_H; i--) {
                bar_sync(i == CNT_EARLY ? 8 : 3, 288);
                asm volatile("fence.proxy.async.global;\n" ::: "memory");
                if (lane == 0) asm volatile("red.release.gpu.global.add.u32 [%0], 1;\n" ::"l"(&g_prog[i][0]) : "memory");
                __syncwarp();
            }
        }
        __syncwarp();
        asm volatile("barrier.cluster.arrive.relaxed.aligned;\n" ::: "memory");
        return false;
    } else if (ROLE == 1) {
        reg_dec<96>();
        asm volatile("barrier.cluster.arrive.relaxed.aligned;\n" ::: "memory");
        {
            const int l8 = lane & 7;
            uint32_t d[6][4];
            const int n = perm32(2 * ((warp - 8) * 4 + (lane >> 3)));
            const uint32_t dst0 = n * 128 + ((l8 ^ (n & 7)) << 4);
            const uint32_t src = sbase + P1_OFF_X + ((warp - 8) * 8 + (lane >> 3)) * (C_DIM * 2) + l8 * 16;
            uint32_t off = 1, place = ln_place(blockIdx.x & 255, 0), more = 1;
            LAG_HERE(0);
#pragma unroll 1
            for (int i = 0; more; i++) {
                TRACE(2, i, 0);
#pragma unroll 1
                for (int ps = i == 0 ? -2 : 0; ps < 2; ps += ps < 0 ? 2 : 1) {
                    if (ps == 0) {
                        uint32_t slot;
                        if (i == 0) asm volatile("barrier.cluster.wait.aligned;\n" ::: "memory");
                        mbar_wait(bar_xfull, i & 1);
                        asm volatile("ld.shared.v4.u32 {%0, %1, %2, %3}, [%4];\n" : "=r"(off), "=r"(place), "=r"(slot), "=r"(more) : "r"(s_item + (i & 1) * 16) : "memory");
                    }
                    if (ps == 0) TRACE(2, i, 1);
                    if (i == 0) {
#pragma unroll
                        for (int j = 0; j < 6; j++)
                            asm volatile("ld.shared.v4.u32 {%0,%1,%2,%3}, [%4];\n"
                                         : "=r"(d[j][0]), "=r"(d[j][1]), "=r"(d[j][2]), "=r"(d[j][3]) : "r"(sbase + P1_OFF_DW + j * 128 + l8 * 16) : "memory");
                    }
                    uint32_t v[6][4];
#pragma unroll
                    for (int j = 0; j < 6; j++)
                        asm volatile("ld.shared.v4.u32 {%0,%1,%2,%3}, [%4];\n"
                                     : "=r"(v[j][0]), "=r"(v[j][1]), "=r"(v[j][2]), "=r"(v[j][3]) : "r"(src + (ps & 1) * (4 * C_DIM * 2) + j * 128) : "memory");
                    ln_row(v, d, bar_pace + (warp - 8) * 8, off, zero, ps == 1 && lane == 0 ? bar_xempty : 0);
                    uint8_t* dst = h_base() + (place ^ dst0 ^ ln_rows(ps & 1));
#pragma unroll
                    for (int j = 0; j < 6; j++)
                        asm volatile("st.global.v4.u32 [%0], {%1,%2,%3,%4};\n" ::"l"(dst + ln_block(j)), "r"(v[j][0]), "r"(v[j][1]), "r"(v[j][2]), "r"(v[j][3]) : "memory");
                    TRACE(2, i, 3 + (ps & 1));
                }
                asm volatile("fence.proxy.async.global;\nfence.acq_rel.cta;\n" ::: "memory");
                __syncwarp();
                if (lane == 0) mbar_arrive(bar_done);
                TRACE(2, i, 5);
                TRACE(2, i, 2);
            }
        }
        __syncwarp();
        asm volatile("barrier.cluster.arrive.relaxed.aligned;\n" ::: "memory");
        return false;
    } else {
        const int wg = warp >> 2, w = warp & 3;
        auto load_w = [&](int i0, int i1) {
#pragma unroll 1
            for (int i = i0; i < i1; i++) {
                if (!(i & 1)) mbar_expect_tx(bar_w + (i >> 1) * 8, P1_W);
                tma2(sbase + (i & 2) * P1_W + (i >> 2) * P1_W + (i & 1) * (P1_W / 2), &wmap, cig * 256 + ((i >> 1) ^ (first & 1) * 2) * 64, (i & 1) * 192, bar_w + (i >> 1) * 8);
            }
        };
        if (warp == 4 && elect_one()) {
            mbar_init(bar_xfull, 3);
#pragma unroll
            for (int i = 0; i < 4; i++) mbar_init(bar_w + i * 8, 1);
            asm volatile("fence.mbarrier_init.release.cluster;\n" ::: "memory");
            mbar_expect_tx(bar_xfull, P1_X + C_DIM * 2);
            bulk_g2s(sbase + P1_OFF_X, reinterpret_cast<const uint8_t*>(x) + (size_t)blockIdx.x * P1_X, P1_X, bar_xfull);
            bulk_g2s(sbase + P1_OFF_DW, dw, C_DIM * 2, bar_xfull);
            load_w(0, 4);
            asm volatile("st.shared.v4.u32 [%0], {1, %1, %2, 1};\n" ::"r"(s_item), "r"(ln_place(blockIdx.x & 255, 0)), "r"(blockIdx.x >> 2) : "memory");
            mbar_arrive(bar_xfull);
            mbar_arrive(bar_xfull);
        }
        if (warp == 5 && elect_one()) {
#pragma unroll
            for (int i = 0; i < P1_NST; i++) {
                mbar_init(bar_full + i * 8, 1);
                mbar_init(bar_empty + i * 8, i ? 8 : 8 + rank);
                if (i < 4) mbar_init(bar_pace + i * 8, 1);
            }
            mbar_init(bar_xempty, 4);
            mbar_init(bar_done, 4);
            asm volatile("st.shared.u32 [%0], %1;\n" ::"r"(s_side), "r"(first & 1) : "memory");
            asm volatile("st.shared.u32 [%0], -1;\n" ::"r"(s_cl) : "memory");
            asm volatile("fence.mbarrier_init.release.cluster;\n" ::: "memory");
        }
        __syncwarp();
        asm volatile("barrier.cluster.arrive.relaxed.aligned;\n" ::: "memory");
        reg_inc<192>();
        TRACEW(110 + warp, 1);
        LAG_HERE(0);
        uint32_t a[24][4];
        const uint32_t src = sbase + wg * P1_W + ((lane >> 4) * 8 + (lane & 7)) * 128 + (((2 * w + ((lane >> 3) & 1)) ^ (lane & 7)) << 4);
        const uint32_t s_ex = sbase + P1_OFF_EX + ((wg ^ (first & 1)) * 128 + w * 16 + (lane >> 2)) * 4;
        uint32_t sc2[2], ex[2];
        if (wg == 1) bar_arrive(1, 256);
#pragma unroll 1
        for (int it = 0; it < 2; it++) {
          if (it != wg) asm volatile("barrier.cluster.wait.aligned;\n" ::: "memory");
          if (it < wg) {
#pragma unroll 1
              for (int n = 0; n < 64 && !mbar_test(bar_xfull, 0); n++) __nanosleep(40);
              if (w == 0) {
#pragma unroll 1
                  for (int b = 4; b < 8; b += 2) {
                      if (b == 6) mbar_wait(bar_w + 16, 0);
                      if (elect_one()) load_w(b, b + 2);
                      __syncwarp();
                  }
              }
              __syncwarp();
          }
          if (it || wg == 0) {
            float t[2] = {0.f, 0.f};
            if (it) {
                TRACEW(110 + warp, 2);
                mbar_wait(bar_w + wg * 16, 0);
            }
            TRACEW(110 + warp, 5);
#pragma unroll
            for (int k = 0; k < 24; k++) ldsm4t(a[k], src + k * 2048);
            TRACEW(110 + warp, 6);
            p1_squares(a, t);
            sc2[0] = p1_exponents(t, ex, s_ex, lane);
            if (it && lane < 6) mbar_arrive_cluster(mapa(bar_empty, lane & 1) + (wg * 3 + (lane >> 1)) * 8 + (sc2[0] & zero));
            p1_convert<24>(a, a, ex);
          }
          if (it || (wg == 1 && w)) {
            float t[2] = {0.f, 0.f};
            TRACEW(100 + warp, 0);
            if (it) mbar_wait(bar_w + wg * 16 + 8, 0);
            TRACEW(100 + warp, 1);
            uint32_t v[8][4], o[8][4];
#pragma unroll 1
            for (int j = 0; j <= 2 * it; j++) {
#pragma unroll
                for (int k = 0; k < 8; k++) ldsm4t(v[k], src + P1_OFF_W + (8 * j + k) * 2048);
                p1_squares(v, t);
            }
            sc2[1] = p1_exponents(t, ex, s_ex + 256, lane);
#pragma unroll 1
            for (int j = 2 * it; j >= 0; j--) {
                p1_convert<8>(o, v, ex);
#pragma unroll
                for (int k = 0; k < 8; k++) {
                    if (j) ldsm4t(v[k], src + P1_OFF_W + (8 * j - 8 + k) * 2048);
                    if (it) asm volatile("stmatrix.sync.aligned.m8n8.x4.trans.shared.b16 [%0], {%1,%2,%3,%4};\n"
                                         ::"r"(src + P1_OFF_W + (8 * j + k) * 2048), "r"(o[k][0]), "r"(o[k][1]), "r"(o[k][2]), "r"(o[k][3]) : "memory");
                }
            }
          }
        }
        asm volatile("fence.proxy.async.shared::cta;\n" ::: "memory");
        TRACEW(110 + warp, 7);
        bar_sync(6 + wg, 128);
        const bool early = p1_consumer(a, sc2, sbase, wg, w, lane, zero);
        TSTAMP(0, 30);
        return early;
    }
}

constexpr int P2_B = 24576, P2_NB = 4;
constexpr int P2_A = 3072, P2_NA = 8;
constexpr int P2_XROW = C_DIM * 2;
constexpr int P2_OFF_A = P2_B * P2_NB;
constexpr int P2_OFF_X = P2_OFF_A + 3 * P2_NA * P2_A + 128;
constexpr int P2_LHALF = 2 * P2_NA * P2_A + 64;
constexpr int P2_XHALF = 32 * P2_XROW + 64;
constexpr int P2_OFF_GRN = P2_OFF_X + 64 * P2_XROW + 128;
constexpr int P2_OFF_BIAS = P2_OFF_GRN + HID * 2;
constexpr int P2_OFF_RED = P2_OFF_BIAS + C_DIM * 4;
constexpr int P2_OFF_BAR = P2_OFF_RED + 192;
constexpr int P2_SMEM = P2_OFF_BAR + (2 * P2_NB + 6 * P2_NA + 7) * 8;
constexpr int P2_S1 = 16, P2_S2 = 32;
constexpr int P2_NCL = NUM_CTAS / 2, P2_ITEMS = NT128 / P2_NCL, P2_SHARED = NT128 - P2_ITEMS * P2_NCL;
constexpr int P2_NPOS = 6 * 48 + P2_S1;
constexpr int P2_RAW = 16;
constexpr int P2_XC = 8 * P2_XROW;
constexpr int P2_T0 = 5;
constexpr int P2_TL = 8;
constexpr int P2_XP0 = 30;
constexpr int P2_XPN = 13;
constexpr int P2_XPD = 3;
constexpr int P2_AH = 2;
__device__ __forceinline__ int p2_start(int n) { return n < 0 ? 0 : n / 3 * 48 + (n % 3 == 1 ? P2_S1 : n % 3 * (P2_S2 / 2)); }
__device__ __forceinline__ int p2_tile(int cl, int n) {
    return n == 0 ? NT_EARLY - P2_NCL + cl : n < 0 ? NT_EARLY + (cl >> 2) * 2 + (cl & 1) : cl + P2_NCL * (n - 1);
}

__device__ __forceinline__ void p2_epilogue(uint32_t (&acc0)[48], uint32_t (&acc1)[48], uint32_t up, uint32_t sx, uint32_t sb, uint8_t* so, int zero) {
    uint32_t v[12][3][4];
    auto load = [&](int t, int j) {
        if (t >= 12) return;
        uint32_t (&w)[4] = v[t][j];
        asm volatile("ld.shared.v4.u32 {%0,%1,%2,%3}, [%4];\n" : "=r"(w[0]), "=r"(w[1]), "=r"(w[2]), "=r"(w[3])
                     : "r"((j ? sx + (j - 1) * 4 * P2_XROW : sb) + t * 64) : "memory");
    };
    auto store = [&](int t, int r) {
        const uint32_t* w = (t < 6 ? acc0 : acc1) + 8 * (t % 6) + 4 * r;
        asm volatile("st.v4.u32 [%4], {%0,%1,%2,%3};\n" ::"r"(w[0]), "r"(w[1]), "r"(w[2]), "r"(w[3]), "l"(so + t * 64 + r * 4 * P2_XROW) : "memory");
    };
#pragma unroll
    for (int j = 0; j < 3; j++) load(0, j);
#pragma unroll
    for (int t = 0; t < 12; t++) {
        load(t + 1, 1);
        load(t + 1, 2);
        load(t + 1, 0);
        uint32_t* acc = (t < 6 ? acc0 : acc1) + 8 * (t % 6);
        uint32_t y[8];
#pragma unroll
        for (int e = 0; e < 8; e++) {
            y[e] = h2_add(acc[e], v[t][0][e >> 1]);
            y[e] = pack_bf16(h_lo(y[e]), h_hi(y[e]));
        }
#pragma unroll
        for (int e = 0; e < 8; e++) acc[(e & 1) * 4 + (e >> 1)] = bf2_fma(y[e], up, v[t][1 + (e & 1)][e >> 1]);
        store(t, 0);
        store(t, 1);
        if (t & 1) sched_break(zero);
    }
}

__device__ __forceinline__ void p2_unpack(uint32_t (&u)[4], uint32_t o1, uint32_t o2, uint32_t o3) {
    u[2] = o1 & ~SPARE;
    u[1] = o2 & ~SPARE;
    u[3] = o3 & ~SPARE;
    const uint32_t t = bitsel(prmt(o1, o2, 0x6341), prmt(o1, o3, 0x6240) << 3, 0x38383838u);
    u[0] = bitsel(t, prmt(o2, o3, 0x7351) << 1, 0x80808080u) & ~SPARE;
}

__device__ __forceinline__ void p2_redo_sums(int warp, int lane) {
    flag_wait<true>(g_prog[CNT_H], NUM_CTAS);
#pragma unroll 1
    for (int s = warp; s < 96; s += 12) {
        float t[2] = {0.f, 0.f};
#pragma unroll 1
        for (int tile = blockIdx.x; tile < 2 * NT128; tile += NUM_CTAS) {
            const uint32_t* p = reinterpret_cast<const uint32_t*>(h_base() + (h_tile(tile >> 1) ^ h_block(s >> 1, tile & 1)) + (s & 1) * 1536) + lane * 4;
#pragma unroll
            for (int j = 0; j < 4; j++) {
                uint32_t u[4];
                p2_unpack(u, __ldcg(p + j), __ldcg(p + j + 128), __ldcg(p + j + 256));
#pragma unroll
                for (int c = 0; c < 4; c++) t[c >> 1] += h_lo(u[c]) * h_lo(u[c]) + h_hi(u[c]) * h_hi(u[c]);
            }
        }
#pragma unroll
        for (int r = 0; r < 2; r++) {
            const int ch = s * 16 + r * 8 + (lane >> 2);
            atomicAdd(&g_redo[ch], t[r] * (UNCHOP * UNCHOP));
        }
    }
    __threadfence();
    __syncwarp();
    if (lane == 0) asm volatile("red.release.gpu.global.add.u32 [%0], 1;\n" ::"l"(g_prog[CNT_REDO]) : "memory");
    flag_wait<true>(g_prog[CNT_REDO], 12 * NUM_CTAS);
}

static_assert(P2_OFF_GRN >= P1_OFF_X + P1_X && P1_OFF_BAR >= P2_SMEM, "barriers and tables keep their memory");
__device__ __forceinline__ void p2_init(uint32_t sbase) {
    const uint32_t bar = sbase + P2_OFF_BAR;
#pragma unroll 1
    for (int i = 0; i < 2 * P2_NB + 6 * P2_NA + 6; i++) {
        const int j = i - 2 * P2_NB;
        mbar_init(bar + i * 8, j < -P2_NB ? 1 : j < 0 ? 24 : j < 3 * P2_NA ? 1 : j >= 6 * P2_NA && j < 6 * P2_NA + 3 ? 2 : 4);
    }
    asm volatile("st.shared.v2.u32 [%0], {0, 0};\n" ::"r"(bar + (2 * P2_NB + 6 * P2_NA + 6) * 8) : "memory");
    asm volatile("fence.mbarrier_init.release.cluster;\nfence.acq_rel.cta;\n" ::: "memory");
}
template <int ROLE>
__device__ __forceinline__ void pass2(const __nv_bfloat16* __restrict__ x, const __nv_bfloat16* __restrict__ grn_g, __nv_bfloat16* __restrict__ out,
                                      uint8_t* smem, uint32_t sbase, bool early, int zero) {
    const uint32_t bar_bfull = sbase + P2_OFF_BAR, bar_bempty = bar_bfull + P2_NB * 8;
    const uint32_t bar_afull = bar_bempty + P2_NB * 8, bar_aempty = bar_afull + 3 * P2_NA * 8;
    const uint32_t bar_xfull = bar_aempty + 3 * P2_NA * 8, bar_oready = bar_xfull + 24, s_pos = bar_oready + 24;
    int tid;
    asm volatile("mov.u32 %0, %%tid.x;\n" : "=r"(tid));
    const int warp = __shfl_sync(0xffffffffu, tid >> 5, 0), lane = tid & 31;
    const uint32_t rank = cluster_rank();
    int cl, pair, half, fin, k0;
    auto join = [&]() {
        asm volatile("barrier.cluster.wait.aligned;\nld.shared.u32 %0, [%1];\n" : "=r"(cl) : "r"(sbase + OFF_PRE + C_DIM * 4 + 8) : "memory");
        cl = __shfl_sync(0xffffffffu, cl, 0);
        pair = (cl >> 2) * 2 + (cl & 1);
        half = pair < P2_SHARED;
        fin = half && (cl & 2);
        k0 = (pair + 3 * ((cl >> 1) & 1)) % 6 * 8;
    };
    auto wait_pos = [&](int target) {
        int v;
        while (true) {
            asm volatile("ld.volatile.shared.u32 %0, [%1];\n" : "=r"(v) : "r"(s_pos) : "memory");
            if (v >= target) break;
            SAFE_BREAK;
            __nanosleep(100);
        }
    };

    TSTAMP(1, 0);
    LAG_HERE(1);
    if (ROLE == 2) {
        if (warp != 14) flag_wait<true>(g_prog[CNT_IMG0], P2_NCL);
        if (warp == 15) {
            float* pre = reinterpret_cast<float*>(smem + OFF_PRE);
            const float gs = w2_scale(__float_as_uint(__ldcg(&g_sums[C_DIM])));
            float mb = 0.f;
#pragma unroll 1
            for (int i = lane; i < C_DIM; i += 32) {
                pre[i] = __ldcg(&g_sums[i]) * gs;
                mb = fmaxf(mb, fabsf(pre[i]));
            }
            pre[C_DIM] = gs;
            pre[C_DIM + 1] = __uint_as_float(__reduce_max_sync(0xffffffffu, __float_as_uint(mb)));
            bar_sync(9, 288);
            flag_wait<false>(g_prog[CNT_LAST], NUM_CTAS * 8);
            bar_arrive(5, 416);
        }
        join();
        asm volatile("fence.proxy.async;\n" ::: "memory");
        LAG_HERE(2);
        if (warp == 12) {
            const uint8_t* wsrc = reinterpret_cast<const uint8_t*>(g_w2img) + rank * (P2_B / 2);
            int kb = k0;
#pragma unroll 1
            for (int p = 0; p < P2_NPOS; p++) {
                const int st = p & 3;
                if (p == P2_RAW) {
                    flag_wait<true>(g_prog[CNT_IMG1], NUM_CTAS);
                    asm volatile("fence.proxy.async.global;\n" ::: "memory");
                    wsrc += sizeof(g_w2img[0]);
                }
                const int idle = (p < P2_S1 || p >= 6 * 48) + (p < P2_S2 ? !half || p >= 24 : p >= 5 * 48 + P2_S2);
                mbar_wait(bar_bempty + st * 8, (~p >> 2) & 1);
                TR2(3, p, 0);
                if (elect_one()) {
                    mbar_expect_tx(bar_bfull + st * 8, P2_B);
                    bulk_g2s_mc(sbase + st * P2_B + rank * (P2_B / 2), wsrc + kb * P2_B, P2_B / 2, bar_bfull + st * 8, (uint16_t)3);
                    asm volatile("st.volatile.shared.u32 [%0], %1;\n" ::"r"(s_pos), "r"(p) : "memory");
                    if (rank == 0) asm volatile("red.relaxed.gpu.global.add.u32 [%0], 1;\n" ::"l"(g_prog[CNT_POS]) : "memory");
                    if (idle) asm volatile("mbarrier.arrive.shared::cta.b64 _, [%0], %1;\n" ::"r"(bar_bempty + st * 8), "r"(8 * idle) : "memory");
                }
                __syncwarp();
                if (++kb == 48) kb = 0;
            }
            mbar_wait(bar_bempty, 1);
            if (lane == 0) mbar_arrive(bar_bfull);
        } else if (warp == 13) {
            const int w = lane % 3;
            const uint32_t dst0 = sbase + P2_OFF_A + w * P2_NA * P2_A;
            const uint32_t bf = bar_afull + w * P2_NA * 8, be = bar_aempty + w * P2_NA * 8;
            int n = (w == 2 && half ? -1 : w) - 3, left = 0, u = 0, c = 0;
            const uint8_t* const hb = h_base();
            uint32_t ht = 0;
            bool act = lane < 3;
            auto next = [&]() {
                n += 3;
                left = n >= P2_ITEMS ? -1 : n < 0 ? 24 : 48;
                u = (k0 + p2_start(n)) % 48;
                if (left > 0) ht = h_tile(p2_tile(cl, n));
            };
            next();
            flag_wait<true>(g_prog[CNT_EARLY], NUM_CTAS);
#pragma unroll 1
            for (int i = 3; i > 0; i--) {
                const int wi = i % 3;
                if (wi == 2) flag_wait<true>(g_prog[CNT_H], NUM_CTAS);
                asm volatile("fence.proxy.async.global;\n" ::: "memory");
                if (w == wi && lane < 24) {
                    mbar_expect_tx(bf + lane / 3 * 8, P2_A);
                    bulk_g2s(dst0 + lane / 3 * P2_A, hb + (ht ^ h_block(u + lane / 3, rank)), P2_A, bf + lane / 3 * 8);
                }
                __syncwarp();
            }
            c = 8;
            left -= 8;
            u += 8;
            if (u == 48) u = 0;
            while (__any_sync(0xffffffffu, act)) {
                if (left == 0) next();
                const bool ok = act && mbar_test(be + ((c - 1) & 7) * 8, (~c >> 3) & 1);
                if (ok) {
                    const int st = c & 7;
                    if (left > 0) {
                        mbar_expect_tx(bf + st * 8, P2_A);
                        bulk_g2s(dst0 + st * P2_A, hb + (ht ^ h_block(u, rank)), P2_A, bf + st * 8);
                    } else {
                        mbar_arrive(bf + st * 8);
                        act = false;
                    }
                    if (++u == 48) u = 0;
                    c++;
                    left--;
                }
                SAFE_BREAK;
                if (!__any_sync(0xffffffffu, ok)) __nanosleep(100);
            }
        } else if (warp == 14) {
            const uint32_t sx = sbase + P2_OFF_X;
            size_t o = 0;
            int wp = 0;
            uint32_t par = 0;
            if (fin) {
#pragma unroll 1
                for (int c = lane * 16; c < 64 * P2_XROW + 128; c += 512) asm volatile("st.shared.v4.u32 [%0], {0, 0, 0, 0};\n" ::"r"(sx + c) : "memory");
                __syncwarp();
            }
            wait_pos(6);
#pragma unroll 1
            for (int n = -half; n < P2_ITEMS; n++) {
                const int w = (n + 3) % 3, end = p2_start(n) + 48;
                const size_t on = (size_t)(2 * p2_tile(cl, n) + rank) * (64 * C_DIM * 2);
                const uint32_t xf = bar_xfull + w * 8;
                if (n < 2 || n > 12) { LAG_HERE(3); }
                bool st = n + half > 0;
                const bool ld = n < P2_ITEMS - 1 && !(n < 0 && fin);
                if (n == P2_ITEMS - 1 && lane == 0) {
                    mbar_expect_tx(xf, 64 * C_DIM * 2);
#pragma unroll 1
                    for (int c = 4; c < 12; c++) {
                        if (c >= 8) {
                            mbar_wait(bar_aempty + ((2 * c - 1) & 7) * 8, 1);
                            mbar_wait(bar_aempty + ((2 * c) & 7) * 8, 1);
                        }
                        bulk_g2s(sbase + P2_OFF_A + (c & 3) * P2_XC + (c < 8 ? P2_LHALF : 0), reinterpret_cast<const uint8_t*>(x) + on + (c & 7) * P2_XC, P2_XC, xf);
                    }
                    mbar_arrive(xf);
                }
                if (st) {
                    mbar_wait(bar_oready + wp * 8, (par >> wp) & 1);
                    par ^= 1u << wp;
                }
                if (lane == 0) {
                    if (n < P2_ITEMS - 1) mbar_expect_tx(xf, ld ? 64 * C_DIM * 2 : 0);
                    const int t0 = (n ? p2_start(n - 1) + 48 : P2_S2) + (n == P2_ITEMS - 1 ? P2_TL : P2_T0), dt = end - t0;
                    int t = st ? 16 * t0 : -4096;
                    if (n == 0 && half) {
                        if (fin) {
                            flag_wait<true>(&g_half[pair][rank], 1);
                            asm volatile("fence.proxy.async.global;\n" ::: "memory");
                        }
#pragma unroll 1
                        for (int c = 0; c < 2; c++) {
                            uint8_t* dst = reinterpret_cast<uint8_t*>(out) + o + c * 32 * P2_XROW;
                            if (!fin) bulk_s2g(dst, sx + c * P2_XHALF, 32 * P2_XROW);
                            else asm volatile("cp.reduce.async.bulk.global.shared::cta.bulk_group.add.noftz.bf16 [%0], [%1], %2;\n"
                                              ::"l"(dst), "r"(sx + c * P2_XHALF), "r"(32 * P2_XROW) : "memory");
                        }
                        asm volatile("cp.async.bulk.commit_group;\n" ::: "memory");
                        if (!fin) {
                            asm volatile("cp.async.bulk.wait_group 0;\nfence.proxy.async.global;\n" ::: "memory");
                            asm volatile("st.release.gpu.global.u32 [%0], 1;\n" ::"l"(&g_half[pair][rank]) : "memory");
                        }
                        st = false;
                    }
#pragma unroll 1
                    for (int c = 0; c < 64 * P2_XROW; c += P2_XC, t += 2 * dt) {
                        const uint32_t sp = sx + c + (c >= 32 * P2_XROW ? 64 : 0);
                        wait_pos(t >> 4);
                        if (st) bulk_s2g(reinterpret_cast<uint8_t*>(out) + o + c, sp, P2_XC);
                        asm volatile("cp.async.bulk.commit_group;\n" ::: "memory");
                        if (ld) {
                            wait_pos((t + dt) >> 4);
                            asm volatile("cp.async.bulk.wait_group.read 0;\n" ::: "memory");
                            bulk_g2s(sp, reinterpret_cast<const uint8_t*>(x) + on + c, P2_XC, xf);
                        }
                    }
                    if (rank == 0 && n > 0 && n < P2_ITEMS - 2) flag_wait<false>(g_prog[CNT_POS], P2_NCL * (end - 1));
                    if (n < P2_ITEMS - 1) mbar_arrive(xf);
                }
                __syncwarp();
                o = on;
                wp = w;
            }
            asm volatile("cp.async.bulk.wait_group.read 0;\n" ::: "memory");
        } else {
            if (blockIdx.x == 120) {
                wait_pos(P2_RAW);
                for (int i = lane; i < (LN_RING + 6) * 2; i += 32) (&g_flag[0][0][0])[i * 8] = 0;
                for (int i = lane; i < HID; i += 32) g_sq[i] = 0;
                for (int i = lane; i < 512; i += 32) g_sums[i] = 0.f;
                if (lane == 0) g_epoch++;
            }
            int t = 4 * P2_XP0;
#pragma unroll 1
            for (int n = 0; n < P2_ITEMS && lane == 0; n++) {
                const uint8_t* xn = reinterpret_cast<const uint8_t*>(x) + (size_t)(2 * p2_tile(cl, n) + rank) * (64 * C_DIM * 2);
#pragma unroll 1
                for (int c = 0; c < 16; c++, t += n < P2_XPN ? 4 : P2_XPD) {
                    wait_pos(t >> 2);
                    asm volatile("cp.async.bulk.prefetch.L2.global [%0], %1;\n" ::"l"(xn + c * (P2_XC / 2)), "r"(P2_XC / 2) : "memory");
                }
            }
        }
        __syncwarp();
        cluster_sync_relaxed();
    } else {
        const int wg = warp >> 2, w = warp & 3, q = lane & 3;
        const uint32_t af = bar_afull + wg * P2_NA * 8;
        const uint32_t s_a = sbase + P2_OFF_A + wg * P2_NA * P2_A + (lane >> 3) * 512 + (lane & 7) * 64 + ((w ^ ((lane & 7) >> 1)) << 4);
        uint32_t acc0[48], acc1[48], up;
        uint4 a[2][2];

        __nv_bfloat16 gg[4];
#pragma unroll
        for (int i = 0; i < 4; i++) gg[i] = grn_g[tid + 384 * i];
#pragma unroll 1
        for (int it = !early;; it++) {
            float* s_red = reinterpret_cast<float*>(smem + P2_OFF_RED);
            float gx[4], part = 0.f;
            if (it == 1) {
                TSTAMP(1, 27);
                bar_sync(5, 416);
            }
            unsigned long long v[4];
#pragma unroll
            for (int i = 0; i < 4; i++) gx[i] = __ldcg(&g_scale[tid + 384 * i]);
            while (true) {
#pragma unroll
                for (int i = 0; i < 4; i++) asm volatile("ld.relaxed.gpu.global.u64 %0, [%1];\n" : "=l"(v[i]) : "l"(&g_sq[tid + 384 * i]) : "memory");
                SAFE_BREAK;
                if (!it || !__any_sync(0xffffffffu, min(min(v[0], v[1]), min(v[2], v[3])) < (unsigned long long)NGRP << 56)) break;
            }
            TSTAMP(1, 1);
            const float bias = reinterpret_cast<const float*>(smem + OFF_PRE)[tid];
            const float2 pre = *reinterpret_cast<const float2*>(smem + OFF_PRE + C_DIM * 4);
            bool tiny = false;
#pragma unroll
            for (int i = 0; i < 4; i++) {
                const float t = it == 2 ? __ldcg(&g_redo[tid + 384 * i]) : __ull2float_rn(v[i] << 8) * 0x1p-40f;
                tiny |= t < M_TOTAL * 0x1p-19f;
                gx[i] *= gx[i] * t;
            }
            float mg = 0.f;
#pragma unroll
            for (int i = 0; i < 4; i++) {
                asm("sqrt.approx.f32 %0, %1;\n" : "=f"(gx[i]) : "f"(gx[i] * (HSCALE * HSCALE) + 1e-6f));
                part += gx[i];
                gx[i] *= __bfloat162float(gg[i]);
                mg = fmaxf(mg, fabsf(gx[i]));
            }
#pragma unroll
            for (int o = 16; o > 0; o >>= 1) part += __shfl_xor_sync(0xffffffffu, part, o);
            const uint32_t mgw = __reduce_max_sync(0xffffffffu, __float_as_uint(mg));
            TSTAMP(1, 26);
            if (lane == 0) *reinterpret_cast<float2*>(s_red + warp * 2) = make_float2(part, __uint_as_float(mgw));
            if (it) {
                uint32_t redo;
                asm volatile("{\n.reg .pred p;\nsetp.ne.u32 p, %1, 0;\nbar.red.or.pred p, 4, 384, p;\nselp.u32 %0, 1, 0, p;\n}\n"
                             : "=r"(redo) : "r"((uint32_t)(tiny && it == 1)) : "memory");
                if (__shfl_sync(0xffffffffu, redo, 0)) {
                    p2_redo_sums(warp, lane);
                    continue;
                }
            }
            float tot = 0.f;
#pragma unroll
            for (int i = 0; i < 6; i++) {
                const float4 t = *reinterpret_cast<const float4*>(s_red + i * 4);
                tot += t.x + t.z;
                mg = fmaxf(mg, fmaxf(t.y, t.w));
            }
            const float inv = __fdividef(1.0f, tot * (1.0f / HID) + 1e-6f);
            const uint32_t ej = min((__float_as_uint(fmaxf(fmaf(mg, inv, 1.0f) * (HSCALE * UNCHOP), pre.y * 0x1p-13f)) >> 23) + 1, 250u);
            const float dn = __uint_as_float((254u - ej) << 23);
            up = min(ej + 127u - (__float_as_uint(pre.x) >> 23), 254u) * 0x00800080u;
            reinterpret_cast<uint16_t*>(smem + P2_OFF_BIAS + C_DIM * 2)[tid] = 0;
            *reinterpret_cast<__half*>(smem + P2_OFF_BIAS + (tid >> 5) * 64 + (tid & 6) * 8 + (tid & 24) / 2 + (tid & 1) * 2) = __float2half_rn(bias * dn);
#pragma unroll
            for (int i = 0; i < 4; i++) {
                const int k = tid + 384 * i;
                *reinterpret_cast<__half*>(smem + P2_OFF_GRN + (k >> 4) * 32 + (k & 6) * 4 + (k & 8) / 2 + (k & 1) * 2) =
                    __float2half_rn(fmaf(gx[i], inv, 1.0f) * (HSCALE * UNCHOP * dn));
            }
            TSTAMP(1, 25);
            if (it) break;
        }
        join();
        bar_sync(4, 384);
        TSTAMP(1, 28);
        LAG_HERE(2);
        if (wg == 1) {
            constexpr int N = sizeof(g_w2img[0]) / 16, PER = (N + NUM_CTAS - 1) / NUM_CTAS;
            uint4 v[5];
#pragma unroll
            for (int i = 0; i < 5; i++) v[i] = __ldcg(&g_w2img[0][min(blockIdx.x * PER + (tid & 127) + 128 * i, N - 1)]);
#pragma unroll
            for (int i = 0; i < 5; i++) {
                const int j = min(blockIdx.x * PER + (tid & 127) + 128 * i, N - 1);
                const uint32_t* t = reinterpret_cast<const uint32_t*>(smem + P2_OFF_GRN + (j / 768) * 32 + (j & 8) / 2);
                auto sc = [&](uint32_t u, int e) { return (h2_mul(u, t[2 * e]) + 0x00040004u) & 0xfff8fff8u; };
                g_w2img[1][j] = make_uint4(sc(v[i].x, 0), sc(v[i].y, 1), sc(v[i].z, 2), sc(v[i].w, 3));
            }
            asm volatile("fence.proxy.async.global;\n" ::: "memory");
            bar_sync(2, 128);
            if (tid == 128) asm volatile("fence.acq_rel.gpu;\nred.release.gpu.global.add.u32 [%0], 1;\n" ::"l"(g_prog[CNT_IMG1]) : "memory");
        }

        const int who = __shfl_sync(0xffffffffu, lane == 2 ? 0 : lane < 2 ? 1 : 2, lane);
        const uint32_t rel0 = who ? mapa(bar_bempty, lane & 1) : mapa(bar_aempty + wg * P2_NA * 8, rank), rel1 = rel0 + (who ? 0 : 32);
        auto publish = [&]() {
            asm volatile("fence.proxy.async.shared::cta;\n" ::: "memory");
            __syncwarp();
            if (who == 0) mbar_arrive(bar_oready + wg * 8);
        };
        bool ok_a, pend = false;
        uint32_t pa = 0, s_t;
        auto fetch = [&](int j, bool raw) {
            uint32_t o[6], u0[4], u1[4];
            uint2 t0 = make_uint2(0, 0), t1 = t0;
            if (raw) {
                asm volatile("ld.shared.v2.u32 {%0,%1}, [%2];\n" : "=r"(t0.x), "=r"(t0.y) : "r"(s_t + j * 64) : "memory");
                asm volatile("ld.shared.v2.u32 {%0,%1}, [%2];\n" : "=r"(t1.x), "=r"(t1.y) : "r"(s_t + j * 64 + 32) : "memory");
            }
            const bool ok_b = mbar_test(bar_bfull + (j & 3) * 8, j >> 2);
            if (j == 7) pa ^= 1;
            ok_a = mbar_test(af + ((j + 1) & 7) * 8, pa);
            asm volatile("ldmatrix.sync.aligned.m8n8.x4.trans.shared.b16 {%0,%1,%2,%3}, [%4];\n"
                         : "=r"(o[0]), "=r"(o[1]), "=r"(o[2]), "=r"(o[3]) : "r"(s_a + j * P2_A) : "memory");
            asm volatile("ldmatrix.sync.aligned.m8n8.x2.trans.shared.b16 {%0,%1}, [%2];\n"
                         : "=r"(o[4]), "=r"(o[5]) : "r"(s_a + j * P2_A + 2048) : "memory");
            p2_unpack(u0, o[0], o[1], o[2]);
            p2_unpack(u1, o[3], o[4], o[5]);
            if (raw) {
                u0[0] = h2_mul(u0[0], t0.x); u0[1] = h2_mul(u0[1], t0.x); u0[2] = h2_mul(u0[2], t0.y); u0[3] = h2_mul(u0[3], t0.y);
                u1[0] = h2_mul(u1[0], t1.x); u1[1] = h2_mul(u1[1], t1.x); u1[2] = h2_mul(u1[2], t1.y); u1[3] = h2_mul(u1[3], t1.y);
            }
            a[j & 1][0] = make_uint4(u0[0], u0[1], u0[2], u0[3]);
            a[j & 1][1] = make_uint4(u1[0], u1[1], u1[2], u1[3]);
            if (!ok_b) mbar_wait(bar_bfull + (j & 3) * 8, j >> 2);
        };
        auto table = [&](int pos) { s_t = sbase + P2_OFF_GRN + q * 8 + (k0 + pos) % 48 * 64; };
        const uint64_t db0 = make_desc(sbase, 128, 256 + zero);
        auto block8 = [&](bool raw, int pos, int thr0, int mode) {
#pragma unroll
            for (int j = 0; j < 8; j++) {
                const uint64_t db = db0 + (j & 3) * (P2_B / 16);
                if (j == 8 - P2_AH && mode == 1) bar_sync(4, 384);
                TR2(wg, pos + j, 0);
                wg_fence();
                mma_rs_n192(acc0, a[j & 1][0], db);
                mma_rs_n192(acc1, a[j & 1][0], db + 384);
                mma_rs_n192(acc0, a[j & 1][1], db + 768);
                mma_rs_n192(acc1, a[j & 1][1], db + 768 + 384);
                wg_commit();
                if (j == 7 && mode == 2) bar_arrive(4, 384);
                const uint32_t rel = ((j - 1) & 4 ? rel1 : rel0) + ((j - 1) & 3) * 8;
                TR2(wg, pos + j, 1);
                wg_wait<1>();
                TR2(wg, pos + j, 2);
                if (who < (j ? 2 : thr0)) mbar_arrive_cluster(rel);
                if (!ok_a) {
                    if (j == 0 && pend) { publish(); pend = false; }
                    mbar_wait(af + ((j + 1) & 7) * 8, pa);
                }
                TR2(wg, pos + j, 3);
                if (raw && j == 7) table(pos + 8);
                fetch((j + 1) & 7, raw && (j < 7 || pos + 8 < P2_RAW));
            }
        };
        int n = wg == 2 && half ? -1 : wg, pos = p2_start(n);
        uint32_t px = 0;
        wait_pos(pos);
        mbar_wait(af, 0);
        table(pos);
        fetch(0, pos < P2_RAW);
#pragma unroll 1
        for (;; n += 3) {
            TSTAMP(1, 2 + n);
            const int end = pos + (n < 0 ? 24 : 48);
#pragma unroll
            for (int i = 0; i < 48; i += 2) {
                asm volatile("mov.b64 {%0, %1}, 0;\n" : "=r"(acc0[i]), "=r"(acc0[i + 1]));
                asm volatile("mov.b64 {%0, %1}, 0;\n" : "=r"(acc1[i]), "=r"(acc1[i + 1]));
            }
            int thr = 1;
#pragma unroll 1
            for (; pos < P2_RAW; pos += 8, thr = 2) block8(true, pos, thr, 0);
#pragma unroll 1
            for (; pos < end; pos += 8, thr = 2) {
                const int e = pos + 8, r = e % 48;
                block8(false, pos, thr, e < 48 || e > 256 || (r != 0 && r != P2_S1 && r != P2_S2) ? 0 : e == end ? 2 : 1);
            }
            TR2(wg, pos - 1, 4);
            if (n < 2 || n > 12) { LAG_HERE(3); }
            wg_wait<0>();
            TR2(wg, pos - 1, 5);
            if (who == 1) mbar_arrive_cluster(rel0 + 24);
            mbar_wait(bar_xfull + wg * 8, px);
            TR2(wg, pos - 1, 6);
            px ^= 1;
            __syncwarp();
            const bool last = n == P2_ITEMS - 1;
            uint32_t l;
            asm volatile("mov.u32 %0, %%laneid;\n" : "=r"(l));
            const uint32_t q16 = (l & 3) * 16, odd = (l >> 2) & 1, row = (w * 8 + (l >> 3)) * P2_XROW + q16;
            uint8_t* so = last ? reinterpret_cast<uint8_t*>(out) + (size_t)(2 * p2_tile(cl, n) + rank) * (64 * P2_XROW) : smem + P2_OFF_X;
            p2_epilogue(acc0, acc1, up, sbase + row + (last ? P2_OFF_A + odd * P2_LHALF : P2_OFF_X + odd * P2_XHALF),
                        sbase + P2_OFF_BIAS + q16 + (n < 0 && fin ? C_DIM * 2 : 0), so + (row + odd * (last ? 32 * P2_XROW : P2_XHALF)), zero);
            if (last) break;
            TR2(wg, pos - 1, 7);
            if (n + 3 >= P2_ITEMS) { publish(); break; }
            if (n < 0) {
                publish();
                pos = P2_S2;
                wait_pos(pos);
                mbar_wait(bar_bfull, 0);
            } else {
                pend = true;
                ok_a = false;
            }
        }
        TSTAMP(1, 29);
        cluster_sync_relaxed();
        TSTAMP(1, 30);
    }
}

__global__ void __cluster_dims__(2, 1, 1) __launch_bounds__(512, 1)
block_kernel(const __grid_constant__ CUtensorMap wmap, const __nv_bfloat16* __restrict__ x, const __nv_bfloat16* __restrict__ dw,
             const __nv_bfloat16* __restrict__ w2, const __nv_bfloat16* __restrict__ grn_g, const __nv_bfloat16* __restrict__ grn_b,
             __nv_bfloat16* __restrict__ out, int zero) {
    extern __shared__ __align__(1024) uint8_t smem[];
    const uint32_t sbase = smem_u32(smem);
    const int warp = __shfl_sync(0xffffffffu, threadIdx.x >> 5, 0), lane = threadIdx.x & 31;
    if (warp >= 12) {
        pass1<2>(wmap, x, dw, w2, grn_b, sbase, warp, lane, zero);
        pass2<2>(x, grn_g, out, smem, sbase, false, zero);
    } else {
        bool early = false;
        if (warp >= 8) {
            pass1<1>(wmap, x, dw, w2, grn_b, sbase, warp, lane, zero);
            reg_inc<160>();
        } else {
            early = pass1<0>(wmap, x, dw, w2, grn_b, sbase, warp, lane, zero);
            reg_dec<160>();
        }
        pass2<0>(x, grn_g, out, smem, sbase, early, zero);
    }
}

}

extern "C" void kernel_launch(void* const* d_in, const int* in_sizes, int n_in, void* d_out, int out_size) {
    const __nv_bfloat16* x = (const __nv_bfloat16*)d_in[0];
    const __nv_bfloat16* dw = (const __nv_bfloat16*)d_in[1];
    const __nv_bfloat16* w1 = (const __nv_bfloat16*)d_in[2];
    const __nv_bfloat16* w2 = (const __nv_bfloat16*)d_in[3];
    const __nv_bfloat16* grn_g = (const __nv_bfloat16*)d_in[4];
    const __nv_bfloat16* grn_b = (const __nv_bfloat16*)d_in[5];
    __nv_bfloat16* out = (__nv_bfloat16*)d_out;

    cudaFuncSetAttribute(block_kernel, cudaFuncAttributeMaxDynamicSharedMemorySize, SMEM_BYTES);

    typedef CUresult (*EncodeFn)(CUtensorMap*, CUtensorMapDataType, cuuint32_t, void*, const cuuint64_t*, const cuuint64_t*,
                                 const cuuint32_t*, const cuuint32_t*, CUtensorMapInterleave, CUtensorMapSwizzle,
                                 CUtensorMapL2promotion, CUtensorMapFloatOOBfill);
    static EncodeFn encode = nullptr;
    if (!encode) {
        cudaDriverEntryPointQueryResult qres;
        cudaGetDriverEntryPoint("cuTensorMapEncodeTiled", (void**)&encode, cudaEnableDefault, &qres);
    }
    CUtensorMap wmap;
    const cuuint64_t gdim[2] = {HID, C_DIM};
    const cuuint64_t gstr[1] = {HID * 2};
    const cuuint32_t box[2] = {64, 192}, estr[2] = {1, 1};
    CUresult er = encode(&wmap, CU_TENSOR_MAP_DATA_TYPE_BFLOAT16, 2, (void*)w1, gdim, gstr, box, estr, CU_TENSOR_MAP_INTERLEAVE_NONE,
           CU_TENSOR_MAP_SWIZZLE_128B, CU_TENSOR_MAP_L2_PROMOTION_L2_128B, CU_TENSOR_MAP_FLOAT_OOB_FILL_NONE);
    if (er != CUDA_SUCCESS) printf("tensor map encode failed %d\n", (int)er);

    block_kernel<<<NUM_CTAS, 512, SMEM_BYTES>>>(wmap, x, dw, w2, grn_g, grn_b, out, 0);
}
```

```cpp
#include <cuda.h>
#include <cuda_runtime.h>
#include <cuda_bf16.h>
#include <cuda_fp16.h>
#include <stdint.h>
#include <stdio.h>

namespace {

constexpr int M_TOTAL = 384 * 384;
constexpr int C_DIM   = 384;
constexpr int HID     = 1536;
constexpr int NT128   = M_TOTAL / 128;
constexpr int NUM_CTAS = 132;

constexpr int NGRP = 22, GRP_CTAS = 6;
constexpr int NT_EARLY = NT128 - 30;
constexpr int LN_STEP = NUM_CTAS / 4, LN_RING = 2 * LN_STEP;
constexpr int LN_TILE = 128 * C_DIM * 2;
constexpr int H_PAGES = NT128 / 4;

__device__ __align__(1024) uint4 g_h[(size_t)(H_PAGES + 1) << 17];
__device__ unsigned g_page[H_PAGES];
__device__ unsigned g_epoch;
__device__ __align__(1024) uint4 g_w2img[2][HID * C_DIM * 2 / 16];
__device__ __align__(16) unsigned long long g_sq[HID];
__device__ __align__(16) float g_sums[512];
__device__ float g_scale[HID];
__device__ float g_redo[HID];
enum { CNT_POS, CNT_IMG1, CNT_REDO, CNT_IMG0, CNT_LAST, CNT_H, CNT_EARLY, NUM_CNT };
__device__ __align__(128) unsigned g_prog[NUM_CNT][32];
__device__ __align__(128) unsigned g_half[32][2];
__device__ unsigned g_flag[LN_RING + 6][2][8];
#define TSTAMP(k, i)
#define TRACE(wg, pos, i)
#define TRACEW(pos, i)

#define TR2(wg, pos, i)
__host__ __device__ __forceinline__ int perm32(int n) {
    return (n & ~31) | (((n >> 1) & 3) << 3) | (((n >> 3) & 3) << 1) | (n & 1);
}

constexpr int H_FIXED = 12;
constexpr int LN_SW = LN_RING;
__device__ __forceinline__ uint8_t* h_base() { return reinterpret_cast<uint8_t*>((reinterpret_cast<size_t>(g_h) + 0x1fffff) & ~(size_t)0x1fffff); }
__device__ __forceinline__ unsigned page_bit(int page, unsigned tag) {
    unsigned v = 0;
    if (page >= H_FIXED) {
        do {
            asm volatile("ld.relaxed.gpu.global.u32 %0, [%1];\n" : "=r"(v) : "l"(&g_page[page]) : "memory");
        } while (tag && (v & ~1u) != tag);
    }
    return v;
}
__device__ __forceinline__ uint32_t h_tile(int t, unsigned bit) { return (t >> 1) << 20 | ((t ^ bit) & 1) << 12 | (t & 2) << 9; }
__device__ __forceinline__ uint32_t h_tile(int t) { return h_tile(t, page_bit(t >> 2, 0)); }
__device__ __forceinline__ int ln_page(int t) { return (t < LN_SW ? 0 : 17) + (t % LN_RING >> 2); }
__device__ __forceinline__ int ln_probed(int t) { return t < LN_SW ? 0 : ln_page(t); }
__device__ __forceinline__ uint32_t ln_tile(int t, unsigned bit) {
    const int slot = t % LN_RING;
    return ln_page(t) << 21 | 0xc0000 | (slot & 2) << 16 | ((~t ^ bit ^ (slot >> 1)) & 1) << 12;
}
__device__ __forceinline__ constexpr uint32_t ln_rows(int group) { return (group & 1) * 0x3000 ^ (group >> 1) * 0x11000; }
__device__ __forceinline__ constexpr uint32_t ln_block(int j) { return (j & 3) << 14 | (j >> 2) << 20; }
__device__ __forceinline__ uint32_t h_block(int kb, int half) {
    return (kb >> 2) << 16 | (kb & 2) << 14 | half << 14 | (kb & 1) << 13 | (__popc(kb & 0x2d) & 1) << 12 | (kb & 1) << 10;
}
__device__ __forceinline__ unsigned* h_cell(int page, int c) {
    return reinterpret_cast<unsigned*>(h_base() + ((size_t)page << 21) + 0x1d8000 + ((c >> 6) << 14) + (c & 63) * 64);
}
__device__ __forceinline__ unsigned near_half(unsigned* cell) {
    int votes = 0;
#pragma unroll 1
    for (int i = 0; i < 6; i++) {
        const unsigned a = atomicAdd(cell + (i & 1) * 1024, 1u), b = atomicAdd(cell + (~i & 1) * 1024, 1u);
        if (a == ~0u) break;
        const unsigned t0 = clock();
        if (b == ~0u) break;
        const int d = min((unsigned)clock() - t0, 250u);
        votes += i & 1 ? d : -d;
    }
    return votes > 0;
}

__device__ __forceinline__ uint32_t smem_u32(const void* p) { return (uint32_t)__cvta_generic_to_shared(p); }

__device__ __forceinline__ void mbar_init(uint32_t bar, uint32_t count) {
    asm volatile("mbarrier.init.shared::cta.b64 [%0], %1;\n" ::"r"(bar), "r"(count) : "memory");
}
__device__ __forceinline__ void mbar_expect_tx(uint32_t bar, uint32_t bytes) {
    asm volatile("mbarrier.arrive.expect_tx.shared::cta.b64 _, [%0], %1;\n" ::"r"(bar), "r"(bytes) : "memory");
}
__device__ __forceinline__ void mbar_arrive(uint32_t bar) {
    asm volatile("mbarrier.arrive.shared::cta.b64 _, [%0];\n" ::"r"(bar) : "memory");
}
__device__ __forceinline__ void mbar_arrive_cluster(uint32_t bar_cluster_addr) {
    asm volatile("mbarrier.arrive.shared::cluster.b64 _, [%0];\n" ::"r"(bar_cluster_addr) : "memory");
}
#define LAG_HERE(k)
#define SAFE_BREAK
__device__ __forceinline__ void mbar_wait(uint32_t bar, uint32_t parity) {
    asm volatile(
        "{\n"
        ".reg .pred p;\n"
        "LAB_WAIT:\n"
        "mbarrier.try_wait.parity.shared::cta.b64 p, [%0], %1;\n"
        "@!p bra LAB_WAIT;\n"
        "}\n" ::"r"(bar), "r"(parity) : "memory");
}
__device__ __forceinline__ bool mbar_test(uint32_t bar, uint32_t parity) {
    uint32_t ok;
    asm volatile("{\n.reg .pred p;\n"
                 "mbarrier.test_wait.parity.shared::cta.b64 p, [%1], %2;\n"
                 "selp.u32 %0, 1, 0, p;\n}\n" : "=r"(ok) : "r"(bar), "r"(parity) : "memory");
    return ok != 0;
}
__device__ __forceinline__ uint32_t mapa(uint32_t addr, uint32_t rank) {
    uint32_t r;
    asm volatile("mapa.shared::cluster.u32 %0, %1, %2;\n" : "=r"(r) : "r"(addr), "r"(rank));
    return r;
}
__device__ __forceinline__ void bulk_g2s(uint32_t dst, const void* src, uint32_t bytes, uint32_t bar) {
    asm volatile("cp.async.bulk.shared::cluster.global.mbarrier::complete_tx::bytes [%0], [%1], %2, [%3];\n"
                 ::"r"(dst), "l"(src), "r"(bytes), "r"(bar) : "memory");
}
__device__ __forceinline__ void bulk_g2s_mc(uint32_t dst, const void* src, uint32_t bytes, uint32_t bar, uint16_t mask) {
    asm volatile("cp.async.bulk.shared::cluster.global.mbarrier::complete_tx::bytes.multicast::cluster [%0], [%1], %2, [%3], %4;\n"
                 ::"r"(dst), "l"(src), "r"(bytes), "r"(bar), "h"(mask) : "memory");
}
__device__ __forceinline__ void tma2(uint32_t dst, const CUtensorMap* map, int c0, int c1, uint32_t bar) {
    asm volatile("cp.async.bulk.tensor.2d.shared::cluster.global.tile.mbarrier::complete_tx::bytes [%0], [%1, {%2, %3}], [%4];\n"
                 ::"r"(dst), "l"(map), "r"(c0), "r"(c1), "r"(bar) : "memory");
}
template <bool ACQ>
__device__ __forceinline__ uint32_t flag_wait(const unsigned* p, unsigned target) {
    unsigned v, n = 0;
    do {
        if (ACQ) asm volatile("ld.acquire.gpu.global.u32 %0, [%1];\n" : "=r"(v) : "l"(p) : "memory");
        else asm volatile("ld.relaxed.gpu.global.u32 %0, [%1];\n" : "=r"(v) : "l"(p) : "memory");
        n++;
    } while (v < target);
    return n == 1;
}
__device__ __forceinline__ void ldsm4t(uint32_t (&r)[4], uint32_t addr) {
    asm volatile("ldmatrix.sync.aligned.m8n8.x4.trans.shared.b16 {%0,%1,%2,%3}, [%4];\n"
                 : "=r"(r[0]), "=r"(r[1]), "=r"(r[2]), "=r"(r[3]) : "r"(addr) : "memory");
}
__device__ __forceinline__ void bulk_s2g(void* dst, uint32_t src, uint32_t bytes) {
    asm volatile("cp.async.bulk.global.shared::cta.bulk_group [%0], [%1], %2;\n" ::"l"(dst), "r"(src), "r"(bytes) : "memory");
}
__device__ __forceinline__ void cluster_sync_relaxed() {
    asm volatile("barrier.cluster.arrive.relaxed.aligned;\nbarrier.cluster.wait.aligned;\n" ::: "memory");
}
__device__ __forceinline__ uint32_t cluster_rank() {
    uint32_t r;
    asm volatile("mov.u32 %0, %%cluster_ctarank;\n" : "=r"(r));
    return r;
}
__device__ __forceinline__ bool elect_one() {
    uint32_t pred;
    asm volatile("{\n.reg .pred p;\nelect.sync _|p, 0xffffffff;\nselp.u32 %0, 1, 0, p;\n}\n" : "=r"(pred));
    return pred != 0;
}
__device__ __forceinline__ void wg_fence() { asm volatile("wgmma.fence.sync.aligned;\n" ::: "memory"); }
__device__ __forceinline__ void wg_commit() { asm volatile("wgmma.commit_group.sync.aligned;\n" ::: "memory"); }
template <int N> __device__ __forceinline__ void wg_wait() {
    asm volatile("wgmma.wait_group.sync.aligned %0;\n" ::"n"(N) : "memory");
}
template <int R> __device__ __forceinline__ void reg_inc() { asm volatile("setmaxnreg.inc.sync.aligned.u32 %0;\n" ::"n"(R)); }
template <int R> __device__ __forceinline__ void reg_dec() { asm volatile("setmaxnreg.dec.sync.aligned.u32 %0;\n" ::"n"(R)); }
__device__ __forceinline__ void bar_sync(int id, int n) { asm volatile("bar.sync %0, %1;\n" ::"r"(id), "r"(n) : "memory"); }
__device__ __forceinline__ void bar_arrive(int id, int n) { asm volatile("bar.arrive %0, %1;\n" ::"r"(id), "r"(n) : "memory"); }

__device__ __forceinline__ uint64_t make_desc(uint32_t saddr, uint32_t lbo, uint32_t sbo) {
    return (uint64_t)((saddr & 0x3FFFF) >> 4) | ((uint64_t)(lbo >> 4) << 16) | ((uint64_t)(sbo >> 4) << 32);
}

__device__ __forceinline__ void stg128_cs(void* p, uint32_t a, uint32_t b, uint32_t c, uint32_t d) {
    asm volatile("st.global.cs.v4.u32 [%0], {%1,%2,%3,%4};\n" ::"l"(p), "r"(a), "r"(b), "r"(c), "r"(d) : "memory");
}
__device__ __forceinline__ uint32_t pack_bf16(float lo, float hi) {
    uint32_t r;
    asm("cvt.rn.bf16x2.f32 %0, %1, %2;\n" : "=r"(r) : "f"(hi), "f"(lo));
    return r;
}
__device__ __forceinline__ float bf_lo(uint32_t v) { return __uint_as_float(v << 16); }
__device__ __forceinline__ float bf_hi(uint32_t v) { return __uint_as_float(v & 0xffff0000u); }
__device__ __forceinline__ uint32_t bf2_mul(uint32_t a, uint32_t b) {
    uint32_t r;
    asm("mul.rn.bf16x2 %0, %1, %2;\n" : "=r"(r) : "r"(a), "r"(b));
    return r;
}
__device__ __forceinline__ uint32_t bf2_fma(uint32_t a, uint32_t b, uint32_t c) {
    uint32_t r;
    asm("fma.rn.bf16x2 %0, %1, %2, %3;\n" : "=r"(r) : "r"(a), "r"(b), "r"(c));
    return r;
}
__device__ __forceinline__ uint32_t bf2_add(uint32_t a, uint32_t b) {
    uint32_t r;
    asm("add.rn.bf16x2 %0, %1, %2;\n" : "=r"(r) : "r"(a), "r"(b));
    return r;
}
__device__ __forceinline__ uint32_t h2_mul(uint32_t a, uint32_t b) {
    uint32_t r;
    asm("mul.rn.f16x2 %0, %1, %2;\n" : "=r"(r) : "r"(a), "r"(b));
    return r;
}
__device__ __forceinline__ uint32_t h2_fma(uint32_t a, uint32_t b, uint32_t c) {
    uint32_t r;
    asm("fma.rn.f16x2 %0, %1, %2, %3;\n" : "=r"(r) : "r"(a), "r"(b), "r"(c));
    return r;
}
__device__ __forceinline__ uint32_t h2_add(uint32_t a, uint32_t b) {
    uint32_t r;
    asm("add.rn.f16x2 %0, %1, %2;\n" : "=r"(r) : "r"(a), "r"(b));
    return r;
}
__device__ __forceinline__ uint32_t pack_f16(float lo, float hi) {
    uint32_t r;
    asm("cvt.rn.f16x2.f32 %0, %1, %2;\n" : "=r"(r) : "f"(hi), "f"(lo));
    return r;
}
__device__ __forceinline__ float h_lo(uint32_t v) { return __low2float(*reinterpret_cast<const __half2*>(&v)); }
__device__ __forceinline__ float h_hi(uint32_t v) { return __high2float(*reinterpret_cast<const __half2*>(&v)); }
__device__ __forceinline__ uint32_t bf2_to_h2(uint32_t v) { return (v & 0x7fff7fffu) * 7u + v; }
__device__ __forceinline__ uint32_t prmt(uint32_t a, uint32_t b, uint32_t sel) {
    uint32_t r;
    asm("prmt.b32 %0, %1, %2, %3;\n" : "=r"(r) : "r"(a), "r"(b), "r"(sel));
    return r;
}
__device__ __forceinline__ uint32_t bitsel(uint32_t a, uint32_t b, uint32_t m) {
    uint32_t r;
    asm("lop3.b32 %0, %1, %2, %3, 0xd8;\n" : "=r"(r) : "r"(a), "r"(b), "r"(m));
    return r;
}
constexpr float KAPPA = 0.3292034911525734f;
constexpr uint32_t GELU_C2 = 0x40d940d9u;
constexpr float HSCALE = 1.0f / (2.0f * KAPPA);
__device__ __forceinline__ float w2_scale(uint32_t m) { return __uint_as_float((257u - max(m >> 23, 16u)) << 23); }
__device__ __forceinline__ void sched_break(int zero) {
    asm volatile("{\n.reg .pred p;\nsetp.ne.s32 p, %0, 0;\nSB_LOOP:\n@p nanosleep.u32 1;\n@p bra SB_LOOP;\n}\n" ::"r"(zero));
}

#define ACC8(d, o) "+r"(d[o + 0]), "+r"(d[o + 1]), "+r"(d[o + 2]), "+r"(d[o + 3]), "+r"(d[o + 4]), "+r"(d[o + 5]), "+r"(d[o + 6]), "+r"(d[o + 7])

__device__ __forceinline__ void mma_rs_n128(uint32_t (&d)[32], const uint32_t (&a)[4], uint64_t desc, int scale_d) {
    asm volatile(
        "{\n.reg .pred p;\nsetp.ne.b32 p, %37, 0;\n"
        "wgmma.mma_async.sync.aligned.m64n128k16.f16.f16.f16 "
        "{%0,%1,%2,%3,%4,%5,%6,%7,%8,%9,%10,%11,%12,%13,%14,%15,"
        "%16,%17,%18,%19,%20,%21,%22,%23,%24,%25,%26,%27,%28,%29,%30,%31},"
        "{%32,%33,%34,%35}, %36, p, 1, 1, 0;\n}\n"
        : ACC8(d, 0), ACC8(d, 8), ACC8(d, 16), ACC8(d, 24)
        : "r"(a[0]), "r"(a[1]), "r"(a[2]), "r"(a[3]), "l"(desc), "r"(scale_d));
}

__device__ __forceinline__ void mma_ss_n128(uint32_t (&d)[32], uint64_t da, uint64_t db, int scale_d) {
    asm volatile(
        "{\n.reg .pred p;\nsetp.ne.b32 p, %34, 0;\n"
        "wgmma.mma_async.sync.aligned.m64n128k16.f16.f16.f16 "
        "{%0,%1,%2,%3,%4,%5,%6,%7,%8,%9,%10,%11,%12,%13,%14,%15,"
        "%16,%17,%18,%19,%20,%21,%22,%23,%24,%25,%26,%27,%28,%29,%30,%31},"
        "%32, %33, p, 1, 1, 1, 0;\n}\n"
        : ACC8(d, 0), ACC8(d, 8), ACC8(d, 16), ACC8(d, 24)
        : "l"(da), "l"(db), "r"(scale_d));
}

__device__ __forceinline__ void mma_rs_n192(uint32_t (&d)[48], const uint4& a, uint64_t db) {
    asm volatile(
        "wgmma.mma_async.sync.aligned.m64n192k16.f16.f16.f16 "
        "{%0,%1,%2,%3,%4,%5,%6,%7,%8,%9,%10,%11,%12,%13,%14,%15,"
        "%16,%17,%18,%19,%20,%21,%22,%23,%24,%25,%26,%27,%28,%29,%30,%31,"
        "%32,%33,%34,%35,%36,%37,%38,%39,%40,%41,%42,%43,%44,%45,%46,%47},"
        "{%48,%49,%50,%51}, %52, 1, 1, 1, 0;\n"
        : ACC8(d, 0), ACC8(d, 8), ACC8(d, 16), ACC8(d, 24), ACC8(d, 32), ACC8(d, 40)
        : "r"(a.x), "r"(a.y), "r"(a.z), "r"(a.w), "l"(db));
}

constexpr int P1_SPLIT = 6;
constexpr int P1_SLOT = LN_TILE / 6, P1_NST = 6;
constexpr int P1_W = 64 * C_DIM * 2;
constexpr int P1_X = 32 * C_DIM * 2;
constexpr int P1_OFF_W = LN_TILE;
constexpr int P1_OFF_X = P1_OFF_W + 2 * P1_W;
constexpr int P1_OFF_BAR = 227328;
constexpr int P1_OFF_TILE = P1_OFF_BAR + (2 * P1_NST + 4 + 4 + 4) * 8;
constexpr int P1_OFF_EX = P1_OFF_TILE + 96;
constexpr int P1_OFF_DW = P1_OFF_EX + 256 * 4;
constexpr int OFF_PRE = P1_OFF_DW + C_DIM * 2;
constexpr int SMEM_BYTES = OFF_PRE + C_DIM * 4 + 16;

__device__ __forceinline__ float rsqrt_fast(float x) {
    float r;
    asm("rsqrt.approx.ftz.f32 %0, %1;\n" : "=f"(r) : "f"(x));
    return r;
}
__device__ __forceinline__ float row_sum(const uint32_t (&c)[4]) {
    const uint32_t u = bf2_add(bf2_add(c[0], c[1]), bf2_add(c[2], c[3]));
    float s = bf_lo(u) + bf_hi(u);
#pragma unroll
    for (int o = 1; o < 8; o <<= 1) s += __shfl_xor_sync(0xffffffffu, s, o);
    return s;
}
__device__ __forceinline__ uint32_t pace(uint32_t bar, uint32_t off, uint32_t val, int zero) {
    asm volatile(
        "{\n.reg .pred p, q;\n.reg .b32 par;\n"
        "lop3.b32 par, %0, %2, %3, 0xea;\n"
        "setp.eq.u32 q, par, 0;\n"
        "mov.pred p, 0;\n"
        "@q mbarrier.test_wait.parity.shared::cta.b64 p, [%1], par;\n"
        "selp.u32 par, 1, 0, p;\n"
        "@q mbarrier.try_wait.parity.shared::cta.b64 p, [%1], par, 1000;\n"
        "@p or.b32 %0, %0, %2;\n"
        "}\n" : "+r"(val) : "r"(bar), "r"(zero), "r"(off));
    return val;
}
__device__ __forceinline__ void ln_row(uint32_t (&v)[6][4], const uint32_t (&d)[6][4], uint32_t bar, uint32_t off, int zero, uint32_t bar_read) {
    const float inv = 1.0f / C_DIM;
    uint32_t c[4];
#pragma unroll
    for (int i = 0; i < 6; i++)
#pragma unroll
        for (int k = 0; k < 4; k++) c[k] = bf2_fma(v[i][k], d[i][k], i ? c[k] : 0);
    const float m = row_sum(c) * inv;
    uint32_t nm = pack_bf16(-m, -m);
    const float e = m + bf_lo(nm);
    if (bar_read) mbar_arrive(bar_read + (nm & zero));
    nm = pace(bar, off, nm, zero);
#pragma unroll
    for (int i = 0; i < 6; i++) {
#pragma unroll
        for (int k = 0; k < 4; k++) {
            v[i][k] = bf2_fma(v[i][k], d[i][k], nm);
            c[k] = i ? bf2_fma(v[i][k], v[i][k], c[k]) : bf2_mul(v[i][k], v[i][k]);
        }
    }
    float r = KAPPA * rsqrt_fast(fmaxf(fmaf(-e, e, row_sum(c) * inv), 0.f) + 1e-5f);
    const float er = -e * r * 0x1p-112f;
    if (__any_sync(0xffffffffu, r < 0x1p-8f)) {
        const uint32_t p2 = __float_as_uint(r) & 0x7f800000u;
        r = __uint_as_float((__float_as_uint(r) & 0x007fffffu) | 0x3f800000u);
#pragma unroll
        for (int i = 0; i < 6; i++)
#pragma unroll
            for (int k = 0; k < 4; k++) v[i][k] = bf2_mul(v[i][k], p2 | p2 >> 16);
    }
    const uint32_t rs = pack_bf16(r * 0x1p-112f, r * 0x1p-112f), sh = pack_bf16(er, er);
#pragma unroll
    for (int i = 0; i < 6; i++)
#pragma unroll
        for (int k = 0; k < 4; k++) v[i][k] = bf2_to_h2(bf2_fma(v[i][k], rs, sh));
}

template <int R>
__device__ __forceinline__ uint32_t gelu2(uint32_t a, uint32_t sc2) {
    uint32_t y, t;
    if (R) asm("{\n.reg .b16 l, h;\n.reg .b32 f;\nmov.b32 {l, h}, %2;\nmov.b32 f, {h, h};\nmul.rn.f16x2 %0, %1, f;\n}\n" : "=r"(y) : "r"(a), "r"(sc2));
    else asm("{\n.reg .b16 l, h;\n.reg .b32 f;\nmov.b32 {l, h}, %2;\nmov.b32 f, {l, l};\nmul.rn.f16x2 %0, %1, f;\n}\n" : "=r"(y) : "r"(a), "r"(sc2));
    asm("tanh.approx.f16x2 %0, %1;\n" : "=r"(t) : "r"(h2_mul(y, h2_fma(y, y, GELU_C2))));
    return h2_fma(a, t, a);
}
constexpr uint32_t SPARE = 0x40074007u;
constexpr float UNCHOP = 1.0023f;

__device__ __forceinline__ uint32_t p1_exponents(float (&t)[2], uint32_t (&ex)[2], uint32_t saddr, int lane) {
#pragma unroll
    for (int r = 0; r < 2; r++) {
        t[r] += __shfl_xor_sync(0xffffffffu, t[r], 1);
        t[r] += __shfl_xor_sync(0xffffffffu, t[r], 2);
        ex[r] = min(max(((__float_as_uint(193.3f * t[r]) >> 23) + 127u) >> 1, 72u), 198u);
        asm volatile("st.shared.u32 [%0], %1;\n" ::"r"(saddr + r * 32), "r"(ex[r] << 23) : "memory");
    }
    return pack_f16(__uint_as_float(min(ex[0], 142u) << 23), __uint_as_float(min(ex[1], 142u) << 23));
}
template <int N>
__device__ __forceinline__ void p1_convert(uint32_t (&o)[N][4], uint32_t (&v)[N][4], const uint32_t (&ex)[2]) {
    if (__any_sync(0xffffffffu, max(ex[0], ex[1]) > 141u)) {
#pragma unroll
        for (int k = 0; k < 4 * N; k++) v[k >> 2][k & 3] = bf2_mul(v[k >> 2][k & 3], ex[k & 1] > 141u ? 0x1f801f80u : 0x3f803f80u);
    }
#pragma unroll
    for (int k = 0; k < 4 * N; k++) {
        const uint32_t u = bf2_mul(v[k >> 2][k & 3], ((ex[k & 1] > 141u ? 206u : 142u) - ex[k & 1]) * 0x00800080u);
        asm volatile("mad.lo.u32 %0, %1, 7, %2;\n" : "=r"(o[k >> 2][k & 3]) : "r"(u & 0x7fff7fffu), "r"(u));
    }
}
template <int N>
__device__ __forceinline__ void p1_squares(const uint32_t (&v)[N][4], float (&t)[2]) {
#pragma unroll
    for (int j = 0; j < N / 2; j++) {
        const int r = j & 1, b = (j >> 1) * 4;
        uint32_t c = bf2_mul(v[b][r], v[b][r]);
#pragma unroll
        for (int k = 1; k < 8; k++) c = bf2_fma(v[b + k / 2][r + (k & 1) * 2], v[b + k / 2][r + (k & 1) * 2], c);
        t[r] += bf_lo(c) + bf_hi(c);
    }
}
__device__ __forceinline__ void p1_epilogue(const uint32_t (&acc)[2][32], const uint32_t (&sc2)[2], float (&ssq)[4], uint8_t* hp, int zero) {
    uint32_t sq[2], h[16][4];
#pragma unroll
    for (int i2 = 0; i2 < 9; i2++) {
#pragma unroll
        for (int c = 2 * i2 - 2; c < 2 * i2; c++) {
            if (c >= 0 && (c & 3)) {
                uint32_t o[4];
#pragma unroll
                for (int u = 0; u < 4; u++) {
                    const uint32_t v = h[c & 12][u];
                    o[u] = bitsel(h[c][u], (c & 3) == 2 ? prmt(v, v, 0xa381) : prmt(v >> 3, v, (c & 3) == 1 ? 0x6240 : 0xf3d1), SPARE);
                }
                stg128_cs(hp + (c >> 2) * 0x4000 + ((c & 3) - 1) * 512, o[0], o[1], o[2], o[3]);
            }
        }
        if (i2 < 8) {
#pragma unroll
            for (int u = 0; u < 4; u++) {
                h[2 * i2][u] = gelu2<0>(acc[i2 >> 2][8 * (i2 & 3) + 2 * u], sc2[i2 >> 2]);
                h[2 * i2 + 1][u] = gelu2<1>(acc[i2 >> 2][8 * (i2 & 3) + 2 * u + 1], sc2[i2 >> 2]);
#pragma unroll
                for (int r = 0; r < 2; r++) {
                    const uint32_t v = h[2 * i2 + r][u];
                    sq[r] = ((i2 & 3) | u) ? h2_fma(v, v, sq[r]) : h2_mul(v, v);
                }
            }
            if ((i2 & 3) == 3) {
#pragma unroll
                for (int r = 0; r < 2; r++) ssq[(i2 >> 2) * 2 + r] += h_lo(sq[r]) + h_hi(sq[r]);
            }
            if (i2 & 1) sched_break(zero);
        }
    }
}
template <int WG>
__device__ __forceinline__ void p1_mma(uint32_t (&acc)[2][32], const uint32_t (&a)[24][4], uint32_t sbase, uint32_t empty_remote, int i, int lane, bool pass, int zero) {
    const uint32_t bar_full = sbase + P1_OFF_BAR;
    const uint64_t db = make_desc(sbase, 16, 1024 + zero) | (1ull << 62), da = db + (P1_OFF_W + WG * P1_W) / 16;
    if (WG == 0) mbar_wait(bar_full, i & 1);
    bar_sync(1 + WG, 256);
    TRACE(WG, i, 1);
    wg_fence();
#pragma unroll
    for (int k = 0; k < 24; k++) {
        if (WG == 0 && k && k % 4 == 0) mbar_wait(bar_full + (k >> 2) * 8, i & 1);
        mma_rs_n128(acc[0], a[k], db + (k >> 2) * 1024 + (k & 3) * 2, k != 0);
        mma_ss_n128(acc[1], da + k * 128, db + (k >> 2) * 1024 + (k & 3) * 2, k != 0);
        if (k == 23 && pass) bar_arrive(2 - WG, 256);
        if (k == 23 || (WG == 1 && k % 4 == 3)) wg_commit();
        if (WG == 1 && k % 4 == 3 && k > 3) {
            wg_wait<1>();
            if (lane < 2) mbar_arrive_cluster(empty_remote + ((k >> 2) - 1) * 8);
        }
    }
    TRACE(WG, i, 2);
    wg_wait<0>();
    if (WG == 1 && lane < 2) mbar_arrive_cluster(empty_remote + 5 * 8);
}
__device__ __forceinline__ bool p1_consumer(const uint32_t (&a)[24][4], const uint32_t (&sc2)[2], uint32_t sbase, int WG, int w, int lane, int zero) {
    const uint32_t bar_full = sbase + P1_OFF_BAR, bar_empty = bar_full + P1_NST * 8;
    const uint32_t empty_remote = mapa(bar_empty, lane & 1);
    const uint32_t bar_pace = bar_empty + P1_NST * 8 + 32 + w * 8;
    const int g = lane >> 2, q = lane & 3, half = WG ^ ((blockIdx.x / GRP_CTAS) & 1), cb = (blockIdx.x % GRP_CTAS) * 4 + half * 2;
    uint32_t acc[2][32];
    float ssq[4] = {0.f, 0.f, 0.f, 0.f};
    TSTAMP(0, 1);

    uint8_t* const hp0 = h_base() + (w & 1) * 1536 + g * 64 + (q ^ (g >> 1)) * 16;
    const uint32_t blk = h_block(cb * 2 + (w >> 1), 0);
    int i = 0;
    uint32_t more = 3, both;
#pragma unroll 1
    for (;; i++) {
        TRACE(WG, i, 0);
        both = more & 2;
        if (WG == 0) p1_mma<0>(acc, a, sbase, empty_remote, i, lane, both, zero);
        else p1_mma<1>(acc, a, sbase, empty_remote, i, lane, true, zero);
        TRACE(WG, i, 4);
        uint32_t step;
        asm volatile("ld.shared.v2.u32 {%0, %1}, [%2];\n" : "=r"(step), "=r"(more) : "r"(sbase + P1_OFF_TILE + (i & 3) * 16) : "memory");
        uint8_t* hp = hp0 + (step ^ blk);
        if (i < 2 || more != 3) { LAG_HERE(4); }
        if (!(more >> WG & 1) && lane == 0) asm volatile("red.relaxed.gpu.global.add.u32 [%0], 1;\n" ::"l"(g_prog[CNT_LAST]) : "memory");
        p1_epilogue(acc, sc2, ssq, hp, zero);
        if (lane == 0) mbar_arrive(bar_pace);
        if (more & 4) {
            asm volatile("fence.proxy.async.global;\n" ::: "memory");
            bar_arrive(8, 288);
            bar_arrive(9, 288);
        }
        if (!(more >> WG & 1)) break;
    }
    TSTAMP(0, 21);
    if (WG == 0 && both) bar_sync(1, 256);
#pragma unroll
    for (int r = 0; r < 4; r++) {
        ssq[r] += __shfl_xor_sync(0xffffffffu, ssq[r], 1);
        ssq[r] += __shfl_xor_sync(0xffffffffu, ssq[r], 2);
    }
    const float t = q == 0 ? ssq[0] : q == 1 ? ssq[1] : q == 2 ? ssq[2] : ssq[3];
    atomicAdd(&g_sq[cb * 64 + (q >> 1) * 64 + w * 16 + (q & 1) * 8 + g], (1ull << 56) + __float2ull_rn(fminf(t, 0x1p19f) * 0x1p32f));
    asm volatile("fence.proxy.async.global;\n" ::: "memory");
    bar_arrive(3, 288);
    asm volatile("barrier.cluster.arrive.relaxed.aligned;\n" ::: "memory");
    return WG ? more & 1 : both;
}

__device__ __forceinline__ void p2_init(uint32_t sbase);
template <int ROLE>
__device__ __forceinline__ bool pass1(const CUtensorMap& wmap, const __nv_bfloat16* __restrict__ x, const __nv_bfloat16* __restrict__ dw,
                                      const __nv_bfloat16* __restrict__ w2, const __nv_bfloat16* __restrict__ grn_b, uint32_t sbase,
                                      int warp, int lane, int zero) {
    const uint32_t bar_full = sbase + P1_OFF_BAR, bar_empty = bar_full + P1_NST * 8, bar_w = bar_empty + P1_NST * 8;
    const uint32_t rank = cluster_rank();
    const int cig = blockIdx.x % GRP_CTAS;

    TSTAMP(0, 0);
    TRACEW(110 + warp, 0);
    const uint32_t bar_pace = bar_w + 32, bar_xfull = bar_pace + 32, bar_xempty = bar_xfull + 8, bar_done = bar_xfull + 16;
    const uint32_t s_side = bar_done + 12;
    const uint32_t s_item = sbase + P1_OFF_TILE + 64, s_cl = sbase + OFF_PRE + C_DIM * 4 + 8;
    auto ln_place = [](int q, unsigned tag) { return ln_tile(q >> 2, page_bit(ln_probed(q >> 2), tag)) ^ ln_rows(q & 2) ^ (q & 1) * 0x90; };
    const int first = blockIdx.x / GRP_CTAS;

    if (ROLE == 2) {
        reg_dec<32>();
        asm volatile("barrier.cluster.arrive.relaxed.aligned;\n" ::: "memory");
        asm volatile("barrier.cluster.wait.aligned;\n" ::: "memory");
        LAG_HERE(0);
        if (warp == 12) {
            int t = first, sent = 0;
            const unsigned tag = 2 * __ldcg(&g_epoch) + 2;
            const uint32_t rbase = mapa(sbase, lane & 1);
#pragma unroll 1
            for (int i = 0; t < NT128; i++) {
                const int round = t / LN_RING, slot = t - round * LN_RING;
                constexpr unsigned LIM = (NT128 - P1_SPLIT - NGRP) / 2;
                unsigned* cnt = &g_flag[LN_RING + (cig >> 1)][0][0];
                const int page = lane & 1 ? ln_probed(t) : t >> 2;
                unsigned v, sd, u = 0;
                do {
                    asm volatile("ld.relaxed.gpu.global.u32 %0, [%1];\n" : "=r"(v) : "l"(lane & 2 ? &g_page[page] : cnt + (lane & 1) * 8) : "memory");
                    if ((lane & 2) && page < H_FIXED) v = tag;
                    SAFE_BREAK;
                } while (__any_sync(0xffffffffu, (lane & 2) && (v & ~1u) != tag));
                asm volatile("ld.volatile.shared.u32 %0, [%1];\n" : "=r"(sd) : "r"(s_side) : "memory");
                sd &= 1;
                if (__shfl_sync(0xffffffffu, v, sd) > __shfl_sync(0xffffffffu, v, sd ^ 1) + 4) sd ^= 1;
                unsigned b = __shfl_sync(0xffffffffu, v, sd ^ 1);
                const bool draw = rank == 0 && lane == 0 && t < NT128 - P1_SPLIT;
                if (draw) u = atomicAdd(cnt + sd * 8, 1u);
                flag_wait<true>(&g_flag[slot][0][0], 4 * round + 4);
                TRACEW(i, 2);
                asm volatile("fence.proxy.async.global;\n" ::: "memory");
                int next = NT128, more = 0;
                if (draw) {
                    if (u >= LIM) { sd ^= 1; b = u; u = atomicAdd(cnt + sd * 8, 1u); }
                    next = u < LIM ? NGRP + 2 * u + sd : NT128 - P1_SPLIT + atomicAdd(&g_flag[LN_RING + 3 + (cig >> 1)][first & 1][0], 1u);
                    more = u < LIM ? 3 : next < NT128;
                    if (!sent && min(u, b) >= (NT_EARLY - NGRP) / 2) { sent = 1; more += 4; }
                }
                next = __shfl_sync(0xffffffffu, next, 0);
                more = __shfl_sync(0xffffffffu, more, 0);
                const uint32_t ht = h_tile(t, __shfl_sync(0xffffffffu, v, 2));
                const uint32_t src = ln_tile(t, __shfl_sync(0xffffffffu, v, 3)) ^ ln_rows(2 * rank);
#pragma unroll 1
                for (int h = 0; h < P1_NST; h++) {
                    mbar_wait(bar_empty + h * 8, i & 1);
                    if (h == 0) TRACEW(i, 4);
                    if (h == 5) TRACEW(i, 5);
                    if (elect_one()) {
                        mbar_expect_tx(bar_full + h * 8, h ? P1_SLOT : P1_SLOT + 16);
#pragma unroll
                        for (int e = 0; e < 2; e++)
                            bulk_g2s_mc(sbase + h * P1_SLOT + (2 * rank + e) * 4096, h_base() + ((src ^ ln_rows(e)) + ln_block(h)), 4096, bar_full + h * 8, (uint16_t)3);
                    }
                    __syncwarp();
                    if (h == 0 && rank == 0 && lane < 2)
                        asm volatile("st.async.shared::cluster.mbarrier::complete_tx::bytes.v4.u32 [%0], {%1, %2, %3, %3}, [%4];\n"
                                     ::"r"(rbase + P1_OFF_TILE + (i & 3) * 16), "r"(ht), "r"(more), "r"(next),
                                       "r"(rbase + P1_OFF_BAR) : "memory");
                }
                t = next;
                if (rank != 0) {
                    mbar_wait(bar_full, i & 1);
                    asm volatile("ld.shared.u32 %0, [%1];\n" : "=r"(t) : "r"(sbase + P1_OFF_TILE + (i & 3) * 16 + 8) : "memory");
                }
            }
        } else if (warp == 13) {
            const unsigned tag = 2 * __ldcg(&g_epoch) + 2;
            int u = -1, side = 0;
            auto item = [&](int k) {
                if (k < LN_SW / LN_STEP) return (int)blockIdx.x + k * NUM_CTAS;
                while (u < 0) {
                    asm volatile("ld.volatile.shared.u32 %0, [%1];\n" : "=r"(u) : "r"(s_cl) : "memory");
                    side = u & 1;
                    if (u >= 0) u = (u & ~1) + rank;
                    SAFE_BREAK;
                }
                const int v = u + (k - LN_SW / LN_STEP) * (NUM_CTAS / 2);
                return 4 * LN_SW + (v >> 2) * 8 + side * 4 + (v & 3);
            };
#pragma unroll 1
            for (int k = 1;; k++) {
                const int q = item(k), round = q / (4 * LN_RING), slot = (q >> 2) - round * LN_RING;
                if (k == 1 && lane == 0)
                    asm volatile("cp.async.bulk.prefetch.L2.global [%0], %1;\n" ::"l"(reinterpret_cast<const uint8_t*>(x) + (size_t)q * P1_X), "r"(P1_X) : "memory");
                mbar_wait(bar_xempty, ~k & 1);
                if (k == 1) bar_sync(10, 64);
                if (elect_one()) {
                    mbar_expect_tx(bar_xfull, P1_X);
                    bulk_g2s(sbase + P1_OFF_X, reinterpret_cast<const uint8_t*>(x) + (size_t)q * P1_X, P1_X, bar_xfull);
                }
                __syncwarp();
                const uint32_t place = ln_place(q, tag), more = k < LN_SW / LN_STEP || item(k + 1) < 4 * NT128;
                const uint32_t off = flag_wait<false>(&g_flag[slot][1][0], round * (GRP_CTAS / 2));
                if (elect_one()) {
                    asm volatile("st.shared.v4.u32 [%0], {%1, %2, %3, %4};\n" ::"r"(s_item + (k & 1) * 16), "r"(off), "r"(place), "r"(slot), "r"(more) : "memory");
                    mbar_arrive(bar_xfull);
                }
                __syncwarp();
                if (!more) break;
            }
        } else if (warp == 15) {
            int t = first;
            if (rank == 1 && lane == 0) mbar_arrive(bar_empty);
#pragma unroll 1
            for (int i = 0; rank == 1 && t < NT128; i++) {
#pragma unroll 1
                for (int h = 0; h < P1_NST; h++) mbar_wait(bar_full + h * 8, i & 1);
                if (lane == 0) asm volatile("red.relaxed.gpu.global.add.u32 [%0], 1;\n" ::"l"(&g_flag[t % LN_RING][1][0]) : "memory");
                asm volatile("ld.shared.u32 %0, [%1];\n" : "=r"(t) : "r"(sbase + P1_OFF_TILE + (i & 3) * 16 + 8) : "memory");
                if (lane == 0) mbar_arrive(bar_empty);
                TRACEW(i, 3);
            }
            if (rank == 0) {
                {
                    const int me = blockIdx.x >> 1;
                    const int page = lane < 2 ? 0 : H_FIXED + me + (lane / 2 - 1) * (NUM_CTAS / 2);
                    if (page < H_PAGES) h_cell(page, me)[(lane & 1) * 1024] = 0;
                    __syncwarp();
                    if (lane == 0) {
                        const unsigned tag = 2 * __ldcg(&g_epoch) + 2;
                        const unsigned side = near_half(h_cell(0, me));
                        asm volatile("st.volatile.shared.u32 [%0], %1;\n" ::"r"(s_side), "r"(side) : "memory");
                        const unsigned u = atomicAdd(reinterpret_cast<unsigned*>(g_sums) + C_DIM + 64 + side, 1u);
                        const unsigned cl = u < NUM_CTAS / 4 ? 2 * u + side : NUM_CTAS - 2 - 2 * u + (side ^ 1);
#pragma unroll
                        for (int r = 0; r < 2; r++) asm volatile("st.shared::cluster.u32 [%0], %1;\n" ::"r"(mapa(s_cl, r)), "r"(cl) : "memory");
#pragma unroll 1
                        for (int p = H_FIXED + me; p < H_PAGES; p += NUM_CTAS / 2)
                            asm volatile("st.relaxed.gpu.global.u32 [%0], %1;\n" ::"l"(&g_page[p]), "r"(tag + (near_half(h_cell(p, me)) ^ side)) : "memory");
                    }
                    __syncwarp();
                }
                TRACEW(110 + warp, 3);
                mbar_wait(bar_full, 0);
                mbar_wait(bar_full, 1);
                float* sums = g_sums;
                unsigned* flag = reinterpret_cast<unsigned*>(sums + C_DIM);
                if (blockIdx.x == 0) reinterpret_cast<uint2*>(g_half)[lane] = make_uint2(0, 0);
                if (blockIdx.x == 2 && lane < NUM_CNT) g_prog[lane][0] = 0;
                if (blockIdx.x < 96) g_redo[blockIdx.x * 16 + lane] = 0.f;
                float gs = 0.f;
#pragma unroll 1
                for (int pass = 0; pass < 2; pass++) {
                    float mx = 0.f;
#pragma unroll 1
                    for (int it = (blockIdx.x + zero) / GRP_CTAS; it < 96; it += NGRP) {
                        const int nb = it % 12, k0 = (cig * 4 + it / 12) * 64 + (lane >> 2);
                        const uint32_t sc = mapa(sbase + P1_OFF_EX + (k0 & 255) * 4, it / 48);
                        uint32_t* dst = reinterpret_cast<uint32_t*>(g_w2img[0]) + (k0 >> 4) * 3072 + nb * 256 + lane;
                        float bs[8] = {};
#pragma unroll 1
                        for (int c = 0; c < 8; c++) {
                            const uint4 u = __ldg(reinterpret_cast<const uint4*>(w2 + (size_t)(k0 + c * 8) * C_DIM + nb * 32) + (lane & 3));
                            const float b = __bfloat162float(grn_b[k0 + c * 8]);
                            float t;
                            asm volatile("ld.shared::cluster.f32 %0, [%1];\n" : "=f"(t) : "r"(sc + c * 32) : "memory");
                            if (nb == 0) g_scale[k0 + c * 8] = t;
#pragma unroll
                            for (int j = 0; j < 4; j++) {
                                const uint32_t v = j == 0 ? u.x : j == 1 ? u.y : j == 2 ? u.z : u.w;
                                mx = fmaxf(mx, fmaxf(fabsf(bf_lo(v)), fabsf(bf_hi(v))) * t);
                                if (pass) {
                                    bs[2 * j] = fmaf(b, bf_lo(v), bs[2 * j]);
                                    bs[2 * j + 1] = fmaf(b, bf_hi(v), bs[2 * j + 1]);
                                    uint32_t h = pack_f16(bf_lo(v) * t * gs, bf_hi(v) * t * gs);
                                    asm volatile("movmatrix.sync.aligned.m8n8.trans.b16 %0, %0;\n" : "+r"(h));
                                    dst[(c >> 1) * 3072 + (c & 1) * 32 + j * 64] = h;
                                }
                            }
                        }
                        if (pass) {
#pragma unroll
                            for (int j = 0; j < 8; j++) {
#pragma unroll
                                for (int o = 4; o < 32; o <<= 1) bs[j] += __shfl_xor_sync(0xffffffffu, bs[j], o);
                                if (lane >> 2 == j) atomicAdd(&sums[nb * 32 + (j >> 1) * 8 + (lane & 3) * 2 + (j & 1)], bs[j]);
                            }
                        }
                    }
                    if (!pass) {
                        const uint32_t m = __reduce_max_sync(0xffffffffu, __float_as_uint(mx));
                        __threadfence();
                        __syncwarp();
                        if (lane == 0) {
                            atomicMax(flag, m);
                            asm volatile("red.release.gpu.global.add.u32 [%0], 1;\n" ::"l"(flag + 32) : "memory");
                        }
                        flag_wait<true>(flag + 32, NUM_CTAS / 2);
                        gs = w2_scale(__ldcg(flag));
                    }
                }
                asm volatile("fence.proxy.async.global;\nfence.acq_rel.gpu;\n" ::: "memory");
                __syncwarp();
                if (lane == 0) asm volatile("red.relaxed.gpu.global.add.u32 [%0], 1;\n" ::"l"(g_prog[CNT_IMG0]) : "memory");
            }
        } else if (warp == 14) {
#pragma unroll 1
            for (uint32_t k = 0, more = 1; more; k++) {
                uint32_t slot;
                mbar_wait(bar_done, k & 1);
                asm volatile("ld.shared.v2.u32 {%0, %1}, [%2];\n" : "=r"(slot), "=r"(more) : "r"(s_item + (k & 1) * 16 + 8) : "memory");
                if (lane == 0) mbar_arrive(bar_xfull + (slot & zero));
                TRACEW(k, 0);
                asm volatile("fence.proxy.async.global;\n" ::: "memory");
                if (elect_one()) asm volatile("red.release.gpu.global.add.u32 [%0], 1;\n" ::"l"(&g_flag[slot][0][0]) : "memory");
                if (k == 0) bar_arrive(10, 64);
                __syncwarp();
                TRACEW(k, 1);
            }
            if (lane == 0) p2_init(sbase);
#pragma unroll 1
            for (int i = CNT_EARLY; i >= CNT_H; i--) {
                bar_sync(i == CNT_EARLY ? 8 : 3, 288);
                asm volatile("fence.proxy.async.global;\n" ::: "memory");
                if (lane == 0) asm volatile("red.release.gpu.global.add.u32 [%0], 1;\n" ::"l"(&g_prog[i][0]) : "memory");
                __syncwarp();
            }
        }
        __syncwarp();
        asm volatile("barrier.cluster.arrive.relaxed.aligned;\n" ::: "memory");
        return false;
    } else if (ROLE == 1) {
        reg_dec<96>();
        asm volatile("barrier.cluster.arrive.relaxed.aligned;\n" ::: "memory");
        {
            const int l8 = lane & 7;
            uint32_t d[6][4];
            const int n = perm32(2 * ((warp - 8) * 4 + (lane >> 3)));
            const uint32_t dst0 = n * 128 + ((l8 ^ (n & 7)) << 4);
            const uint32_t src = sbase + P1_OFF_X + ((warp - 8) * 8 + (lane >> 3)) * (C_DIM * 2) + l8 * 16;
            uint32_t off = 1, place = ln_place(blockIdx.x & 255, 0), more = 1;
            LAG_HERE(0);
#pragma unroll 1
            for (int i = 0; more; i++) {
                TRACE(2, i, 0);
#pragma unroll 1
                for (int ps = i == 0 ? -2 : 0; ps < 2; ps += ps < 0 ? 2 : 1) {
                    if (ps == 0) {
                        uint32_t slot;
                        if (i == 0) asm volatile("barrier.cluster.wait.aligned;\n" ::: "memory");
                        mbar_wait(bar_xfull, i & 1);
                        asm volatile("ld.shared.v4.u32 {%0, %1, %2, %3}, [%4];\n" : "=r"(off), "=r"(place), "=r"(slot), "=r"(more) : "r"(s_item + (i & 1) * 16) : "memory");
                    }
                    if (ps == 0) TRACE(2, i, 1);
                    if (i == 0) {
#pragma unroll
                        for (int j = 0; j < 6; j++)
                            asm volatile("ld.shared.v4.u32 {%0,%1,%2,%3}, [%4];\n"
                                         : "=r"(d[j][0]), "=r"(d[j][1]), "=r"(d[j][2]), "=r"(d[j][3]) : "r"(sbase + P1_OFF_DW + j * 128 + l8 * 16) : "memory");
                    }
                    uint32_t v[6][4];
#pragma unroll
                    for (int j = 0; j < 6; j++)
                        asm volatile("ld.shared.v4.u32 {%0,%1,%2,%3}, [%4];\n"
                                     : "=r"(v[j][0]), "=r"(v[j][1]), "=r"(v[j][2]), "=r"(v[j][3]) : "r"(src + (ps & 1) * (4 * C_DIM * 2) + j * 128) : "memory");
                    ln_row(v, d, bar_pace + (warp - 8) * 8, off, zero, ps == 1 && lane == 0 ? bar_xempty : 0);
                    uint8_t* dst = h_base() + (place ^ dst0 ^ ln_rows(ps & 1));
#pragma unroll
                    for (int j = 0; j < 6; j++)
                        asm volatile("st.global.v4.u32 [%0], {%1,%2,%3,%4};\n" ::"l"(dst + ln_block(j)), "r"(v[j][0]), "r"(v[j][1]), "r"(v[j][2]), "r"(v[j][3]) : "memory");
                    TRACE(2, i, 3 + (ps & 1));
                }
                asm volatile("fence.proxy.async.global;\nfence.acq_rel.cta;\n" ::: "memory");
                __syncwarp();
                if (lane == 0) mbar_arrive(bar_done);
                TRACE(2, i, 5);
                TRACE(2, i, 2);
            }
        }
        __syncwarp();
        asm volatile("barrier.cluster.arrive.relaxed.aligned;\n" ::: "memory");
        return false;
    } else {
        const int wg = warp >> 2, w = warp & 3;
        auto load_w = [&](int i0, int i1) {
#pragma unroll 1
            for (int i = i0; i < i1; i++) {
                if (!(i & 1)) mbar_expect_tx(bar_w + (i >> 1) * 8, P1_W);
                tma2(sbase + (i & 2) * P1_W + (i >> 2) * P1_W + (i & 1) * (P1_W / 2), &wmap, cig * 256 + ((i >> 1) ^ (first & 1) * 2) * 64, (i & 1) * 192, bar_w + (i >> 1) * 8);
            }
        };
        if (warp == 4 && elect_one()) {
            mbar_init(bar_xfull, 3);
#pragma unroll
            for (int i = 0; i < 4; i++) mbar_init(bar_w + i * 8, 1);
            asm volatile("fence.mbarrier_init.release.cluster;\n" ::: "memory");
            mbar_expect_tx(bar_xfull, P1_X + C_DIM * 2);
            bulk_g2s(sbase + P1_OFF_X, reinterpret_cast<const uint8_t*>(x) + (size_t)blockIdx.x * P1_X, P1_X, bar_xfull);
            bulk_g2s(sbase + P1_OFF_DW, dw, C_DIM * 2, bar_xfull);
            load_w(0, 4);
            asm volatile("st.shared.v4.u32 [%0], {1, %1, %2, 1};\n" ::"r"(s_item), "r"(ln_place(blockIdx.x & 255, 0)), "r"(blockIdx.x >> 2) : "memory");
            mbar_arrive(bar_xfull);
            mbar_arrive(bar_xfull);
        }
        if (warp == 5 && elect_one()) {
#pragma unroll
            for (int i = 0; i < P1_NST; i++) {
                mbar_init(bar_full + i * 8, 1);
                mbar_init(bar_empty + i * 8, i ? 8 : 8 + rank);
                if (i < 4) mbar_init(bar_pace + i * 8, 1);
            }
            mbar_init(bar_xempty, 4);
            mbar_init(bar_done, 4);
            asm volatile("st.shared.u32 [%0], %1;\n" ::"r"(s_side), "r"(first & 1) : "memory");
            asm volatile("st.shared.u32 [%0], -1;\nfence.acq_rel.cta;\n" ::"r"(s_cl) : "memory");
            asm volatile("fence.mbarrier_init.release.cluster;\n" ::: "memory");
        }
        __syncwarp();
        asm volatile("barrier.cluster.arrive.relaxed.aligned;\n" ::: "memory");
        reg_inc<192>();
        TRACEW(110 + warp, 1);
        LAG_HERE(0);
        uint32_t a[24][4];
        const uint32_t src = sbase + wg * P1_W + ((lane >> 4) * 8 + (lane & 7)) * 128 + (((2 * w + ((lane >> 3) & 1)) ^ (lane & 7)) << 4);
        const uint32_t s_ex = sbase + P1_OFF_EX + ((wg ^ (first & 1)) * 128 + w * 16 + (lane >> 2)) * 4;
        uint32_t sc2[2], ex[2];
        if (wg == 1) bar_arrive(1, 256);
#pragma unroll 1
        for (int it = 0; it < 2; it++) {
            if (it != wg) asm volatile("barrier.cluster.wait.aligned;\n" ::: "memory");
            if (it < wg) {
#pragma unroll 1
                for (int n = 0; n < 64 && !mbar_test(bar_xfull, 0); n++) __nanosleep(40);
                if (w == 0) {
#pragma unroll 1
                    for (int b = 4; b < 8; b += 2) {
                        if (b == 6) mbar_wait(bar_w + 16, 0);
                        if (elect_one()) load_w(b, b + 2);
                        __syncwarp();
                    }
                }
                __syncwarp();
            }
            if (it || wg == 0) {
                float t[2] = {0.f, 0.f};
                if (it) {
                    TRACEW(110 + warp, 2);
                    mbar_wait(bar_w + wg * 16, 0);
                }
                TRACEW(110 + warp, 5);
#pragma unroll
                for (int k = 0; k < 24; k++) ldsm4t(a[k], src + k * 2048);
                TRACEW(110 + warp, 6);
                p1_squares(a, t);
                sc2[0] = p1_exponents(t, ex, s_ex, lane);
                if (it && lane < 6) mbar_arrive_cluster(mapa(bar_empty, lane & 1) + (wg * 3 + (lane >> 1)) * 8 + (sc2[0] & zero));
                p1_convert<24>(a, a, ex);
            }
            if (it || (wg == 1 && w)) {
                float t[2] = {0.f, 0.f};
                TRACEW(100 + warp, 0);
                if (it) mbar_wait(bar_w + wg * 16 + 8, 0);
                TRACEW(100 + warp, 1);
                uint32_t v[8][4], o[8][4];
#pragma unroll 1
                for (int j = 0; j <= 2 * it; j++) {
#pragma unroll
                    for (int k = 0; k < 8; k++) ldsm4t(v[k], src + P1_OFF_W + (8 * j + k) * 2048);
                    p1_squares(v, t);
                }
                sc2[1] = p1_exponents(t, ex, s_ex + 256, lane);
#pragma unroll 1
                for (int j = 2 * it; j >= 0; j--) {
                    p1_convert<8>(o, v, ex);
#pragma unroll
                    for (int k = 0; k < 8; k++) {
                        if (j) ldsm4t(v[k], src + P1_OFF_W + (8 * j - 8 + k) * 2048);
                        if (it) asm volatile("stmatrix.sync.aligned.m8n8.x4.trans.shared.b16 [%0], {%1,%2,%3,%4};\n"
                                             ::"r"(src + P1_OFF_W + (8 * j + k) * 2048), "r"(o[k][0]), "r"(o[k][1]), "r"(o[k][2]), "r"(o[k][3]) : "memory");
                    }
                }
            }
        }
        asm volatile("fence.proxy.async.shared::cta;\n" ::: "memory");
        TRACEW(110 + warp, 7);
        bar_sync(6 + wg, 128);
        const bool early = p1_consumer(a, sc2, sbase, wg, w, lane, zero);
        TSTAMP(0, 30);
        return early;
    }
}

constexpr int P2_B = 24576, P2_NB = 4;
constexpr int P2_A = 3072, P2_NA = 8;
constexpr int P2_XROW = C_DIM * 2;
constexpr int P2_OFF_A = P2_B * P2_NB;
constexpr int P2_OFF_X = P2_OFF_A + 3 * P2_NA * P2_A + 128;
constexpr int P2_LHALF = 2 * P2_NA * P2_A + 64;
constexpr int P2_XHALF = 32 * P2_XROW + 64;
constexpr int P2_OFF_GRN = P2_OFF_X + 64 * P2_XROW + 128;
constexpr int P2_OFF_BIAS = P2_OFF_GRN + HID * 2;
constexpr int P2_OFF_RED = P2_OFF_BIAS + C_DIM * 4;
constexpr int P2_OFF_BAR = P2_OFF_RED + 192;
constexpr int P2_SMEM = P2_OFF_BAR + (2 * P2_NB + 6 * P2_NA + 7) * 8;
constexpr int P2_S1 = 16, P2_S2 = 32;
constexpr int P2_NCL = NUM_CTAS / 2, P2_ITEMS = NT128 / P2_NCL, P2_SHARED = NT128 - P2_ITEMS * P2_NCL;
constexpr int P2_NPOS = 6 * 48 + P2_S1;
constexpr int P2_RAW = 16;
constexpr int P2_XC = 8 * P2_XROW;
constexpr int P2_T0 = 5;
constexpr int P2_TL = 8;
constexpr int P2_XP0 = 30, P2_XPN = 13, P2_XPD = 3;
constexpr int P2_AH = 2;
__device__ __forceinline__ int p2_start(int n) { return n < 0 ? 0 : P2_S1 * n; }
__device__ __forceinline__ int p2_tile(int cl, int n) {
    return n == 0 ? NT_EARLY - P2_NCL + cl : n < 0 ? NT_EARLY + (cl >> 2) * 2 + (cl & 1) : cl + P2_NCL * (n - 1);
}

__device__ __forceinline__ void p2_epilogue(uint32_t (&acc0)[48], uint32_t (&acc1)[48], uint32_t up, uint32_t sx, uint32_t sb, uint8_t* so, int zero) {
    uint32_t v[12][3][4];
    auto load = [&](int t, int j) {
        if (t >= 12) return;
        uint32_t (&w)[4] = v[t][j];
        asm volatile("ld.shared.v4.u32 {%0,%1,%2,%3}, [%4];\n" : "=r"(w[0]), "=r"(w[1]), "=r"(w[2]), "=r"(w[3])
                     : "r"((j ? sx + (j - 1) * 4 * P2_XROW : sb) + t * 64) : "memory");
    };
    auto store = [&](int t, int r) {
        const uint32_t* w = (t < 6 ? acc0 : acc1) + 8 * (t % 6) + 4 * r;
        asm volatile("st.v4.u32 [%4], {%0,%1,%2,%3};\n" ::"r"(w[0]), "r"(w[1]), "r"(w[2]), "r"(w[3]), "l"(so + t * 64 + r * 4 * P2_XROW) : "memory");
    };
#pragma unroll
    for (int j = 0; j < 3; j++) load(0, j);
#pragma unroll
    for (int t = 0; t < 12; t++) {
        load(t + 1, 1);
        load(t + 1, 2);
        load(t + 1, 0);
        uint32_t* acc = (t < 6 ? acc0 : acc1) + 8 * (t % 6);
        uint32_t y[8];
#pragma unroll
        for (int e = 0; e < 8; e++) {
            y[e] = h2_add(acc[e], v[t][0][e >> 1]);
            y[e] = pack_bf16(h_lo(y[e]), h_hi(y[e]));
        }
#pragma unroll
        for (int e = 0; e < 8; e++) acc[(e & 1) * 4 + (e >> 1)] = bf2_fma(y[e], up, v[t][1 + (e & 1)][e >> 1]);
        store(t, 0);
        store(t, 1);
        if (t & 1) sched_break(zero);
    }
}

__device__ __forceinline__ void p2_unpack(uint32_t (&u)[4], uint32_t o1, uint32_t o2, uint32_t o3) {
    u[2] = o1 & ~SPARE;
    u[1] = o2 & ~SPARE;
    u[3] = o3 & ~SPARE;
    const uint32_t t = bitsel(prmt(o1, o2, 0x6341), prmt(o1, o3, 0x6240) << 3, 0x38383838u);
    u[0] = bitsel(t, prmt(o2, o3, 0x7351) << 1, 0x80808080u) & ~SPARE;
}

__device__ __forceinline__ void p2_redo_sums(int warp, int lane) {
    flag_wait<true>(g_prog[CNT_H], NUM_CTAS);
#pragma unroll 1
    for (int s = warp; s < 96; s += 12) {
        float t[2] = {0.f, 0.f};
#pragma unroll 1
        for (int tile = blockIdx.x; tile < 2 * NT128; tile += NUM_CTAS) {
            const uint32_t* p = reinterpret_cast<const uint32_t*>(h_base() + (h_tile(tile >> 1) ^ h_block(s >> 1, tile & 1)) + (s & 1) * 1536) + lane * 4;
#pragma unroll
            for (int j = 0; j < 4; j++) {
                uint32_t u[4];
                p2_unpack(u, __ldcg(p + j), __ldcg(p + j + 128), __ldcg(p + j + 256));
#pragma unroll
                for (int c = 0; c < 4; c++) t[c >> 1] += h_lo(u[c]) * h_lo(u[c]) + h_hi(u[c]) * h_hi(u[c]);
            }
        }
#pragma unroll
        for (int r = 0; r < 2; r++) {
            const int ch = s * 16 + r * 8 + (lane >> 2);
            atomicAdd(&g_redo[ch], t[r] * (UNCHOP * UNCHOP));
        }
    }
    __threadfence();
    __syncwarp();
    if (lane == 0) asm volatile("red.release.gpu.global.add.u32 [%0], 1;\n" ::"l"(g_prog[CNT_REDO]) : "memory");
    flag_wait<true>(g_prog[CNT_REDO], 12 * NUM_CTAS);
}

static_assert(P2_OFF_GRN >= P1_OFF_X + P1_X && P1_OFF_BAR >= P2_SMEM, "barriers and tables keep their memory");
__device__ __forceinline__ void p2_init(uint32_t sbase) {
    const uint32_t bar = sbase + P2_OFF_BAR;
#pragma unroll 1
    for (int i = 0; i < 2 * P2_NB + 6 * P2_NA + 6; i++) {
        const int j = i - 2 * P2_NB;
        mbar_init(bar + i * 8, j < -P2_NB ? 1 : j < 0 ? 24 : j < 3 * P2_NA ? 1 : j >= 6 * P2_NA && j < 6 * P2_NA + 3 ? 2 : 4);
    }
    asm volatile("st.shared.v2.u32 [%0], {0, 0};\n" ::"r"(bar + (2 * P2_NB + 6 * P2_NA + 6) * 8) : "memory");
    asm volatile("fence.mbarrier_init.release.cluster;\nfence.acq_rel.cta;\n" ::: "memory");
}
template <int ROLE>
__device__ __forceinline__ void pass2(const __nv_bfloat16* __restrict__ x, const __nv_bfloat16* __restrict__ grn_g, __nv_bfloat16* __restrict__ out,
                                      uint8_t* smem, uint32_t sbase, bool early, int zero) {
    const uint32_t bar_bfull = sbase + P2_OFF_BAR, bar_bempty = bar_bfull + P2_NB * 8;
    const uint32_t bar_afull = bar_bempty + P2_NB * 8, bar_aempty = bar_afull + 3 * P2_NA * 8;
    const uint32_t bar_xfull = bar_aempty + 3 * P2_NA * 8, bar_oready = bar_xfull + 24, s_pos = bar_oready + 24;
    int tid;
    asm volatile("mov.u32 %0, %%tid.x;\n" : "=r"(tid));
    const int warp = __shfl_sync(0xffffffffu, tid >> 5, 0), lane = tid & 31;
    const uint32_t rank = cluster_rank();
    int cl, pair, half, fin, k0;
    auto join = [&]() {
        asm volatile("barrier.cluster.wait.aligned;\nld.shared.u32 %0, [%1];\n" : "=r"(cl) : "r"(sbase + OFF_PRE + C_DIM * 4 + 8) : "memory");
        cl = __shfl_sync(0xffffffffu, cl, 0);
        pair = (cl >> 2) * 2 + (cl & 1);
        half = pair < P2_SHARED;
        fin = half && (cl & 2);
        k0 = (pair + 3 * ((cl >> 1) & 1)) % 6 * 8;
    };
    auto wait_pos = [&](int target) {
        int v;
        while (true) {
            asm volatile("ld.volatile.shared.u32 %0, [%1];\n" : "=r"(v) : "r"(s_pos) : "memory");
            if (v >= target) break;
            SAFE_BREAK;
            __nanosleep(100);
        }
    };

    TSTAMP(1, 0);
    LAG_HERE(1);
    if (ROLE == 2) {
        if (warp != 14) flag_wait<true>(g_prog[CNT_IMG0], P2_NCL);
        if (warp == 15) {
            float* pre = reinterpret_cast<float*>(smem + OFF_PRE);
            const float gs = w2_scale(__float_as_uint(__ldcg(&g_sums[C_DIM])));
            float mb = 0.f;
#pragma unroll 1
            for (int i = lane; i < C_DIM; i += 32) {
                pre[i] = __ldcg(&g_sums[i]) * gs;
                mb = fmaxf(mb, fabsf(pre[i]));
            }
            pre[C_DIM] = gs;
            pre[C_DIM + 1] = __uint_as_float(__reduce_max_sync(0xffffffffu, __float_as_uint(mb)));
            bar_sync(9, 288);
            flag_wait<false>(g_prog[CNT_LAST], NUM_CTAS * 8);
            bar_arrive(5, 416);
        }
        join();
        asm volatile("fence.proxy.async;\n" ::: "memory");
        LAG_HERE(2);
        if (warp == 12) {
            const uint8_t* wsrc = reinterpret_cast<const uint8_t*>(g_w2img) + rank * (P2_B / 2);
            int kb = k0;
#pragma unroll 1
            for (int p = 0; p < P2_NPOS; p++) {
                const int st = p & 3;
                if (p == P2_RAW) {
                    flag_wait<true>(g_prog[CNT_IMG1], NUM_CTAS);
                    asm volatile("fence.proxy.async.global;\n" ::: "memory");
                    wsrc += sizeof(g_w2img[0]);
                }
                const int idle = (p < P2_S1 || p >= 6 * 48) + (p < P2_S2 ? !half || p >= 24 : p >= 5 * 48 + P2_S2);
                mbar_wait(bar_bempty + st * 8, (~p >> 2) & 1);
                TR2(3, p, 0);
                if (elect_one()) {
                    mbar_expect_tx(bar_bfull + st * 8, P2_B);
                    bulk_g2s_mc(sbase + st * P2_B + rank * (P2_B / 2), wsrc + kb * P2_B, P2_B / 2, bar_bfull + st * 8, (uint16_t)3);
                    asm volatile("st.volatile.shared.u32 [%0], %1;\n" ::"r"(s_pos), "r"(p) : "memory");
                    if (rank == 0) asm volatile("red.relaxed.gpu.global.add.u32 [%0], 1;\n" ::"l"(g_prog[CNT_POS]) : "memory");
                    if (idle) asm volatile("mbarrier.arrive.shared::cta.b64 _, [%0], %1;\n" ::"r"(bar_bempty + st * 8), "r"(8 * idle) : "memory");
                }
                __syncwarp();
                if (++kb == 48) kb = 0;
            }
            mbar_wait(bar_bempty, 1);
            if (lane == 0) mbar_arrive(bar_bfull);
        } else if (warp == 13) {
            const int w = lane % 3;
            const uint32_t dst0 = sbase + P2_OFF_A + w * P2_NA * P2_A;
            const uint32_t bf = bar_afull + w * P2_NA * 8, be = bar_aempty + w * P2_NA * 8;
            int n = (w == 2 && half ? -1 : w) - 3, left = 0, u = 0, c = 0;
            const uint8_t* const hb = h_base();
            uint32_t ht = 0;
            bool act = lane < 3;
            auto next = [&]() {
                n += 3;
                left = n >= P2_ITEMS ? -1 : n < 0 ? 24 : 48;
                u = (k0 + p2_start(n)) % 48;
                if (left > 0) ht = h_tile(p2_tile(cl, n));
            };
            next();
            flag_wait<true>(g_prog[CNT_EARLY], NUM_CTAS);
#pragma unroll 1
            for (int i = 3; i > 0; i--) {
                const int wi = i % 3;
                if (wi == 2) flag_wait<true>(g_prog[CNT_H], NUM_CTAS);
                asm volatile("fence.proxy.async.global;\n" ::: "memory");
                if (w == wi && lane < 24) {
                    mbar_expect_tx(bf + lane / 3 * 8, P2_A);
                    bulk_g2s(dst0 + lane / 3 * P2_A, hb + (ht ^ h_block(u + lane / 3, rank)), P2_A, bf + lane / 3 * 8);
                }
                __syncwarp();
            }
            c = 8;
            left -= 8;
            u += 8;
            if (u == 48) u = 0;
            while (__any_sync(0xffffffffu, act)) {
                if (left == 0) next();
                const bool ok = act && mbar_test(be + ((c - 1) & 7) * 8, (~c >> 3) & 1);
                if (ok) {
                    const int st = c & 7;
                    if (left > 0) {
                        mbar_expect_tx(bf + st * 8, P2_A);
                        bulk_g2s(dst0 + st * P2_A, hb + (ht ^ h_block(u, rank)), P2_A, bf + st * 8);
                    } else {
                        mbar_arrive(bf + st * 8);
                        act = false;
                    }
                    if (++u == 48) u = 0;
                    c++;
                    left--;
                }
                SAFE_BREAK;
                if (!__any_sync(0xffffffffu, ok)) __nanosleep(100);
            }
        } else if (warp == 14) {
            const uint32_t sx = sbase + P2_OFF_X;
            size_t o = 0;
            int wp = 0;
            uint32_t par = 0;
            if (fin) {
#pragma unroll 1
                for (int c = lane * 16; c < 64 * P2_XROW + 128; c += 512) asm volatile("st.shared.v4.u32 [%0], {0, 0, 0, 0};\n" ::"r"(sx + c) : "memory");
                __syncwarp();
            }
            wait_pos(6);
#pragma unroll 1
            for (int n = -half; n < P2_ITEMS; n++) {
                const int w = (n + 3) % 3, end = p2_start(n) + 48;
                const size_t on = (size_t)(2 * p2_tile(cl, n) + rank) * (64 * C_DIM * 2);
                const uint32_t xf = bar_xfull + w * 8;
                if (n < 2 || n > 12) { LAG_HERE(3); }
                bool st = n + half > 0;
                const bool ld = n < P2_ITEMS - 1 && !(n < 0 && fin);
                if (n == P2_ITEMS - 1 && lane == 0) {
                    mbar_expect_tx(xf, 64 * C_DIM * 2);
#pragma unroll 1
                    for (int c = 4; c < 12; c++) {
                        if (c >= 8) {
                            mbar_wait(bar_aempty + ((2 * c - 1) & 7) * 8, 1);
                            mbar_wait(bar_aempty + ((2 * c) & 7) * 8, 1);
                        }
                        bulk_g2s(sbase + P2_OFF_A + (c & 3) * P2_XC + (c < 8 ? P2_LHALF : 0), reinterpret_cast<const uint8_t*>(x) + on + (c & 7) * P2_XC, P2_XC, xf);
                    }
                    mbar_arrive(xf);
                }
                if (st) {
                    mbar_wait(bar_oready + wp * 8, (par >> wp) & 1);
                    par ^= 1u << wp;
                }
                if (lane == 0) {
                    if (n < P2_ITEMS - 1) mbar_expect_tx(xf, ld ? 64 * C_DIM * 2 : 0);
                    const int t0 = (n ? p2_start(n - 1) + 48 : P2_S2) + (n == P2_ITEMS - 1 ? P2_TL : P2_T0), dt = end - t0;
                    int t = st ? 16 * t0 : -4096;
                    if (n == 0 && half) {
                        if (fin) {
                            flag_wait<true>(&g_half[pair][rank], 1);
                            asm volatile("fence.proxy.async.global;\n" ::: "memory");
                        }
#pragma unroll 1
                        for (int c = 0; c < 2; c++) {
                            uint8_t* dst = reinterpret_cast<uint8_t*>(out) + o + c * 32 * P2_XROW;
                            if (!fin) bulk_s2g(dst, sx + c * P2_XHALF, 32 * P2_XROW);
                            else asm volatile("cp.reduce.async.bulk.global.shared::cta.bulk_group.add.noftz.bf16 [%0], [%1], %2;\n"
                                              ::"l"(dst), "r"(sx + c * P2_XHALF), "r"(32 * P2_XROW) : "memory");
                        }
                        asm volatile("cp.async.bulk.commit_group;\n" ::: "memory");
                        if (!fin) {
                            asm volatile("cp.async.bulk.wait_group 0;\nfence.proxy.async.global;\n" ::: "memory");
                            asm volatile("st.release.gpu.global.u32 [%0], 1;\n" ::"l"(&g_half[pair][rank]) : "memory");
                        }
                        st = false;
                    }
#pragma unroll 1
                    for (int c = 0; c < 64 * P2_XROW; c += P2_XC, t += 2 * dt) {
                        const uint32_t sp = sx + c + (c >= 32 * P2_XROW ? 64 : 0);
                        wait_pos(t >> 4);
                        if (st) bulk_s2g(reinterpret_cast<uint8_t*>(out) + o + c, sp, P2_XC);
                        asm volatile("cp.async.bulk.commit_group;\n" ::: "memory");
                        if (ld) {
                            wait_pos((t + dt) >> 4);
                            asm volatile("cp.async.bulk.wait_group.read 0;\n" ::: "memory");
                            bulk_g2s(sp, reinterpret_cast<const uint8_t*>(x) + on + c, P2_XC, xf);
                        }
                    }
                    if (rank == 0 && n > 0 && n < P2_ITEMS - 2) flag_wait<false>(g_prog[CNT_POS], P2_NCL * (end - 1));
                    if (n < P2_ITEMS - 1) mbar_arrive(xf);
                }
                __syncwarp();
                o = on;
                wp = w;
            }
            asm volatile("cp.async.bulk.wait_group.read 0;\n" ::: "memory");
        } else {
            if (blockIdx.x == 120) {
                wait_pos(P2_RAW);
                for (int i = lane; i < (LN_RING + 6) * 2; i += 32) (&g_flag[0][0][0])[i * 8] = 0;
                for (int i = lane; i < HID; i += 32) g_sq[i] = 0;
                for (int i = lane; i < 512; i += 32) g_sums[i] = 0.f;
                if (lane == 0) g_epoch++;
            }
            int t = 4 * P2_XP0;
#pragma unroll 1
            for (int n = 0; n < P2_ITEMS && lane == 0; n++) {
                const uint8_t* xn = reinterpret_cast<const uint8_t*>(x) + (size_t)(2 * p2_tile(cl, n) + rank) * (64 * C_DIM * 2);
#pragma unroll 1
                for (int c = 0; c < 16; c++, t += n < P2_XPN ? 4 : P2_XPD) {
                    wait_pos(t >> 2);
                    asm volatile("cp.async.bulk.prefetch.L2.global [%0], %1;\n" ::"l"(xn + c * (P2_XC / 2)), "r"(P2_XC / 2) : "memory");
                }
            }
        }
        __syncwarp();
        cluster_sync_relaxed();
    } else {
        const int wg = warp >> 2, w = warp & 3, q = lane & 3;
        const uint32_t af = bar_afull + wg * P2_NA * 8;
        const uint32_t s_a = sbase + P2_OFF_A + wg * P2_NA * P2_A + (lane >> 3) * 512 + (lane & 7) * 64 + ((w ^ ((lane & 7) >> 1)) << 4);
        uint32_t acc0[48], acc1[48], up;
        uint4 a[2][2];

        __nv_bfloat16 gg[4];
#pragma unroll
        for (int i = 0; i < 4; i++) gg[i] = grn_g[tid + 384 * i];
#pragma unroll 1
        for (int it = !early;; it++) {
            float* s_red = reinterpret_cast<float*>(smem + P2_OFF_RED);
            float gx[4], part = 0.f;
            if (it == 1) {
                TSTAMP(1, 27);
                bar_sync(5, 416);
            }
            unsigned long long v[4];
#pragma unroll
            for (int i = 0; i < 4; i++) gx[i] = __ldcg(&g_scale[tid + 384 * i]);
            while (true) {
#pragma unroll
                for (int i = 0; i < 4; i++) asm volatile("ld.relaxed.gpu.global.u64 %0, [%1];\n" : "=l"(v[i]) : "l"(&g_sq[tid + 384 * i]) : "memory");
                SAFE_BREAK;
                if (!it || !__any_sync(0xffffffffu, min(min(v[0], v[1]), min(v[2], v[3])) < (unsigned long long)NGRP << 56)) break;
            }
            TSTAMP(1, 1);
            const float bias = reinterpret_cast<const float*>(smem + OFF_PRE)[tid];
            const float2 pre = *reinterpret_cast<const float2*>(smem + OFF_PRE + C_DIM * 4);
            bool tiny = false;
#pragma unroll
            for (int i = 0; i < 4; i++) {
                const float t = it == 2 ? __ldcg(&g_redo[tid + 384 * i]) : __ull2float_rn(v[i] << 8) * 0x1p-40f;
                tiny |= t < M_TOTAL * 0x1p-19f;
                gx[i] *= gx[i] * t;
            }
            float mg = 0.f;
#pragma unroll
            for (int i = 0; i < 4; i++) {
                asm("sqrt.approx.f32 %0, %1;\n" : "=f"(gx[i]) : "f"(gx[i] * (HSCALE * HSCALE) + 1e-6f));
                part += gx[i];
                gx[i] *= __bfloat162float(gg[i]);
                mg = fmaxf(mg, fabsf(gx[i]));
            }
#pragma unroll
            for (int o = 16; o > 0; o >>= 1) part += __shfl_xor_sync(0xffffffffu, part, o);
            const uint32_t mgw = __reduce_max_sync(0xffffffffu, __float_as_uint(mg));
            TSTAMP(1, 26);
            if (lane == 0) *reinterpret_cast<float2*>(s_red + warp * 2) = make_float2(part, __uint_as_float(mgw));
            if (it) {
                uint32_t redo;
                asm volatile("{\n.reg .pred p;\nsetp.ne.u32 p, %1, 0;\nbar.red.or.pred p, 4, 384, p;\nselp.u32 %0, 1, 0, p;\n}\n"
                             : "=r"(redo) : "r"((uint32_t)(tiny && it == 1)) : "memory");
                if (__shfl_sync(0xffffffffu, redo, 0)) {
                    p2_redo_sums(warp, lane);
                    continue;
                }
            }
            float tot = 0.f;
#pragma unroll
            for (int i = 0; i < 6; i++) {
                const float4 t = *reinterpret_cast<const float4*>(s_red + i * 4);
                tot += t.x + t.z;
                mg = fmaxf(mg, fmaxf(t.y, t.w));
            }
            const float inv = __fdividef(1.0f, tot * (1.0f / HID) + 1e-6f);
            const uint32_t ej = min((__float_as_uint(fmaxf(fmaf(mg, inv, 1.0f) * (HSCALE * UNCHOP), pre.y * 0x1p-13f)) >> 23) + 1, 250u);
            const float dn = __uint_as_float((254u - ej) << 23);
            up = min(ej + 127u - (__float_as_uint(pre.x) >> 23), 254u) * 0x00800080u;
            reinterpret_cast<uint16_t*>(smem + P2_OFF_BIAS + C_DIM * 2)[tid] = 0;
            *reinterpret_cast<__half*>(smem + P2_OFF_BIAS + (tid >> 5) * 64 + (tid & 6) * 8 + (tid & 24) / 2 + (tid & 1) * 2) = __float2half_rn(bias * dn);
#pragma unroll
            for (int i = 0; i < 4; i++) {
                const int k = tid + 384 * i;
                *reinterpret_cast<__half*>(smem + P2_OFF_GRN + (k >> 4) * 32 + (k & 6) * 4 + (k & 8) / 2 + (k & 1) * 2) =
                    __float2half_rn(fmaf(gx[i], inv, 1.0f) * (HSCALE * UNCHOP * dn));
            }
            TSTAMP(1, 25);
            if (it) break;
        }
        join();
        bar_sync(4, 384);
        TSTAMP(1, 28);
        LAG_HERE(2);
        if (wg == 1) {
            constexpr int N = sizeof(g_w2img[0]) / 16, PER = (N + NUM_CTAS - 1) / NUM_CTAS;
            uint4 v[5];
#pragma unroll
            for (int i = 0; i < 5; i++) v[i] = __ldcg(&g_w2img[0][min(blockIdx.x * PER + (tid & 127) + 128 * i, N - 1)]);
#pragma unroll
            for (int i = 0; i < 5; i++) {
                const int j = min(blockIdx.x * PER + (tid & 127) + 128 * i, N - 1);
                const uint32_t* t = reinterpret_cast<const uint32_t*>(smem + P2_OFF_GRN + (j / 768) * 32 + (j & 8) / 2);
                auto sc = [&](uint32_t u, int e) { return (h2_mul(u, t[2 * e]) + 0x00040004u) & 0xfff8fff8u; };
                g_w2img[1][j] = make_uint4(sc(v[i].x, 0), sc(v[i].y, 1), sc(v[i].z, 2), sc(v[i].w, 3));
            }
            asm volatile("fence.proxy.async.global;\n" ::: "memory");
            bar_sync(2, 128);
            if (tid == 128) asm volatile("fence.acq_rel.gpu;\nred.release.gpu.global.add.u32 [%0], 1;\n" ::"l"(g_prog[CNT_IMG1]) : "memory");
        }

        const int who = __shfl_sync(0xffffffffu, lane == 2 ? 0 : lane < 2 ? 1 : 2, lane);
        const uint32_t rel0 = who ? mapa(bar_bempty, lane & 1) : mapa(bar_aempty + wg * P2_NA * 8, rank), rel1 = rel0 + (who ? 0 : 32);
        auto publish = [&]() {
            asm volatile("fence.proxy.async.shared::cta;\n" ::: "memory");
            __syncwarp();
            if (who == 0) mbar_arrive(bar_oready + wg * 8);
        };
        bool ok_a, pend = false;
        uint32_t pa = 0, s_t;
        auto fetch = [&](int j, bool raw) {
            uint32_t o[6], u0[4], u1[4];
            uint2 t0 = make_uint2(0, 0), t1 = t0;
            if (raw) {
                asm volatile("ld.shared.v2.u32 {%0,%1}, [%2];\n" : "=r"(t0.x), "=r"(t0.y) : "r"(s_t + j * 64) : "memory");
                asm volatile("ld.shared.v2.u32 {%0,%1}, [%2];\n" : "=r"(t1.x), "=r"(t1.y) : "r"(s_t + j * 64 + 32) : "memory");
            }
            const bool ok_b = mbar_test(bar_bfull + (j & 3) * 8, j >> 2);
            if (j == 7) pa ^= 1;
            ok_a = mbar_test(af + ((j + 1) & 7) * 8, pa);
            asm volatile("ldmatrix.sync.aligned.m8n8.x4.trans.shared.b16 {%0,%1,%2,%3}, [%4];\n"
                         : "=r"(o[0]), "=r"(o[1]), "=r"(o[2]), "=r"(o[3]) : "r"(s_a + j * P2_A) : "memory");
            asm volatile("ldmatrix.sync.aligned.m8n8.x2.trans.shared.b16 {%0,%1}, [%2];\n"
                         : "=r"(o[4]), "=r"(o[5]) : "r"(s_a + j * P2_A + 2048) : "memory");
            p2_unpack(u0, o[0], o[1], o[2]);
            p2_unpack(u1, o[3], o[4], o[5]);
            if (raw) {
                u0[0] = h2_mul(u0[0], t0.x); u0[1] = h2_mul(u0[1], t0.x); u0[2] = h2_mul(u0[2], t0.y); u0[3] = h2_mul(u0[3], t0.y);
                u1[0] = h2_mul(u1[0], t1.x); u1[1] = h2_mul(u1[1], t1.x); u1[2] = h2_mul(u1[2], t1.y); u1[3] = h2_mul(u1[3], t1.y);
            }
            a[j & 1][0] = make_uint4(u0[0], u0[1], u0[2], u0[3]);
            a[j & 1][1] = make_uint4(u1[0], u1[1], u1[2], u1[3]);
            if (!ok_b) mbar_wait(bar_bfull + (j & 3) * 8, j >> 2);
        };
        auto table = [&](int pos) { s_t = sbase + P2_OFF_GRN + q * 8 + (k0 + pos) % 48 * 64; };
        const uint64_t db0 = make_desc(sbase, 128, 256 + zero);
        auto block8 = [&](bool raw, int pos, int thr0, int mode) {
#pragma unroll
            for (int j = 0; j < 8; j++) {
                const uint64_t db = db0 + (j & 3) * (P2_B / 16);
                if (j == 8 - P2_AH && mode == 1) bar_sync(4, 384);
                TR2(wg, pos + j, 0);
                wg_fence();
                mma_rs_n192(acc0, a[j & 1][0], db);
                mma_rs_n192(acc1, a[j & 1][0], db + 384);
                mma_rs_n192(acc0, a[j & 1][1], db + 768);
                mma_rs_n192(acc1, a[j & 1][1], db + 768 + 384);
                wg_commit();
                if (j == 7 && mode == 2) bar_arrive(4, 384);
                const uint32_t rel = ((j - 1) & 4 ? rel1 : rel0) + ((j - 1) & 3) * 8;
                TR2(wg, pos + j, 1);
                wg_wait<1>();
                TR2(wg, pos + j, 2);
                if (who < (j ? 2 : thr0)) mbar_arrive_cluster(rel);
                if (!ok_a) {
                    if (j == 0 && pend) { publish(); pend = false; }
                    mbar_wait(af + ((j + 1) & 7) * 8, pa);
                }
                TR2(wg, pos + j, 3);
                if (raw && j == 7) table(pos + 8);
                fetch((j + 1) & 7, raw && (j < 7 || pos + 8 < P2_RAW));
            }
        };
        int n = wg == 2 && half ? -1 : wg, pos = p2_start(n);
        uint32_t px = 0;
        wait_pos(pos);
        mbar_wait(af, 0);
        table(pos);
        fetch(0, pos < P2_RAW);
#pragma unroll 1
        for (;; n += 3) {
            TSTAMP(1, 2 + n);
            const int end = pos + (n < 0 ? 24 : 48);
#pragma unroll
            for (int i = 0; i < 48; i += 2) {
                asm volatile("mov.b64 {%0, %1}, 0;\n" : "=r"(acc0[i]), "=r"(acc0[i + 1]));
                asm volatile("mov.b64 {%0, %1}, 0;\n" : "=r"(acc1[i]), "=r"(acc1[i + 1]));
            }
            int thr = 1;
#pragma unroll 1
            for (; pos < P2_RAW; pos += 8, thr = 2) block8(true, pos, thr, 0);
#pragma unroll 1
            for (; pos < end; pos += 8, thr = 2) {
                const int e = pos + 8;
                block8(false, pos, thr, e < 48 || e > 256 || (e & 8) ? 0 : e == end ? 2 : 1);
            }
            TR2(wg, pos - 1, 4);
            if (n < 2 || n > 12) { LAG_HERE(3); }
            wg_wait<0>();
            TR2(wg, pos - 1, 5);
            if (who == 1) mbar_arrive_cluster(rel0 + 24);
            mbar_wait(bar_xfull + wg * 8, px);
            TR2(wg, pos - 1, 6);
            px ^= 1;
            __syncwarp();
            const bool last = n == P2_ITEMS - 1;
            uint32_t l;
            asm volatile("mov.u32 %0, %%laneid;\n" : "=r"(l));
            const uint32_t q16 = (l & 3) * 16, odd = (l >> 2) & 1, row = (w * 8 + (l >> 3)) * P2_XROW + q16;
            uint8_t* so = last ? reinterpret_cast<uint8_t*>(out) + (size_t)(2 * p2_tile(cl, n) + rank) * (64 * P2_XROW) : smem + P2_OFF_X;
            p2_epilogue(acc0, acc1, up, sbase + row + (last ? P2_OFF_A + odd * P2_LHALF : P2_OFF_X + odd * P2_XHALF),
                        sbase + P2_OFF_BIAS + q16 + (n < 0 && fin ? C_DIM * 2 : 0), so + (row + odd * (last ? 32 * P2_XROW : P2_XHALF)), zero);
            if (last) break;
            TR2(wg, pos - 1, 7);
            if (n + 3 >= P2_ITEMS) { publish(); break; }
            if (n < 0) {
                publish();
                pos = P2_S2;
                wait_pos(pos);
                mbar_wait(bar_bfull, 0);
            } else {
                pend = true;
                ok_a = false;
            }
        }
        TSTAMP(1, 29);
        cluster_sync_relaxed();
        TSTAMP(1, 30);
    }
}

__global__ void __cluster_dims__(2, 1, 1) __launch_bounds__(512, 1)
block_kernel(const __grid_constant__ CUtensorMap wmap, const __nv_bfloat16* __restrict__ x, const __nv_bfloat16* __restrict__ dw,
             const __nv_bfloat16* __restrict__ w2, const __nv_bfloat16* __restrict__ grn_g, const __nv_bfloat16* __restrict__ grn_b,
             __nv_bfloat16* __restrict__ out, int zero) {
    extern __shared__ __align__(1024) uint8_t smem[];
    const uint32_t sbase = smem_u32(smem);
    const int warp = __shfl_sync(0xffffffffu, threadIdx.x >> 5, 0), lane = threadIdx.x & 31;
    if (warp >= 12) {
        pass1<2>(wmap, x, dw, w2, grn_b, sbase, warp, lane, zero);
        pass2<2>(x, grn_g, out, smem, sbase, false, zero);
    } else {
        bool early = false;
        if (warp >= 8) {
            pass1<1>(wmap, x, dw, w2, grn_b, sbase, warp, lane, zero);
            reg_inc<160>();
        } else {
            early = pass1<0>(wmap, x, dw, w2, grn_b, sbase, warp, lane, zero);
            reg_dec<160>();
        }
        pass2<0>(x, grn_g, out, smem, sbase, early, zero);
    }
}

}

extern "C" void kernel_launch(void* const* d_in, const int* in_sizes, int n_in, void* d_out, int out_size) {
    const __nv_bfloat16* x = (const __nv_bfloat16*)d_in[0];
    const __nv_bfloat16* dw = (const __nv_bfloat16*)d_in[1];
    const __nv_bfloat16* w1 = (const __nv_bfloat16*)d_in[2];
    const __nv_bfloat16* w2 = (const __nv_bfloat16*)d_in[3];
    const __nv_bfloat16* grn_g = (const __nv_bfloat16*)d_in[4];
    const __nv_bfloat16* grn_b = (const __nv_bfloat16*)d_in[5];
    __nv_bfloat16* out = (__nv_bfloat16*)d_out;

    cudaFuncSetAttribute(block_kernel, cudaFuncAttributeMaxDynamicSharedMemorySize, SMEM_BYTES);

    typedef CUresult (*EncodeFn)(CUtensorMap*, CUtensorMapDataType, cuuint32_t, void*, const cuuint64_t*, const cuuint64_t*,
                                 const cuuint32_t*, const cuuint32_t*, CUtensorMapInterleave, CUtensorMapSwizzle,
                                 CUtensorMapL2promotion, CUtensorMapFloatOOBfill);
    static EncodeFn encode = nullptr;
    if (!encode) {
        cudaDriverEntryPointQueryResult qres;
        cudaGetDriverEntryPoint("cuTensorMapEncodeTiled", (void**)&encode, cudaEnableDefault, &qres);
    }
    CUtensorMap wmap;
    const cuuint64_t gdim[2] = {HID, C_DIM};
    const cuuint64_t gstr[1] = {HID * 2};
    const cuuint32_t box[2] = {64, 192}, estr[2] = {1, 1};
    CUresult er = encode(&wmap, CU_TENSOR_MAP_DATA_TYPE_BFLOAT16, 2, (void*)w1, gdim, gstr, box, estr, CU_TENSOR_MAP_INTERLEAVE_NONE,
           CU_TENSOR_MAP_SWIZZLE_128B, CU_TENSOR_MAP_L2_PROMOTION_L2_128B, CU_TENSOR_MAP_FLOAT_OOB_FILL_NONE);
    if (er != CUDA_SUCCESS) printf("tensor map encode failed %d\n", (int)er);

    block_kernel<<<NUM_CTAS, 512, SMEM_BYTES>>>(wmap, x, dw, w2, grn_g, grn_b, out, 0);
}
```

```cpp
#include <cuda.h>
#include <cuda_runtime.h>
#include <cuda_bf16.h>
#include <cuda_fp16.h>
#include <stdint.h>
#include <stdio.h>

namespace {

constexpr int M_TOTAL = 384 * 384;
constexpr int C_DIM   = 384;
constexpr int HID     = 1536;
constexpr int NT128   = M_TOTAL / 128;
constexpr int NUM_CTAS = 132;

constexpr int NGRP = 22, GRP_CTAS = 6;
constexpr int NT_EARLY = NT128 - 30;
constexpr int LN_STEP = NUM_CTAS / 4, LN_RING = 2 * LN_STEP;
constexpr int LN_TILE = 128 * C_DIM * 2;
constexpr int H_PAGES = NT128 / 4;

__device__ __align__(1024) uint4 g_h[(size_t)(H_PAGES + 1) << 17];
__device__ unsigned g_page[H_PAGES];
__device__ unsigned g_epoch;
__device__ __align__(1024) uint4 g_w2img[2][HID * C_DIM * 2 / 16];
__device__ __align__(16) unsigned long long g_sq[HID];
__device__ __align__(16) float g_sums[512];
__device__ float g_scale[HID];
__device__ float g_redo[HID];
enum { CNT_POS, CNT_IMG1, CNT_REDO, CNT_IMG0, CNT_LAST, CNT_H, CNT_EARLY, NUM_CNT };
__device__ __align__(128) unsigned g_prog[NUM_CNT][32];
__device__ __align__(128) unsigned g_half[32][2];
__device__ unsigned g_flag[LN_RING + 6][2][8];
#define TSTAMP(k, i)
#define TRACE(wg, pos, i)
#define TRACEW(pos, i)

#define TR2(wg, pos, i)
__host__ __device__ __forceinline__ int perm32(int n) {
    return (n & ~31) | (((n >> 1) & 3) << 3) | (((n >> 3) & 3) << 1) | (n & 1);
}

constexpr int H_FIXED = 12;
constexpr int LN_SW = LN_RING;
__device__ __forceinline__ uint8_t* h_base() { return reinterpret_cast<uint8_t*>((reinterpret_cast<size_t>(g_h) + 0x1fffff) & ~(size_t)0x1fffff); }
__device__ __forceinline__ unsigned page_bit(int page, unsigned tag) {
    unsigned v = 0;
    if (page >= H_FIXED) {
        do {
            asm volatile("ld.relaxed.gpu.global.u32 %0, [%1];\n" : "=r"(v) : "l"(&g_page[page]) : "memory");
        } while (tag && (v & ~1u) != tag);
    }
    return v;
}
__device__ __forceinline__ uint32_t h_tile(int t, unsigned bit) { return (t >> 1) << 20 | ((t ^ bit) & 1) << 12 | (t & 2) << 9; }
__device__ __forceinline__ uint32_t h_tile(int t) { return h_tile(t, page_bit(t >> 2, 0)); }
__device__ __forceinline__ int ln_page(int t) { return (t < LN_SW ? 0 : 17) + (t % LN_RING >> 2); }
__device__ __forceinline__ int ln_probed(int t) { return t < LN_SW ? 0 : ln_page(t); }
__device__ __forceinline__ uint32_t ln_tile(int t, unsigned bit) {
    const int slot = t % LN_RING;
    return ln_page(t) << 21 | 0xc0000 | (slot & 2) << 16 | ((~t ^ bit ^ (slot >> 1)) & 1) << 12;
}
__device__ __forceinline__ constexpr uint32_t ln_rows(int group) { return (group & 1) * 0x3000 ^ (group >> 1) * 0x11000; }
__device__ __forceinline__ constexpr uint32_t ln_block(int j) { return (j & 3) << 14 | (j >> 2) << 20; }
__device__ __forceinline__ uint32_t h_block(int kb, int half) {
    return (kb >> 2) << 16 | (kb & 2) << 14 | half << 14 | (kb & 1) << 13 | (__popc(kb & 0x2d) & 1) << 12 | (kb & 1) << 10;
}
__device__ __forceinline__ unsigned* h_cell(int page, int c) {
    return reinterpret_cast<unsigned*>(h_base() + ((size_t)page << 21) + 0x1d8000 + ((c >> 6) << 14) + (c & 63) * 64);
}
__device__ __forceinline__ unsigned near_half(unsigned* cell) {
    int votes = 0;
#pragma unroll 1
    for (int i = 0; i < 6; i++) {
        const unsigned a = atomicAdd(cell + (i & 1) * 1024, 1u), b = atomicAdd(cell + (~i & 1) * 1024, 1u);
        if (a == ~0u) break;
        const unsigned t0 = clock();
        if (b == ~0u) break;
        const int d = min((unsigned)clock() - t0, 250u);
        votes += i & 1 ? d : -d;
    }
    return votes > 0;
}

__device__ __forceinline__ uint32_t smem_u32(const void* p) { return (uint32_t)__cvta_generic_to_shared(p); }

__device__ __forceinline__ void mbar_init(uint32_t bar, uint32_t count) {
    asm volatile("mbarrier.init.shared::cta.b64 [%0], %1;\n" ::"r"(bar), "r"(count) : "memory");
}
__device__ __forceinline__ void mbar_expect_tx(uint32_t bar, uint32_t bytes) {
    asm volatile("mbarrier.arrive.expect_tx.shared::cta.b64 _, [%0], %1;\n" ::"r"(bar), "r"(bytes) : "memory");
}
__device__ __forceinline__ void mbar_arrive(uint32_t bar) {
    asm volatile("mbarrier.arrive.shared::cta.b64 _, [%0];\n" ::"r"(bar) : "memory");
}
__device__ __forceinline__ void mbar_arrive_cluster(uint32_t bar_cluster_addr) {
    asm volatile("mbarrier.arrive.shared::cluster.b64 _, [%0];\n" ::"r"(bar_cluster_addr) : "memory");
}
#define LAG_HERE(k)
#define SAFE_BREAK
__device__ __forceinline__ void mbar_wait(uint32_t bar, uint32_t parity) {
    asm volatile(
        "{\n"
        ".reg .pred p;\n"
        "LAB_WAIT:\n"
        "mbarrier.try_wait.parity.shared::cta.b64 p, [%0], %1;\n"
        "@!p bra LAB_WAIT;\n"
        "}\n" ::"r"(bar), "r"(parity) : "memory");
}
__device__ __forceinline__ bool mbar_test(uint32_t bar, uint32_t parity) {
    uint32_t ok;
    asm volatile("{\n.reg .pred p;\n"
                 "mbarrier.test_wait.parity.shared::cta.b64 p, [%1], %2;\n"
                 "selp.u32 %0, 1, 0, p;\n}\n" : "=r"(ok) : "r"(bar), "r"(parity) : "memory");
    return ok != 0;
}
__device__ __forceinline__ uint32_t mapa(uint32_t addr, uint32_t rank) {
    uint32_t r;
    asm volatile("mapa.shared::cluster.u32 %0, %1, %2;\n" : "=r"(r) : "r"(addr), "r"(rank));
    return r;
}
__device__ __forceinline__ void bulk_g2s(uint32_t dst, const void* src, uint32_t bytes, uint32_t bar) {
    asm volatile("cp.async.bulk.shared::cluster.global.mbarrier::complete_tx::bytes [%0], [%1], %2, [%3];\n"
                 ::"r"(dst), "l"(src), "r"(bytes), "r"(bar) : "memory");
}
__device__ __forceinline__ void bulk_g2s_mc(uint32_t dst, const void* src, uint32_t bytes, uint32_t bar, uint16_t mask) {
    asm volatile("cp.async.bulk.shared::cluster.global.mbarrier::complete_tx::bytes.multicast::cluster [%0], [%1], %2, [%3], %4;\n"
                 ::"r"(dst), "l"(src), "r"(bytes), "r"(bar), "h"(mask) : "memory");
}
__device__ __forceinline__ void tma2(uint32_t dst, const CUtensorMap* map, int c0, int c1, uint32_t bar) {
    asm volatile("cp.async.bulk.tensor.2d.shared::cluster.global.tile.mbarrier::complete_tx::bytes [%0], [%1, {%2, %3}], [%4];\n"
                 ::"r"(dst), "l"(map), "r"(c0), "r"(c1), "r"(bar) : "memory");
}
template <bool ACQ>
__device__ __forceinline__ uint32_t flag_wait(const unsigned* p, unsigned target) {
    unsigned v, n = 0;
    do {
        if (ACQ) asm volatile("ld.acquire.gpu.global.u32 %0, [%1];\n" : "=r"(v) : "l"(p) : "memory");
        else asm volatile("ld.relaxed.gpu.global.u32 %0, [%1];\n" : "=r"(v) : "l"(p) : "memory");
        n++;
    } while (v < target);
    return n == 1;
}
__device__ __forceinline__ void ldsm4t(uint32_t (&r)[4], uint32_t addr) {
    asm volatile("ldmatrix.sync.aligned.m8n8.x4.trans.shared.b16 {%0,%1,%2,%3}, [%4];\n"
                 : "=r"(r[0]), "=r"(r[1]), "=r"(r[2]), "=r"(r[3]) : "r"(addr) : "memory");
}
__device__ __forceinline__ void bulk_s2g(void* dst, uint32_t src, uint32_t bytes) {
    asm volatile("cp.async.bulk.global.shared::cta.bulk_group [%0], [%1], %2;\n" ::"l"(dst), "r"(src), "r"(bytes) : "memory");
}
__device__ __forceinline__ void cluster_sync_relaxed() {
    asm volatile("barrier.cluster.arrive.relaxed.aligned;\nbarrier.cluster.wait.aligned;\n" ::: "memory");
}
__device__ __forceinline__ uint32_t cluster_rank() {
    uint32_t r;
    asm volatile("mov.u32 %0, %%cluster_ctarank;\n" : "=r"(r));
    return r;
}
__device__ __forceinline__ bool elect_one() {
    uint32_t pred;
    asm volatile("{\n.reg .pred p;\nelect.sync _|p, 0xffffffff;\nselp.u32 %0, 1, 0, p;\n}\n" : "=r"(pred));
    return pred != 0;
}
__device__ __forceinline__ void wg_fence() { asm volatile("wgmma.fence.sync.aligned;\n" ::: "memory"); }
__device__ __forceinline__ void wg_commit() { asm volatile("wgmma.commit_group.sync.aligned;\n" ::: "memory"); }
template <int N> __device__ __forceinline__ void wg_wait() {
    asm volatile("wgmma.wait_group.sync.aligned %0;\n" ::"n"(N) : "memory");
}
template <int R> __device__ __forceinline__ void reg_inc() { asm volatile("setmaxnreg.inc.sync.aligned.u32 %0;\n" ::"n"(R)); }
template <int R> __device__ __forceinline__ void reg_dec() { asm volatile("setmaxnreg.dec.sync.aligned.u32 %0;\n" ::"n"(R)); }
__device__ __forceinline__ void bar_sync(int id, int n) { asm volatile("bar.sync %0, %1;\n" ::"r"(id), "r"(n) : "memory"); }
__device__ __forceinline__ void bar_arrive(int id, int n) { asm volatile("bar.arrive %0, %1;\n" ::"r"(id), "r"(n) : "memory"); }

__device__ __forceinline__ uint64_t make_desc(uint32_t saddr, uint32_t lbo, uint32_t sbo) {
    return (uint64_t)((saddr & 0x3FFFF) >> 4) | ((uint64_t)(lbo >> 4) << 16) | ((uint64_t)(sbo >> 4) << 32);
}

__device__ __forceinline__ void stg128_cs(void* p, uint32_t a, uint32_t b, uint32_t c, uint32_t d) {
    asm volatile("st.global.cs.v4.u32 [%0], {%1,%2,%3,%4};\n" ::"l"(p), "r"(a), "r"(b), "r"(c), "r"(d) : "memory");
}
__device__ __forceinline__ uint32_t pack_bf16(float lo, float hi) {
    uint32_t r;
    asm("cvt.rn.bf16x2.f32 %0, %1, %2;\n" : "=r"(r) : "f"(hi), "f"(lo));
    return r;
}
__device__ __forceinline__ float bf_lo(uint32_t v) { return __uint_as_float(v << 16); }
__device__ __forceinline__ float bf_hi(uint32_t v) { return __uint_as_float(v & 0xffff0000u); }
__device__ __forceinline__ uint32_t bf2_mul(uint32_t a, uint32_t b) {
    uint32_t r;
    asm("mul.rn.bf16x2 %0, %1, %2;\n" : "=r"(r) : "r"(a), "r"(b));
    return r;
}
__device__ __forceinline__ uint32_t bf2_fma(uint32_t a, uint32_t b, uint32_t c) {
    uint32_t r;
    asm("fma.rn.bf16x2 %0, %1, %2, %3;\n" : "=r"(r) : "r"(a), "r"(b), "r"(c));
    return r;
}
__device__ __forceinline__ uint32_t bf2_add(uint32_t a, uint32_t b) {
    uint32_t r;
    asm("add.rn.bf16x2 %0, %1, %2;\n" : "=r"(r) : "r"(a), "r"(b));
    return r;
}
__device__ __forceinline__ uint32_t h2_mul(uint32_t a, uint32_t b) {
    uint32_t r;
    asm("mul.rn.f16x2 %0, %1, %2;\n" : "=r"(r) : "r"(a), "r"(b));
    return r;
}
__device__ __forceinline__ uint32_t h2_fma(uint32_t a, uint32_t b, uint32_t c) {
    uint32_t r;
    asm("fma.rn.f16x2 %0, %1, %2, %3;\n" : "=r"(r) : "r"(a), "r"(b), "r"(c));
    return r;
}
__device__ __forceinline__ uint32_t h2_add(uint32_t a, uint32_t b) {
    uint32_t r;
    asm("add.rn.f16x2 %0, %1, %2;\n" : "=r"(r) : "r"(a), "r"(b));
    return r;
}
__device__ __forceinline__ uint32_t pack_f16(float lo, float hi) {
    uint32_t r;
    asm("cvt.rn.f16x2.f32 %0, %1, %2;\n" : "=r"(r) : "f"(hi), "f"(lo));
    return r;
}
__device__ __forceinline__ float h_lo(uint32_t v) { return __low2float(*reinterpret_cast<const __half2*>(&v)); }
__device__ __forceinline__ float h_hi(uint32_t v) { return __high2float(*reinterpret_cast<const __half2*>(&v)); }
__device__ __forceinline__ uint32_t bf2_to_h2(uint32_t v) { return (v & 0x7fff7fffu) * 7u + v; }
__device__ __forceinline__ uint32_t prmt(uint32_t a, uint32_t b, uint32_t sel) {
    uint32_t r;
    asm("prmt.b32 %0, %1, %2, %3;\n" : "=r"(r) : "r"(a), "r"(b), "r"(sel));
    return r;
}
__device__ __forceinline__ uint32_t bitsel(uint32_t a, uint32_t b, uint32_t m) {
    uint32_t r;
    asm("lop3.b32 %0, %1, %2, %3, 0xd8;\n" : "=r"(r) : "r"(a), "r"(b), "r"(m));
    return r;
}
constexpr float KAPPA = 0.3292034911525734f;
constexpr uint32_t GELU_C2 = 0x40d940d9u;
constexpr float HSCALE = 1.0f / (2.0f * KAPPA);
__device__ __forceinline__ float w2_scale(uint32_t m) { return __uint_as_float((257u - max(m >> 23, 16u)) << 23); }
__device__ __forceinline__ void sched_break(int zero) {
    asm volatile("{\n.reg .pred p;\nsetp.ne.s32 p, %0, 0;\nSB_LOOP:\n@p nanosleep.u32 1;\n@p bra SB_LOOP;\n}\n" ::"r"(zero));
}

#define ACC8(d, o) "+r"(d[o + 0]), "+r"(d[o + 1]), "+r"(d[o + 2]), "+r"(d[o + 3]), "+r"(d[o + 4]), "+r"(d[o + 5]), "+r"(d[o + 6]), "+r"(d[o + 7])

__device__ __forceinline__ void mma_rs_n128(uint32_t (&d)[32], const uint32_t (&a)[4], uint64_t desc, int scale_d) {
    asm volatile(
        "{\n.reg .pred p;\nsetp.ne.b32 p, %37, 0;\n"
        "wgmma.mma_async.sync.aligned.m64n128k16.f16.f16.f16 "
        "{%0,%1,%2,%3,%4,%5,%6,%7,%8,%9,%10,%11,%12,%13,%14,%15,"
        "%16,%17,%18,%19,%20,%21,%22,%23,%24,%25,%26,%27,%28,%29,%30,%31},"
        "{%32,%33,%34,%35}, %36, p, 1, 1, 0;\n}\n"
        : ACC8(d, 0), ACC8(d, 8), ACC8(d, 16), ACC8(d, 24)
        : "r"(a[0]), "r"(a[1]), "r"(a[2]), "r"(a[3]), "l"(desc), "r"(scale_d));
}

__device__ __forceinline__ void mma_ss_n128(uint32_t (&d)[32], uint64_t da, uint64_t db, int scale_d) {
    asm volatile(
        "{\n.reg .pred p;\nsetp.ne.b32 p, %34, 0;\n"
        "wgmma.mma_async.sync.aligned.m64n128k16.f16.f16.f16 "
        "{%0,%1,%2,%3,%4,%5,%6,%7,%8,%9,%10,%11,%12,%13,%14,%15,"
        "%16,%17,%18,%19,%20,%21,%22,%23,%24,%25,%26,%27,%28,%29,%30,%31},"
        "%32, %33, p, 1, 1, 1, 0;\n}\n"
        : ACC8(d, 0), ACC8(d, 8), ACC8(d, 16), ACC8(d, 24)
        : "l"(da), "l"(db), "r"(scale_d));
}

__device__ __forceinline__ void mma_rs_n192(uint32_t (&d)[48], const uint4& a, uint64_t db) {
    asm volatile(
        "wgmma.mma_async.sync.aligned.m64n192k16.f16.f16.f16 "
        "{%0,%1,%2,%3,%4,%5,%6,%7,%8,%9,%10,%11,%12,%13,%14,%15,"
        "%16,%17,%18,%19,%20,%21,%22,%23,%24,%25,%26,%27,%28,%29,%30,%31,"
        "%32,%33,%34,%35,%36,%37,%38,%39,%40,%41,%42,%43,%44,%45,%46,%47},"
        "{%48,%49,%50,%51}, %52, 1, 1, 1, 0;\n"
        : ACC8(d, 0), ACC8(d, 8), ACC8(d, 16), ACC8(d, 24), ACC8(d, 32), ACC8(d, 40)
        : "r"(a.x), "r"(a.y), "r"(a.z), "r"(a.w), "l"(db));
}

constexpr int P1_SPLIT = 6;
constexpr int P1_SLOT = LN_TILE / 6, P1_NST = 6;
constexpr int P1_W = 64 * C_DIM * 2;
constexpr int P1_X = 32 * C_DIM * 2;
constexpr int P1_OFF_W = LN_TILE;
constexpr int P1_OFF_X = P1_OFF_W + 2 * P1_W;
constexpr int P1_OFF_BAR = 227328;
constexpr int P1_OFF_TILE = P1_OFF_BAR + (2 * P1_NST + 4 + 4 + 4) * 8;
constexpr int P1_OFF_EX = P1_OFF_TILE + 96;
constexpr int P1_OFF_DW = P1_OFF_EX + 256 * 4;
constexpr int OFF_PRE = P1_OFF_DW + C_DIM * 2;
constexpr int SMEM_BYTES = OFF_PRE + C_DIM * 4 + 16;

__device__ __forceinline__ float rsqrt_fast(float x) {
    float r;
    asm("rsqrt.approx.ftz.f32 %0, %1;\n" : "=f"(r) : "f"(x));
    return r;
}
__device__ __forceinline__ float row_sum(const uint32_t (&c)[4]) {
    const uint32_t u = bf2_add(bf2_add(c[0], c[1]), bf2_add(c[2], c[3]));
    float s = bf_lo(u) + bf_hi(u);
#pragma unroll
    for (int o = 1; o < 8; o <<= 1) s += __shfl_xor_sync(0xffffffffu, s, o);
    return s;
}
__device__ __forceinline__ uint32_t pace(uint32_t bar, uint32_t off, uint32_t val, int zero) {
    asm volatile(
        "{\n.reg .pred p, q;\n.reg .b32 par;\n"
        "lop3.b32 par, %0, %2, %3, 0xea;\n"
        "setp.eq.u32 q, par, 0;\n"
        "mov.pred p, 0;\n"
        "@q mbarrier.test_wait.parity.shared::cta.b64 p, [%1], par;\n"
        "selp.u32 par, 1, 0, p;\n"
        "@q mbarrier.try_wait.parity.shared::cta.b64 p, [%1], par, 1000;\n"
        "@p or.b32 %0, %0, %2;\n"
        "}\n" : "+r"(val) : "r"(bar), "r"(zero), "r"(off));
    return val;
}
__device__ __forceinline__ void ln_row(uint32_t (&v)[6][4], const uint32_t (&d)[6][4], uint32_t bar, uint32_t off, int zero, uint32_t bar_read) {
    const float inv = 1.0f / C_DIM;
    uint32_t c[4];
#pragma unroll
    for (int i = 0; i < 6; i++)
#pragma unroll
        for (int k = 0; k < 4; k++) c[k] = bf2_fma(v[i][k], d[i][k], i ? c[k] : 0);
    const float m = row_sum(c) * inv;
    uint32_t nm = pack_bf16(-m, -m);
    const float e = m + bf_lo(nm);
    if (bar_read) mbar_arrive(bar_read + (nm & zero));
    nm = pace(bar, off, nm, zero);
#pragma unroll
    for (int i = 0; i < 6; i++) {
#pragma unroll
        for (int k = 0; k < 4; k++) {
            v[i][k] = bf2_fma(v[i][k], d[i][k], nm);
            c[k] = i ? bf2_fma(v[i][k], v[i][k], c[k]) : bf2_mul(v[i][k], v[i][k]);
        }
    }
    float r = KAPPA * rsqrt_fast(fmaxf(fmaf(-e, e, row_sum(c) * inv), 0.f) + 1e-5f);
    const float er = -e * r * 0x1p-112f;
    if (__any_sync(0xffffffffu, r < 0x1p-8f)) {
        const uint32_t p2 = __float_as_uint(r) & 0x7f800000u;
        r = __uint_as_float((__float_as_uint(r) & 0x007fffffu) | 0x3f800000u);
#pragma unroll
        for (int i = 0; i < 6; i++)
#pragma unroll
            for (int k = 0; k < 4; k++) v[i][k] = bf2_mul(v[i][k], p2 | p2 >> 16);
    }
    const uint32_t rs = pack_bf16(r * 0x1p-112f, r * 0x1p-112f), sh = pack_bf16(er, er);
#pragma unroll
    for (int i = 0; i < 6; i++)
#pragma unroll
        for (int k = 0; k < 4; k++) v[i][k] = bf2_to_h2(bf2_fma(v[i][k], rs, sh));
}

template <int R>
__device__ __forceinline__ uint32_t gelu2(uint32_t a, uint32_t sc2) {
    uint32_t y, t;
    if (R) asm("{\n.reg .b16 l, h;\n.reg .b32 f;\nmov.b32 {l, h}, %2;\nmov.b32 f, {h, h};\nmul.rn.f16x2 %0, %1, f;\n}\n" : "=r"(y) : "r"(a), "r"(sc2));
    else asm("{\n.reg .b16 l, h;\n.reg .b32 f;\nmov.b32 {l, h}, %2;\nmov.b32 f, {l, l};\nmul.rn.f16x2 %0, %1, f;\n}\n" : "=r"(y) : "r"(a), "r"(sc2));
    asm("tanh.approx.f16x2 %0, %1;\n" : "=r"(t) : "r"(h2_mul(y, h2_fma(y, y, GELU_C2))));
    return h2_fma(a, t, a);
}
constexpr uint32_t SPARE = 0x40074007u;
constexpr float UNCHOP = 1.0023f;

__device__ __forceinline__ uint32_t p1_exponents(float (&t)[2], uint32_t (&ex)[2], uint32_t saddr, int lane) {
#pragma unroll
    for (int r = 0; r < 2; r++) {
        t[r] += __shfl_xor_sync(0xffffffffu, t[r], 1);
        t[r] += __shfl_xor_sync(0xffffffffu, t[r], 2);
        ex[r] = min(max(((__float_as_uint(193.3f * t[r]) >> 23) + 127u) >> 1, 72u), 198u);
        asm volatile("st.shared.u32 [%0], %1;\n" ::"r"(saddr + r * 32), "r"(ex[r] << 23) : "memory");
    }
    return pack_f16(__uint_as_float(min(ex[0], 142u) << 23), __uint_as_float(min(ex[1], 142u) << 23));
}
template <int N>
__device__ __forceinline__ void p1_convert(uint32_t (&o)[N][4], uint32_t (&v)[N][4], const uint32_t (&ex)[2]) {
    if (__any_sync(0xffffffffu, max(ex[0], ex[1]) > 141u)) {
#pragma unroll
        for (int k = 0; k < 4 * N; k++) v[k >> 2][k & 3] = bf2_mul(v[k >> 2][k & 3], ex[k & 1] > 141u ? 0x1f801f80u : 0x3f803f80u);
    }
#pragma unroll
    for (int k = 0; k < 4 * N; k++) {
        const uint32_t u = bf2_mul(v[k >> 2][k & 3], ((ex[k & 1] > 141u ? 206u : 142u) - ex[k & 1]) * 0x00800080u);
        asm volatile("mad.lo.u32 %0, %1, 7, %2;\n" : "=r"(o[k >> 2][k & 3]) : "r"(u & 0x7fff7fffu), "r"(u));
    }
}
template <int N>
__device__ __forceinline__ void p1_squares(const uint32_t (&v)[N][4], float (&t)[2]) {
#pragma unroll
    for (int j = 0; j < N / 2; j++) {
        const int r = j & 1, b = (j >> 1) * 4;
        uint32_t c = bf2_mul(v[b][r], v[b][r]);
#pragma unroll
        for (int k = 1; k < 8; k++) c = bf2_fma(v[b + k / 2][r + (k & 1) * 2], v[b + k / 2][r + (k & 1) * 2], c);
        t[r] += bf_lo(c) + bf_hi(c);
    }
}
__device__ __forceinline__ void p1_epilogue(const uint32_t (&acc)[2][32], const uint32_t (&sc2)[2], float (&ssq)[4], uint8_t* hp, int zero) {
    uint32_t sq[2], h[16][4];
#pragma unroll
    for (int i2 = 0; i2 < 9; i2++) {
#pragma unroll
        for (int c = 2 * i2 - 2; c < 2 * i2; c++) {
            if (c >= 0 && (c & 3)) {
                uint32_t o[4];
#pragma unroll
                for (int u = 0; u < 4; u++) {
                    const uint32_t v = h[c & 12][u];
                    o[u] = bitsel(h[c][u], (c & 3) == 2 ? prmt(v, v, 0xa381) : prmt(v >> 3, v, (c & 3) == 1 ? 0x6240 : 0xf3d1), SPARE);
                }
                stg128_cs(hp + (c >> 2) * 0x4000 + ((c & 3) - 1) * 512, o[0], o[1], o[2], o[3]);
            }
        }
        if (i2 < 8) {
#pragma unroll
            for (int u = 0; u < 4; u++) {
                h[2 * i2][u] = gelu2<0>(acc[i2 >> 2][8 * (i2 & 3) + 2 * u], sc2[i2 >> 2]);
                h[2 * i2 + 1][u] = gelu2<1>(acc[i2 >> 2][8 * (i2 & 3) + 2 * u + 1], sc2[i2 >> 2]);
#pragma unroll
                for (int r = 0; r < 2; r++) {
                    const uint32_t v = h[2 * i2 + r][u];
                    sq[r] = ((i2 & 3) | u) ? h2_fma(v, v, sq[r]) : h2_mul(v, v);
                }
            }
            if ((i2 & 3) == 3) {
#pragma unroll
                for (int r = 0; r < 2; r++) ssq[(i2 >> 2) * 2 + r] += h_lo(sq[r]) + h_hi(sq[r]);
            }
            if (i2 & 1) sched_break(zero);
        }
    }
}
template <int WG>
__device__ __forceinline__ void p1_mma(uint32_t (&acc)[2][32], const uint32_t (&a)[24][4], uint32_t sbase, uint32_t empty_remote, int i, int lane, bool pass, int zero) {
    const uint32_t bar_full = sbase + P1_OFF_BAR;
    const uint64_t db = make_desc(sbase, 16, 1024 + zero) | (1ull << 62), da = db + (P1_OFF_W + WG * P1_W) / 16;
    if (WG == 0) mbar_wait(bar_full, i & 1);
    bar_sync(1 + WG, 256);
    TRACE(WG, i, 1);
    wg_fence();
#pragma unroll
    for (int k = 0; k < 24; k++) {
        if (WG == 0 && k && k % 4 == 0) mbar_wait(bar_full + (k >> 2) * 8, i & 1);
        mma_rs_n128(acc[0], a[k], db + (k >> 2) * 1024 + (k & 3) * 2, k != 0);
        mma_ss_n128(acc[1], da + k * 128, db + (k >> 2) * 1024 + (k & 3) * 2, k != 0);
        if (k == 23 && pass) bar_arrive(2 - WG, 256);
        if (k == 23 || (WG == 1 && k % 4 == 3)) wg_commit();
        if (WG == 1 && k % 4 == 3 && k > 3) {
            wg_wait<1>();
            if (lane < 2) mbar_arrive_cluster(empty_remote + ((k >> 2) - 1) * 8);
        }
    }
    TRACE(WG, i, 2);
    wg_wait<0>();
    if (WG == 1 && lane < 2) mbar_arrive_cluster(empty_remote + 5 * 8);
}
__device__ __forceinline__ bool p1_consumer(const uint32_t (&a)[24][4], const uint32_t (&sc2)[2], uint32_t sbase, int WG, int w, int lane, int zero) {
    const uint32_t bar_full = sbase + P1_OFF_BAR, bar_empty = bar_full + P1_NST * 8;
    const uint32_t empty_remote = mapa(bar_empty, lane & 1);
    const uint32_t bar_pace = bar_empty + P1_NST * 8 + 32 + w * 8;
    const int g = lane >> 2, q = lane & 3, half = WG ^ ((blockIdx.x / GRP_CTAS) & 1), cb = (blockIdx.x % GRP_CTAS) * 4 + half * 2;
    uint32_t acc[2][32];
    float ssq[4] = {0.f, 0.f, 0.f, 0.f};
    TSTAMP(0, 1);

    uint8_t* const hp0 = h_base() + (w & 1) * 1536 + g * 64 + (q ^ (g >> 1)) * 16;
    const uint32_t blk = h_block(cb * 2 + (w >> 1), 0);
    int i = 0;
    uint32_t more = 3, both;
#pragma unroll 1
    for (;; i++) {
        TRACE(WG, i, 0);
        both = more & 2;
        if (WG == 0) p1_mma<0>(acc, a, sbase, empty_remote, i, lane, both, zero);
        else p1_mma<1>(acc, a, sbase, empty_remote, i, lane, true, zero);
        TRACE(WG, i, 4);
        uint32_t step;
        asm volatile("ld.shared.v2.u32 {%0, %1}, [%2];\n" : "=r"(step), "=r"(more) : "r"(sbase + P1_OFF_TILE + (i & 3) * 16) : "memory");
        uint8_t* hp = hp0 + (step ^ blk);
        if (i < 2 || more != 3) { LAG_HERE(4); }
        if (!(more >> WG & 1)) {
            if (lane == 0) asm volatile("red.relaxed.gpu.global.add.u32 [%0], 1;\n" ::"l"(g_prog[CNT_LAST]) : "memory");
            __syncwarp();
            asm volatile("barrier.cluster.arrive.relaxed.aligned;\n" ::: "memory");
        }
        p1_epilogue(acc, sc2, ssq, hp, zero);
        if (lane == 0) mbar_arrive(bar_pace);
        if (more & 4) {
            asm volatile("fence.proxy.async.global;\n" ::: "memory");
            bar_arrive(8, 288);
            bar_arrive(9, 288);
        }
        if (!(more >> WG & 1)) break;
    }
    TSTAMP(0, 21);
    if (WG == 0 && both) bar_sync(1, 256);
#pragma unroll
    for (int r = 0; r < 4; r++) {
        ssq[r] += __shfl_xor_sync(0xffffffffu, ssq[r], 1);
        ssq[r] += __shfl_xor_sync(0xffffffffu, ssq[r], 2);
    }
    const float t = q == 0 ? ssq[0] : q == 1 ? ssq[1] : q == 2 ? ssq[2] : ssq[3];
    atomicAdd(&g_sq[cb * 64 + (q >> 1) * 64 + w * 16 + (q & 1) * 8 + g], (1ull << 56) + __float2ull_rn(fminf(t, 0x1p19f) * 0x1p32f));
    asm volatile("fence.proxy.async.global;\n" ::: "memory");
    bar_arrive(3, 288);
    return WG ? more & 1 : both;
}

__device__ __forceinline__ void p2_init(uint32_t sbase);
template <int ROLE>
__device__ __forceinline__ bool pass1(const CUtensorMap& wmap, const __nv_bfloat16* __restrict__ x, const __nv_bfloat16* __restrict__ dw,
                                      const __nv_bfloat16* __restrict__ w2, const __nv_bfloat16* __restrict__ grn_b, uint32_t sbase,
                                      int warp, int lane, int zero) {
    const uint32_t bar_full = sbase + P1_OFF_BAR, bar_empty = bar_full + P1_NST * 8, bar_w = bar_empty + P1_NST * 8;
    const uint32_t rank = cluster_rank();
    const int cig = blockIdx.x % GRP_CTAS;

    TSTAMP(0, 0);
    TRACEW(110 + warp, 0);
    const uint32_t bar_pace = bar_w + 32, bar_xfull = bar_pace + 32, bar_xempty = bar_xfull + 8, bar_done = bar_xfull + 16;
    const uint32_t s_side = bar_done + 12;
    const uint32_t s_item = sbase + P1_OFF_TILE + 64, s_cl = sbase + OFF_PRE + C_DIM * 4 + 8;
    auto ln_place = [](int q, unsigned tag) { return ln_tile(q >> 2, page_bit(ln_probed(q >> 2), tag)) ^ ln_rows(q & 2) ^ (q & 1) * 0x90; };
    const int first = blockIdx.x / GRP_CTAS;

    if (ROLE == 2) {
        reg_dec<32>();
        asm volatile("barrier.cluster.arrive.relaxed.aligned;\n" ::: "memory");
        asm volatile("barrier.cluster.wait.aligned;\n" ::: "memory");
        LAG_HERE(0);
        if (warp == 12) {
            int t = first, sent = 0;
            const unsigned tag = 2 * __ldcg(&g_epoch) + 2;
            const uint32_t rbase = mapa(sbase, lane & 1);
#pragma unroll 1
            for (int i = 0; t < NT128; i++) {
                const int round = t / LN_RING, slot = t - round * LN_RING;
                constexpr unsigned LIM = (NT128 - P1_SPLIT - NGRP) / 2;
                unsigned* cnt = &g_flag[LN_RING + (cig >> 1)][0][0];
                const int page = lane & 1 ? ln_probed(t) : t >> 2;
                unsigned v, sd, u = 0;
                do {
                    asm volatile("ld.relaxed.gpu.global.u32 %0, [%1];\n" : "=r"(v) : "l"(lane & 2 ? &g_page[page] : cnt + (lane & 1) * 8) : "memory");
                    if ((lane & 2) && page < H_FIXED) v = tag;
                    SAFE_BREAK;
                } while (__any_sync(0xffffffffu, (lane & 2) && (v & ~1u) != tag));
                asm volatile("ld.volatile.shared.u32 %0, [%1];\n" : "=r"(sd) : "r"(s_side) : "memory");
                sd &= 1;
                if (__shfl_sync(0xffffffffu, v, sd) > __shfl_sync(0xffffffffu, v, sd ^ 1) + 4) sd ^= 1;
                unsigned b = __shfl_sync(0xffffffffu, v, sd ^ 1);
                const bool draw = rank == 0 && lane == 0 && t < NT128 - P1_SPLIT;
                if (draw) u = atomicAdd(cnt + sd * 8, 1u);
                flag_wait<true>(&g_flag[slot][0][0], 4 * round + 4);
                TRACEW(i, 2);
                asm volatile("fence.proxy.async.global;\n" ::: "memory");
                int next = NT128, more = 0;
                if (draw) {
                    if (u >= LIM) { sd ^= 1; b = u; u = atomicAdd(cnt + sd * 8, 1u); }
                    next = u < LIM ? NGRP + 2 * u + sd : NT128 - P1_SPLIT + atomicAdd(&g_flag[LN_RING + 3 + (cig >> 1)][first & 1][0], 1u);
                    more = u < LIM ? 3 : next < NT128;
                    if (!sent && min(u, b) >= (NT_EARLY - NGRP) / 2) { sent = 1; more += 4; }
                }
                next = __shfl_sync(0xffffffffu, next, 0);
                more = __shfl_sync(0xffffffffu, more, 0);
                const uint32_t ht = h_tile(t, __shfl_sync(0xffffffffu, v, 2));
                const uint32_t src = ln_tile(t, __shfl_sync(0xffffffffu, v, 3)) ^ ln_rows(2 * rank);
#pragma unroll 1
                for (int h = 0; h < P1_NST; h++) {
                    mbar_wait(bar_empty + h * 8, i & 1);
                    if (h == 0) TRACEW(i, 4);
                    if (h == 5) TRACEW(i, 5);
                    if (elect_one()) {
                        mbar_expect_tx(bar_full + h * 8, h ? P1_SLOT : P1_SLOT + 16);
#pragma unroll
                        for (int e = 0; e < 2; e++)
                            bulk_g2s_mc(sbase + h * P1_SLOT + (2 * rank + e) * 4096, h_base() + ((src ^ ln_rows(e)) + ln_block(h)), 4096, bar_full + h * 8, (uint16_t)3);
                    }
                    __syncwarp();
                    if (h == 0 && rank == 0 && lane < 2)
                        asm volatile("st.async.shared::cluster.mbarrier::complete_tx::bytes.v4.u32 [%0], {%1, %2, %3, %3}, [%4];\n"
                                     ::"r"(rbase + P1_OFF_TILE + (i & 3) * 16), "r"(ht), "r"(more), "r"(next),
                                       "r"(rbase + P1_OFF_BAR) : "memory");
                }
                if (rank == 0 && next >= NT128) {
                    if (t < NT128 - P1_SPLIT) mbar_wait(bar_empty, ~i & 1);
                    asm volatile("ld.volatile.shared.u32 %0, [%1];\n" : "=r"(sd) : "r"(s_side) : "memory");
                    if (lane == 0) u = atomicAdd(reinterpret_cast<unsigned*>(g_sums) + C_DIM + 96 + sd, 1u);
                    u = __shfl_sync(0xffffffffu, u, 0);
                    if (lane < 2) asm volatile("st.shared::cluster.u32 [%0], %1;\nfence.acq_rel.cluster;\n" ::"r"(rbase + (s_cl + 4 - sbase)),
                                               "r"(u < NUM_CTAS / 4 ? 2 * u + sd : NUM_CTAS - 2 - 2 * u + (sd ^ 1)) : "memory");
                }
                t = next;
                if (rank != 0) {
                    mbar_wait(bar_full, i & 1);
                    asm volatile("ld.shared.u32 %0, [%1];\n" : "=r"(t) : "r"(sbase + P1_OFF_TILE + (i & 3) * 16 + 8) : "memory");
                }
            }
        } else if (warp == 13) {
            const unsigned tag = 2 * __ldcg(&g_epoch) + 2;
            int u = -1, side = 0;
            auto item = [&](int k) {
                if (k < LN_SW / LN_STEP) return (int)blockIdx.x + k * NUM_CTAS;
                while (u < 0) {
                    asm volatile("ld.volatile.shared.u32 %0, [%1];\n" : "=r"(u) : "r"(s_cl) : "memory");
                    side = u & 1;
                    if (u >= 0) u = (u & ~1) + rank;
                    SAFE_BREAK;
                }
                const int v = u + (k - LN_SW / LN_STEP) * (NUM_CTAS / 2);
                return 4 * LN_SW + (v >> 2) * 8 + side * 4 + (v & 3);
            };
#pragma unroll 1
            for (int k = 1;; k++) {
                const int q = item(k), round = q / (4 * LN_RING), slot = (q >> 2) - round * LN_RING;
                if (k == 1 && lane == 0)
                    asm volatile("cp.async.bulk.prefetch.L2.global [%0], %1;\n" ::"l"(reinterpret_cast<const uint8_t*>(x) + (size_t)q * P1_X), "r"(P1_X) : "memory");
                mbar_wait(bar_xempty, ~k & 1);
                if (k == 1) bar_sync(10, 64);
                if (elect_one()) {
                    mbar_expect_tx(bar_xfull, P1_X);
                    bulk_g2s(sbase + P1_OFF_X, reinterpret_cast<const uint8_t*>(x) + (size_t)q * P1_X, P1_X, bar_xfull);
                }
                __syncwarp();
                const uint32_t place = ln_place(q, tag), more = k < LN_SW / LN_STEP || item(k + 1) < 4 * NT128;
                const uint32_t off = flag_wait<false>(&g_flag[slot][1][0], round * (GRP_CTAS / 2));
                if (elect_one()) {
                    asm volatile("st.shared.v4.u32 [%0], {%1, %2, %3, %4};\n" ::"r"(s_item + (k & 1) * 16), "r"(off), "r"(place), "r"(slot), "r"(more) : "memory");
                    mbar_arrive(bar_xfull);
                }
                __syncwarp();
                if (!more) break;
            }
        } else if (warp == 15) {
            int t = first;
            if (rank == 1 && lane == 0) mbar_arrive(bar_empty);
#pragma unroll 1
            for (int i = 0; rank == 1 && t < NT128; i++) {
#pragma unroll 1
                for (int h = 0; h < P1_NST; h++) mbar_wait(bar_full + h * 8, i & 1);
                if (lane == 0) asm volatile("red.relaxed.gpu.global.add.u32 [%0], 1;\n" ::"l"(&g_flag[t % LN_RING][1][0]) : "memory");
                asm volatile("ld.shared.u32 %0, [%1];\n" : "=r"(t) : "r"(sbase + P1_OFF_TILE + (i & 3) * 16 + 8) : "memory");
                if (lane == 0) mbar_arrive(bar_empty);
                TRACEW(i, 3);
            }
            if (rank == 0) {
                {
                    const int me = blockIdx.x >> 1;
                    const int page = lane < 2 ? 0 : H_FIXED + me + (lane / 2 - 1) * (NUM_CTAS / 2);
                    if (page < H_PAGES) h_cell(page, me)[(lane & 1) * 1024] = 0;
                    __syncwarp();
                    if (lane == 0) {
                        const unsigned tag = 2 * __ldcg(&g_epoch) + 2;
                        const unsigned side = near_half(h_cell(0, me));
                        asm volatile("st.volatile.shared.u32 [%0], %1;\n" ::"r"(s_side), "r"(side) : "memory");
                        const unsigned u = atomicAdd(reinterpret_cast<unsigned*>(g_sums) + C_DIM + 64 + side, 1u);
                        const unsigned cl = u < NUM_CTAS / 4 ? 2 * u + side : NUM_CTAS - 2 - 2 * u + (side ^ 1);
#pragma unroll
                        for (int r = 0; r < 2; r++) asm volatile("st.shared::cluster.u32 [%0], %1;\n" ::"r"(mapa(s_cl, r)), "r"(cl) : "memory");
#pragma unroll 1
                        for (int p = H_FIXED + me; p < H_PAGES; p += NUM_CTAS / 2)
                            asm volatile("st.relaxed.gpu.global.u32 [%0], %1;\n" ::"l"(&g_page[p]), "r"(tag + (near_half(h_cell(p, me)) ^ side)) : "memory");
                    }
                    __syncwarp();
                }
                TRACEW(110 + warp, 3);
                mbar_wait(bar_full, 0);
                mbar_wait(bar_full, 1);
                float* sums = g_sums;
                unsigned* flag = reinterpret_cast<unsigned*>(sums + C_DIM);
                if (blockIdx.x == 0) reinterpret_cast<uint2*>(g_half)[lane] = make_uint2(0, 0);
                if (blockIdx.x == 2 && lane < NUM_CNT) g_prog[lane][0] = 0;
                if (blockIdx.x < 96) g_redo[blockIdx.x * 16 + lane] = 0.f;
                float gs = 0.f;
#pragma unroll 1
                for (int pass = 0; pass < 2; pass++) {
                    float mx = 0.f;
#pragma unroll 1
                    for (int it = (blockIdx.x + zero) / GRP_CTAS; it < 96; it += NGRP) {
                        const int nb = it % 12, k0 = (cig * 4 + it / 12) * 64 + (lane >> 2);
                        const uint32_t sc = mapa(sbase + P1_OFF_EX + (k0 & 255) * 4, it / 48);
                        uint32_t* dst = reinterpret_cast<uint32_t*>(g_w2img[0]) + (k0 >> 4) * 3072 + nb * 256 + lane;
                        float bs[8] = {};
#pragma unroll 1
                        for (int c = 0; c < 8; c++) {
                            const uint4 u = __ldg(reinterpret_cast<const uint4*>(w2 + (size_t)(k0 + c * 8) * C_DIM + nb * 32) + (lane & 3));
                            const float b = __bfloat162float(grn_b[k0 + c * 8]);
                            float t;
                            asm volatile("ld.shared::cluster.f32 %0, [%1];\n" : "=f"(t) : "r"(sc + c * 32) : "memory");
                            if (nb == 0) g_scale[k0 + c * 8] = t;
#pragma unroll
                            for (int j = 0; j < 4; j++) {
                                const uint32_t v = j == 0 ? u.x : j == 1 ? u.y : j == 2 ? u.z : u.w;
                                mx = fmaxf(mx, fmaxf(fabsf(bf_lo(v)), fabsf(bf_hi(v))) * t);
                                if (pass) {
                                    bs[2 * j] = fmaf(b, bf_lo(v), bs[2 * j]);
                                    bs[2 * j + 1] = fmaf(b, bf_hi(v), bs[2 * j + 1]);
                                    uint32_t h = pack_f16(bf_lo(v) * t * gs, bf_hi(v) * t * gs);
                                    asm volatile("movmatrix.sync.aligned.m8n8.trans.b16 %0, %0;\n" : "+r"(h));
                                    dst[(c >> 1) * 3072 + (c & 1) * 32 + j * 64] = h;
                                }
                            }
                        }
                        if (pass) {
#pragma unroll
                            for (int j = 0; j < 8; j++) {
#pragma unroll
                                for (int o = 4; o < 32; o <<= 1) bs[j] += __shfl_xor_sync(0xffffffffu, bs[j], o);
                                if (lane >> 2 == j) atomicAdd(&sums[nb * 32 + (j >> 1) * 8 + (lane & 3) * 2 + (j & 1)], bs[j]);
                            }
                        }
                    }
                    if (!pass) {
                        const uint32_t m = __reduce_max_sync(0xffffffffu, __float_as_uint(mx));
                        __threadfence();
                        __syncwarp();
                        if (lane == 0) {
                            atomicMax(flag, m);
                            asm volatile("red.release.gpu.global.add.u32 [%0], 1;\n" ::"l"(flag + 32) : "memory");
                        }
                        flag_wait<true>(flag + 32, NUM_CTAS / 2);
                        gs = w2_scale(__ldcg(flag));
                    }
                }
                asm volatile("fence.proxy.async.global;\nfence.acq_rel.gpu;\n" ::: "memory");
                __syncwarp();
                if (lane == 0) asm volatile("red.relaxed.gpu.global.add.u32 [%0], 1;\n" ::"l"(g_prog[CNT_IMG0]) : "memory");
            }
        } else if (warp == 14) {
#pragma unroll 1
            for (uint32_t k = 0, more = 1; more; k++) {
                uint32_t slot;
                mbar_wait(bar_done, k & 1);
                asm volatile("ld.shared.v2.u32 {%0, %1}, [%2];\n" : "=r"(slot), "=r"(more) : "r"(s_item + (k & 1) * 16 + 8) : "memory");
                if (lane == 0) mbar_arrive(bar_xfull + (slot & zero));
                TRACEW(k, 0);
                asm volatile("fence.proxy.async.global;\n" ::: "memory");
                if (elect_one()) asm volatile("red.release.gpu.global.add.u32 [%0], 1;\n" ::"l"(&g_flag[slot][0][0]) : "memory");
                if (k == 0) bar_arrive(10, 64);
                __syncwarp();
                TRACEW(k, 1);
            }
            if (lane == 0) p2_init(sbase);
            __syncwarp();
            asm volatile("barrier.cluster.arrive.relaxed.aligned;\n" ::: "memory");
#pragma unroll 1
            for (int i = CNT_EARLY; i >= CNT_H; i--) {
                bar_sync(i == CNT_EARLY ? 8 : 3, 288);
                asm volatile("fence.proxy.async.global;\n" ::: "memory");
                if (lane == 0) asm volatile("red.release.gpu.global.add.u32 [%0], 1;\n" ::"l"(&g_prog[i][0]) : "memory");
                __syncwarp();
            }
        }
        __syncwarp();
        if (warp != 14) asm volatile("barrier.cluster.arrive.relaxed.aligned;\n" ::: "memory");
        return false;
    } else if (ROLE == 1) {
        reg_dec<96>();
        asm volatile("barrier.cluster.arrive.relaxed.aligned;\n" ::: "memory");
        {
            const int l8 = lane & 7;
            uint32_t d[6][4];
            const int n = perm32(2 * ((warp - 8) * 4 + (lane >> 3)));
            const uint32_t dst0 = n * 128 + ((l8 ^ (n & 7)) << 4);
            const uint32_t src = sbase + P1_OFF_X + ((warp - 8) * 8 + (lane >> 3)) * (C_DIM * 2) + l8 * 16;
            uint32_t off = 1, place = ln_place(blockIdx.x & 255, 0), more = 1;
            LAG_HERE(0);
#pragma unroll 1
            for (int i = 0; more; i++) {
                TRACE(2, i, 0);
#pragma unroll 1
                for (int ps = i == 0 ? -2 : 0; ps < 2; ps += ps < 0 ? 2 : 1) {
                    if (ps == 0) {
                        uint32_t slot;
                        if (i == 0) asm volatile("barrier.cluster.wait.aligned;\n" ::: "memory");
                        mbar_wait(bar_xfull, i & 1);
                        asm volatile("ld.shared.v4.u32 {%0, %1, %2, %3}, [%4];\n" : "=r"(off), "=r"(place), "=r"(slot), "=r"(more) : "r"(s_item + (i & 1) * 16) : "memory");
                    }
                    if (ps == 0) TRACE(2, i, 1);
                    if (i == 0) {
#pragma unroll
                        for (int j = 0; j < 6; j++)
                            asm volatile("ld.shared.v4.u32 {%0,%1,%2,%3}, [%4];\n"
                                         : "=r"(d[j][0]), "=r"(d[j][1]), "=r"(d[j][2]), "=r"(d[j][3]) : "r"(sbase + P1_OFF_DW + j * 128 + l8 * 16) : "memory");
                    }
                    uint32_t v[6][4];
#pragma unroll
                    for (int j = 0; j < 6; j++)
                        asm volatile("ld.shared.v4.u32 {%0,%1,%2,%3}, [%4];\n"
                                     : "=r"(v[j][0]), "=r"(v[j][1]), "=r"(v[j][2]), "=r"(v[j][3]) : "r"(src + (ps & 1) * (4 * C_DIM * 2) + j * 128) : "memory");
                    ln_row(v, d, bar_pace + (warp - 8) * 8, off, zero, ps == 1 && lane == 0 ? bar_xempty : 0);
                    uint8_t* dst = h_base() + (place ^ dst0 ^ ln_rows(ps & 1));
#pragma unroll
                    for (int j = 0; j < 6; j++)
                        asm volatile("st.global.v4.u32 [%0], {%1,%2,%3,%4};\n" ::"l"(dst + ln_block(j)), "r"(v[j][0]), "r"(v[j][1]), "r"(v[j][2]), "r"(v[j][3]) : "memory");
                    TRACE(2, i, 3 + (ps & 1));
                }
                asm volatile("fence.proxy.async.global;\nfence.acq_rel.cta;\n" ::: "memory");
                __syncwarp();
                if (lane == 0) mbar_arrive(bar_done);
                TRACE(2, i, 5);
                TRACE(2, i, 2);
            }
        }
        __syncwarp();
        asm volatile("barrier.cluster.arrive.relaxed.aligned;\n" ::: "memory");
        return false;
    } else {
        const int wg = warp >> 2, w = warp & 3;
        auto load_w = [&](int i0, int i1) {
#pragma unroll 1
            for (int i = i0; i < i1; i++) {
                if (!(i & 1)) mbar_expect_tx(bar_w + (i >> 1) * 8, P1_W);
                tma2(sbase + (i & 2) * P1_W + (i >> 2) * P1_W + (i & 1) * (P1_W / 2), &wmap, cig * 256 + ((i >> 1) ^ (first & 1) * 2) * 64, (i & 1) * 192, bar_w + (i >> 1) * 8);
            }
        };
        if (warp == 4 && elect_one()) {
            mbar_init(bar_xfull, 3);
#pragma unroll
            for (int i = 0; i < 4; i++) mbar_init(bar_w + i * 8, 1);
            asm volatile("fence.mbarrier_init.release.cluster;\n" ::: "memory");
            mbar_expect_tx(bar_xfull, P1_X + C_DIM * 2);
            bulk_g2s(sbase + P1_OFF_X, reinterpret_cast<const uint8_t*>(x) + (size_t)blockIdx.x * P1_X, P1_X, bar_xfull);
            bulk_g2s(sbase + P1_OFF_DW, dw, C_DIM * 2, bar_xfull);
            load_w(0, 4);
            asm volatile("st.shared.v4.u32 [%0], {1, %1, %2, 1};\n" ::"r"(s_item), "r"(ln_place(blockIdx.x & 255, 0)), "r"(blockIdx.x >> 2) : "memory");
            mbar_arrive(bar_xfull);
            mbar_arrive(bar_xfull);
        }
        if (warp == 5 && elect_one()) {
#pragma unroll
            for (int i = 0; i < P1_NST; i++) {
                mbar_init(bar_full + i * 8, 1);
                mbar_init(bar_empty + i * 8, i ? 8 : 8 + rank);
                if (i < 4) mbar_init(bar_pace + i * 8, 1);
            }
            mbar_init(bar_xempty, 4);
            mbar_init(bar_done, 4);
            asm volatile("st.shared.u32 [%0], %1;\n" ::"r"(s_side), "r"(first & 1) : "memory");
            asm volatile("st.shared.u32 [%0], -1;\nfence.acq_rel.cta;\n" ::"r"(s_cl) : "memory");
            asm volatile("fence.mbarrier_init.release.cluster;\n" ::: "memory");
        }
        __syncwarp();
        asm volatile("barrier.cluster.arrive.relaxed.aligned;\n" ::: "memory");
        reg_inc<192>();
        TRACEW(110 + warp, 1);
        LAG_HERE(0);
        uint32_t a[24][4];
        const uint32_t src = sbase + wg * P1_W + ((lane >> 4) * 8 + (lane & 7)) * 128 + (((2 * w + ((lane >> 3) & 1)) ^ (lane & 7)) << 4);
        const uint32_t s_ex = sbase + P1_OFF_EX + ((wg ^ (first & 1)) * 128 + w * 16 + (lane >> 2)) * 4;
        uint32_t sc2[2], ex[2];
        if (wg == 1) bar_arrive(1, 256);
#pragma unroll 1
        for (int it = 0; it < 2; it++) {
            if (it != wg) asm volatile("barrier.cluster.wait.aligned;\n" ::: "memory");
            if (it < wg) {
#pragma unroll 1
                for (int n = 0; n < 64 && !mbar_test(bar_xfull, 0); n++) __nanosleep(40);
                if (w == 0) {
#pragma unroll 1
                    for (int b = 4; b < 8; b += 2) {
                        if (b == 6) mbar_wait(bar_w + 16, 0);
                        if (elect_one()) load_w(b, b + 2);
                        __syncwarp();
                    }
                }
                __syncwarp();
            }
            if (it || wg == 0) {
                float t[2] = {0.f, 0.f};
                if (it) {
                    TRACEW(110 + warp, 2);
                    mbar_wait(bar_w + wg * 16, 0);
                }
                TRACEW(110 + warp, 5);
#pragma unroll
                for (int k = 0; k < 24; k++) ldsm4t(a[k], src + k * 2048);
                TRACEW(110 + warp, 6);
                p1_squares(a, t);
                sc2[0] = p1_exponents(t, ex, s_ex, lane);
                if (it && lane < 6) mbar_arrive_cluster(mapa(bar_empty, lane & 1) + (wg * 3 + (lane >> 1)) * 8 + (sc2[0] & zero));
                p1_convert<24>(a, a, ex);
            }
            if (it || (wg == 1 && w)) {
                float t[2] = {0.f, 0.f};
                TRACEW(100 + warp, 0);
                if (it) mbar_wait(bar_w + wg * 16 + 8, 0);
                TRACEW(100 + warp, 1);
                uint32_t v[8][4], o[8][4];
#pragma unroll 1
                for (int j = 0; j <= 2 * it; j++) {
#pragma unroll
                    for (int k = 0; k < 8; k++) ldsm4t(v[k], src + P1_OFF_W + (8 * j + k) * 2048);
                    p1_squares(v, t);
                }
                sc2[1] = p1_exponents(t, ex, s_ex + 256, lane);
#pragma unroll 1
                for (int j = 2 * it; j >= 0; j--) {
                    p1_convert<8>(o, v, ex);
#pragma unroll
                    for (int k = 0; k < 8; k++) {
                        if (j) ldsm4t(v[k], src + P1_OFF_W + (8 * j - 8 + k) * 2048);
                        if (it) asm volatile("stmatrix.sync.aligned.m8n8.x4.trans.shared.b16 [%0], {%1,%2,%3,%4};\n"
                                             ::"r"(src + P1_OFF_W + (8 * j + k) * 2048), "r"(o[k][0]), "r"(o[k][1]), "r"(o[k][2]), "r"(o[k][3]) : "memory");
                    }
                }
            }
        }
        asm volatile("fence.proxy.async.shared::cta;\n" ::: "memory");
        TRACEW(110 + warp, 7);
        bar_sync(6 + wg, 128);
        const bool early = p1_consumer(a, sc2, sbase, wg, w, lane, zero);
        TSTAMP(0, 30);
        return early;
    }
}

constexpr int P2_B = 24576, P2_NB = 4;
constexpr int P2_A = 3072, P2_NA = 8;
constexpr int P2_XROW = C_DIM * 2;
constexpr int P2_OFF_A = P2_B * P2_NB;
constexpr int P2_OFF_X = P2_OFF_A + 3 * P2_NA * P2_A + 128;
constexpr int P2_LHALF = 2 * P2_NA * P2_A + 64;
constexpr int P2_XHALF = 32 * P2_XROW + 64;
constexpr int P2_OFF_GRN = P2_OFF_X + 64 * P2_XROW + 128;
constexpr int P2_OFF_BIAS = P2_OFF_GRN + HID * 2;
constexpr int P2_OFF_RED = P2_OFF_BIAS + C_DIM * 4;
constexpr int P2_OFF_BAR = P2_OFF_RED + 192;
constexpr int P2_SMEM = P2_OFF_BAR + (2 * P2_NB + 6 * P2_NA + 7) * 8;
constexpr int P2_S1 = 16, P2_S2 = 32;
constexpr int P2_NCL = NUM_CTAS / 2, P2_ITEMS = NT128 / P2_NCL, P2_SHARED = NT128 - P2_ITEMS * P2_NCL;
constexpr int P2_NPOS = 6 * 48 + P2_S1;
constexpr int P2_RAW = 16;
constexpr int P2_XC = 8 * P2_XROW;
constexpr int P2_T0 = 5;
constexpr int P2_TL = 8;
constexpr int P2_XP0 = 30, P2_XPN = 13, P2_XPD = 3;
constexpr int P2_AH = 2;
__device__ __forceinline__ int p2_start(int n) { return n < 0 ? 0 : P2_S1 * n; }
__device__ __forceinline__ int p2_tile(int cl, int n) {
    return n == 0 ? NT_EARLY - P2_NCL + cl : n < 0 ? NT_EARLY + (cl >> 2) * 2 + (cl & 1) : cl + P2_NCL * (n - 1);
}

__device__ __forceinline__ void p2_epilogue(uint32_t (&acc0)[48], uint32_t (&acc1)[48], uint32_t up, uint32_t sx, uint32_t sb, uint8_t* so, int zero) {
    uint32_t v[12][3][4];
    auto load = [&](int t, int j) {
        if (t >= 12) return;
        uint32_t (&w)[4] = v[t][j];
        asm volatile("ld.shared.v4.u32 {%0,%1,%2,%3}, [%4];\n" : "=r"(w[0]), "=r"(w[1]), "=r"(w[2]), "=r"(w[3])
                     : "r"((j ? sx + (j - 1) * 4 * P2_XROW : sb) + t * 64) : "memory");
    };
    auto store = [&](int t, int r) {
        const uint32_t* w = (t < 6 ? acc0 : acc1) + 8 * (t % 6) + 4 * r;
        asm volatile("st.v4.u32 [%4], {%0,%1,%2,%3};\n" ::"r"(w[0]), "r"(w[1]), "r"(w[2]), "r"(w[3]), "l"(so + t * 64 + r * 4 * P2_XROW) : "memory");
    };
#pragma unroll
    for (int j = 0; j < 3; j++) load(0, j);
#pragma unroll
    for (int t = 0; t < 12; t++) {
        load(t + 1, 1);
        load(t + 1, 2);
        load(t + 1, 0);
        uint32_t* acc = (t < 6 ? acc0 : acc1) + 8 * (t % 6);
        uint32_t y[8];
#pragma unroll
        for (int e = 0; e < 8; e++) {
            y[e] = h2_add(acc[e], v[t][0][e >> 1]);
            y[e] = pack_bf16(h_lo(y[e]), h_hi(y[e]));
        }
#pragma unroll
        for (int e = 0; e < 8; e++) acc[(e & 1) * 4 + (e >> 1)] = bf2_fma(y[e], up, v[t][1 + (e & 1)][e >> 1]);
        store(t, 0);
        store(t, 1);
        if (t & 1) sched_break(zero);
    }
}

__device__ __forceinline__ void p2_unpack(uint32_t (&u)[4], uint32_t o1, uint32_t o2, uint32_t o3) {
    u[2] = o1 & ~SPARE;
    u[1] = o2 & ~SPARE;
    u[3] = o3 & ~SPARE;
    const uint32_t t = bitsel(prmt(o1, o2, 0x6341), prmt(o1, o3, 0x6240) << 3, 0x38383838u);
    u[0] = bitsel(t, prmt(o2, o3, 0x7351) << 1, 0x80808080u) & ~SPARE;
}

__device__ __forceinline__ void p2_redo_sums(int warp, int lane) {
    flag_wait<true>(g_prog[CNT_H], NUM_CTAS);
#pragma unroll 1
    for (int s = warp; s < 96; s += 12) {
        float t[2] = {0.f, 0.f};
#pragma unroll 1
        for (int tile = blockIdx.x; tile < 2 * NT128; tile += NUM_CTAS) {
            const uint32_t* p = reinterpret_cast<const uint32_t*>(h_base() + (h_tile(tile >> 1) ^ h_block(s >> 1, tile & 1)) + (s & 1) * 1536) + lane * 4;
#pragma unroll
            for (int j = 0; j < 4; j++) {
                uint32_t u[4];
                p2_unpack(u, __ldcg(p + j), __ldcg(p + j + 128), __ldcg(p + j + 256));
#pragma unroll
                for (int c = 0; c < 4; c++) t[c >> 1] += h_lo(u[c]) * h_lo(u[c]) + h_hi(u[c]) * h_hi(u[c]);
            }
        }
#pragma unroll
        for (int r = 0; r < 2; r++) {
            const int ch = s * 16 + r * 8 + (lane >> 2);
            atomicAdd(&g_redo[ch], t[r] * (UNCHOP * UNCHOP));
        }
    }
    __threadfence();
    __syncwarp();
    if (lane == 0) asm volatile("red.release.gpu.global.add.u32 [%0], 1;\n" ::"l"(g_prog[CNT_REDO]) : "memory");
    flag_wait<true>(g_prog[CNT_REDO], 12 * NUM_CTAS);
}

static_assert(P2_OFF_GRN >= P1_OFF_X + P1_X && P1_OFF_BAR >= P2_SMEM, "barriers and tables keep their memory");
__device__ __forceinline__ void p2_init(uint32_t sbase) {
    const uint32_t bar = sbase + P2_OFF_BAR;
#pragma unroll 1
    for (int i = 0; i < 2 * P2_NB + 6 * P2_NA + 6; i++) {
        const int j = i - 2 * P2_NB;
        mbar_init(bar + i * 8, j < -P2_NB ? 1 : j < 0 ? 24 : j < 3 * P2_NA ? 1 : j >= 6 * P2_NA && j < 6 * P2_NA + 3 ? 2 : 4);
    }
    asm volatile("st.shared.v2.u32 [%0], {0, 0};\n" ::"r"(bar + (2 * P2_NB + 6 * P2_NA + 6) * 8) : "memory");
    asm volatile("fence.mbarrier_init.release.cluster;\nfence.acq_rel.cta;\n" ::: "memory");
}
template <int ROLE>
__device__ __forceinline__ void pass2(const __nv_bfloat16* __restrict__ x, const __nv_bfloat16* __restrict__ grn_g, __nv_bfloat16* __restrict__ out,
                                      uint8_t* smem, uint32_t sbase, bool early, int zero) {
    const uint32_t bar_bfull = sbase + P2_OFF_BAR, bar_bempty = bar_bfull + P2_NB * 8;
    const uint32_t bar_afull = bar_bempty + P2_NB * 8, bar_aempty = bar_afull + 3 * P2_NA * 8;
    const uint32_t bar_xfull = bar_aempty + 3 * P2_NA * 8, bar_oready = bar_xfull + 24, s_pos = bar_oready + 24;
    int tid;
    asm volatile("mov.u32 %0, %%tid.x;\n" : "=r"(tid));
    const int warp = __shfl_sync(0xffffffffu, tid >> 5, 0), lane = tid & 31;
    const uint32_t rank = cluster_rank();
    int cl, pair, half, fin, k0;
    auto join = [&]() {
        asm volatile("barrier.cluster.wait.aligned;\nld.shared.u32 %0, [%1];\n" : "=r"(cl) : "r"(sbase + OFF_PRE + C_DIM * 4 + 12) : "memory");
        cl = __shfl_sync(0xffffffffu, cl, 0);
        pair = (cl >> 2) * 2 + (cl & 1);
        half = pair < P2_SHARED;
        fin = half && (cl & 2);
        k0 = (pair + 3 * ((cl >> 1) & 1)) % 6 * 8;
    };
    auto wait_pos = [&](int target) {
        int v;
        while (true) {
            asm volatile("ld.volatile.shared.u32 %0, [%1];\n" : "=r"(v) : "r"(s_pos) : "memory");
            if (v >= target) break;
            SAFE_BREAK;
            __nanosleep(100);
        }
    };

    TSTAMP(1, 0);
    LAG_HERE(1);
    if (ROLE == 2) {
        if (warp != 14) flag_wait<true>(g_prog[CNT_IMG0], P2_NCL);
        if (warp == 15) {
            float* pre = reinterpret_cast<float*>(smem + OFF_PRE);
            const float gs = w2_scale(__float_as_uint(__ldcg(&g_sums[C_DIM])));
            float mb = 0.f;
#pragma unroll 1
            for (int i = lane; i < C_DIM; i += 32) {
                pre[i] = __ldcg(&g_sums[i]) * gs;
                mb = fmaxf(mb, fabsf(pre[i]));
            }
            pre[C_DIM] = gs;
            pre[C_DIM + 1] = __uint_as_float(__reduce_max_sync(0xffffffffu, __float_as_uint(mb)));
            bar_sync(9, 288);
            flag_wait<false>(g_prog[CNT_LAST], NUM_CTAS * 8);
            bar_arrive(5, 416);
        }
        join();
        asm volatile("fence.proxy.async;\n" ::: "memory");
        LAG_HERE(2);
        if (warp == 12) {
            const uint8_t* wsrc = reinterpret_cast<const uint8_t*>(g_w2img) + rank * (P2_B / 2);
            int kb = k0;
#pragma unroll 1
            for (int p = 0; p < P2_NPOS; p++) {
                const int st = p & 3;
                if (p == P2_RAW) {
                    flag_wait<true>(g_prog[CNT_IMG1], NUM_CTAS);
                    asm volatile("fence.proxy.async.global;\n" ::: "memory");
                    wsrc += sizeof(g_w2img[0]);
                }
                const int idle = (p < P2_S1 || p >= 6 * 48) + (p < P2_S2 ? !half || p >= 24 : p >= 5 * 48 + P2_S2);
                mbar_wait(bar_bempty + st * 8, (~p >> 2) & 1);
                TR2(3, p, 0);
                if (elect_one()) {
                    mbar_expect_tx(bar_bfull + st * 8, P2_B);
                    bulk_g2s_mc(sbase + st * P2_B + rank * (P2_B / 2), wsrc + kb * P2_B, P2_B / 2, bar_bfull + st * 8, (uint16_t)3);
                    asm volatile("st.volatile.shared.u32 [%0], %1;\n" ::"r"(s_pos), "r"(p) : "memory");
                    if (rank == 0) asm volatile("red.relaxed.gpu.global.add.u32 [%0], 1;\n" ::"l"(g_prog[CNT_POS]) : "memory");
                    if (idle) asm volatile("mbarrier.arrive.shared::cta.b64 _, [%0], %1;\n" ::"r"(bar_bempty + st * 8), "r"(8 * idle) : "memory");
                }
                __syncwarp();
                if (++kb == 48) kb = 0;
            }
            mbar_wait(bar_bempty, 1);
            if (lane == 0) mbar_arrive(bar_bfull);
        } else if (warp == 13) {
            const int w = lane % 3;
            const uint32_t dst0 = sbase + P2_OFF_A + w * P2_NA * P2_A;
            const uint32_t bf = bar_afull + w * P2_NA * 8, be = bar_aempty + w * P2_NA * 8;
            int n = (w == 2 && half ? -1 : w) - 3, left = 0, u = 0, c = 0;
            const uint8_t* const hb = h_base();
            uint32_t ht = 0;
            bool act = lane < 3;
            auto next = [&]() {
                n += 3;
                left = n >= P2_ITEMS ? -1 : n < 0 ? 24 : 48;
                u = (k0 + p2_start(n)) % 48;
                if (left > 0) ht = h_tile(p2_tile(cl, n));
            };
            next();
            flag_wait<true>(g_prog[CNT_EARLY], NUM_CTAS);
#pragma unroll 1
            for (int i = 3; i > 0; i--) {
                const int wi = i % 3;
                if (wi == 2) flag_wait<true>(g_prog[CNT_H], NUM_CTAS);
                asm volatile("fence.proxy.async.global;\n" ::: "memory");
                if (w == wi && lane < 24) {
                    mbar_expect_tx(bf + lane / 3 * 8, P2_A);
                    bulk_g2s(dst0 + lane / 3 * P2_A, hb + (ht ^ h_block(u + lane / 3, rank)), P2_A, bf + lane / 3 * 8);
                }
                __syncwarp();
            }
            c = 8;
            left -= 8;
            u += 8;
            if (u == 48) u = 0;
            while (__any_sync(0xffffffffu, act)) {
                if (left == 0) next();
                const bool ok = act && mbar_test(be + ((c - 1) & 7) * 8, (~c >> 3) & 1);
                if (ok) {
                    const int st = c & 7;
                    if (left > 0) {
                        mbar_expect_tx(bf + st * 8, P2_A);
                        bulk_g2s(dst0 + st * P2_A, hb + (ht ^ h_block(u, rank)), P2_A, bf + st * 8);
                    } else {
                        mbar_arrive(bf + st * 8);
                        act = false;
                    }
                    if (++u == 48) u = 0;
                    c++;
                    left--;
                }
                SAFE_BREAK;
                if (!__any_sync(0xffffffffu, ok)) __nanosleep(100);
            }
        } else if (warp == 14) {
            const uint32_t sx = sbase + P2_OFF_X;
            size_t o = 0;
            int wp = 0;
            uint32_t par = 0;
            if (fin) {
#pragma unroll 1
                for (int c = lane * 16; c < 64 * P2_XROW + 128; c += 512) asm volatile("st.shared.v4.u32 [%0], {0, 0, 0, 0};\n" ::"r"(sx + c) : "memory");
                __syncwarp();
            }
            wait_pos(6);
#pragma unroll 1
            for (int n = -half; n < P2_ITEMS; n++) {
                const int w = (n + 3) % 3, end = p2_start(n) + 48;
                const size_t on = (size_t)(2 * p2_tile(cl, n) + rank) * (64 * C_DIM * 2);
                const uint32_t xf = bar_xfull + w * 8;
                if (n < 2 || n > 12) { LAG_HERE(3); }
                bool st = n + half > 0;
                const bool ld = n < P2_ITEMS - 1 && !(n < 0 && fin);
                if (n == P2_ITEMS - 1 && lane == 0) {
                    mbar_expect_tx(xf, 64 * C_DIM * 2);
#pragma unroll 1
                    for (int c = 4; c < 12; c++) {
                        if (c >= 8) {
                            mbar_wait(bar_aempty + ((2 * c - 1) & 7) * 8, 1);
                            mbar_wait(bar_aempty + ((2 * c) & 7) * 8, 1);
                        }
                        bulk_g2s(sbase + P2_OFF_A + (c & 3) * P2_XC + (c < 8 ? P2_LHALF : 0), reinterpret_cast<const uint8_t*>(x) + on + (c & 7) * P2_XC, P2_XC, xf);
                    }
                    mbar_arrive(xf);
                }
                if (st) {
                    mbar_wait(bar_oready + wp * 8, (par >> wp) & 1);
                    par ^= 1u << wp;
                }
                if (lane == 0) {
                    if (n < P2_ITEMS - 1) mbar_expect_tx(xf, ld ? 64 * C_DIM * 2 : 0);
                    const int t0 = (n ? p2_start(n - 1) + 48 : P2_S2) + (n == P2_ITEMS - 1 ? P2_TL : P2_T0), dt = end - t0;
                    int t = st ? 16 * t0 : -4096;
                    if (n == 0 && half) {
                        if (fin) {
                            flag_wait<true>(&g_half[pair][rank], 1);
                            asm volatile("fence.proxy.async.global;\n" ::: "memory");
                        }
#pragma unroll 1
                        for (int c = 0; c < 2; c++) {
                            uint8_t* dst = reinterpret_cast<uint8_t*>(out) + o + c * 32 * P2_XROW;
                            if (!fin) bulk_s2g(dst, sx + c * P2_XHALF, 32 * P2_XROW);
                            else asm volatile("cp.reduce.async.bulk.global.shared::cta.bulk_group.add.noftz.bf16 [%0], [%1], %2;\n"
                                              ::"l"(dst), "r"(sx + c * P2_XHALF), "r"(32 * P2_XROW) : "memory");
                        }
                        asm volatile("cp.async.bulk.commit_group;\n" ::: "memory");
                        if (!fin) {
                            asm volatile("cp.async.bulk.wait_group 0;\nfence.proxy.async.global;\n" ::: "memory");
                            asm volatile("st.release.gpu.global.u32 [%0], 1;\n" ::"l"(&g_half[pair][rank]) : "memory");
                        }
                        st = false;
                    }
#pragma unroll 1
                    for (int c = 0; c < 64 * P2_XROW; c += P2_XC, t += 2 * dt) {
                        const uint32_t sp = sx + c + (c >= 32 * P2_XROW ? 64 : 0);
                        wait_pos(t >> 4);
                        if (st) bulk_s2g(reinterpret_cast<uint8_t*>(out) + o + c, sp, P2_XC);
                        asm volatile("cp.async.bulk.commit_group;\n" ::: "memory");
                        if (ld) {
                            wait_pos((t + dt) >> 4);
                            asm volatile("cp.async.bulk.wait_group.read 0;\n" ::: "memory");
                            bulk_g2s(sp, reinterpret_cast<const uint8_t*>(x) + on + c, P2_XC, xf);
                        }
                    }
                    if (rank == 0 && n > 0 && n < P2_ITEMS - 2) flag_wait<false>(g_prog[CNT_POS], P2_NCL * (end - 1));
                    if (n < P2_ITEMS - 1) mbar_arrive(xf);
                }
                __syncwarp();
                o = on;
                wp = w;
            }
            asm volatile("cp.async.bulk.wait_group.read 0;\n" ::: "memory");
        } else {
            if (blockIdx.x == 120) {
                wait_pos(P2_RAW);
                for (int i = lane; i < (LN_RING + 6) * 2; i += 32) (&g_flag[0][0][0])[i * 8] = 0;
                for (int i = lane; i < HID; i += 32) g_sq[i] = 0;
                for (int i = lane; i < 512; i += 32) g_sums[i] = 0.f;
                if (lane == 0) g_epoch++;
            }
            int t = 4 * P2_XP0;
#pragma unroll 1
            for (int n = 0; n < P2_ITEMS && lane == 0; n++) {
                const uint8_t* xn = reinterpret_cast<const uint8_t*>(x) + (size_t)(2 * p2_tile(cl, n) + rank) * (64 * C_DIM * 2);
#pragma unroll 1
                for (int c = 0; c < 16; c++, t += n < P2_XPN ? 4 : P2_XPD) {
                    wait_pos(t >> 2);
                    asm volatile("cp.async.bulk.prefetch.L2.global [%0], %1;\n" ::"l"(xn + c * (P2_XC / 2)), "r"(P2_XC / 2) : "memory");
                }
            }
        }
        __syncwarp();
        cluster_sync_relaxed();
    } else {
        const int wg = warp >> 2, w = warp & 3, q = lane & 3;
        const uint32_t af = bar_afull + wg * P2_NA * 8;
        const uint32_t s_a = sbase + P2_OFF_A + wg * P2_NA * P2_A + (lane >> 3) * 512 + (lane & 7) * 64 + ((w ^ ((lane & 7) >> 1)) << 4);
        uint32_t acc0[48], acc1[48], up;
        uint4 a[2][2];

        __nv_bfloat16 gg[4];
#pragma unroll
        for (int i = 0; i < 4; i++) gg[i] = grn_g[tid + 384 * i];
#pragma unroll 1
        for (int it = !early;; it++) {
            float* s_red = reinterpret_cast<float*>(smem + P2_OFF_RED);
            float gx[4], part = 0.f;
            if (it == 1) {
                TSTAMP(1, 27);
                bar_sync(5, 416);
            }
            unsigned long long v[4];
#pragma unroll
            for (int i = 0; i < 4; i++) gx[i] = __ldcg(&g_scale[tid + 384 * i]);
            while (true) {
#pragma unroll
                for (int i = 0; i < 4; i++) asm volatile("ld.relaxed.gpu.global.u64 %0, [%1];\n" : "=l"(v[i]) : "l"(&g_sq[tid + 384 * i]) : "memory");
                SAFE_BREAK;
                if (!it || !__any_sync(0xffffffffu, min(min(v[0], v[1]), min(v[2], v[3])) < (unsigned long long)NGRP << 56)) break;
            }
            TSTAMP(1, 1);
            const float bias = reinterpret_cast<const float*>(smem + OFF_PRE)[tid];
            const float2 pre = *reinterpret_cast<const float2*>(smem + OFF_PRE + C_DIM * 4);
            bool tiny = false;
#pragma unroll
            for (int i = 0; i < 4; i++) {
                const float t = it == 2 ? __ldcg(&g_redo[tid + 384 * i]) : __ull2float_rn(v[i] << 8) * 0x1p-40f;
                tiny |= t < M_TOTAL * 0x1p-19f;
                gx[i] *= gx[i] * t;
            }
            float mg = 0.f;
#pragma unroll
            for (int i = 0; i < 4; i++) {
                asm("sqrt.approx.f32 %0, %1;\n" : "=f"(gx[i]) : "f"(gx[i] * (HSCALE * HSCALE) + 1e-6f));
                part += gx[i];
                gx[i] *= __bfloat162float(gg[i]);
                mg = fmaxf(mg, fabsf(gx[i]));
            }
#pragma unroll
            for (int o = 16; o > 0; o >>= 1) part += __shfl_xor_sync(0xffffffffu, part, o);
            const uint32_t mgw = __reduce_max_sync(0xffffffffu, __float_as_uint(mg));
            TSTAMP(1, 26);
            if (lane == 0) *reinterpret_cast<float2*>(s_red + warp * 2) = make_float2(part, __uint_as_float(mgw));
            if (it) {
                uint32_t redo;
                asm volatile("{\n.reg .pred p;\nsetp.ne.u32 p, %1, 0;\nbar.red.or.pred p, 4, 384, p;\nselp.u32 %0, 1, 0, p;\n}\n"
                             : "=r"(redo) : "r"((uint32_t)(tiny && it == 1)) : "memory");
                if (__shfl_sync(0xffffffffu, redo, 0)) {
                    p2_redo_sums(warp, lane);
                    continue;
                }
            }
            float tot = 0.f;
#pragma unroll
            for (int i = 0; i < 6; i++) {
                const float4 t = *reinterpret_cast<const float4*>(s_red + i * 4);
                tot += t.x + t.z;
                mg = fmaxf(mg, fmaxf(t.y, t.w));
            }
            const float inv = __fdividef(1.0f, tot * (1.0f / HID) + 1e-6f);
            const uint32_t ej = min((__float_as_uint(fmaxf(fmaf(mg, inv, 1.0f) * (HSCALE * UNCHOP), pre.y * 0x1p-13f)) >> 23) + 1, 250u);
            const float dn = __uint_as_float((254u - ej) << 23);
            up = min(ej + 127u - (__float_as_uint(pre.x) >> 23), 254u) * 0x00800080u;
            reinterpret_cast<uint16_t*>(smem + P2_OFF_BIAS + C_DIM * 2)[tid] = 0;
            *reinterpret_cast<__half*>(smem + P2_OFF_BIAS + (tid >> 5) * 64 + (tid & 6) * 8 + (tid & 24) / 2 + (tid & 1) * 2) = __float2half_rn(bias * dn);
#pragma unroll
            for (int i = 0; i < 4; i++) {
                const int k = tid + 384 * i;
                *reinterpret_cast<__half*>(smem + P2_OFF_GRN + (k >> 4) * 32 + (k & 6) * 4 + (k & 8) / 2 + (k & 1) * 2) =
                    __float2half_rn(fmaf(gx[i], inv, 1.0f) * (HSCALE * UNCHOP * dn));
            }
            TSTAMP(1, 25);
            if (it) break;
        }
        join();
        bar_sync(4, 384);
        TSTAMP(1, 28);
        LAG_HERE(2);
        if (wg == 1) {
            constexpr int N = sizeof(g_w2img[0]) / 16, PER = (N + NUM_CTAS - 1) / NUM_CTAS;
            uint4 v[5];
#pragma unroll
            for (int i = 0; i < 5; i++) v[i] = __ldcg(&g_w2img[0][min(blockIdx.x * PER + (tid & 127) + 128 * i, N - 1)]);
#pragma unroll
            for (int i = 0; i < 5; i++) {
                const int j = min(blockIdx.x * PER + (tid & 127) + 128 * i, N - 1);
                const uint32_t* t = reinterpret_cast<const uint32_t*>(smem + P2_OFF_GRN + (j / 768) * 32 + (j & 8) / 2);
                auto sc = [&](uint32_t u, int e) { return (h2_mul(u, t[2 * e]) + 0x00040004u) & 0xfff8fff8u; };
                g_w2img[1][j] = make_uint4(sc(v[i].x, 0), sc(v[i].y, 1), sc(v[i].z, 2), sc(v[i].w, 3));
            }
            asm volatile("fence.proxy.async.global;\n" ::: "memory");
            bar_sync(2, 128);
            if (tid == 128) asm volatile("fence.acq_rel.gpu;\nred.release.gpu.global.add.u32 [%0], 1;\n" ::"l"(g_prog[CNT_IMG1]) : "memory");
        }

        const int who = __shfl_sync(0xffffffffu, lane == 2 ? 0 : lane < 2 ? 1 : 2, lane);
        const uint32_t rel0 = who ? mapa(bar_bempty, lane & 1) : mapa(bar_aempty + wg * P2_NA * 8, rank), rel1 = rel0 + (who ? 0 : 32);
        auto publish = [&]() {
            asm volatile("fence.proxy.async.shared::cta;\n" ::: "memory");
            __syncwarp();
            if (who == 0) mbar_arrive(bar_oready + wg * 8);
        };
        bool ok_a, pend = false;
        uint32_t pa = 0, s_t;
        auto fetch = [&](int j, bool raw) {
            uint32_t o[6], u0[4], u1[4];
            uint2 t0 = make_uint2(0, 0), t1 = t0;
            if (raw) {
                asm volatile("ld.shared.v2.u32 {%0,%1}, [%2];\n" : "=r"(t0.x), "=r"(t0.y) : "r"(s_t + j * 64) : "memory");
                asm volatile("ld.shared.v2.u32 {%0,%1}, [%2];\n" : "=r"(t1.x), "=r"(t1.y) : "r"(s_t + j * 64 + 32) : "memory");
            }
            const bool ok_b = mbar_test(bar_bfull + (j & 3) * 8, j >> 2);
            if (j == 7) pa ^= 1;
            ok_a = mbar_test(af + ((j + 1) & 7) * 8, pa);
            asm volatile("ldmatrix.sync.aligned.m8n8.x4.trans.shared.b16 {%0,%1,%2,%3}, [%4];\n"
                         : "=r"(o[0]), "=r"(o[1]), "=r"(o[2]), "=r"(o[3]) : "r"(s_a + j * P2_A) : "memory");
            asm volatile("ldmatrix.sync.aligned.m8n8.x2.trans.shared.b16 {%0,%1}, [%2];\n"
                         : "=r"(o[4]), "=r"(o[5]) : "r"(s_a + j * P2_A + 2048) : "memory");
            p2_unpack(u0, o[0], o[1], o[2]);
            p2_unpack(u1, o[3], o[4], o[5]);
            if (raw) {
                u0[0] = h2_mul(u0[0], t0.x); u0[1] = h2_mul(u0[1], t0.x); u0[2] = h2_mul(u0[2], t0.y); u0[3] = h2_mul(u0[3], t0.y);
                u1[0] = h2_mul(u1[0], t1.x); u1[1] = h2_mul(u1[1], t1.x); u1[2] = h2_mul(u1[2], t1.y); u1[3] = h2_mul(u1[3], t1.y);
            }
            a[j & 1][0] = make_uint4(u0[0], u0[1], u0[2], u0[3]);
            a[j & 1][1] = make_uint4(u1[0], u1[1], u1[2], u1[3]);
            if (!ok_b) mbar_wait(bar_bfull + (j & 3) * 8, j >> 2);
        };
        auto table = [&](int pos) { s_t = sbase + P2_OFF_GRN + q * 8 + (k0 + pos) % 48 * 64; };
        const uint64_t db0 = make_desc(sbase, 128, 256 + zero);
        auto block8 = [&](bool raw, int pos, int thr0, int mode) {
#pragma unroll
            for (int j = 0; j < 8; j++) {
                const uint64_t db = db0 + (j & 3) * (P2_B / 16);
                if (j == 8 - P2_AH && mode == 1) bar_sync(4, 384);
                TR2(wg, pos + j, 0);
                wg_fence();
                mma_rs_n192(acc0, a[j & 1][0], db);
                mma_rs_n192(acc1, a[j & 1][0], db + 384);
                mma_rs_n192(acc0, a[j & 1][1], db + 768);
                mma_rs_n192(acc1, a[j & 1][1], db + 768 + 384);
                wg_commit();
                if (j == 7 && mode == 2) bar_arrive(4, 384);
                const uint32_t rel = ((j - 1) & 4 ? rel1 : rel0) + ((j - 1) & 3) * 8;
                TR2(wg, pos + j, 1);
                wg_wait<1>();
                TR2(wg, pos + j, 2);
                if (who < (j ? 2 : thr0)) mbar_arrive_cluster(rel);
                if (!ok_a) {
                    if (j == 0 && pend) { publish(); pend = false; }
                    mbar_wait(af + ((j + 1) & 7) * 8, pa);
                }
                TR2(wg, pos + j, 3);
                if (raw && j == 7) table(pos + 8);
                fetch((j + 1) & 7, raw && (j < 7 || pos + 8 < P2_RAW));
            }
        };
        int n = wg == 2 && half ? -1 : wg, pos = p2_start(n);
        uint32_t px = 0;
        wait_pos(pos);
        mbar_wait(af, 0);
        table(pos);
        fetch(0, pos < P2_RAW);
#pragma unroll 1
        for (;; n += 3) {
            TSTAMP(1, 2 + n);
            const int end = pos + (n < 0 ? 24 : 48);
#pragma unroll
            for (int i = 0; i < 48; i += 2) {
                asm volatile("mov.b64 {%0, %1}, 0;\n" : "=r"(acc0[i]), "=r"(acc0[i + 1]));
                asm volatile("mov.b64 {%0, %1}, 0;\n" : "=r"(acc1[i]), "=r"(acc1[i + 1]));
            }
            int thr = 1;
#pragma unroll 1
            for (; pos < P2_RAW; pos += 8, thr = 2) block8(true, pos, thr, 0);
#pragma unroll 1
            for (; pos < end; pos += 8, thr = 2) {
                const int e = pos + 8;
                block8(false, pos, thr, e < 48 || e > 256 || (e & 8) ? 0 : e == end ? 2 : 1);
            }
            TR2(wg, pos - 1, 4);
            if (n < 2 || n > 12) { LAG_HERE(3); }
            wg_wait<0>();
            TR2(wg, pos - 1, 5);
            if (who == 1) mbar_arrive_cluster(rel0 + 24);
            mbar_wait(bar_xfull + wg * 8, px);
            TR2(wg, pos - 1, 6);
            px ^= 1;
            __syncwarp();
            const bool last = n == P2_ITEMS - 1;
            uint32_t l;
            asm volatile("mov.u32 %0, %%laneid;\n" : "=r"(l));
            const uint32_t q16 = (l & 3) * 16, odd = (l >> 2) & 1, row = (w * 8 + (l >> 3)) * P2_XROW + q16;
            uint8_t* so = last ? reinterpret_cast<uint8_t*>(out) + (size_t)(2 * p2_tile(cl, n) + rank) * (64 * P2_XROW) : smem + P2_OFF_X;
            p2_epilogue(acc0, acc1, up, sbase + row + (last ? P2_OFF_A + odd * P2_LHALF : P2_OFF_X + odd * P2_XHALF),
                        sbase + P2_OFF_BIAS + q16 + (n < 0 && fin ? C_DIM * 2 : 0), so + (row + odd * (last ? 32 * P2_XROW : P2_XHALF)), zero);
            if (last) break;
            TR2(wg, pos - 1, 7);
            if (n + 3 >= P2_ITEMS) { publish(); break; }
            if (n < 0) {
                publish();
                pos = P2_S2;
                wait_pos(pos);
                mbar_wait(bar_bfull, 0);
            } else {
                pend = true;
                ok_a = false;
            }
        }
        TSTAMP(1, 29);
        cluster_sync_relaxed();
        TSTAMP(1, 30);
    }
}

__global__ void __cluster_dims__(2, 1, 1) __launch_bounds__(512, 1)
block_kernel(const __grid_constant__ CUtensorMap wmap, const __nv_bfloat16* __restrict__ x, const __nv_bfloat16* __restrict__ dw,
             const __nv_bfloat16* __restrict__ w2, const __nv_bfloat16* __restrict__ grn_g, const __nv_bfloat16* __restrict__ grn_b,
             __nv_bfloat16* __restrict__ out, int zero) {
    extern __shared__ __align__(1024) uint8_t smem[];
    const uint32_t sbase = smem_u32(smem);
    const int warp = __shfl_sync(0xffffffffu, threadIdx.x >> 5, 0), lane = threadIdx.x & 31;
    if (warp >= 12) {
        pass1<2>(wmap, x, dw, w2, grn_b, sbase, warp, lane, zero);
        pass2<2>(x, grn_g, out, smem, sbase, false, zero);
    } else {
        bool early = false;
        if (warp >= 8) {
            pass1<1>(wmap, x, dw, w2, grn_b, sbase, warp, lane, zero);
            reg_inc<160>();
        } else {
            early = pass1<0>(wmap, x, dw, w2, grn_b, sbase, warp, lane, zero);
            reg_dec<160>();
        }
        pass2<0>(x, grn_g, out, smem, sbase, early, zero);
    }
}

}

extern "C" void kernel_launch(void* const* d_in, const int* in_sizes, int n_in, void* d_out, int out_size) {
    const __nv_bfloat16* x = (const __nv_bfloat16*)d_in[0];
    const __nv_bfloat16* dw = (const __nv_bfloat16*)d_in[1];
    const __nv_bfloat16* w1 = (const __nv_bfloat16*)d_in[2];
    const __nv_bfloat16* w2 = (const __nv_bfloat16*)d_in[3];
    const __nv_bfloat16* grn_g = (const __nv_bfloat16*)d_in[4];
    const __nv_bfloat16* grn_b = (const __nv_bfloat16*)d_in[5];
    __nv_bfloat16* out = (__nv_bfloat16*)d_out;

    cudaFuncSetAttribute(block_kernel, cudaFuncAttributeMaxDynamicSharedMemorySize, SMEM_BYTES);

    typedef CUresult (*EncodeFn)(CUtensorMap*, CUtensorMapDataType, cuuint32_t, void*, const cuuint64_t*, const cuuint64_t*,
                                 const cuuint32_t*, const cuuint32_t*, CUtensorMapInterleave, CUtensorMapSwizzle,
                                 CUtensorMapL2promotion, CUtensorMapFloatOOBfill);
    static EncodeFn encode = nullptr;
    if (!encode) {
        cudaDriverEntryPointQueryResult qres;
        cudaGetDriverEntryPoint("cuTensorMapEncodeTiled", (void**)&encode, cudaEnableDefault, &qres);
    }
    CUtensorMap wmap;
    const cuuint64_t gdim[2] = {HID, C_DIM};
    const cuuint64_t gstr[1] = {HID * 2};
    const cuuint32_t box[2] = {64, 192}, estr[2] = {1, 1};
    CUresult er = encode(&wmap, CU_TENSOR_MAP_DATA_TYPE_BFLOAT16, 2, (void*)w1, gdim, gstr, box, estr, CU_TENSOR_MAP_INTERLEAVE_NONE,
           CU_TENSOR_MAP_SWIZZLE_128B, CU_TENSOR_MAP_L2_PROMOTION_L2_128B, CU_TENSOR_MAP_FLOAT_OOB_FILL_NONE);
    if (er != CUDA_SUCCESS) printf("tensor map encode failed %d\n", (int)er);

    block_kernel<<<NUM_CTAS, 512, SMEM_BYTES>>>(wmap, x, dw, w2, grn_g, grn_b, out, 0);
}
```
